```python
import torch

def _softmax(x, axis=-1):
    return torch.softmax(x, dim=axis)
def _gelu(x):
    return torch.nn.functional.gelu(x, approximate="tanh")
def _silu(x):
    return torch.nn.functional.silu(x)
def _sigmoid(x):
    return torch.sigmoid(x)
def _layernorm(x, axis=-1, eps=1e-5):
    m = x.mean(dim=axis, keepdim=True)
    v = x.var(dim=axis, keepdim=True, unbiased=False)
    return (x - m) / torch.sqrt(v + eps)
def _scatter_add(tgt, idx, src, axis=0):
    return tgt.clone().index_add_(axis, idx, src)
def _segment_sum(src, seg, n):
    out = torch.zeros((n,) + src.shape[1:], dtype=src.dtype)
    return out.index_add_(0, seg, src)
def _pad(x, pw):
    flat = tuple(v for pair in reversed(pw) for v in pair)
    return torch.nn.functional.pad(x, flat)

kernel_name = 'gated_mix__linear_attn_block__glu_gated_bilinear__prompt'

def setup_inputs():

    _w = (lambda a: (lambda t: t.to(torch.bfloat16) if t.is_floating_point() else t)(torch.as_tensor(a)))
    def _A_setup():
        B, S, D = 1, 2048, 512
        return {
            "x": _w((lambda *s: torch.randn(*s, dtype=torch.bfloat16) * 0.05)(B, S, D)),
            "wqkv": _w((lambda *s: torch.randn(*s, dtype=torch.bfloat16) * 0.8)(D, 3 * D)),
            "wo": _w((lambda *s: torch.randn(*s, dtype=torch.bfloat16) * 0.05)(D, D)),
        }
    _A_in = _A_setup()

    def _B_setup():
        B, S, D, F = 1, 2048, 512, 1792
        return {
            "x": _w((lambda *s: torch.randn(*s, dtype=torch.bfloat16) * 0.05)(B, S, D)),
            "w_gate": _w((lambda *s: torch.randn(*s, dtype=torch.bfloat16) * 1.6)(D, F) * (D ** -0.5)),
            "w_up": _w((lambda *s: torch.randn(*s, dtype=torch.bfloat16) * 1.6)(D, F) * (D ** -0.5)),
            "w_down": _w((lambda *s: torch.randn(*s, dtype=torch.bfloat16) * 1.6)(F, D) * (F ** -0.5)),
        }
    _B_in = _B_setup()

    return {
        "A_x": _A_in["x"],
        "A_wqkv": _A_in["wqkv"],
        "A_wo": _A_in["wo"],
        "B_x": _B_in["x"],
        "B_w_gate": _B_in["w_gate"],
        "B_w_up": _B_in["w_up"],
        "B_w_down": _B_in["w_down"],
        "gate_w": _w((lambda *s: torch.randn(*s, dtype=torch.bfloat16) * 0.05)(512) * 16.0),
    }

def reference(A_x, A_wqkv, A_wo, B_x, B_w_gate, B_w_up, B_w_down, gate_w):
    def _A_ref(x, wqkv, wo):
        B, S, D = x.shape
        H = 32; Dh = D // H
        qkv = (lambda x, *d: x.permute(*d))((x @ wqkv).reshape(B, S, 3, H, Dh), 2, 0, 3, 1, 4)
        q, k, v = qkv[0], qkv[1], qkv[2]
        phi = lambda t: torch.where(t > 0, t + 1, torch.exp(t)) + 1e-6
        pq, pk = phi(q), phi(k)
        kv = torch.einsum("bhsd,bhse->bhde", pk, v)
        z = torch.einsum("bhsd->bhd", pk)
        num = torch.einsum("bhqd,bhde->bhqe", pq, kv)
        den = torch.einsum("bhqd,bhd->bhq", pq, z)[..., None] + 1e-6
        o = num / den
        return (lambda x, *d: x.permute(*d))(o, 0, 2, 1, 3).reshape(B, S, D) @ wo

    def _B_ref(x, w_gate, w_up, w_down):
        g = torch.einsum("bsd,df->bsf", x, w_gate)
        u = torch.einsum("bsd,df->bsf", x, w_up)
        h = g * u
        return torch.einsum("bsf,fd->bsd", h, w_down)

    x = A_x
    g = _sigmoid((x * gate_w).sum(-1, keepdims=True))
    a = _A_ref(x, A_wqkv, A_wo)
    b = _B_ref(x, B_w_gate, B_w_up, B_w_down)
    return g * a + (1 - g) * b
```

```cpp
#include <cuda_runtime.h>
#include <cuda.h>
#include <cuda_bf16.h>
#include <stdint.h>

#define MC 0
#define PROF 0

namespace {

constexpr int kD = 512, kF = 1792;
constexpr uint32_t OFF_X = 0, OFF_STG = 131072, OFF_RING = 147456, OFF_MISC = 229376;
constexpr uint32_t B_FULL = OFF_MISC, B_EMPTY = OFF_MISC + 64, B_XFULL = OFF_MISC + 128;
constexpr uint32_t B_GRDY = OFF_MISC + 192, B_STGFULL = OFF_MISC + 200, B_STGFREE = OFF_MISC + 208, B_KVRDY = OFF_MISC + 216;
constexpr uint32_t OFF_EPOCH = OFF_MISC + 240, OFF_G = OFF_MISC + 256;
constexpr uint32_t SMEM_BYTES = OFF_MISC + 256 + 512;
constexpr uint32_t SPIN_MBAR = 1u << 16, SPIN_GLOBAL = 1u << 14;

struct alignas(64) Maps { CUtensorMap x, gu, kv, q64, gu64, wd, wo; };

}

__device__ uint4 g_part[16 * 8 * 8 * 1024];
__device__ float g_kvacc[2 * 8 * 4 * 272];
__device__ unsigned g_kvcnt[8 * 32];
__device__ unsigned g_epoch[128];
#define TS(role, idx)
#define TSG(role, idx)

namespace {

__device__ __forceinline__ void mbar_init(uint32_t bar, uint32_t cnt) { asm volatile("mbarrier.init.shared::cta.b64 [%0], %1;" :: "r"(bar), "r"(cnt) : "memory"); }
__device__ __forceinline__ void mbar_expect(uint32_t bar, uint32_t bytes) { asm volatile("mbarrier.arrive.expect_tx.shared::cta.b64 _, [%0], %1;" :: "r"(bar), "r"(bytes) : "memory"); }
__device__ __forceinline__ void mbar_arrive(uint32_t bar) { asm volatile("mbarrier.arrive.shared::cta.b64 _, [%0];" :: "r"(bar) : "memory"); }
__device__ __forceinline__ void mbar_arrive_cta(uint32_t bar, uint32_t cta) {
    asm volatile("{\n.reg .b32 ra;\nmapa.shared::cluster.u32 ra, %0, %1;\nmbarrier.arrive.shared::cluster.b64 _, [ra];\n}" :: "r"(bar), "r"(cta) : "memory");
}
__device__ __forceinline__ void mbar_wait(uint32_t bar, uint32_t parity) {
    uint32_t ok, it = 0;
    do {
        asm volatile("{\n.reg .pred p;\nmbarrier.try_wait.parity.shared::cta.b64 p, [%1], %2;\nselp.u32 %0, 1, 0, p;\n}" : "=r"(ok) : "r"(bar), "r"(parity) : "memory");
    } while (!ok && ++it < SPIN_MBAR);
}
__device__ __forceinline__ void tma2(uint32_t dst, const CUtensorMap* m, int c0, int c1, uint32_t bar) {
    asm volatile("cp.async.bulk.tensor.2d.shared::cluster.global.mbarrier::complete_tx::bytes [%0], [%1, {%3, %4}], [%2];"
        :: "r"(dst), "l"(m), "r"(bar), "r"(c0), "r"(c1) : "memory");
}
__device__ __forceinline__ void tmaw2(uint32_t dst, const CUtensorMap* m, int c0, int c1, uint32_t bar) {
    tma2(dst, m, c0, c1, bar);
}
__device__ __forceinline__ void tmaw3(uint32_t dst, const CUtensorMap* m, int c0, int c1, int c2, uint32_t bar) {
    asm volatile("cp.async.bulk.tensor.3d.shared::cluster.global.mbarrier::complete_tx::bytes [%0], [%1, {%3, %4, %5}], [%2];"
        :: "r"(dst), "l"(m), "r"(bar), "r"(c0), "r"(c1), "r"(c2) : "memory");
}
__device__ __forceinline__ void l2_prefetch(const void* p, uint32_t bytes) { asm volatile("cp.async.bulk.prefetch.L2.global [%0], %1;" :: "l"(p), "r"(bytes) : "memory"); }
__device__ __forceinline__ void wg_fence() { asm volatile("wgmma.fence.sync.aligned;" ::: "memory"); }
__device__ __forceinline__ void wg_commit() { asm volatile("wgmma.commit_group.sync.aligned;" ::: "memory"); }
template <int N> __device__ __forceinline__ void wg_wait() { asm volatile("wgmma.wait_group.sync.aligned %0;" :: "n"(N) : "memory"); }
template <int O, int N> __device__ __forceinline__ void pin(float (&d)[128]) {
#pragma unroll
    for (int i = 0; i < N; i++) asm volatile("" : "+f"(d[O + i]) :: "memory");
}
__device__ __forceinline__ uint32_t pack2(float lo, float hi) { uint32_t r; asm("cvt.rn.bf16x2.f32 %0, %1, %2;" : "=r"(r) : "f"(hi), "f"(lo)); return r; }
__device__ __forceinline__ float phi(float t) { return (t > 0.f ? t + 1.f : __expf(t)) + 1e-6f; }
__device__ __forceinline__ void stsm4(uint32_t a, uint32_t r0, uint32_t r1, uint32_t r2, uint32_t r3) {
    asm volatile("stmatrix.sync.aligned.m8n8.x4.shared.b16 [%0], {%1,%2,%3,%4};" :: "r"(a), "r"(r0), "r"(r1), "r"(r2), "r"(r3) : "memory");
}
__device__ __forceinline__ void ldsm4(uint32_t (&r)[4], uint32_t a) {
    asm volatile("ldmatrix.sync.aligned.m8n8.x4.shared.b16 {%0,%1,%2,%3}, [%4];" : "=r"(r[0]), "=r"(r[1]), "=r"(r[2]), "=r"(r[3]) : "r"(a) : "memory");
}
__device__ __forceinline__ void ldsm4t(uint32_t (&r)[4], uint32_t a) {
    asm volatile("ldmatrix.sync.aligned.m8n8.x4.trans.shared.b16 {%0,%1,%2,%3}, [%4];" : "=r"(r[0]), "=r"(r[1]), "=r"(r[2]), "=r"(r[3]) : "r"(a) : "memory");
}
__device__ __forceinline__ void mma16816(float (&c)[4], uint32_t a0, uint32_t a1, uint32_t a2, uint32_t a3, uint32_t b0, uint32_t b1) {
    asm volatile("mma.sync.aligned.m16n8k16.row.col.f32.bf16.bf16.f32 {%0,%1,%2,%3}, {%4,%5,%6,%7}, {%8,%9}, {%0,%1,%2,%3};"
        : "+f"(c[0]), "+f"(c[1]), "+f"(c[2]), "+f"(c[3]) : "r"(a0), "r"(a1), "r"(a2), "r"(a3), "r"(b0), "r"(b1));
}
__device__ __forceinline__ float bf_lo(uint32_t w) { return __uint_as_float(w << 16); }
__device__ __forceinline__ float bf_hi(uint32_t w) { return __uint_as_float(w & 0xffff0000u); }
__device__ __forceinline__ void st_pkt(uint4* p, uint32_t w0, uint32_t w1, uint32_t w2, uint32_t w3) {
    asm volatile("{\n.reg .b64 lo, hi;\n.reg .b128 v;\nmov.b64 lo, {%1, %2};\nmov.b64 hi, {%3, %4};\nmov.b128 v, {lo, hi};\nst.relaxed.gpu.global.b128 [%0], v;\n}"
        :: "l"(p), "r"(w0), "r"(w1), "r"(w2), "r"(w3) : "memory");
}
__device__ __forceinline__ void ld_pkt(const uint4* p, uint32_t& w0, uint32_t& w1, uint32_t& w2, uint32_t& w3) {
    asm volatile("{\n.reg .b64 lo, hi;\n.reg .b128 v;\nld.relaxed.gpu.global.b128 v, [%4];\nmov.b128 {lo, hi}, v;\nmov.b64 {%0, %1}, lo;\nmov.b64 {%2, %3}, hi;\n}"
        : "=r"(w0), "=r"(w1), "=r"(w2), "=r"(w3) : "l"(p) : "memory");
}

template<int O> __device__ __forceinline__ void wg_ss256(float (&d)[128], uint32_t alo, uint32_t ahi, uint32_t blo, uint32_t bhi, int sc) {
    asm volatile("{\n.reg .pred p;\n.reg .b64 da, db;\nmov.b64 da, {%128, %129};\nmov.b64 db, {%130, %131};\nsetp.ne.b32 p, %132, 0;\n"
        "wgmma.mma_async.sync.aligned.m64n256k16.f32.bf16.bf16 {%0,%1,%2,%3,%4,%5,%6,%7,%8,%9,%10,%11,%12,%13,%14,%15,%16,%17,%18,%19,%20,%21,%22,%23,%24,%25,%26,%27,%28,%29,%30,%31,%32,%33,%34,%35,%36,%37,%38,%39,%40,%41,%42,%43,%44,%45,%46,%47,%48,%49,%50,%51,%52,%53,%54,%55,%56,%57,%58,%59,%60,%61,%62,%63,%64,%65,%66,%67,%68,%69,%70,%71,%72,%73,%74,%75,%76,%77,%78,%79,%80,%81,%82,%83,%84,%85,%86,%87,%88,%89,%90,%91,%92,%93,%94,%95,%96,%97,%98,%99,%100,%101,%102,%103,%104,%105,%106,%107,%108,%109,%110,%111,%112,%113,%114,%115,%116,%117,%118,%119,%120,%121,%122,%123,%124,%125,%126,%127}, da, db, p, 1, 1, 0, 1;\n}\n"
        : "+f"(d[O+0]),"+f"(d[O+1]),"+f"(d[O+2]),"+f"(d[O+3]),"+f"(d[O+4]),"+f"(d[O+5]),"+f"(d[O+6]),"+f"(d[O+7]),"+f"(d[O+8]),"+f"(d[O+9]),"+f"(d[O+10]),"+f"(d[O+11]),"+f"(d[O+12]),"+f"(d[O+13]),"+f"(d[O+14]),"+f"(d[O+15]),"+f"(d[O+16]),"+f"(d[O+17]),"+f"(d[O+18]),"+f"(d[O+19]),"+f"(d[O+20]),"+f"(d[O+21]),"+f"(d[O+22]),"+f"(d[O+23]),"+f"(d[O+24]),"+f"(d[O+25]),"+f"(d[O+26]),"+f"(d[O+27]),"+f"(d[O+28]),"+f"(d[O+29]),"+f"(d[O+30]),"+f"(d[O+31]),"+f"(d[O+32]),"+f"(d[O+33]),"+f"(d[O+34]),"+f"(d[O+35]),"+f"(d[O+36]),"+f"(d[O+37]),"+f"(d[O+38]),"+f"(d[O+39]),"+f"(d[O+40]),"+f"(d[O+41]),"+f"(d[O+42]),"+f"(d[O+43]),"+f"(d[O+44]),"+f"(d[O+45]),"+f"(d[O+46]),"+f"(d[O+47]),"+f"(d[O+48]),"+f"(d[O+49]),"+f"(d[O+50]),"+f"(d[O+51]),"+f"(d[O+52]),"+f"(d[O+53]),"+f"(d[O+54]),"+f"(d[O+55]),"+f"(d[O+56]),"+f"(d[O+57]),"+f"(d[O+58]),"+f"(d[O+59]),"+f"(d[O+60]),"+f"(d[O+61]),"+f"(d[O+62]),"+f"(d[O+63]),"+f"(d[O+64]),"+f"(d[O+65]),"+f"(d[O+66]),"+f"(d[O+67]),"+f"(d[O+68]),"+f"(d[O+69]),"+f"(d[O+70]),"+f"(d[O+71]),"+f"(d[O+72]),"+f"(d[O+73]),"+f"(d[O+74]),"+f"(d[O+75]),"+f"(d[O+76]),"+f"(d[O+77]),"+f"(d[O+78]),"+f"(d[O+79]),"+f"(d[O+80]),"+f"(d[O+81]),"+f"(d[O+82]),"+f"(d[O+83]),"+f"(d[O+84]),"+f"(d[O+85]),"+f"(d[O+86]),"+f"(d[O+87]),"+f"(d[O+88]),"+f"(d[O+89]),"+f"(d[O+90]),"+f"(d[O+91]),"+f"(d[O+92]),"+f"(d[O+93]),"+f"(d[O+94]),"+f"(d[O+95]),"+f"(d[O+96]),"+f"(d[O+97]),"+f"(d[O+98]),"+f"(d[O+99]),"+f"(d[O+100]),"+f"(d[O+101]),"+f"(d[O+102]),"+f"(d[O+103]),"+f"(d[O+104]),"+f"(d[O+105]),"+f"(d[O+106]),"+f"(d[O+107]),"+f"(d[O+108]),"+f"(d[O+109]),"+f"(d[O+110]),"+f"(d[O+111]),"+f"(d[O+112]),"+f"(d[O+113]),"+f"(d[O+114]),"+f"(d[O+115]),"+f"(d[O+116]),"+f"(d[O+117]),"+f"(d[O+118]),"+f"(d[O+119]),"+f"(d[O+120]),"+f"(d[O+121]),"+f"(d[O+122]),"+f"(d[O+123]),"+f"(d[O+124]),"+f"(d[O+125]),"+f"(d[O+126]),"+f"(d[O+127])
        : "r"(alo), "r"(ahi), "r"(blo), "r"(bhi), "r"(sc));
}
template<int O> __device__ __forceinline__ void wg_ss128(float (&d)[128], uint32_t alo, uint32_t ahi, uint32_t blo, uint32_t bhi, int sc) {
    asm volatile("{\n.reg .pred p;\n.reg .b64 da, db;\nmov.b64 da, {%64, %65};\nmov.b64 db, {%66, %67};\nsetp.ne.b32 p, %68, 0;\n"
        "wgmma.mma_async.sync.aligned.m64n128k16.f32.bf16.bf16 {%0,%1,%2,%3,%4,%5,%6,%7,%8,%9,%10,%11,%12,%13,%14,%15,%16,%17,%18,%19,%20,%21,%22,%23,%24,%25,%26,%27,%28,%29,%30,%31,%32,%33,%34,%35,%36,%37,%38,%39,%40,%41,%42,%43,%44,%45,%46,%47,%48,%49,%50,%51,%52,%53,%54,%55,%56,%57,%58,%59,%60,%61,%62,%63}, da, db, p, 1, 1, 0, 1;\n}\n"
        : "+f"(d[O+0]),"+f"(d[O+1]),"+f"(d[O+2]),"+f"(d[O+3]),"+f"(d[O+4]),"+f"(d[O+5]),"+f"(d[O+6]),"+f"(d[O+7]),"+f"(d[O+8]),"+f"(d[O+9]),"+f"(d[O+10]),"+f"(d[O+11]),"+f"(d[O+12]),"+f"(d[O+13]),"+f"(d[O+14]),"+f"(d[O+15]),"+f"(d[O+16]),"+f"(d[O+17]),"+f"(d[O+18]),"+f"(d[O+19]),"+f"(d[O+20]),"+f"(d[O+21]),"+f"(d[O+22]),"+f"(d[O+23]),"+f"(d[O+24]),"+f"(d[O+25]),"+f"(d[O+26]),"+f"(d[O+27]),"+f"(d[O+28]),"+f"(d[O+29]),"+f"(d[O+30]),"+f"(d[O+31]),"+f"(d[O+32]),"+f"(d[O+33]),"+f"(d[O+34]),"+f"(d[O+35]),"+f"(d[O+36]),"+f"(d[O+37]),"+f"(d[O+38]),"+f"(d[O+39]),"+f"(d[O+40]),"+f"(d[O+41]),"+f"(d[O+42]),"+f"(d[O+43]),"+f"(d[O+44]),"+f"(d[O+45]),"+f"(d[O+46]),"+f"(d[O+47]),"+f"(d[O+48]),"+f"(d[O+49]),"+f"(d[O+50]),"+f"(d[O+51]),"+f"(d[O+52]),"+f"(d[O+53]),"+f"(d[O+54]),"+f"(d[O+55]),"+f"(d[O+56]),"+f"(d[O+57]),"+f"(d[O+58]),"+f"(d[O+59]),"+f"(d[O+60]),"+f"(d[O+61]),"+f"(d[O+62]),"+f"(d[O+63])
        : "r"(alo), "r"(ahi), "r"(blo), "r"(bhi), "r"(sc));
}
template<int O> __device__ __forceinline__ void wg_rs128(float (&d)[128], uint32_t a0, uint32_t a1, uint32_t a2, uint32_t a3, uint32_t blo, uint32_t bhi, int sc) {
    asm volatile("{\n.reg .pred p;\n.reg .b64 da, db;\nmov.b64 db, {%68, %69};\nsetp.ne.b32 p, %70, 0;\n"
        "wgmma.mma_async.sync.aligned.m64n128k16.f32.bf16.bf16 {%0,%1,%2,%3,%4,%5,%6,%7,%8,%9,%10,%11,%12,%13,%14,%15,%16,%17,%18,%19,%20,%21,%22,%23,%24,%25,%26,%27,%28,%29,%30,%31,%32,%33,%34,%35,%36,%37,%38,%39,%40,%41,%42,%43,%44,%45,%46,%47,%48,%49,%50,%51,%52,%53,%54,%55,%56,%57,%58,%59,%60,%61,%62,%63}, {%64,%65,%66,%67}, db, p, 1, 1, 1;\n}\n"
        : "+f"(d[O+0]),"+f"(d[O+1]),"+f"(d[O+2]),"+f"(d[O+3]),"+f"(d[O+4]),"+f"(d[O+5]),"+f"(d[O+6]),"+f"(d[O+7]),"+f"(d[O+8]),"+f"(d[O+9]),"+f"(d[O+10]),"+f"(d[O+11]),"+f"(d[O+12]),"+f"(d[O+13]),"+f"(d[O+14]),"+f"(d[O+15]),"+f"(d[O+16]),"+f"(d[O+17]),"+f"(d[O+18]),"+f"(d[O+19]),"+f"(d[O+20]),"+f"(d[O+21]),"+f"(d[O+22]),"+f"(d[O+23]),"+f"(d[O+24]),"+f"(d[O+25]),"+f"(d[O+26]),"+f"(d[O+27]),"+f"(d[O+28]),"+f"(d[O+29]),"+f"(d[O+30]),"+f"(d[O+31]),"+f"(d[O+32]),"+f"(d[O+33]),"+f"(d[O+34]),"+f"(d[O+35]),"+f"(d[O+36]),"+f"(d[O+37]),"+f"(d[O+38]),"+f"(d[O+39]),"+f"(d[O+40]),"+f"(d[O+41]),"+f"(d[O+42]),"+f"(d[O+43]),"+f"(d[O+44]),"+f"(d[O+45]),"+f"(d[O+46]),"+f"(d[O+47]),"+f"(d[O+48]),"+f"(d[O+49]),"+f"(d[O+50]),"+f"(d[O+51]),"+f"(d[O+52]),"+f"(d[O+53]),"+f"(d[O+54]),"+f"(d[O+55]),"+f"(d[O+56]),"+f"(d[O+57]),"+f"(d[O+58]),"+f"(d[O+59]),"+f"(d[O+60]),"+f"(d[O+61]),"+f"(d[O+62]),"+f"(d[O+63])
        : "r"(a0), "r"(a1), "r"(a2), "r"(a3), "r"(blo), "r"(bhi), "r"(sc));
}
template<int O> __device__ __forceinline__ void wg_ss64(float (&d)[128], uint32_t alo, uint32_t ahi, uint32_t blo, uint32_t bhi, int sc) {
    asm volatile("{\n.reg .pred p;\n.reg .b64 da, db;\nmov.b64 da, {%32, %33};\nmov.b64 db, {%34, %35};\nsetp.ne.b32 p, %36, 0;\n"
        "wgmma.mma_async.sync.aligned.m64n64k16.f32.bf16.bf16 {%0,%1,%2,%3,%4,%5,%6,%7,%8,%9,%10,%11,%12,%13,%14,%15,%16,%17,%18,%19,%20,%21,%22,%23,%24,%25,%26,%27,%28,%29,%30,%31}, da, db, p, 1, 1, 0, 1;\n}\n"
        : "+f"(d[O+0]),"+f"(d[O+1]),"+f"(d[O+2]),"+f"(d[O+3]),"+f"(d[O+4]),"+f"(d[O+5]),"+f"(d[O+6]),"+f"(d[O+7]),"+f"(d[O+8]),"+f"(d[O+9]),"+f"(d[O+10]),"+f"(d[O+11]),"+f"(d[O+12]),"+f"(d[O+13]),"+f"(d[O+14]),"+f"(d[O+15]),"+f"(d[O+16]),"+f"(d[O+17]),"+f"(d[O+18]),"+f"(d[O+19]),"+f"(d[O+20]),"+f"(d[O+21]),"+f"(d[O+22]),"+f"(d[O+23]),"+f"(d[O+24]),"+f"(d[O+25]),"+f"(d[O+26]),"+f"(d[O+27]),"+f"(d[O+28]),"+f"(d[O+29]),"+f"(d[O+30]),"+f"(d[O+31])
        : "r"(alo), "r"(ahi), "r"(blo), "r"(bhi), "r"(sc));
}

constexpr uint32_t DH128 = 64u | 0x40000000u;
constexpr uint32_t DH64 = 32u | 0x80000000u;
constexpr uint32_t LBO4K = (4096u >> 4) << 16, LBO8K = (8192u >> 4) << 16, LBO1 = 1u << 16;

__device__ __forceinline__ uint32_t slot_addr(uint32_t sb, int slot) { return sb + (slot < 5 ? OFF_RING + slot * 16384 : OFF_X + slot * 16384); }

template <int O, bool SW64> __device__ __forceinline__ void g1_issue(float (&acc)[128], uint32_t alo, uint32_t blo, int first) {
    wg_fence();
#pragma unroll
    for (int k = 0; k < 4; k++)
        wg_ss128<O>(acc, alo + 2 * k, DH128, blo + (SW64 ? 64 * k : (k >> 1) * 512 + (k & 1) * 128), SW64 ? DH64 : DH128, (k == 0) ? !first : 1);
    wg_commit();
}

template <int N> __device__ __forceinline__ void stash(uint32_t base, uint32_t sw, const uint32_t (&f)[N]) {
#pragma unroll
    for (int t = 0; t < N / 4; t++) stsm4(base + ((sw ^ (2 * t)) << 4), f[4 * t], f[4 * t + 1], f[4 * t + 2], f[4 * t + 3]);
}

template <int O> __device__ __forceinline__ void send_block(const float (&acc)[128], uint4* p, uint32_t tag) {
#pragma unroll
    for (int v = 0; v < 4; v++) {
        uint32_t w0 = pack2(acc[O + 8 * v], acc[O + 8 * v + 1]);
        w0 = (w0 & ~1u) | tag;
        st_pkt(p + v * 32, w0, pack2(acc[O + 8 * v + 2], acc[O + 8 * v + 3]), pack2(acc[O + 8 * v + 4], acc[O + 8 * v + 5]), pack2(acc[O + 8 * v + 6], acc[O + 8 * v + 7]));
    }
}
__device__ __forceinline__ void recv_issue(uint32_t (&q)[16], const uint4* p) {
#pragma unroll
    for (int v = 0; v < 4; v++) ld_pkt(p + v * 32, q[4 * v], q[4 * v + 1], q[4 * v + 2], q[4 * v + 3]);
}
template <bool FIRST> __device__ __forceinline__ void recv_finish(uint32_t (&q)[16], const uint4* p, uint32_t tag, float (&sum)[32]) {
    uint32_t it = 0;
    while (true) {
        bool ok = (((q[0] ^ tag) | (q[4] ^ tag) | (q[8] ^ tag) | (q[12] ^ tag)) & 1u) == 0;
        if (__all_sync(0xffffffffu, ok) || ++it > SPIN_GLOBAL) break;
        recv_issue(q, p);
    }
#pragma unroll
    for (int i = 0; i < 16; i++) {
        if (FIRST) { sum[2 * i] = bf_lo(q[i]); sum[2 * i + 1] = bf_hi(q[i]); }
        else { sum[2 * i] += bf_lo(q[i]); sum[2 * i + 1] += bf_hi(q[i]); }
    }
}

}

__global__ void __launch_bounds__(384, 1)
fused_kernel(const __grid_constant__ Maps maps, const __nv_bfloat16* __restrict__ gate_w,
             const char* __restrict__ pf_qkv, const char* __restrict__ pf_g, const char* __restrict__ pf_u,
             const char* __restrict__ pf_d, const char* __restrict__ pf_o, __nv_bfloat16* __restrict__ out) {
    extern __shared__ __align__(1024) uint8_t smem_raw[];
    const uint32_t sb = (uint32_t)__cvta_generic_to_shared(smem_raw);
    const int tid = threadIdx.x, lane = tid & 31;
    const int warp = __shfl_sync(0xffffffffu, tid >> 5, 0);
    const int j = (blockIdx.x >> 1) & 7;
    const int r = ((blockIdx.x >> 4) << 1) | (blockIdx.x & 1);
    const uint32_t rank = blockIdx.x & 1;

    if (warp == 0) { TSG(0, 30); TS(0, 0); }
    if (warp == 9 && lane < 7) asm volatile("prefetch.tensormap [%0];" :: "l"(&maps.x + lane) : "memory");
    if (tid == 256) {
        for (int i = 0; i < 8; i++) { mbar_init(sb + B_FULL + 8 * i, 1); mbar_init(sb + B_EMPTY + 8 * i, MC ? 4 : 2); mbar_init(sb + B_XFULL + 8 * i, 1); }
        mbar_init(sb + B_GRDY, 3); mbar_init(sb + B_STGFULL, 4); mbar_init(sb + B_STGFREE, 2); mbar_init(sb + B_KVRDY, 2);
        asm volatile("fence.mbarrier_init.release.cluster;" ::: "memory");
        asm volatile("fence.proxy.async.shared::cta;" ::: "memory");
        mbar_expect(sb + B_XFULL, 16384);
        tma2(sb + OFF_X, &maps.x, 0, r * 128, sb + B_XFULL);
    }
    __syncthreads();

    if (warp >= 8) {
        asm volatile("setmaxnreg.dec.sync.aligned.u32 56;");
        if (warp == 8) {
            if (lane == 0) {
                int slot = 0, ph = 1;
                for (int s = 0; s < 16; s++) {
                    const uint32_t full = sb + B_FULL + 8 * slot, dst = sb + OFF_RING + slot * 16384;
                    mbar_wait(sb + B_EMPTY + 8 * slot, ph);
                    mbar_expect(full, 16384);
                    if (!MC || rank == 0) tmaw3(dst, &maps.gu, 224 * j, 32 * s, 0, full);
                    if (!MC || rank == 1) tmaw3(dst + 8192, &maps.kv, 64 * j, 32 * s, 1, full);
                    int xb = (s == 1) ? 1 : (s == 3) ? 2 : (s == 4) ? 3 : ((s & 1) && s >= 5 && s <= 11) ? (s + 3) / 2 : 0;
                    if (xb) { mbar_expect(sb + B_XFULL + 8 * xb, 16384); tma2(sb + OFF_X + xb * 16384, &maps.x, 64 * xb, r * 128, sb + B_XFULL + 8 * xb); }
                    if (++slot == 5) { slot = 0; ph ^= 1; }
                }
                for (int s = 0; s < 24; s++) {
                    const uint32_t full = sb + B_FULL + 8 * slot, dst = sb + OFF_RING + slot * 16384;
                    const int k0 = (s & 7) * 64;
                    mbar_wait(sb + B_EMPTY + 8 * slot, ph);
                    mbar_expect(full, 16384);
                    if (s < 8) {
                        if (!MC || rank == 0) tmaw3(dst, &maps.q64, 0, k0, 2 * j, full);
                        if (!MC || rank == 1) tmaw3(dst + 8192, &maps.gu64, 224 * j + 192, k0, 0, full);
                    } else {
                        const int c0 = 224 * j + 64 * (s >> 3);
                        if (!MC || rank == 0) tmaw3(dst, &maps.gu, c0, k0, 0, full);
                        if (!MC || rank == 1) tmaw3(dst + 8192, &maps.gu, c0, k0 + 32, 0, full);
                    }
                    if (++slot == 5) { slot = 0; ph ^= 1; }
                }
                for (int t = 0; t < 21; t++) {
                    const int sl = t & 7;
                    const uint32_t full = sb + B_FULL + 8 * sl, dst = slot_addr(sb, sl);
                    mbar_wait(sb + B_EMPTY + 8 * sl, ((t >> 3) + (sl < 5 ? 1 : 0)) & 1);
                    if (t < 15) {
                        const int p = t / 5, u = t - 5 * p;
                        const int ca = ((j + 2 * p + 1) & 7) * 64, cb = ((j + 2 * p + 2) & 7) * 64;
                        const CUtensorMap* m = (u == 3) ? &maps.wo : &maps.wd;
                        const int row = (u == 3) ? 64 * j : 224 * j + (u == 0 ? 192 : u == 1 ? 0 : u == 2 ? 64 : 128);
                        mbar_expect(full, u == 0 ? 8192 : 16384);
                        if (!MC || rank == 0) { tmaw2(dst, m, ca, row, full); if (u) tmaw2(dst + 4096, m, ca, row + 32, full); }
                        if (!MC || rank == 1) { tmaw2(dst + 8192, m, cb, row, full); if (u) tmaw2(dst + 12288, m, cb, row + 32, full); }
                    } else {
                        const int p = (t - 15) / 3, u = (t - 15) - 3 * p;
                        const int c = ((j + 7 + p) & 7) * 64;
                        const CUtensorMap* m = (u == 2) ? &maps.wo : &maps.wd;
                        const int row = (u == 2) ? 64 * j : 224 * j + 128 * u;
                        const int nb = 4 - u;
                        mbar_expect(full, nb * 4096);
                        for (int b = 0; b < nb; b++)
                            if (!MC || (b & 1) == (int)rank) tmaw2(dst + b * 4096, m, c, row + 32 * b, full);
                    }
                }
            }
        } else if (warp < 11) {
            const int hx = warp - 9;
            const uint32_t* gw = (const uint32_t*)gate_w + (lane & 3);
            {
                float s[4][4];
#pragma unroll
                for (int i = 0; i < 4; i++) { s[i][0] = s[i][1] = s[i][2] = s[i][3] = 0.f; }
                const int rr = (lane & 7) + 8 * ((lane >> 3) & 1);
                const uint32_t xa = sb + OFF_X + (hx * 64 + rr) * 128;
                const uint32_t sw = (lane >> 4) ^ (lane & 7);
#pragma unroll 1
                for (int kb = 0; kb < 8; kb++) {
                    uint32_t b[8];
#pragma unroll
                    for (int i = 0; i < 8; i++) b[i] = __ldg(gw + kb * 32 + i * 4);
                    mbar_wait(sb + B_XFULL + 8 * kb, 0);
#pragma unroll
                    for (int t = 0; t < 4; t++) {
#pragma unroll
                        for (int i = 0; i < 4; i++) {
                            uint32_t a[4];
                            ldsm4(a, xa + kb * 16384 + i * 2048 + ((sw ^ (2 * t)) << 4));
                            mma16816(s[i], a[0], a[1], a[2], a[3], b[2 * t], b[2 * t + 1]);
                        }
                    }
                }
                if ((lane & 3) == 0) {
#pragma unroll
                    for (int i = 0; i < 4; i++) {
                        const uint32_t ga = sb + OFF_G + (hx * 64 + i * 16 + (lane >> 2)) * 4;
                        asm volatile("st.shared.f32 [%0], %1;" :: "r"(ga), "f"(1.f / (1.f + __expf(-s[i][0]))) : "memory");
                        asm volatile("st.shared.f32 [%0], %1;" :: "r"(ga + 32), "f"(1.f / (1.f + __expf(-s[i][2]))) : "memory");
                    }
                }
                __syncwarp();
                if (lane == 0) mbar_arrive(sb + B_GRDY);
            }
            TS(2 + hx, 1);
            float d[2][2][4], z[2][2];
#pragma unroll
            for (int h = 0; h < 2; h++)
#pragma unroll
                for (int n = 0; n < 2; n++) { d[h][n][0] = d[h][n][1] = d[h][n][2] = d[h][n][3] = 0.f; z[h][n] = 0.f; }
            {
                const uint32_t ka = sb + OFF_STG + ((lane & 7) + 8 * ((lane >> 3) & 1)) * 128, ksw = (lane >> 4) ^ (lane & 7);
                const uint32_t va = sb + OFF_STG + 8192 + ((lane & 7) + 8 * (lane >> 4)) * 128, vsw = ((lane >> 3) & 1) ^ (lane & 7);
#pragma unroll 1
                for (int rnd = 0; rnd < 2; rnd++) {
                    mbar_wait(sb + B_STGFULL, rnd);
#pragma unroll
                    for (int sl = 0; sl < 4; sl++) {
#pragma unroll
                        for (int h = 0; h < 2; h++) {
                            uint32_t a[4], b[4];
                            const uint32_t cs = (uint32_t)(4 * hx + 2 * h);
                            ldsm4t(a, va + sl * 2048 + ((vsw ^ cs) << 4));
                            ldsm4t(b, ka + sl * 2048 + ((ksw ^ cs) << 4));
                            mma16816(d[h][0], a[0], a[1], a[2], a[3], b[0], b[1]);
                            mma16816(d[h][1], a[0], a[1], a[2], a[3], b[2], b[3]);
                            z[h][0] += (bf_lo(b[0]) + bf_hi(b[0])) + (bf_lo(b[1]) + bf_hi(b[1]));
                            z[h][1] += (bf_lo(b[2]) + bf_hi(b[2])) + (bf_lo(b[3]) + bf_hi(b[3]));
                        }
                    }
                    __syncwarp();
                    if (rnd == 0 && lane == 0) mbar_arrive(sb + B_STGFREE);
                }
            }
            mbar_wait(sb + B_GRDY, 0);
            uint32_t epoch;
            asm volatile("ld.shared.u32 %0, [%1];" : "=r"(epoch) : "r"(sb + OFF_EPOCH) : "memory");
            float* accp = g_kvacc + (((epoch & 1) * 8 + j) * 4 + 2 * hx) * 272;
#pragma unroll
            for (int h = 0; h < 2; h++) {
#pragma unroll
                for (int n = 0; n < 2; n++) {
                    asm volatile("red.global.add.v4.f32 [%0], {%1,%2,%3,%4};" :: "l"(accp + h * 272 + n * 128 + lane * 4),
                                 "f"(d[h][n][0]), "f"(d[h][n][1]), "f"(d[h][n][2]), "f"(d[h][n][3]) : "memory");
                    float zz = z[h][n];
                    zz += __shfl_xor_sync(0xffffffffu, zz, 1);
                    zz += __shfl_xor_sync(0xffffffffu, zz, 2);
                    if ((lane & 3) == 0) asm volatile("red.global.add.f32 [%0], %1;" :: "l"(accp + h * 272 + 256 + n * 8 + (lane >> 2)), "f"(zz) : "memory");
                }
            }
            __threadfence();
            __syncwarp();
            unsigned* cnt = g_kvcnt + j * 32;
            if (lane == 0) asm volatile("red.release.gpu.global.add.u32 [%0], 1;" :: "l"(cnt) : "memory");
            TS(2 + hx, 2);
            {
                const unsigned target = 32u * (epoch + 1);
                uint32_t it = 0, v;
                do {
                    asm volatile("ld.acquire.gpu.global.u32 %0, [%1];" : "=r"(v) : "l"(cnt) : "memory");
                } while ((int)(v - target) < 0 && ++it < SPIN_GLOBAL);
            }
            TS(2 + hx, 3);
#pragma unroll
            for (int h = 0; h < 2; h++) {
                const float4 d0 = __ldcg((const float4*)(accp + h * 272) + lane);
                const float4 d1 = __ldcg((const float4*)(accp + h * 272 + 128) + lane);
                const float2 z0 = __ldcg((const float2*)(accp + h * 272 + 256) + (lane & 3));
                const float2 z1 = __ldcg((const float2*)(accp + h * 272 + 264) + (lane & 3));
                const uint32_t ka = sb + OFF_STG + (2 * hx + h) * 1024;
                asm volatile("st.shared.v4.u32 [%0], {%1,%2,%3,%4};" :: "r"(ka + lane * 16),
                             "r"(pack2(d0.x, d0.y)), "r"(pack2(d1.x, d1.y)), "r"(pack2(d0.z, d0.w)), "r"(pack2(d1.z, d1.w)) : "memory");
                asm volatile("st.shared.v2.u32 [%0], {%1,%2};" :: "r"(ka + 512 + lane * 8), "r"(pack2(z0.x, z0.y)), "r"(pack2(z1.x, z1.y)) : "memory");
            }
            __syncwarp();
            if (lane == 0) mbar_arrive(sb + B_KVRDY);
            TS(2 + hx, 4);
        } else {
            uint32_t epoch = 0;
            if (lane == 0) {
                asm volatile("ld.relaxed.gpu.global.u32 %0, [%1];" : "=r"(epoch) : "l"(g_epoch + blockIdx.x) : "memory");
                asm volatile("st.shared.u32 [%0], %1;" :: "r"(sb + OFF_EPOCH), "r"(epoch) : "memory");
                mbar_arrive(sb + B_GRDY);
                g_epoch[blockIdx.x] = epoch + 1;
            }
            epoch = __shfl_sync(0xffffffffu, epoch, 0);
            if (r == 0) {
                float4* zp = (float4*)(g_kvacc + (((epoch & 1) ^ 1) * 8 + j) * 4 * 272);
                for (int i = lane; i < 272; i += 32) zp[i] = make_float4(0.f, 0.f, 0.f, 0.f);
            }
            mbar_wait(sb + B_XFULL, 0);
            const int b = blockIdx.x;
            if (lane == 0) l2_prefetch(pf_qkv + b * 12288, 12288);
            if (lane == 1) l2_prefetch(pf_g + b * 14336, 14336);
            if (lane == 2) l2_prefetch(pf_u + b * 14336, 14336);
            mbar_wait(sb + B_XFULL + 8 * 7, 0);
            if (lane == 0) l2_prefetch(pf_d + b * 14336, 14336);
            if (lane == 1) l2_prefetch(pf_o + b * 4096, 4096);
        }
    } else {
        asm volatile("setmaxnreg.inc.sync.aligned.u32 224;");
        const int wg = warp >> 2;
        const bool elect = (tid & 127) == 0;
        float acc[128];
        const uint32_t xlo = ((sb + OFF_X + wg * 8192) >> 4) | LBO1;
        const uint32_t ringlo = (sb + OFF_RING) >> 4;
        int slot = 0, ph = 0, prev = 0;
        auto release = [&](int s) {
            if (elect) {
                mbar_arrive(sb + B_EMPTY + 8 * s);
            }
        };
        auto adv = [&]() { prev = slot; if (++slot == 5) { slot = 0; ph ^= 1; } };

#pragma unroll 1
        for (int kb = 0; kb < 8; kb++) {
            mbar_wait(sb + B_XFULL + 8 * kb, 0);
#pragma unroll
            for (int h = 0; h < 2; h++) {
                mbar_wait(sb + B_FULL + 8 * slot, ph);
                if (PROF && kb == 0 && h == 0 && (warp & 3) == 0) TS(wg, 1);
                const uint32_t blo = (ringlo + slot * 1024) | LBO4K, alo = xlo + kb * 1024 + 4 * h;
                wg_fence();
                wg_ss256<0>(acc, alo, DH128, blo, DH128, (kb | h) != 0);
                wg_ss256<0>(acc, alo + 2, DH128, blo + 128, DH128, 1);
                wg_commit();
                wg_wait<1>();
                if (kb | h) release(prev);
                adv();
            }
        }
        mbar_wait(sb + B_GRDY, 0);
        float g_lo, g_hi;
        uint32_t tag;
        {
            const uint32_t ga = sb + OFF_G + (warp * 16 + (lane >> 2)) * 4;
            asm volatile("ld.shared.f32 %0, [%1];" : "=f"(g_lo) : "r"(ga) : "memory");
            asm volatile("ld.shared.f32 %0, [%1];" : "=f"(g_hi) : "r"(ga + 32) : "memory");
            asm volatile("ld.shared.u32 %0, [%1];" : "=r"(tag) : "r"(sb + OFF_EPOCH) : "memory");
            tag = (tag + 1) & 1;
        }
        const float m_lo = 1.f - g_lo, m_hi = 1.f - g_hi;
        wg_wait<0>();
        pin<0, 128>(acc);
        release(prev);
        if ((warp & 3) == 0) TS(wg, 2);

        uint32_t fh0[16], fh1[16], fh2[16], fh3[8], fo[16];
#define H_EPI(F, N, OG, OU) _Pragma("unroll") for (int i = 0; i < (N); i++) { \
            const float m_ = (i & 1) ? m_hi : m_lo; \
            F[i] = pack2(acc[(OG) + 2 * i] * acc[(OU) + 2 * i] * m_, acc[(OG) + 2 * i + 1] * acc[(OU) + 2 * i + 1] * m_); }
        H_EPI(fh0, 16, 0, 32);

        const uint32_t srow = ((warp & 3) * 16 + (lane & 7) + 8 * ((lane >> 3) & 1)) * 128;
        const uint32_t ssw = (lane >> 4) ^ (lane & 7);

#define G1_STAGE(O, SW, KB, FIRST) do { mbar_wait(sb + B_FULL + 8 * slot, ph); \
            g1_issue<O, SW>(acc, xlo + (KB) * 1024, (ringlo + slot * 1024) | LBO4K, FIRST); } while (0)
#define G1_RETIRE() do { wg_wait<1>(); release(prev); adv(); } while (0)

        G1_STAGE(0, true, 0, 1); adv();
        G1_STAGE(0, true, 1, 0);
        {
            uint32_t pk[16], pv[16];
#pragma unroll
            for (int i = 0; i < 16; i++) {
                pk[i] = pack2(phi(acc[64 + 2 * i]), phi(acc[64 + 2 * i + 1]));
                pv[i] = pack2(acc[96 + 2 * i], acc[96 + 2 * i + 1]);
            }
            if (wg == 0) {
                stash<16>(sb + OFF_STG + srow, ssw, pk); stash<16>(sb + OFF_STG + 8192 + srow, ssw, pv);
                __syncwarp();
                if (lane == 0) mbar_arrive(sb + B_STGFULL);
            }
            G1_RETIRE();
            G1_STAGE(0, true, 2, 0); G1_RETIRE();
            G1_STAGE(0, true, 3, 0);
            if (wg == 1) {
                mbar_wait(sb + B_STGFREE, 0);
                stash<16>(sb + OFF_STG + srow, ssw, pk); stash<16>(sb + OFF_STG + 8192 + srow, ssw, pv);
                __syncwarp();
                if (lane == 0) mbar_arrive(sb + B_STGFULL);
            }
            G1_RETIRE();
        }
#pragma unroll 1
        for (int kb = 4; kb < 8; kb++) { G1_STAGE(0, true, kb, 0); G1_RETIRE(); }
        if ((warp & 3) == 0) TS(wg, 3);

        G1_STAGE(64, false, 0, 1); G1_RETIRE();
        pin<0, 64>(acc);
        G1_STAGE(64, false, 1, 0);
#pragma unroll
        for (int i = 0; i < 16; i++) fo[i] = pack2(phi(acc[2 * i]), phi(acc[2 * i + 1]));
        H_EPI(fh3, 8, 32, 48);
        G1_RETIRE();
#pragma unroll 1
        for (int kb = 2; kb < 8; kb++) { G1_STAGE(64, false, kb, 0); G1_RETIRE(); }
        if ((warp & 3) == 0) TS(wg, 4);

        G1_STAGE(0, false, 0, 1); G1_RETIRE();
        pin<64, 64>(acc);
        G1_STAGE(0, false, 1, 0);
        H_EPI(fh1, 16, 64, 96);
        G1_RETIRE();
#pragma unroll 1
        for (int kb = 2; kb < 6; kb++) { G1_STAGE(0, false, kb, 0); G1_RETIRE(); }
        G1_STAGE(0, false, 6, 0);
        if ((warp & 3) == 0) TS(wg, 5);
        mbar_wait(sb + B_KVRDY, 0);
        if ((warp & 3) == 0) TS(wg, 6);
#pragma unroll
        for (int h = 0; h < 4; h++) {
            uint32_t b0, b1, b2, b3, z0, z1;
            asm volatile("ld.shared.v4.u32 {%0,%1,%2,%3}, [%4];" : "=r"(b0), "=r"(b1), "=r"(b2), "=r"(b3) : "r"(sb + OFF_STG + h * 1024 + lane * 16) : "memory");
            asm volatile("ld.shared.v2.u32 {%0,%1}, [%2];" : "=r"(z0), "=r"(z1) : "r"(sb + OFF_STG + h * 1024 + 512 + lane * 8) : "memory");
            float n0[4] = {0.f, 0.f, 0.f, 0.f}, n1[4] = {0.f, 0.f, 0.f, 0.f}, dn[4] = {0.f, 0.f, 0.f, 0.f};
            mma16816(dn, fo[4 * h], fo[4 * h + 1], fo[4 * h + 2], fo[4 * h + 3], z0, z1);
            mma16816(n0, fo[4 * h], fo[4 * h + 1], fo[4 * h + 2], fo[4 * h + 3], b0, b1);
            mma16816(n1, fo[4 * h], fo[4 * h + 1], fo[4 * h + 2], fo[4 * h + 3], b2, b3);
            const float s_lo = __fdividef(g_lo, dn[0] + 1e-6f), s_hi = __fdividef(g_hi, dn[2] + 1e-6f);
            fo[4 * h] = pack2(n0[0] * s_lo, n0[1] * s_lo); fo[4 * h + 1] = pack2(n0[2] * s_hi, n0[3] * s_hi);
            fo[4 * h + 2] = pack2(n1[0] * s_lo, n1[1] * s_lo); fo[4 * h + 3] = pack2(n1[2] * s_hi, n1[3] * s_hi);
        }
        G1_RETIRE();
        G1_STAGE(0, false, 7, 0); G1_RETIRE();
        if ((warp & 3) == 0) TS(wg, 7);

#define G2_B(T) ((slot_addr(sb, (T) & 7) >> 4))
#define G2_WAIT(T) mbar_wait(sb + B_FULL + 8 * ((T) & 7), ((T) >> 3) & 1)
#define G2_REL(T) do { if ((T) <= 12) release((T) & 7); } while (0)
#define G2_RS(T, F, NK, FIRST) do { G2_WAIT(T); wg_fence(); _Pragma("unroll") for (int k = 0; k < (NK); k++) \
            wg_rs128<64>(acc, F[4 * k], F[4 * k + 1], F[4 * k + 2], F[4 * k + 3], (G2_B(T) | LBO8K) + 128 * k, DH128, (FIRST) ? (k != 0) : 1); wg_commit(); } while (0)
#define G2_SS(T, O, PIECE, NK, FIRST) do { G2_WAIT(T); wg_fence(); _Pragma("unroll") for (int k = 0; k < (NK); k++) \
            wg_ss128<O>(acc, xlo + (PIECE) * 1024 + 2 * k, DH128, (G2_B(T) | LBO8K) + 128 * k, DH128, (FIRST) ? (k != 0) : 1); wg_commit(); } while (0)
#define G2_N64(T, O, PA, PB, NK, FIRST) do { G2_WAIT(T); wg_fence(); _Pragma("unroll") for (int k = 0; k < (NK); k++) \
            wg_ss64<O>(acc, xlo + (k < 4 ? (PA) : (PB)) * 1024 + 2 * (k & 3), DH128, (G2_B(T) | LBO1) + 128 * k, DH128, (FIRST) ? (k != 0) : 1); wg_commit(); } while (0)

        uint4* const pbase = g_part + (size_t)r * 65536 + warp * 128 + lane;
        auto sendp = [&](int d) { return pbase + ((((j + d) & 7) * 8 + j) << 10); };
        auto recvp = [&](int d) { return pbase + ((j * 8 + ((j - d) & 7)) << 10); };
        const uint32_t a2 = sb + OFF_X + wg * 8192 + srow;

        G2_RS(0, fh3, 2, 1);
        wg_wait<1>();
        release(prev); release(5); release(6); release(7);
        pin<0, 64>(acc);
        G2_RS(1, fh0, 4, 0);
        H_EPI(fh2, 16, 0, 32);
        stash<16>(a2, ssw, fh0); stash<8>(a2 + 4 * 16384, ssw, fh3);
        G2_RS(2, fh1, 4, 0);
        stash<16>(a2 + 16384, ssw, fh1); stash<16>(a2 + 2 * 16384, ssw, fh2); stash<16>(a2 + 3 * 16384, ssw, fo);
        asm volatile("fence.proxy.async.shared::cta;" ::: "memory");
        wg_wait<1>(); G2_REL(0); G2_REL(1);
        G2_RS(3, fo, 4, 0); wg_wait<1>(); G2_REL(2);
        G2_RS(4, fh2, 4, 0);
        asm volatile("bar.sync %0, 128;" :: "r"(wg + 1) : "memory");
        wg_wait<1>(); G2_REL(3);
        if ((warp & 3) == 0) TS(wg, 8);
        G2_SS(5, 0, 4, 2, 1); wg_wait<1>(); G2_REL(4);
        pin<64, 64>(acc);
        G2_SS(6, 0, 0, 4, 0);
        send_block<64>(acc, sendp(1), tag); send_block<96>(acc, sendp(2), tag);
        wg_wait<1>(); G2_REL(5);
        G2_SS(7, 0, 1, 4, 0); wg_wait<1>(); G2_REL(6);
        G2_SS(8, 0, 3, 4, 0); wg_wait<1>(); G2_REL(7);
        G2_SS(9, 0, 2, 4, 0); wg_wait<1>(); G2_REL(8);
        if ((warp & 3) == 0) TS(wg, 9);
        float sum[32];
        uint32_t qa[16], qb[16];
        G2_SS(10, 64, 4, 2, 1); wg_wait<1>(); G2_REL(9);
        pin<0, 64>(acc);
        G2_SS(11, 64, 0, 4, 0);
        send_block<0>(acc, sendp(3), tag); send_block<32>(acc, sendp(4), tag);
        recv_issue(qa, recvp(1)); recv_issue(qb, recvp(2));
        wg_wait<1>(); G2_REL(10);
        G2_SS(12, 64, 1, 4, 0); wg_wait<1>(); G2_REL(11);
        G2_SS(13, 64, 3, 4, 0);
        recv_finish<true>(qa, recvp(1), tag, sum); recv_finish<false>(qb, recvp(2), tag, sum);
        recv_issue(qa, recvp(3)); recv_issue(qb, recvp(4));
        wg_wait<1>(); G2_REL(12);
        G2_SS(14, 64, 2, 4, 0);
        if ((warp & 3) == 0) TS(wg, 10);
        G2_N64(15, 0, 0, 1, 8, 1); wg_wait<1>();
        pin<64, 64>(acc);
        G2_N64(16, 0, 2, 4, 6, 0);
        send_block<64>(acc, sendp(5), tag); send_block<96>(acc, sendp(6), tag);
        G2_N64(17, 0, 3, 3, 4, 0);
        recv_finish<false>(qa, recvp(3), tag, sum);
        if ((warp & 3) == 0) TS(wg, 11);
        G2_N64(18, 32, 0, 1, 8, 1); wg_wait<1>();
        pin<0, 32>(acc);
        send_block<0>(acc, sendp(7), tag);
        G2_N64(19, 32, 2, 4, 6, 0);
        recv_finish<false>(qb, recvp(4), tag, sum);
        recv_issue(qa, recvp(5)); recv_issue(qb, recvp(6));
        G2_N64(20, 32, 3, 3, 4, 0);
        uint32_t qc[16];
        recv_issue(qc, recvp(7));
        recv_finish<false>(qa, recvp(5), tag, sum); recv_finish<false>(qb, recvp(6), tag, sum);
        if ((warp & 3) == 0) TS(wg, 12);
        recv_finish<false>(qc, recvp(7), tag, sum);
        if ((warp & 3) == 0) TS(wg, 13);
        wg_wait<0>();
        pin<32, 32>(acc);
        {
            uint32_t f[16];
#pragma unroll
            for (int i = 0; i < 16; i++) f[i] = pack2(acc[32 + 2 * i] + sum[2 * i], acc[32 + 2 * i + 1] + sum[2 * i + 1]);
            const uint32_t slab = sb + OFF_STG + wg * 8192;
            stash<16>(slab + srow, ssw, f);
            __syncwarp();
            __nv_bfloat16* op = out + (size_t)(r * 128 + warp * 16 + (lane >> 3)) * kD + j * 64 + (lane & 7) * 8;
#pragma unroll
            for (int i = 0; i < 4; i++) {
                const int row = i * 4 + (lane >> 3);
                uint4 v;
                asm volatile("ld.shared.v4.u32 {%0,%1,%2,%3}, [%4];" : "=r"(v.x), "=r"(v.y), "=r"(v.z), "=r"(v.w)
                             : "r"(slab + ((warp & 3) * 16 + row) * 128 + (((lane & 7) ^ (row & 7)) << 4)) : "memory");
                *(uint4*)(op + i * 4 * kD) = v;
            }
        }
        if ((warp & 3) == 0) { TS(wg, 14); TSG(wg, 31); }
    }
}

typedef CUresult (*EncodeFn)(CUtensorMap*, CUtensorMapDataType, cuuint32_t, void*, const cuuint64_t*, const cuuint64_t*, const cuuint32_t*,
                             const cuuint32_t*, CUtensorMapInterleave, CUtensorMapSwizzle, CUtensorMapL2promotion, CUtensorMapFloatOOBfill);

static void encode(EncodeFn fn, CUtensorMap* m, int rank, const void* base, uint64_t d0, uint64_t d1, uint64_t d2, uint64_t s1, uint64_t s2,
                   uint32_t b0, uint32_t b1, uint32_t b2, CUtensorMapSwizzle sw) {
    cuuint64_t gd[3] = {d0, d1, d2}, gs[2] = {s1, s2};
    cuuint32_t bd[3] = {b0, b1, b2}, es[3] = {1, 1, 1};
    fn(m, CU_TENSOR_MAP_DATA_TYPE_BFLOAT16, rank, const_cast<void*>(base), gd, gs, bd, es, CU_TENSOR_MAP_INTERLEAVE_NONE, sw,
       CU_TENSOR_MAP_L2_PROMOTION_L2_128B, CU_TENSOR_MAP_FLOAT_OOB_FILL_NONE);
}

extern "C" void kernel_launch(void* const* d_in, const int* in_sizes, int n_in, void* d_out, int out_size) {
    const char* x = (const char*)d_in[0];
    const char* wqkv = (const char*)d_in[1];
    const char* wo = (const char*)d_in[2];
    const char* wg = (const char*)d_in[4];
    const char* wu = (const char*)d_in[5];
    const char* wd = (const char*)d_in[6];
    void* fnp = nullptr;
    cudaDriverEntryPointQueryResult qr;
    cudaGetDriverEntryPoint("cuTensorMapEncodeTiled", &fnp, cudaEnableDefault, &qr);
    EncodeFn fn = (EncodeFn)fnp;
    Maps maps;
    const char* lo = wg < wu ? wg : wu;
    const uint64_t diff = wg < wu ? (uint64_t)(wu - wg) : (uint64_t)(wg - wu);
    encode(fn, &maps.x, 2, x, kD, 2048, 1, kD * 2, 0, 64, 128, 1, CU_TENSOR_MAP_SWIZZLE_128B);
    encode(fn, &maps.gu, 3, lo, kF, kD, 2, kF * 2, diff, 64, 32, 2, CU_TENSOR_MAP_SWIZZLE_128B);
    encode(fn, &maps.kv, 3, wqkv, kD, kD, 3, 3 * kD * 2, kD * 2, 64, 32, 2, CU_TENSOR_MAP_SWIZZLE_128B);
    encode(fn, &maps.q64, 3, wqkv, 32, kD, 48, 3 * kD * 2, 64, 32, 64, 2, CU_TENSOR_MAP_SWIZZLE_64B);
    encode(fn, &maps.gu64, 3, lo, kF, kD, 2, kF * 2, diff, 32, 64, 2, CU_TENSOR_MAP_SWIZZLE_64B);
    encode(fn, &maps.wd, 2, wd, kD, kF, 1, kD * 2, 0, 64, 32, 1, CU_TENSOR_MAP_SWIZZLE_128B);
    encode(fn, &maps.wo, 2, wo, kD, kD, 1, kD * 2, 0, 64, 32, 1, CU_TENSOR_MAP_SWIZZLE_128B);
    cudaFuncSetAttribute(fused_kernel, cudaFuncAttributeMaxDynamicSharedMemorySize, SMEM_BYTES);
    cudaLaunchConfig_t cfg = {};
    cfg.gridDim = dim3(128);
    cfg.blockDim = dim3(384);
    cfg.dynamicSmemBytes = SMEM_BYTES;
    cfg.stream = cudaStreamPerThread;
    cudaLaunchAttribute at[1];
    at[0].id = cudaLaunchAttributeClusterDimension;
    at[0].val.clusterDim.x = 2; at[0].val.clusterDim.y = 1; at[0].val.clusterDim.z = 1;
    cfg.attrs = at;
    cfg.numAttrs = MC ? 1 : 0;
    cudaLaunchKernelEx(&cfg, fused_kernel, maps, (const __nv_bfloat16*)d_in[7], wqkv, wg, wu, wd, wo, (__nv_bfloat16*)d_out);
}
```

```cpp
#include <cuda_runtime.h>
#include <cuda.h>
#include <cuda_bf16.h>
#include <stdint.h>

#define MC 0
#define PROF 0

namespace {

constexpr int kD = 512, kF = 1792;
constexpr uint32_t OFF_X = 0, OFF_STG = 131072, OFF_RING = 147456, OFF_MISC = 229376;
constexpr uint32_t B_FULL = OFF_MISC, B_EMPTY = OFF_MISC + 64, B_XFULL = OFF_MISC + 128;
constexpr uint32_t B_GRDY = OFF_MISC + 192, B_STGFULL = OFF_MISC + 200, B_STGFREE = OFF_MISC + 208, B_KVRDY = OFF_MISC + 216;
constexpr uint32_t OFF_EPOCH = OFF_MISC + 240, OFF_G = OFF_MISC + 256;
constexpr uint32_t SMEM_BYTES = OFF_MISC + 256 + 512;
constexpr uint32_t SPIN_MBAR = 1u << 16, SPIN_GLOBAL = 1u << 14;

struct alignas(64) Maps { CUtensorMap x, gu, kv, q64, gu64, wd, wo; };

}

__device__ uint4 g_part[16 * 8 * 8 * 1024];
__device__ float g_kvacc[2 * 8 * 4 * 272];
__device__ unsigned g_kvcnt[8 * 32];
__device__ unsigned g_epoch[128];
#define TS(role, idx)
#define TSG(role, idx)

namespace {

__device__ __forceinline__ void mbar_init(uint32_t bar, uint32_t cnt) { asm volatile("mbarrier.init.shared::cta.b64 [%0], %1;" :: "r"(bar), "r"(cnt) : "memory"); }
__device__ __forceinline__ void mbar_expect(uint32_t bar, uint32_t bytes) { asm volatile("mbarrier.arrive.expect_tx.shared::cta.b64 _, [%0], %1;" :: "r"(bar), "r"(bytes) : "memory"); }
__device__ __forceinline__ void mbar_arrive(uint32_t bar) { asm volatile("mbarrier.arrive.shared::cta.b64 _, [%0];" :: "r"(bar) : "memory"); }
__device__ __forceinline__ void mbar_arrive_cta(uint32_t bar, uint32_t cta) {
    asm volatile("{\n.reg .b32 ra;\nmapa.shared::cluster.u32 ra, %0, %1;\nmbarrier.arrive.shared::cluster.b64 _, [ra];\n}" :: "r"(bar), "r"(cta) : "memory");
}
__device__ __forceinline__ void mbar_wait(uint32_t bar, uint32_t parity) {
    uint32_t ok, it = 0;
    do {
        asm volatile("{\n.reg .pred p;\nmbarrier.try_wait.parity.shared::cta.b64 p, [%1], %2;\nselp.u32 %0, 1, 0, p;\n}" : "=r"(ok) : "r"(bar), "r"(parity) : "memory");
    } while (!ok && ++it < SPIN_MBAR);
}
__device__ __forceinline__ void tma2(uint32_t dst, const CUtensorMap* m, int c0, int c1, uint32_t bar) {
    asm volatile("cp.async.bulk.tensor.2d.shared::cluster.global.mbarrier::complete_tx::bytes [%0], [%1, {%3, %4}], [%2];"
        :: "r"(dst), "l"(m), "r"(bar), "r"(c0), "r"(c1) : "memory");
}
__device__ __forceinline__ void tmaw2(uint32_t dst, const CUtensorMap* m, int c0, int c1, uint32_t bar) {
    tma2(dst, m, c0, c1, bar);
}
__device__ __forceinline__ void tmaw3(uint32_t dst, const CUtensorMap* m, int c0, int c1, int c2, uint32_t bar) {
    asm volatile("cp.async.bulk.tensor.3d.shared::cluster.global.mbarrier::complete_tx::bytes [%0], [%1, {%3, %4, %5}], [%2];"
        :: "r"(dst), "l"(m), "r"(bar), "r"(c0), "r"(c1), "r"(c2) : "memory");
}
__device__ __forceinline__ void l2_prefetch(const void* p, uint32_t bytes) { asm volatile("cp.async.bulk.prefetch.L2.global [%0], %1;" :: "l"(p), "r"(bytes) : "memory"); }
__device__ __forceinline__ void wg_fence() { asm volatile("wgmma.fence.sync.aligned;" ::: "memory"); }
__device__ __forceinline__ void wg_commit() { asm volatile("wgmma.commit_group.sync.aligned;" ::: "memory"); }
template <int N> __device__ __forceinline__ void wg_wait() { asm volatile("wgmma.wait_group.sync.aligned %0;" :: "n"(N) : "memory"); }
template <int N> __device__ __forceinline__ void pin(float (&d)[N]) {
#pragma unroll
    for (int i = 0; i < N; i++) asm volatile("" : "+f"(d[i]) :: "memory");
}
__device__ __forceinline__ uint32_t pack2(float lo, float hi) { uint32_t r; asm("cvt.rn.bf16x2.f32 %0, %1, %2;" : "=r"(r) : "f"(hi), "f"(lo)); return r; }
__device__ __forceinline__ float phi(float t) { return (t > 0.f ? t + 1.f : __expf(t)) + 1e-6f; }
__device__ __forceinline__ void stsm4(uint32_t a, uint32_t r0, uint32_t r1, uint32_t r2, uint32_t r3) {
    asm volatile("stmatrix.sync.aligned.m8n8.x4.shared.b16 [%0], {%1,%2,%3,%4};" :: "r"(a), "r"(r0), "r"(r1), "r"(r2), "r"(r3) : "memory");
}
__device__ __forceinline__ void ldsm4(uint32_t (&r)[4], uint32_t a) {
    asm volatile("ldmatrix.sync.aligned.m8n8.x4.shared.b16 {%0,%1,%2,%3}, [%4];" : "=r"(r[0]), "=r"(r[1]), "=r"(r[2]), "=r"(r[3]) : "r"(a) : "memory");
}
__device__ __forceinline__ void ldsm4t(uint32_t (&r)[4], uint32_t a) {
    asm volatile("ldmatrix.sync.aligned.m8n8.x4.trans.shared.b16 {%0,%1,%2,%3}, [%4];" : "=r"(r[0]), "=r"(r[1]), "=r"(r[2]), "=r"(r[3]) : "r"(a) : "memory");
}
__device__ __forceinline__ void mma16816(float (&c)[4], uint32_t a0, uint32_t a1, uint32_t a2, uint32_t a3, uint32_t b0, uint32_t b1) {
    asm volatile("mma.sync.aligned.m16n8k16.row.col.f32.bf16.bf16.f32 {%0,%1,%2,%3}, {%4,%5,%6,%7}, {%8,%9}, {%0,%1,%2,%3};"
        : "+f"(c[0]), "+f"(c[1]), "+f"(c[2]), "+f"(c[3]) : "r"(a0), "r"(a1), "r"(a2), "r"(a3), "r"(b0), "r"(b1));
}
__device__ __forceinline__ float bf_lo(uint32_t w) { return __uint_as_float(w << 16); }
__device__ __forceinline__ float bf_hi(uint32_t w) { return __uint_as_float(w & 0xffff0000u); }
__device__ __forceinline__ void st_pkt(uint4* p, uint32_t w0, uint32_t w1, uint32_t w2, uint32_t w3) {
    asm volatile("{\n.reg .b64 lo, hi;\n.reg .b128 v;\nmov.b64 lo, {%1, %2};\nmov.b64 hi, {%3, %4};\nmov.b128 v, {lo, hi};\nst.relaxed.gpu.global.b128 [%0], v;\n}"
        :: "l"(p), "r"(w0), "r"(w1), "r"(w2), "r"(w3) : "memory");
}
__device__ __forceinline__ void ld_pkt(const uint4* p, uint32_t& w0, uint32_t& w1, uint32_t& w2, uint32_t& w3) {
    asm volatile("{\n.reg .b64 lo, hi;\n.reg .b128 v;\nld.relaxed.gpu.global.b128 v, [%4];\nmov.b128 {lo, hi}, v;\nmov.b64 {%0, %1}, lo;\nmov.b64 {%2, %3}, hi;\n}"
        : "=r"(w0), "=r"(w1), "=r"(w2), "=r"(w3) : "l"(p) : "memory");
}

__device__ __forceinline__ void wg_ss256(float (&d)[128], uint32_t alo, uint32_t ahi, uint32_t blo, uint32_t bhi) {
    asm volatile("{\n.reg .b64 da, db;\nmov.b64 da, {%128, %129};\nmov.b64 db, {%130, %131};\n"
        "wgmma.mma_async.sync.aligned.m64n256k16.f32.bf16.bf16 {%0,%1,%2,%3,%4,%5,%6,%7,%8,%9,%10,%11,%12,%13,%14,%15,%16,%17,%18,%19,%20,%21,%22,%23,%24,%25,%26,%27,%28,%29,%30,%31,%32,%33,%34,%35,%36,%37,%38,%39,%40,%41,%42,%43,%44,%45,%46,%47,%48,%49,%50,%51,%52,%53,%54,%55,%56,%57,%58,%59,%60,%61,%62,%63,%64,%65,%66,%67,%68,%69,%70,%71,%72,%73,%74,%75,%76,%77,%78,%79,%80,%81,%82,%83,%84,%85,%86,%87,%88,%89,%90,%91,%92,%93,%94,%95,%96,%97,%98,%99,%100,%101,%102,%103,%104,%105,%106,%107,%108,%109,%110,%111,%112,%113,%114,%115,%116,%117,%118,%119,%120,%121,%122,%123,%124,%125,%126,%127}, da, db, 1, 1, 1, 0, 1;\n}\n"
        : "+f"(d[0]),"+f"(d[1]),"+f"(d[2]),"+f"(d[3]),"+f"(d[4]),"+f"(d[5]),"+f"(d[6]),"+f"(d[7]),"+f"(d[8]),"+f"(d[9]),"+f"(d[10]),"+f"(d[11]),"+f"(d[12]),"+f"(d[13]),"+f"(d[14]),"+f"(d[15]),"+f"(d[16]),"+f"(d[17]),"+f"(d[18]),"+f"(d[19]),"+f"(d[20]),"+f"(d[21]),"+f"(d[22]),"+f"(d[23]),"+f"(d[24]),"+f"(d[25]),"+f"(d[26]),"+f"(d[27]),"+f"(d[28]),"+f"(d[29]),"+f"(d[30]),"+f"(d[31]),"+f"(d[32]),"+f"(d[33]),"+f"(d[34]),"+f"(d[35]),"+f"(d[36]),"+f"(d[37]),"+f"(d[38]),"+f"(d[39]),"+f"(d[40]),"+f"(d[41]),"+f"(d[42]),"+f"(d[43]),"+f"(d[44]),"+f"(d[45]),"+f"(d[46]),"+f"(d[47]),"+f"(d[48]),"+f"(d[49]),"+f"(d[50]),"+f"(d[51]),"+f"(d[52]),"+f"(d[53]),"+f"(d[54]),"+f"(d[55]),"+f"(d[56]),"+f"(d[57]),"+f"(d[58]),"+f"(d[59]),"+f"(d[60]),"+f"(d[61]),"+f"(d[62]),"+f"(d[63]),"+f"(d[64]),"+f"(d[65]),"+f"(d[66]),"+f"(d[67]),"+f"(d[68]),"+f"(d[69]),"+f"(d[70]),"+f"(d[71]),"+f"(d[72]),"+f"(d[73]),"+f"(d[74]),"+f"(d[75]),"+f"(d[76]),"+f"(d[77]),"+f"(d[78]),"+f"(d[79]),"+f"(d[80]),"+f"(d[81]),"+f"(d[82]),"+f"(d[83]),"+f"(d[84]),"+f"(d[85]),"+f"(d[86]),"+f"(d[87]),"+f"(d[88]),"+f"(d[89]),"+f"(d[90]),"+f"(d[91]),"+f"(d[92]),"+f"(d[93]),"+f"(d[94]),"+f"(d[95]),"+f"(d[96]),"+f"(d[97]),"+f"(d[98]),"+f"(d[99]),"+f"(d[100]),"+f"(d[101]),"+f"(d[102]),"+f"(d[103]),"+f"(d[104]),"+f"(d[105]),"+f"(d[106]),"+f"(d[107]),"+f"(d[108]),"+f"(d[109]),"+f"(d[110]),"+f"(d[111]),"+f"(d[112]),"+f"(d[113]),"+f"(d[114]),"+f"(d[115]),"+f"(d[116]),"+f"(d[117]),"+f"(d[118]),"+f"(d[119]),"+f"(d[120]),"+f"(d[121]),"+f"(d[122]),"+f"(d[123]),"+f"(d[124]),"+f"(d[125]),"+f"(d[126]),"+f"(d[127])
        : "r"(alo), "r"(ahi), "r"(blo), "r"(bhi));
}
__device__ __forceinline__ void wg_ss256_z(float (&d)[128], uint32_t alo, uint32_t ahi, uint32_t blo, uint32_t bhi) {
    asm volatile("{\n.reg .b64 da, db;\nmov.b64 da, {%128, %129};\nmov.b64 db, {%130, %131};\n"
        "wgmma.mma_async.sync.aligned.m64n256k16.f32.bf16.bf16 {%0,%1,%2,%3,%4,%5,%6,%7,%8,%9,%10,%11,%12,%13,%14,%15,%16,%17,%18,%19,%20,%21,%22,%23,%24,%25,%26,%27,%28,%29,%30,%31,%32,%33,%34,%35,%36,%37,%38,%39,%40,%41,%42,%43,%44,%45,%46,%47,%48,%49,%50,%51,%52,%53,%54,%55,%56,%57,%58,%59,%60,%61,%62,%63,%64,%65,%66,%67,%68,%69,%70,%71,%72,%73,%74,%75,%76,%77,%78,%79,%80,%81,%82,%83,%84,%85,%86,%87,%88,%89,%90,%91,%92,%93,%94,%95,%96,%97,%98,%99,%100,%101,%102,%103,%104,%105,%106,%107,%108,%109,%110,%111,%112,%113,%114,%115,%116,%117,%118,%119,%120,%121,%122,%123,%124,%125,%126,%127}, da, db, 0, 1, 1, 0, 1;\n}\n"
        : "=f"(d[0]),"=f"(d[1]),"=f"(d[2]),"=f"(d[3]),"=f"(d[4]),"=f"(d[5]),"=f"(d[6]),"=f"(d[7]),"=f"(d[8]),"=f"(d[9]),"=f"(d[10]),"=f"(d[11]),"=f"(d[12]),"=f"(d[13]),"=f"(d[14]),"=f"(d[15]),"=f"(d[16]),"=f"(d[17]),"=f"(d[18]),"=f"(d[19]),"=f"(d[20]),"=f"(d[21]),"=f"(d[22]),"=f"(d[23]),"=f"(d[24]),"=f"(d[25]),"=f"(d[26]),"=f"(d[27]),"=f"(d[28]),"=f"(d[29]),"=f"(d[30]),"=f"(d[31]),"=f"(d[32]),"=f"(d[33]),"=f"(d[34]),"=f"(d[35]),"=f"(d[36]),"=f"(d[37]),"=f"(d[38]),"=f"(d[39]),"=f"(d[40]),"=f"(d[41]),"=f"(d[42]),"=f"(d[43]),"=f"(d[44]),"=f"(d[45]),"=f"(d[46]),"=f"(d[47]),"=f"(d[48]),"=f"(d[49]),"=f"(d[50]),"=f"(d[51]),"=f"(d[52]),"=f"(d[53]),"=f"(d[54]),"=f"(d[55]),"=f"(d[56]),"=f"(d[57]),"=f"(d[58]),"=f"(d[59]),"=f"(d[60]),"=f"(d[61]),"=f"(d[62]),"=f"(d[63]),"=f"(d[64]),"=f"(d[65]),"=f"(d[66]),"=f"(d[67]),"=f"(d[68]),"=f"(d[69]),"=f"(d[70]),"=f"(d[71]),"=f"(d[72]),"=f"(d[73]),"=f"(d[74]),"=f"(d[75]),"=f"(d[76]),"=f"(d[77]),"=f"(d[78]),"=f"(d[79]),"=f"(d[80]),"=f"(d[81]),"=f"(d[82]),"=f"(d[83]),"=f"(d[84]),"=f"(d[85]),"=f"(d[86]),"=f"(d[87]),"=f"(d[88]),"=f"(d[89]),"=f"(d[90]),"=f"(d[91]),"=f"(d[92]),"=f"(d[93]),"=f"(d[94]),"=f"(d[95]),"=f"(d[96]),"=f"(d[97]),"=f"(d[98]),"=f"(d[99]),"=f"(d[100]),"=f"(d[101]),"=f"(d[102]),"=f"(d[103]),"=f"(d[104]),"=f"(d[105]),"=f"(d[106]),"=f"(d[107]),"=f"(d[108]),"=f"(d[109]),"=f"(d[110]),"=f"(d[111]),"=f"(d[112]),"=f"(d[113]),"=f"(d[114]),"=f"(d[115]),"=f"(d[116]),"=f"(d[117]),"=f"(d[118]),"=f"(d[119]),"=f"(d[120]),"=f"(d[121]),"=f"(d[122]),"=f"(d[123]),"=f"(d[124]),"=f"(d[125]),"=f"(d[126]),"=f"(d[127])
        : "r"(alo), "r"(ahi), "r"(blo), "r"(bhi));
}
__device__ __forceinline__ void wg_ss128(float (&d)[64], uint32_t alo, uint32_t ahi, uint32_t blo, uint32_t bhi) {
    asm volatile("{\n.reg .b64 da, db;\nmov.b64 da, {%64, %65};\nmov.b64 db, {%66, %67};\n"
        "wgmma.mma_async.sync.aligned.m64n128k16.f32.bf16.bf16 {%0,%1,%2,%3,%4,%5,%6,%7,%8,%9,%10,%11,%12,%13,%14,%15,%16,%17,%18,%19,%20,%21,%22,%23,%24,%25,%26,%27,%28,%29,%30,%31,%32,%33,%34,%35,%36,%37,%38,%39,%40,%41,%42,%43,%44,%45,%46,%47,%48,%49,%50,%51,%52,%53,%54,%55,%56,%57,%58,%59,%60,%61,%62,%63}, da, db, 1, 1, 1, 0, 1;\n}\n"
        : "+f"(d[0]),"+f"(d[1]),"+f"(d[2]),"+f"(d[3]),"+f"(d[4]),"+f"(d[5]),"+f"(d[6]),"+f"(d[7]),"+f"(d[8]),"+f"(d[9]),"+f"(d[10]),"+f"(d[11]),"+f"(d[12]),"+f"(d[13]),"+f"(d[14]),"+f"(d[15]),"+f"(d[16]),"+f"(d[17]),"+f"(d[18]),"+f"(d[19]),"+f"(d[20]),"+f"(d[21]),"+f"(d[22]),"+f"(d[23]),"+f"(d[24]),"+f"(d[25]),"+f"(d[26]),"+f"(d[27]),"+f"(d[28]),"+f"(d[29]),"+f"(d[30]),"+f"(d[31]),"+f"(d[32]),"+f"(d[33]),"+f"(d[34]),"+f"(d[35]),"+f"(d[36]),"+f"(d[37]),"+f"(d[38]),"+f"(d[39]),"+f"(d[40]),"+f"(d[41]),"+f"(d[42]),"+f"(d[43]),"+f"(d[44]),"+f"(d[45]),"+f"(d[46]),"+f"(d[47]),"+f"(d[48]),"+f"(d[49]),"+f"(d[50]),"+f"(d[51]),"+f"(d[52]),"+f"(d[53]),"+f"(d[54]),"+f"(d[55]),"+f"(d[56]),"+f"(d[57]),"+f"(d[58]),"+f"(d[59]),"+f"(d[60]),"+f"(d[61]),"+f"(d[62]),"+f"(d[63])
        : "r"(alo), "r"(ahi), "r"(blo), "r"(bhi));
}
__device__ __forceinline__ void wg_ss128_z(float (&d)[64], uint32_t alo, uint32_t ahi, uint32_t blo, uint32_t bhi) {
    asm volatile("{\n.reg .b64 da, db;\nmov.b64 da, {%64, %65};\nmov.b64 db, {%66, %67};\n"
        "wgmma.mma_async.sync.aligned.m64n128k16.f32.bf16.bf16 {%0,%1,%2,%3,%4,%5,%6,%7,%8,%9,%10,%11,%12,%13,%14,%15,%16,%17,%18,%19,%20,%21,%22,%23,%24,%25,%26,%27,%28,%29,%30,%31,%32,%33,%34,%35,%36,%37,%38,%39,%40,%41,%42,%43,%44,%45,%46,%47,%48,%49,%50,%51,%52,%53,%54,%55,%56,%57,%58,%59,%60,%61,%62,%63}, da, db, 0, 1, 1, 0, 1;\n}\n"
        : "=f"(d[0]),"=f"(d[1]),"=f"(d[2]),"=f"(d[3]),"=f"(d[4]),"=f"(d[5]),"=f"(d[6]),"=f"(d[7]),"=f"(d[8]),"=f"(d[9]),"=f"(d[10]),"=f"(d[11]),"=f"(d[12]),"=f"(d[13]),"=f"(d[14]),"=f"(d[15]),"=f"(d[16]),"=f"(d[17]),"=f"(d[18]),"=f"(d[19]),"=f"(d[20]),"=f"(d[21]),"=f"(d[22]),"=f"(d[23]),"=f"(d[24]),"=f"(d[25]),"=f"(d[26]),"=f"(d[27]),"=f"(d[28]),"=f"(d[29]),"=f"(d[30]),"=f"(d[31]),"=f"(d[32]),"=f"(d[33]),"=f"(d[34]),"=f"(d[35]),"=f"(d[36]),"=f"(d[37]),"=f"(d[38]),"=f"(d[39]),"=f"(d[40]),"=f"(d[41]),"=f"(d[42]),"=f"(d[43]),"=f"(d[44]),"=f"(d[45]),"=f"(d[46]),"=f"(d[47]),"=f"(d[48]),"=f"(d[49]),"=f"(d[50]),"=f"(d[51]),"=f"(d[52]),"=f"(d[53]),"=f"(d[54]),"=f"(d[55]),"=f"(d[56]),"=f"(d[57]),"=f"(d[58]),"=f"(d[59]),"=f"(d[60]),"=f"(d[61]),"=f"(d[62]),"=f"(d[63])
        : "r"(alo), "r"(ahi), "r"(blo), "r"(bhi));
}
__device__ __forceinline__ void wg_ss64(float (&d)[32], uint32_t alo, uint32_t ahi, uint32_t blo, uint32_t bhi) {
    asm volatile("{\n.reg .b64 da, db;\nmov.b64 da, {%32, %33};\nmov.b64 db, {%34, %35};\n"
        "wgmma.mma_async.sync.aligned.m64n64k16.f32.bf16.bf16 {%0,%1,%2,%3,%4,%5,%6,%7,%8,%9,%10,%11,%12,%13,%14,%15,%16,%17,%18,%19,%20,%21,%22,%23,%24,%25,%26,%27,%28,%29,%30,%31}, da, db, 1, 1, 1, 0, 1;\n}\n"
        : "+f"(d[0]),"+f"(d[1]),"+f"(d[2]),"+f"(d[3]),"+f"(d[4]),"+f"(d[5]),"+f"(d[6]),"+f"(d[7]),"+f"(d[8]),"+f"(d[9]),"+f"(d[10]),"+f"(d[11]),"+f"(d[12]),"+f"(d[13]),"+f"(d[14]),"+f"(d[15]),"+f"(d[16]),"+f"(d[17]),"+f"(d[18]),"+f"(d[19]),"+f"(d[20]),"+f"(d[21]),"+f"(d[22]),"+f"(d[23]),"+f"(d[24]),"+f"(d[25]),"+f"(d[26]),"+f"(d[27]),"+f"(d[28]),"+f"(d[29]),"+f"(d[30]),"+f"(d[31])
        : "r"(alo), "r"(ahi), "r"(blo), "r"(bhi));
}
__device__ __forceinline__ void wg_ss64_z(float (&d)[32], uint32_t alo, uint32_t ahi, uint32_t blo, uint32_t bhi) {
    asm volatile("{\n.reg .b64 da, db;\nmov.b64 da, {%32, %33};\nmov.b64 db, {%34, %35};\n"
        "wgmma.mma_async.sync.aligned.m64n64k16.f32.bf16.bf16 {%0,%1,%2,%3,%4,%5,%6,%7,%8,%9,%10,%11,%12,%13,%14,%15,%16,%17,%18,%19,%20,%21,%22,%23,%24,%25,%26,%27,%28,%29,%30,%31}, da, db, 0, 1, 1, 0, 1;\n}\n"
        : "=f"(d[0]),"=f"(d[1]),"=f"(d[2]),"=f"(d[3]),"=f"(d[4]),"=f"(d[5]),"=f"(d[6]),"=f"(d[7]),"=f"(d[8]),"=f"(d[9]),"=f"(d[10]),"=f"(d[11]),"=f"(d[12]),"=f"(d[13]),"=f"(d[14]),"=f"(d[15]),"=f"(d[16]),"=f"(d[17]),"=f"(d[18]),"=f"(d[19]),"=f"(d[20]),"=f"(d[21]),"=f"(d[22]),"=f"(d[23]),"=f"(d[24]),"=f"(d[25]),"=f"(d[26]),"=f"(d[27]),"=f"(d[28]),"=f"(d[29]),"=f"(d[30]),"=f"(d[31])
        : "r"(alo), "r"(ahi), "r"(blo), "r"(bhi));
}

constexpr uint32_t DH128 = 64u | 0x40000000u;
constexpr uint32_t DH64 = 32u | 0x80000000u;
constexpr uint32_t LBO4K = (4096u >> 4) << 16, LBO8K = (8192u >> 4) << 16, LBO1 = 1u << 16;

__device__ __forceinline__ uint32_t slot_addr(uint32_t sb, int slot) { return sb + (slot < 5 ? OFF_RING + slot * 16384 : OFF_X + slot * 16384); }

template <bool SW64, bool FIRST> __device__ __forceinline__ void g1_issue(float (&acc)[64], uint32_t alo, uint32_t blo) {
    wg_fence();
#pragma unroll
    for (int k = 0; k < 4; k++) {
        if (FIRST && k == 0) wg_ss128_z(acc, alo, DH128, blo, SW64 ? DH64 : DH128);
        else wg_ss128(acc, alo + 2 * k, DH128, blo + (SW64 ? 64 * k : (k >> 1) * 512 + (k & 1) * 128), SW64 ? DH64 : DH128);
    }
    wg_commit();
}

template <int N> __device__ __forceinline__ void stash(uint32_t base, uint32_t sw, const uint32_t (&f)[N]) {
#pragma unroll
    for (int t = 0; t < N / 4; t++) stsm4(base + ((sw ^ (2 * t)) << 4), f[4 * t], f[4 * t + 1], f[4 * t + 2], f[4 * t + 3]);
}

template <int O, int N> __device__ __forceinline__ void send_block(const float (&acc)[N], uint4* p, uint32_t tag) {
#pragma unroll
    for (int v = 0; v < 4; v++) {
        uint32_t w0 = pack2(acc[O + 8 * v], acc[O + 8 * v + 1]);
        w0 = (w0 & ~1u) | tag;
        st_pkt(p + v * 32, w0, pack2(acc[O + 8 * v + 2], acc[O + 8 * v + 3]), pack2(acc[O + 8 * v + 4], acc[O + 8 * v + 5]), pack2(acc[O + 8 * v + 6], acc[O + 8 * v + 7]));
    }
}
__device__ __forceinline__ void recv_issue(uint32_t (&q)[16], const uint4* p) {
#pragma unroll
    for (int v = 0; v < 4; v++) ld_pkt(p + v * 32, q[4 * v], q[4 * v + 1], q[4 * v + 2], q[4 * v + 3]);
}
template <bool FIRST> __device__ __forceinline__ void recv_finish(uint32_t (&q)[16], const uint4* p, uint32_t tag, float (&sum)[32]) {
    uint32_t it = 0;
    while (true) {
        bool ok = (((q[0] ^ tag) | (q[4] ^ tag) | (q[8] ^ tag) | (q[12] ^ tag)) & 1u) == 0;
        if (__all_sync(0xffffffffu, ok) || ++it > SPIN_GLOBAL) break;
        recv_issue(q, p);
    }
#pragma unroll
    for (int i = 0; i < 16; i++) {
        if (FIRST) { sum[2 * i] = bf_lo(q[i]); sum[2 * i + 1] = bf_hi(q[i]); }
        else { sum[2 * i] += bf_lo(q[i]); sum[2 * i + 1] += bf_hi(q[i]); }
    }
}

}

__global__ void __launch_bounds__(384, 1)
fused_kernel(const __grid_constant__ Maps maps, const __nv_bfloat16* __restrict__ gate_w,
             const char* __restrict__ pf_qkv, const char* __restrict__ pf_g, const char* __restrict__ pf_u,
             const char* __restrict__ pf_d, const char* __restrict__ pf_o, __nv_bfloat16* __restrict__ out) {
    extern __shared__ __align__(1024) uint8_t smem_raw[];
    const uint32_t sb = (uint32_t)__cvta_generic_to_shared(smem_raw);
    const int tid = threadIdx.x, lane = tid & 31;
    const int warp = __shfl_sync(0xffffffffu, tid >> 5, 0);
    const int j = (blockIdx.x >> 1) & 7;
    const int r = ((blockIdx.x >> 4) << 1) | (blockIdx.x & 1);
    const uint32_t rank = blockIdx.x & 1;

    if (warp == 0) { TSG(0, 30); TS(0, 0); }
    if (warp == 9 && lane < 7) asm volatile("prefetch.tensormap [%0];" :: "l"(&maps.x + lane) : "memory");
    if (tid == 256) {
        for (int i = 0; i < 8; i++) { mbar_init(sb + B_FULL + 8 * i, 1); mbar_init(sb + B_EMPTY + 8 * i, MC ? 4 : 2); mbar_init(sb + B_XFULL + 8 * i, 1); }
        mbar_init(sb + B_GRDY, 3); mbar_init(sb + B_STGFULL, 4); mbar_init(sb + B_STGFREE, 2); mbar_init(sb + B_KVRDY, 2);
        asm volatile("fence.mbarrier_init.release.cluster;" ::: "memory");
        asm volatile("fence.proxy.async.shared::cta;" ::: "memory");
        mbar_expect(sb + B_XFULL, 16384);
        tma2(sb + OFF_X, &maps.x, 0, r * 128, sb + B_XFULL);
    }
    __syncthreads();

    if (warp >= 8) {
        asm volatile("setmaxnreg.dec.sync.aligned.u32 56;");
        if (warp == 8) {
            if (lane == 0) {
                int slot = 0, ph = 1;
                for (int s = 0; s < 16; s++) {
                    const uint32_t full = sb + B_FULL + 8 * slot, dst = sb + OFF_RING + slot * 16384;
                    mbar_wait(sb + B_EMPTY + 8 * slot, ph);
                    mbar_expect(full, 16384);
                    if (!MC || rank == 0) tmaw3(dst, &maps.gu, 224 * j, 32 * s, 0, full);
                    if (!MC || rank == 1) tmaw3(dst + 8192, &maps.kv, 64 * j, 32 * s, 1, full);
                    int xb = (s == 1) ? 1 : (s == 3) ? 2 : (s == 4) ? 3 : ((s & 1) && s >= 5 && s <= 11) ? (s + 3) / 2 : 0;
                    if (xb) { mbar_expect(sb + B_XFULL + 8 * xb, 16384); tma2(sb + OFF_X + xb * 16384, &maps.x, 64 * xb, r * 128, sb + B_XFULL + 8 * xb); }
                    if (++slot == 5) { slot = 0; ph ^= 1; }
                }
                for (int s = 0; s < 24; s++) {
                    const uint32_t full = sb + B_FULL + 8 * slot, dst = sb + OFF_RING + slot * 16384;
                    const int k0 = (s & 7) * 64;
                    mbar_wait(sb + B_EMPTY + 8 * slot, ph);
                    mbar_expect(full, 16384);
                    if (s < 8) {
                        if (!MC || rank == 0) tmaw3(dst, &maps.q64, 0, k0, 2 * j, full);
                        if (!MC || rank == 1) tmaw3(dst + 8192, &maps.gu64, 224 * j + 192, k0, 0, full);
                    } else {
                        const int c0 = 224 * j + 64 * (s >> 3);
                        if (!MC || rank == 0) tmaw3(dst, &maps.gu, c0, k0, 0, full);
                        if (!MC || rank == 1) tmaw3(dst + 8192, &maps.gu, c0, k0 + 32, 0, full);
                    }
                    if (++slot == 5) { slot = 0; ph ^= 1; }
                }
                for (int t = 0; t < 21; t++) {
                    const int sl = t & 7;
                    const uint32_t full = sb + B_FULL + 8 * sl, dst = slot_addr(sb, sl);
                    mbar_wait(sb + B_EMPTY + 8 * sl, ((t >> 3) + (sl < 5 ? 1 : 0)) & 1);
                    if (t < 15) {
                        const int p = t / 5, u = t - 5 * p;
                        const int ca = ((j + 2 * p + 1) & 7) * 64, cb = ((j + 2 * p + 2) & 7) * 64;
                        const CUtensorMap* m = (u == 3) ? &maps.wo : &maps.wd;
                        const int row = (u == 3) ? 64 * j : 224 * j + (u == 0 ? 192 : u == 1 ? 0 : u == 2 ? 64 : 128);
                        mbar_expect(full, u == 0 ? 8192 : 16384);
                        if (!MC || rank == 0) { tmaw2(dst, m, ca, row, full); if (u) tmaw2(dst + 4096, m, ca, row + 32, full); }
                        if (!MC || rank == 1) { tmaw2(dst + 8192, m, cb, row, full); if (u) tmaw2(dst + 12288, m, cb, row + 32, full); }
                    } else {
                        const int p = (t - 15) / 3, u = (t - 15) - 3 * p;
                        const int c = ((j + 7 + p) & 7) * 64;
                        const CUtensorMap* m = (u == 2) ? &maps.wo : &maps.wd;
                        const int row = (u == 2) ? 64 * j : 224 * j + 128 * u;
                        const int nb = 4 - u;
                        mbar_expect(full, nb * 4096);
                        for (int b = 0; b < nb; b++)
                            if (!MC || (b & 1) == (int)rank) tmaw2(dst + b * 4096, m, c, row + 32 * b, full);
                    }
                }
            }
        } else if (warp < 11) {
            const int hx = warp - 9;
            const uint32_t* gw = (const uint32_t*)gate_w + (lane & 3);
            {
                float s[4][4];
#pragma unroll
                for (int i = 0; i < 4; i++) { s[i][0] = s[i][1] = s[i][2] = s[i][3] = 0.f; }
                const int rr = (lane & 7) + 8 * ((lane >> 3) & 1);
                const uint32_t xa = sb + OFF_X + (hx * 64 + rr) * 128;
                const uint32_t sw = (lane >> 4) ^ (lane & 7);
#pragma unroll 1
                for (int kb = 0; kb < 8; kb++) {
                    uint32_t b[8];
#pragma unroll
                    for (int i = 0; i < 8; i++) b[i] = __ldg(gw + kb * 32 + i * 4);
                    mbar_wait(sb + B_XFULL + 8 * kb, 0);
#pragma unroll
                    for (int t = 0; t < 4; t++) {
#pragma unroll
                        for (int i = 0; i < 4; i++) {
                            uint32_t a[4];
                            ldsm4(a, xa + kb * 16384 + i * 2048 + ((sw ^ (2 * t)) << 4));
                            mma16816(s[i], a[0], a[1], a[2], a[3], b[2 * t], b[2 * t + 1]);
                        }
                    }
                }
                if ((lane & 3) == 0) {
#pragma unroll
                    for (int i = 0; i < 4; i++) {
                        const uint32_t ga = sb + OFF_G + (hx * 64 + i * 16 + (lane >> 2)) * 4;
                        asm volatile("st.shared.f32 [%0], %1;" :: "r"(ga), "f"(1.f / (1.f + __expf(-s[i][0]))) : "memory");
                        asm volatile("st.shared.f32 [%0], %1;" :: "r"(ga + 32), "f"(1.f / (1.f + __expf(-s[i][2]))) : "memory");
                    }
                }
                __syncwarp();
                if (lane == 0) mbar_arrive(sb + B_GRDY);
            }
            TS(2 + hx, 1);
            float d[2][2][4], z[2][2];
#pragma unroll
            for (int h = 0; h < 2; h++)
#pragma unroll
                for (int n = 0; n < 2; n++) { d[h][n][0] = d[h][n][1] = d[h][n][2] = d[h][n][3] = 0.f; z[h][n] = 0.f; }
            {
                const uint32_t ka = sb + OFF_STG + ((lane & 7) + 8 * ((lane >> 3) & 1)) * 128, ksw = (lane >> 4) ^ (lane & 7);
                const uint32_t va = sb + OFF_STG + 8192 + ((lane & 7) + 8 * (lane >> 4)) * 128, vsw = ((lane >> 3) & 1) ^ (lane & 7);
#pragma unroll 1
                for (int rnd = 0; rnd < 2; rnd++) {
                    mbar_wait(sb + B_STGFULL, rnd);
#pragma unroll
                    for (int sl = 0; sl < 4; sl++) {
#pragma unroll
                        for (int h = 0; h < 2; h++) {
                            uint32_t a[4], b[4];
                            const uint32_t cs = (uint32_t)(4 * hx + 2 * h);
                            ldsm4t(a, va + sl * 2048 + ((vsw ^ cs) << 4));
                            ldsm4t(b, ka + sl * 2048 + ((ksw ^ cs) << 4));
                            mma16816(d[h][0], a[0], a[1], a[2], a[3], b[0], b[1]);
                            mma16816(d[h][1], a[0], a[1], a[2], a[3], b[2], b[3]);
                            z[h][0] += (bf_lo(b[0]) + bf_hi(b[0])) + (bf_lo(b[1]) + bf_hi(b[1]));
                            z[h][1] += (bf_lo(b[2]) + bf_hi(b[2])) + (bf_lo(b[3]) + bf_hi(b[3]));
                        }
                    }
                    __syncwarp();
                    if (rnd == 0 && lane == 0) mbar_arrive(sb + B_STGFREE);
                }
            }
            mbar_wait(sb + B_GRDY, 0);
            uint32_t epoch;
            asm volatile("ld.shared.u32 %0, [%1];" : "=r"(epoch) : "r"(sb + OFF_EPOCH) : "memory");
            float* accp = g_kvacc + (((epoch & 1) * 8 + j) * 4 + 2 * hx) * 272;
#pragma unroll
            for (int h = 0; h < 2; h++) {
#pragma unroll
                for (int n = 0; n < 2; n++) {
                    asm volatile("red.global.add.v4.f32 [%0], {%1,%2,%3,%4};" :: "l"(accp + h * 272 + n * 128 + lane * 4),
                                 "f"(d[h][n][0]), "f"(d[h][n][1]), "f"(d[h][n][2]), "f"(d[h][n][3]) : "memory");
                    float zz = z[h][n];
                    zz += __shfl_xor_sync(0xffffffffu, zz, 1);
                    zz += __shfl_xor_sync(0xffffffffu, zz, 2);
                    if ((lane & 3) == 0) asm volatile("red.global.add.f32 [%0], %1;" :: "l"(accp + h * 272 + 256 + n * 8 + (lane >> 2)), "f"(zz) : "memory");
                }
            }
            __threadfence();
            __syncwarp();
            unsigned* cnt = g_kvcnt + j * 32;
            if (lane == 0) asm volatile("red.release.gpu.global.add.u32 [%0], 1;" :: "l"(cnt) : "memory");
            TS(2 + hx, 2);
            {
                const unsigned target = 32u * (epoch + 1);
                uint32_t it = 0, v;
                do {
                    asm volatile("ld.acquire.gpu.global.u32 %0, [%1];" : "=r"(v) : "l"(cnt) : "memory");
                } while ((int)(v - target) < 0 && ++it < SPIN_GLOBAL);
            }
            TS(2 + hx, 3);
#pragma unroll
            for (int h = 0; h < 2; h++) {
                const float4 d0 = __ldcg((const float4*)(accp + h * 272) + lane);
                const float4 d1 = __ldcg((const float4*)(accp + h * 272 + 128) + lane);
                const float2 z0 = __ldcg((const float2*)(accp + h * 272 + 256) + (lane & 3));
                const float2 z1 = __ldcg((const float2*)(accp + h * 272 + 264) + (lane & 3));
                const uint32_t ka = sb + OFF_STG + (2 * hx + h) * 1024;
                asm volatile("st.shared.v4.u32 [%0], {%1,%2,%3,%4};" :: "r"(ka + lane * 16),
                             "r"(pack2(d0.x, d0.y)), "r"(pack2(d1.x, d1.y)), "r"(pack2(d0.z, d0.w)), "r"(pack2(d1.z, d1.w)) : "memory");
                asm volatile("st.shared.v2.u32 [%0], {%1,%2};" :: "r"(ka + 512 + lane * 8), "r"(pack2(z0.x, z0.y)), "r"(pack2(z1.x, z1.y)) : "memory");
            }
            __syncwarp();
            if (lane == 0) mbar_arrive(sb + B_KVRDY);
            TS(2 + hx, 4);
        } else {
            uint32_t epoch = 0;
            if (lane == 0) {
                asm volatile("ld.relaxed.gpu.global.u32 %0, [%1];" : "=r"(epoch) : "l"(g_epoch + blockIdx.x) : "memory");
                asm volatile("st.shared.u32 [%0], %1;" :: "r"(sb + OFF_EPOCH), "r"(epoch) : "memory");
                mbar_arrive(sb + B_GRDY);
                g_epoch[blockIdx.x] = epoch + 1;
            }
            epoch = __shfl_sync(0xffffffffu, epoch, 0);
            if (r == 0) {
                float4* zp = (float4*)(g_kvacc + (((epoch & 1) ^ 1) * 8 + j) * 4 * 272);
                for (int i = lane; i < 272; i += 32) zp[i] = make_float4(0.f, 0.f, 0.f, 0.f);
            }
            mbar_wait(sb + B_XFULL, 0);
            const int b = blockIdx.x;
            if (lane == 0) l2_prefetch(pf_qkv + b * 12288, 12288);
            if (lane == 1) l2_prefetch(pf_g + b * 14336, 14336);
            if (lane == 2) l2_prefetch(pf_u + b * 14336, 14336);
            mbar_wait(sb + B_XFULL + 8 * 7, 0);
            if (lane == 0) l2_prefetch(pf_d + b * 14336, 14336);
            if (lane == 1) l2_prefetch(pf_o + b * 4096, 4096);
        }
    } else {
        asm volatile("setmaxnreg.inc.sync.aligned.u32 224;");
        const int wg = warp >> 2;
        const bool elect = (tid & 127) == 0;
        float a0[128];
        const uint32_t xlo = ((sb + OFF_X + wg * 8192) >> 4) | LBO1;
        const uint32_t ringlo = (sb + OFF_RING) >> 4;
        int slot = 0, ph = 0, prev = 0;
        auto release = [&](int s) {
            if (elect) {
                mbar_arrive(sb + B_EMPTY + 8 * s);
            }
        };
        auto adv = [&]() { prev = slot; if (++slot == 5) { slot = 0; ph ^= 1; } };

        mbar_wait(sb + B_XFULL, 0);
        mbar_wait(sb + B_FULL, 0);
        if ((warp & 3) == 0) TS(wg, 1);
        wg_fence();
        wg_ss256_z(a0, xlo, DH128, ringlo | LBO4K, DH128);
        wg_ss256(a0, xlo + 2, DH128, (ringlo | LBO4K) + 128, DH128);
        wg_commit();
        adv();
#pragma unroll 1
        for (int s = 1; s < 16; s++) {
            if (!(s & 1)) mbar_wait(sb + B_XFULL + 4 * s, 0);
            mbar_wait(sb + B_FULL + 8 * slot, ph);
            const uint32_t blo = (ringlo + slot * 1024) | LBO4K, alo = xlo + (s >> 1) * 1024 + 4 * (s & 1);
            wg_fence();
            wg_ss256(a0, alo, DH128, blo, DH128);
            wg_ss256(a0, alo + 2, DH128, blo + 128, DH128);
            wg_commit();
            wg_wait<1>();
            release(prev);
            adv();
        }
        mbar_wait(sb + B_GRDY, 0);
        float g_lo, g_hi;
        uint32_t tag;
        {
            const uint32_t ga = sb + OFF_G + (warp * 16 + (lane >> 2)) * 4;
            asm volatile("ld.shared.f32 %0, [%1];" : "=f"(g_lo) : "r"(ga) : "memory");
            asm volatile("ld.shared.f32 %0, [%1];" : "=f"(g_hi) : "r"(ga + 32) : "memory");
            asm volatile("ld.shared.u32 %0, [%1];" : "=r"(tag) : "r"(sb + OFF_EPOCH) : "memory");
            tag = (tag + 1) & 1;
        }
        const float m_lo = 1.f - g_lo, m_hi = 1.f - g_hi;
        wg_wait<0>();
        pin(a0);
        release(prev);
        if ((warp & 3) == 0) TS(wg, 2);

        uint32_t fh0[16], fh1[16], fh2[16], fh3[8], fo[16];
#define H_EPI(acc, F, N, OG, OU) _Pragma("unroll") for (int i = 0; i < (N); i++) { \
            const float m_ = (i & 1) ? m_hi : m_lo; \
            F[i] = pack2(acc[(OG) + 2 * i] * acc[(OU) + 2 * i] * m_, acc[(OG) + 2 * i + 1] * acc[(OU) + 2 * i + 1] * m_); }
        H_EPI(a0, fh0, 16, 0, 32);

        const uint32_t srow = ((warp & 3) * 16 + (lane & 7) + 8 * ((lane >> 3) & 1)) * 128;
        const uint32_t ssw = (lane >> 4) ^ (lane & 7);

#define G1_STAGE(acc, SW, KB, FIRST) do { mbar_wait(sb + B_FULL + 8 * slot, ph); \
            g1_issue<SW, FIRST>(acc, xlo + (KB) * 1024, (ringlo + slot * 1024) | LBO4K); } while (0)
#define G1_RETIRE() do { wg_wait<1>(); release(prev); adv(); } while (0)

        float a1[64], a2_[64], a3[64];
        G1_STAGE(a1, true, 0, 1); adv();
        G1_STAGE(a1, true, 1, 0);
        {
            uint32_t pk[16], pv[16];
#pragma unroll
            for (int i = 0; i < 16; i++) {
                pk[i] = pack2(phi(a0[64 + 2 * i]), phi(a0[64 + 2 * i + 1]));
                pv[i] = pack2(a0[96 + 2 * i], a0[96 + 2 * i + 1]);
            }
            if (wg == 0) {
                stash<16>(sb + OFF_STG + srow, ssw, pk); stash<16>(sb + OFF_STG + 8192 + srow, ssw, pv);
                __syncwarp();
                if (lane == 0) mbar_arrive(sb + B_STGFULL);
            }
            G1_RETIRE();
            G1_STAGE(a1, true, 2, 0); G1_RETIRE();
            G1_STAGE(a1, true, 3, 0);
            if (wg == 1) {
                mbar_wait(sb + B_STGFREE, 0);
                stash<16>(sb + OFF_STG + srow, ssw, pk); stash<16>(sb + OFF_STG + 8192 + srow, ssw, pv);
                __syncwarp();
                if (lane == 0) mbar_arrive(sb + B_STGFULL);
            }
            G1_RETIRE();
        }
#pragma unroll 1
        for (int kb = 4; kb < 8; kb++) { G1_STAGE(a1, true, kb, 0); G1_RETIRE(); }
        if ((warp & 3) == 0) TS(wg, 3);

        G1_STAGE(a2_, false, 0, 1); G1_RETIRE();
        pin(a1);
        G1_STAGE(a2_, false, 1, 0);
#pragma unroll
        for (int i = 0; i < 16; i++) fo[i] = pack2(phi(a1[2 * i]), phi(a1[2 * i + 1]));
        H_EPI(a1, fh3, 8, 32, 48);
        G1_RETIRE();
#pragma unroll 1
        for (int kb = 2; kb < 8; kb++) { G1_STAGE(a2_, false, kb, 0); G1_RETIRE(); }
        if ((warp & 3) == 0) TS(wg, 4);

        const uint32_t a2 = sb + OFF_X + wg * 8192 + srow;
        G1_STAGE(a3, false, 0, 1); G1_RETIRE();
        pin(a2_);
        G1_STAGE(a3, false, 1, 0);
        H_EPI(a2_, fh1, 16, 0, 32);
        G1_RETIRE();
        G1_STAGE(a3, false, 2, 0); stash<16>(a2, ssw, fh0); G1_RETIRE();
        G1_STAGE(a3, false, 3, 0); stash<16>(a2 + 16384, ssw, fh1); G1_RETIRE();
        G1_STAGE(a3, false, 4, 0); G1_RETIRE();
        G1_STAGE(a3, false, 5, 0); G1_RETIRE();
        G1_STAGE(a3, false, 6, 0);
        stash<8>(a2 + 4 * 16384, ssw, fh3);
        if ((warp & 3) == 0) TS(wg, 5);
        mbar_wait(sb + B_KVRDY, 0);
        if ((warp & 3) == 0) TS(wg, 6);
#pragma unroll
        for (int h = 0; h < 4; h++) {
            uint32_t b0, b1, b2, b3, z0, z1;
            asm volatile("ld.shared.v4.u32 {%0,%1,%2,%3}, [%4];" : "=r"(b0), "=r"(b1), "=r"(b2), "=r"(b3) : "r"(sb + OFF_STG + h * 1024 + lane * 16) : "memory");
            asm volatile("ld.shared.v2.u32 {%0,%1}, [%2];" : "=r"(z0), "=r"(z1) : "r"(sb + OFF_STG + h * 1024 + 512 + lane * 8) : "memory");
            float n0[4] = {0.f, 0.f, 0.f, 0.f}, n1[4] = {0.f, 0.f, 0.f, 0.f}, dn[4] = {0.f, 0.f, 0.f, 0.f};
            mma16816(dn, fo[4 * h], fo[4 * h + 1], fo[4 * h + 2], fo[4 * h + 3], z0, z1);
            mma16816(n0, fo[4 * h], fo[4 * h + 1], fo[4 * h + 2], fo[4 * h + 3], b0, b1);
            mma16816(n1, fo[4 * h], fo[4 * h + 1], fo[4 * h + 2], fo[4 * h + 3], b2, b3);
            const float s_lo = __fdividef(g_lo, dn[0] + 1e-6f), s_hi = __fdividef(g_hi, dn[2] + 1e-6f);
            fo[4 * h] = pack2(n0[0] * s_lo, n0[1] * s_lo); fo[4 * h + 1] = pack2(n0[2] * s_hi, n0[3] * s_hi);
            fo[4 * h + 2] = pack2(n1[0] * s_lo, n1[1] * s_lo); fo[4 * h + 3] = pack2(n1[2] * s_hi, n1[3] * s_hi);
        }
        stash<16>(a2 + 3 * 16384, ssw, fo);
        G1_RETIRE();
        G1_STAGE(a3, false, 7, 0);
        asm volatile("fence.proxy.async.shared::cta;" ::: "memory");
        asm volatile("bar.sync %0, 128;" :: "r"(wg + 1) : "memory");
        G1_RETIRE();
        if ((warp & 3) == 0) TS(wg, 7);

#define G2_B(T) ((slot_addr(sb, (T) & 7) >> 4))
#define G2_WAIT(T) mbar_wait(sb + B_FULL + 8 * ((T) & 7), ((T) >> 3) & 1)
#define G2_REL(T) do { if ((T) <= 12) release((T) & 7); } while (0)
#define G2_SS(T, acc, PIECE, NK, FIRST) do { G2_WAIT(T); wg_fence(); _Pragma("unroll") for (int k = 0; k < (NK); k++) { \
            if ((FIRST) && k == 0) wg_ss128_z(acc, xlo + (PIECE) * 1024, DH128, G2_B(T) | LBO8K, DH128); \
            else wg_ss128(acc, xlo + (PIECE) * 1024 + 2 * k, DH128, (G2_B(T) | LBO8K) + 128 * k, DH128); } wg_commit(); } while (0)
#define G2_N64(T, acc, PA, PB, NK, FIRST) do { G2_WAIT(T); wg_fence(); _Pragma("unroll") for (int k = 0; k < (NK); k++) { \
            if ((FIRST) && k == 0) wg_ss64_z(acc, xlo + (PA) * 1024, DH128, G2_B(T) | LBO1, DH128); \
            else wg_ss64(acc, xlo + (k < 4 ? (PA) : (PB)) * 1024 + 2 * (k & 3), DH128, (G2_B(T) | LBO1) + 128 * k, DH128); } wg_commit(); } while (0)

        uint4* const pbase = g_part + (size_t)r * 65536 + warp * 128 + lane;
        auto sendp = [&](int d) { return pbase + ((((j + d) & 7) * 8 + j) << 10); };
        auto recvp = [&](int d) { return pbase + ((j * 8 + ((j - d) & 7)) << 10); };

        float p1[64], p2[64], p3[64], p4[32], p5[32];
        G2_SS(0, p1, 4, 2, 1);
        wg_wait<1>();
        release(prev); release(5); release(6); release(7);
        pin(a3);
        G2_SS(1, p1, 0, 4, 0);
        H_EPI(a3, fh2, 16, 0, 32);
        stash<16>(a2 + 2 * 16384, ssw, fh2);
        wg_wait<1>(); G2_REL(0);
        G2_SS(2, p1, 1, 4, 0);
        asm volatile("fence.proxy.async.shared::cta;" ::: "memory");
        asm volatile("bar.sync %0, 128;" :: "r"(wg + 1) : "memory");
        wg_wait<1>(); G2_REL(1);
        G2_SS(3, p1, 3, 4, 0); wg_wait<1>(); G2_REL(2);
        G2_SS(4, p1, 2, 4, 0); wg_wait<1>(); G2_REL(3);
        if ((warp & 3) == 0) TS(wg, 8);
        G2_SS(5, p2, 4, 2, 1); wg_wait<1>(); G2_REL(4);
        pin(p1);
        G2_SS(6, p2, 0, 4, 0);
        send_block<0>(p1, sendp(1), tag); send_block<32>(p1, sendp(2), tag);
        wg_wait<1>(); G2_REL(5);
        G2_SS(7, p2, 1, 4, 0); wg_wait<1>(); G2_REL(6);
        G2_SS(8, p2, 3, 4, 0); wg_wait<1>(); G2_REL(7);
        G2_SS(9, p2, 2, 4, 0); wg_wait<1>(); G2_REL(8);
        if ((warp & 3) == 0) TS(wg, 9);
        float sum[32];
        uint32_t qa[16], qb[16];
        G2_SS(10, p3, 4, 2, 1); wg_wait<1>(); G2_REL(9);
        pin(p2);
        G2_SS(11, p3, 0, 4, 0);
        send_block<0>(p2, sendp(3), tag); send_block<32>(p2, sendp(4), tag);
        recv_issue(qa, recvp(1)); recv_issue(qb, recvp(2));
        wg_wait<1>(); G2_REL(10);
        G2_SS(12, p3, 1, 4, 0); wg_wait<1>(); G2_REL(11);
        G2_SS(13, p3, 3, 4, 0);
        recv_finish<true>(qa, recvp(1), tag, sum); recv_finish<false>(qb, recvp(2), tag, sum);
        recv_issue(qa, recvp(3)); recv_issue(qb, recvp(4));
        wg_wait<1>(); G2_REL(12);
        G2_SS(14, p3, 2, 4, 0);
        if ((warp & 3) == 0) TS(wg, 10);
        G2_N64(15, p4, 0, 1, 8, 1); wg_wait<1>();
        pin(p3);
        G2_N64(16, p4, 2, 4, 6, 0);
        send_block<0>(p3, sendp(5), tag); send_block<32>(p3, sendp(6), tag);
        G2_N64(17, p4, 3, 3, 4, 0);
        recv_finish<false>(qa, recvp(3), tag, sum);
        if ((warp & 3) == 0) TS(wg, 11);
        G2_N64(18, p5, 0, 1, 8, 1); wg_wait<1>();
        pin(p4);
        send_block<0>(p4, sendp(7), tag);
        G2_N64(19, p5, 2, 4, 6, 0);
        recv_finish<false>(qb, recvp(4), tag, sum);
        recv_issue(qa, recvp(5)); recv_issue(qb, recvp(6));
        G2_N64(20, p5, 3, 3, 4, 0);
        uint32_t qc[16];
        recv_issue(qc, recvp(7));
        recv_finish<false>(qa, recvp(5), tag, sum); recv_finish<false>(qb, recvp(6), tag, sum);
        if ((warp & 3) == 0) TS(wg, 12);
        recv_finish<false>(qc, recvp(7), tag, sum);
        if ((warp & 3) == 0) TS(wg, 13);
        wg_wait<0>();
        pin(p5);
        {
            uint32_t f[16];
#pragma unroll
            for (int i = 0; i < 16; i++) f[i] = pack2(p5[2 * i] + sum[2 * i], p5[2 * i + 1] + sum[2 * i + 1]);
            const uint32_t slab = sb + OFF_STG + wg * 8192;
            stash<16>(slab + srow, ssw, f);
            __syncwarp();
            __nv_bfloat16* op = out + (size_t)(r * 128 + warp * 16 + (lane >> 3)) * kD + j * 64 + (lane & 7) * 8;
#pragma unroll
            for (int i = 0; i < 4; i++) {
                const int row = i * 4 + (lane >> 3);
                uint4 v;
                asm volatile("ld.shared.v4.u32 {%0,%1,%2,%3}, [%4];" : "=r"(v.x), "=r"(v.y), "=r"(v.z), "=r"(v.w)
                             : "r"(slab + ((warp & 3) * 16 + row) * 128 + (((lane & 7) ^ (row & 7)) << 4)) : "memory");
                *(uint4*)(op + i * 4 * kD) = v;
            }
        }
        if ((warp & 3) == 0) { TS(wg, 14); TSG(wg, 31); }
    }
}

typedef CUresult (*EncodeFn)(CUtensorMap*, CUtensorMapDataType, cuuint32_t, void*, const cuuint64_t*, const cuuint64_t*, const cuuint32_t*,
                             const cuuint32_t*, CUtensorMapInterleave, CUtensorMapSwizzle, CUtensorMapL2promotion, CUtensorMapFloatOOBfill);

static void encode(EncodeFn fn, CUtensorMap* m, int rank, const void* base, uint64_t d0, uint64_t d1, uint64_t d2, uint64_t s1, uint64_t s2,
                   uint32_t b0, uint32_t b1, uint32_t b2, CUtensorMapSwizzle sw) {
    cuuint64_t gd[3] = {d0, d1, d2}, gs[2] = {s1, s2};
    cuuint32_t bd[3] = {b0, b1, b2}, es[3] = {1, 1, 1};
    fn(m, CU_TENSOR_MAP_DATA_TYPE_BFLOAT16, rank, const_cast<void*>(base), gd, gs, bd, es, CU_TENSOR_MAP_INTERLEAVE_NONE, sw,
       CU_TENSOR_MAP_L2_PROMOTION_L2_128B, CU_TENSOR_MAP_FLOAT_OOB_FILL_NONE);
}

extern "C" void kernel_launch(void* const* d_in, const int* in_sizes, int n_in, void* d_out, int out_size) {
    const char* x = (const char*)d_in[0];
    const char* wqkv = (const char*)d_in[1];
    const char* wo = (const char*)d_in[2];
    const char* wg = (const char*)d_in[4];
    const char* wu = (const char*)d_in[5];
    const char* wd = (const char*)d_in[6];
    void* fnp = nullptr;
    cudaDriverEntryPointQueryResult qr;
    cudaGetDriverEntryPoint("cuTensorMapEncodeTiled", &fnp, cudaEnableDefault, &qr);
    EncodeFn fn = (EncodeFn)fnp;
    Maps maps;
    const char* lo = wg < wu ? wg : wu;
    const uint64_t diff = wg < wu ? (uint64_t)(wu - wg) : (uint64_t)(wg - wu);
    encode(fn, &maps.x, 2, x, kD, 2048, 1, kD * 2, 0, 64, 128, 1, CU_TENSOR_MAP_SWIZZLE_128B);
    encode(fn, &maps.gu, 3, lo, kF, kD, 2, kF * 2, diff, 64, 32, 2, CU_TENSOR_MAP_SWIZZLE_128B);
    encode(fn, &maps.kv, 3, wqkv, kD, kD, 3, 3 * kD * 2, kD * 2, 64, 32, 2, CU_TENSOR_MAP_SWIZZLE_128B);
    encode(fn, &maps.q64, 3, wqkv, 32, kD, 48, 3 * kD * 2, 64, 32, 64, 2, CU_TENSOR_MAP_SWIZZLE_64B);
    encode(fn, &maps.gu64, 3, lo, kF, kD, 2, kF * 2, diff, 32, 64, 2, CU_TENSOR_MAP_SWIZZLE_64B);
    encode(fn, &maps.wd, 2, wd, kD, kF, 1, kD * 2, 0, 64, 32, 1, CU_TENSOR_MAP_SWIZZLE_128B);
    encode(fn, &maps.wo, 2, wo, kD, kD, 1, kD * 2, 0, 64, 32, 1, CU_TENSOR_MAP_SWIZZLE_128B);
    cudaFuncSetAttribute(fused_kernel, cudaFuncAttributeMaxDynamicSharedMemorySize, SMEM_BYTES);
    cudaLaunchConfig_t cfg = {};
    cfg.gridDim = dim3(128);
    cfg.blockDim = dim3(384);
    cfg.dynamicSmemBytes = SMEM_BYTES;
    cfg.stream = cudaStreamPerThread;
    cudaLaunchAttribute at[1];
    at[0].id = cudaLaunchAttributeClusterDimension;
    at[0].val.clusterDim.x = 2; at[0].val.clusterDim.y = 1; at[0].val.clusterDim.z = 1;
    cfg.attrs = at;
    cfg.numAttrs = MC ? 1 : 0;
    cudaLaunchKernelEx(&cfg, fused_kernel, maps, (const __nv_bfloat16*)d_in[7], wqkv, wg, wu, wd, wo, (__nv_bfloat16*)d_out);
}
```

```cpp
#include <cuda_runtime.h>
#include <cuda.h>
#include <cuda_bf16.h>
#include <stdint.h>

#define MC 0
#define PROF 0

namespace {

constexpr int kD = 512, kF = 1792;
constexpr uint32_t OFF_X = 0, OFF_STG = 131072, OFF_RING = 147456, OFF_MISC = 229376;
constexpr uint32_t B_FULL = OFF_MISC, B_EMPTY = OFF_MISC + 64, B_XFULL = OFF_MISC + 128;
constexpr uint32_t B_GRDY = OFF_MISC + 192, B_STGFULL = OFF_MISC + 200, B_STGFREE = OFF_MISC + 208, B_KVRDY = OFF_MISC + 216;
constexpr uint32_t OFF_EPOCH = OFF_MISC + 240, OFF_G = OFF_MISC + 256;
constexpr uint32_t OFF_KVF = OFF_MISC + 768, OFF_ZF = OFF_KVF + 2048;
constexpr uint32_t SMEM_BYTES = OFF_ZF + 128;
constexpr uint32_t SPIN_MBAR = 1u << 16, SPIN_GLOBAL = 1u << 14;

struct alignas(64) Maps { CUtensorMap x, gu, kv, q64, gu64, wd, wo; };

}

__device__ uint4 g_part[16 * 2 * 4 * 4 * 1024];
__device__ uint4 g_hx[16 * 8 * 5 * 1024];
__device__ float g_kvacc[2 * 8 * 4 * 272];
__device__ unsigned g_kvcnt[8 * 32];
__device__ unsigned g_epoch[128];
#define TS(role, idx)
#define TSG(role, idx)

namespace {

__device__ __forceinline__ void mbar_init(uint32_t bar, uint32_t cnt) { asm volatile("mbarrier.init.shared::cta.b64 [%0], %1;" :: "r"(bar), "r"(cnt) : "memory"); }
__device__ __forceinline__ void mbar_expect(uint32_t bar, uint32_t bytes) { asm volatile("mbarrier.arrive.expect_tx.shared::cta.b64 _, [%0], %1;" :: "r"(bar), "r"(bytes) : "memory"); }
__device__ __forceinline__ void mbar_arrive(uint32_t bar) { asm volatile("mbarrier.arrive.shared::cta.b64 _, [%0];" :: "r"(bar) : "memory"); }
__device__ __forceinline__ void mbar_arrive_cta(uint32_t bar, uint32_t cta) {
    asm volatile("{\n.reg .b32 ra;\nmapa.shared::cluster.u32 ra, %0, %1;\nmbarrier.arrive.shared::cluster.b64 _, [ra];\n}" :: "r"(bar), "r"(cta) : "memory");
}
__device__ __forceinline__ void mbar_wait(uint32_t bar, uint32_t parity) {
    uint32_t ok, it = 0;
    do {
        asm volatile("{\n.reg .pred p;\nmbarrier.try_wait.parity.shared::cta.b64 p, [%1], %2;\nselp.u32 %0, 1, 0, p;\n}" : "=r"(ok) : "r"(bar), "r"(parity) : "memory");
    } while (!ok && ++it < SPIN_MBAR);
}
__device__ __forceinline__ void tma2(uint32_t dst, const CUtensorMap* m, int c0, int c1, uint32_t bar) {
    asm volatile("cp.async.bulk.tensor.2d.shared::cluster.global.mbarrier::complete_tx::bytes [%0], [%1, {%3, %4}], [%2];"
        :: "r"(dst), "l"(m), "r"(bar), "r"(c0), "r"(c1) : "memory");
}
__device__ __forceinline__ void tmaw2(uint32_t dst, const CUtensorMap* m, int c0, int c1, uint32_t bar) {
    tma2(dst, m, c0, c1, bar);
}
__device__ __forceinline__ void tmaw3(uint32_t dst, const CUtensorMap* m, int c0, int c1, int c2, uint32_t bar) {
    asm volatile("cp.async.bulk.tensor.3d.shared::cluster.global.mbarrier::complete_tx::bytes [%0], [%1, {%3, %4, %5}], [%2];"
        :: "r"(dst), "l"(m), "r"(bar), "r"(c0), "r"(c1), "r"(c2) : "memory");
}
__device__ __forceinline__ void l2_prefetch(const void* p, uint32_t bytes) { asm volatile("cp.async.bulk.prefetch.L2.global [%0], %1;" :: "l"(p), "r"(bytes) : "memory"); }
__device__ __forceinline__ void wg_fence() { asm volatile("wgmma.fence.sync.aligned;" ::: "memory"); }
__device__ __forceinline__ void wg_commit() { asm volatile("wgmma.commit_group.sync.aligned;" ::: "memory"); }
template <int N> __device__ __forceinline__ void wg_wait() { asm volatile("wgmma.wait_group.sync.aligned %0;" :: "n"(N) : "memory"); }
template <int N> __device__ __forceinline__ void pin(float (&d)[N]) {
#pragma unroll
    for (int i = 0; i < N; i++) asm volatile("" : "+f"(d[i]) :: "memory");
}
__device__ __forceinline__ uint32_t pack2(float lo, float hi) { uint32_t r; asm("cvt.rn.bf16x2.f32 %0, %1, %2;" : "=r"(r) : "f"(hi), "f"(lo)); return r; }
__device__ __forceinline__ float phi(float t) { return (t > 0.f ? t + 1.f : __expf(t)) + 1e-6f; }
__device__ __forceinline__ void stsm4(uint32_t a, uint32_t r0, uint32_t r1, uint32_t r2, uint32_t r3) {
    asm volatile("stmatrix.sync.aligned.m8n8.x4.shared.b16 [%0], {%1,%2,%3,%4};" :: "r"(a), "r"(r0), "r"(r1), "r"(r2), "r"(r3) : "memory");
}
__device__ __forceinline__ void ldsm4(uint32_t (&r)[4], uint32_t a) {
    asm volatile("ldmatrix.sync.aligned.m8n8.x4.shared.b16 {%0,%1,%2,%3}, [%4];" : "=r"(r[0]), "=r"(r[1]), "=r"(r[2]), "=r"(r[3]) : "r"(a) : "memory");
}
__device__ __forceinline__ void ldsm4t(uint32_t (&r)[4], uint32_t a) {
    asm volatile("ldmatrix.sync.aligned.m8n8.x4.trans.shared.b16 {%0,%1,%2,%3}, [%4];" : "=r"(r[0]), "=r"(r[1]), "=r"(r[2]), "=r"(r[3]) : "r"(a) : "memory");
}
__device__ __forceinline__ void mma16816(float (&c)[4], uint32_t a0, uint32_t a1, uint32_t a2, uint32_t a3, uint32_t b0, uint32_t b1) {
    asm volatile("mma.sync.aligned.m16n8k16.row.col.f32.bf16.bf16.f32 {%0,%1,%2,%3}, {%4,%5,%6,%7}, {%8,%9}, {%0,%1,%2,%3};"
        : "+f"(c[0]), "+f"(c[1]), "+f"(c[2]), "+f"(c[3]) : "r"(a0), "r"(a1), "r"(a2), "r"(a3), "r"(b0), "r"(b1));
}
__device__ __forceinline__ float bf_lo(uint32_t w) { return __uint_as_float(w << 16); }
__device__ __forceinline__ float bf_hi(uint32_t w) { return __uint_as_float(w & 0xffff0000u); }
__device__ __forceinline__ void st_pkt(uint4* p, uint32_t w0, uint32_t w1, uint32_t w2, uint32_t w3) {
    asm volatile("{\n.reg .b64 lo, hi;\n.reg .b128 v;\nmov.b64 lo, {%1, %2};\nmov.b64 hi, {%3, %4};\nmov.b128 v, {lo, hi};\nst.relaxed.gpu.global.b128 [%0], v;\n}"
        :: "l"(p), "r"(w0), "r"(w1), "r"(w2), "r"(w3) : "memory");
}
__device__ __forceinline__ void ld_pkt(const uint4* p, uint32_t& w0, uint32_t& w1, uint32_t& w2, uint32_t& w3) {
    asm volatile("{\n.reg .b64 lo, hi;\n.reg .b128 v;\nld.relaxed.gpu.global.b128 v, [%4];\nmov.b128 {lo, hi}, v;\nmov.b64 {%0, %1}, lo;\nmov.b64 {%2, %3}, hi;\n}"
        : "=r"(w0), "=r"(w1), "=r"(w2), "=r"(w3) : "l"(p) : "memory");
}

__device__ __forceinline__ void wg_ss256(float (&d)[128], uint32_t alo, uint32_t ahi, uint32_t blo, uint32_t bhi) {
    asm volatile("{\n.reg .b64 da, db;\nmov.b64 da, {%128, %129};\nmov.b64 db, {%130, %131};\n"
        "wgmma.mma_async.sync.aligned.m64n256k16.f32.bf16.bf16 {%0,%1,%2,%3,%4,%5,%6,%7,%8,%9,%10,%11,%12,%13,%14,%15,%16,%17,%18,%19,%20,%21,%22,%23,%24,%25,%26,%27,%28,%29,%30,%31,%32,%33,%34,%35,%36,%37,%38,%39,%40,%41,%42,%43,%44,%45,%46,%47,%48,%49,%50,%51,%52,%53,%54,%55,%56,%57,%58,%59,%60,%61,%62,%63,%64,%65,%66,%67,%68,%69,%70,%71,%72,%73,%74,%75,%76,%77,%78,%79,%80,%81,%82,%83,%84,%85,%86,%87,%88,%89,%90,%91,%92,%93,%94,%95,%96,%97,%98,%99,%100,%101,%102,%103,%104,%105,%106,%107,%108,%109,%110,%111,%112,%113,%114,%115,%116,%117,%118,%119,%120,%121,%122,%123,%124,%125,%126,%127}, da, db, 1, 1, 1, 0, 1;\n}\n"
        : "+f"(d[0]),"+f"(d[1]),"+f"(d[2]),"+f"(d[3]),"+f"(d[4]),"+f"(d[5]),"+f"(d[6]),"+f"(d[7]),"+f"(d[8]),"+f"(d[9]),"+f"(d[10]),"+f"(d[11]),"+f"(d[12]),"+f"(d[13]),"+f"(d[14]),"+f"(d[15]),"+f"(d[16]),"+f"(d[17]),"+f"(d[18]),"+f"(d[19]),"+f"(d[20]),"+f"(d[21]),"+f"(d[22]),"+f"(d[23]),"+f"(d[24]),"+f"(d[25]),"+f"(d[26]),"+f"(d[27]),"+f"(d[28]),"+f"(d[29]),"+f"(d[30]),"+f"(d[31]),"+f"(d[32]),"+f"(d[33]),"+f"(d[34]),"+f"(d[35]),"+f"(d[36]),"+f"(d[37]),"+f"(d[38]),"+f"(d[39]),"+f"(d[40]),"+f"(d[41]),"+f"(d[42]),"+f"(d[43]),"+f"(d[44]),"+f"(d[45]),"+f"(d[46]),"+f"(d[47]),"+f"(d[48]),"+f"(d[49]),"+f"(d[50]),"+f"(d[51]),"+f"(d[52]),"+f"(d[53]),"+f"(d[54]),"+f"(d[55]),"+f"(d[56]),"+f"(d[57]),"+f"(d[58]),"+f"(d[59]),"+f"(d[60]),"+f"(d[61]),"+f"(d[62]),"+f"(d[63]),"+f"(d[64]),"+f"(d[65]),"+f"(d[66]),"+f"(d[67]),"+f"(d[68]),"+f"(d[69]),"+f"(d[70]),"+f"(d[71]),"+f"(d[72]),"+f"(d[73]),"+f"(d[74]),"+f"(d[75]),"+f"(d[76]),"+f"(d[77]),"+f"(d[78]),"+f"(d[79]),"+f"(d[80]),"+f"(d[81]),"+f"(d[82]),"+f"(d[83]),"+f"(d[84]),"+f"(d[85]),"+f"(d[86]),"+f"(d[87]),"+f"(d[88]),"+f"(d[89]),"+f"(d[90]),"+f"(d[91]),"+f"(d[92]),"+f"(d[93]),"+f"(d[94]),"+f"(d[95]),"+f"(d[96]),"+f"(d[97]),"+f"(d[98]),"+f"(d[99]),"+f"(d[100]),"+f"(d[101]),"+f"(d[102]),"+f"(d[103]),"+f"(d[104]),"+f"(d[105]),"+f"(d[106]),"+f"(d[107]),"+f"(d[108]),"+f"(d[109]),"+f"(d[110]),"+f"(d[111]),"+f"(d[112]),"+f"(d[113]),"+f"(d[114]),"+f"(d[115]),"+f"(d[116]),"+f"(d[117]),"+f"(d[118]),"+f"(d[119]),"+f"(d[120]),"+f"(d[121]),"+f"(d[122]),"+f"(d[123]),"+f"(d[124]),"+f"(d[125]),"+f"(d[126]),"+f"(d[127])
        : "r"(alo), "r"(ahi), "r"(blo), "r"(bhi));
}
__device__ __forceinline__ void wg_ss256_z(float (&d)[128], uint32_t alo, uint32_t ahi, uint32_t blo, uint32_t bhi) {
    asm volatile("{\n.reg .b64 da, db;\nmov.b64 da, {%128, %129};\nmov.b64 db, {%130, %131};\n"
        "wgmma.mma_async.sync.aligned.m64n256k16.f32.bf16.bf16 {%0,%1,%2,%3,%4,%5,%6,%7,%8,%9,%10,%11,%12,%13,%14,%15,%16,%17,%18,%19,%20,%21,%22,%23,%24,%25,%26,%27,%28,%29,%30,%31,%32,%33,%34,%35,%36,%37,%38,%39,%40,%41,%42,%43,%44,%45,%46,%47,%48,%49,%50,%51,%52,%53,%54,%55,%56,%57,%58,%59,%60,%61,%62,%63,%64,%65,%66,%67,%68,%69,%70,%71,%72,%73,%74,%75,%76,%77,%78,%79,%80,%81,%82,%83,%84,%85,%86,%87,%88,%89,%90,%91,%92,%93,%94,%95,%96,%97,%98,%99,%100,%101,%102,%103,%104,%105,%106,%107,%108,%109,%110,%111,%112,%113,%114,%115,%116,%117,%118,%119,%120,%121,%122,%123,%124,%125,%126,%127}, da, db, 0, 1, 1, 0, 1;\n}\n"
        : "=f"(d[0]),"=f"(d[1]),"=f"(d[2]),"=f"(d[3]),"=f"(d[4]),"=f"(d[5]),"=f"(d[6]),"=f"(d[7]),"=f"(d[8]),"=f"(d[9]),"=f"(d[10]),"=f"(d[11]),"=f"(d[12]),"=f"(d[13]),"=f"(d[14]),"=f"(d[15]),"=f"(d[16]),"=f"(d[17]),"=f"(d[18]),"=f"(d[19]),"=f"(d[20]),"=f"(d[21]),"=f"(d[22]),"=f"(d[23]),"=f"(d[24]),"=f"(d[25]),"=f"(d[26]),"=f"(d[27]),"=f"(d[28]),"=f"(d[29]),"=f"(d[30]),"=f"(d[31]),"=f"(d[32]),"=f"(d[33]),"=f"(d[34]),"=f"(d[35]),"=f"(d[36]),"=f"(d[37]),"=f"(d[38]),"=f"(d[39]),"=f"(d[40]),"=f"(d[41]),"=f"(d[42]),"=f"(d[43]),"=f"(d[44]),"=f"(d[45]),"=f"(d[46]),"=f"(d[47]),"=f"(d[48]),"=f"(d[49]),"=f"(d[50]),"=f"(d[51]),"=f"(d[52]),"=f"(d[53]),"=f"(d[54]),"=f"(d[55]),"=f"(d[56]),"=f"(d[57]),"=f"(d[58]),"=f"(d[59]),"=f"(d[60]),"=f"(d[61]),"=f"(d[62]),"=f"(d[63]),"=f"(d[64]),"=f"(d[65]),"=f"(d[66]),"=f"(d[67]),"=f"(d[68]),"=f"(d[69]),"=f"(d[70]),"=f"(d[71]),"=f"(d[72]),"=f"(d[73]),"=f"(d[74]),"=f"(d[75]),"=f"(d[76]),"=f"(d[77]),"=f"(d[78]),"=f"(d[79]),"=f"(d[80]),"=f"(d[81]),"=f"(d[82]),"=f"(d[83]),"=f"(d[84]),"=f"(d[85]),"=f"(d[86]),"=f"(d[87]),"=f"(d[88]),"=f"(d[89]),"=f"(d[90]),"=f"(d[91]),"=f"(d[92]),"=f"(d[93]),"=f"(d[94]),"=f"(d[95]),"=f"(d[96]),"=f"(d[97]),"=f"(d[98]),"=f"(d[99]),"=f"(d[100]),"=f"(d[101]),"=f"(d[102]),"=f"(d[103]),"=f"(d[104]),"=f"(d[105]),"=f"(d[106]),"=f"(d[107]),"=f"(d[108]),"=f"(d[109]),"=f"(d[110]),"=f"(d[111]),"=f"(d[112]),"=f"(d[113]),"=f"(d[114]),"=f"(d[115]),"=f"(d[116]),"=f"(d[117]),"=f"(d[118]),"=f"(d[119]),"=f"(d[120]),"=f"(d[121]),"=f"(d[122]),"=f"(d[123]),"=f"(d[124]),"=f"(d[125]),"=f"(d[126]),"=f"(d[127])
        : "r"(alo), "r"(ahi), "r"(blo), "r"(bhi));
}
__device__ __forceinline__ void wg_ss128(float (&d)[64], uint32_t alo, uint32_t ahi, uint32_t blo, uint32_t bhi) {
    asm volatile("{\n.reg .b64 da, db;\nmov.b64 da, {%64, %65};\nmov.b64 db, {%66, %67};\n"
        "wgmma.mma_async.sync.aligned.m64n128k16.f32.bf16.bf16 {%0,%1,%2,%3,%4,%5,%6,%7,%8,%9,%10,%11,%12,%13,%14,%15,%16,%17,%18,%19,%20,%21,%22,%23,%24,%25,%26,%27,%28,%29,%30,%31,%32,%33,%34,%35,%36,%37,%38,%39,%40,%41,%42,%43,%44,%45,%46,%47,%48,%49,%50,%51,%52,%53,%54,%55,%56,%57,%58,%59,%60,%61,%62,%63}, da, db, 1, 1, 1, 0, 1;\n}\n"
        : "+f"(d[0]),"+f"(d[1]),"+f"(d[2]),"+f"(d[3]),"+f"(d[4]),"+f"(d[5]),"+f"(d[6]),"+f"(d[7]),"+f"(d[8]),"+f"(d[9]),"+f"(d[10]),"+f"(d[11]),"+f"(d[12]),"+f"(d[13]),"+f"(d[14]),"+f"(d[15]),"+f"(d[16]),"+f"(d[17]),"+f"(d[18]),"+f"(d[19]),"+f"(d[20]),"+f"(d[21]),"+f"(d[22]),"+f"(d[23]),"+f"(d[24]),"+f"(d[25]),"+f"(d[26]),"+f"(d[27]),"+f"(d[28]),"+f"(d[29]),"+f"(d[30]),"+f"(d[31]),"+f"(d[32]),"+f"(d[33]),"+f"(d[34]),"+f"(d[35]),"+f"(d[36]),"+f"(d[37]),"+f"(d[38]),"+f"(d[39]),"+f"(d[40]),"+f"(d[41]),"+f"(d[42]),"+f"(d[43]),"+f"(d[44]),"+f"(d[45]),"+f"(d[46]),"+f"(d[47]),"+f"(d[48]),"+f"(d[49]),"+f"(d[50]),"+f"(d[51]),"+f"(d[52]),"+f"(d[53]),"+f"(d[54]),"+f"(d[55]),"+f"(d[56]),"+f"(d[57]),"+f"(d[58]),"+f"(d[59]),"+f"(d[60]),"+f"(d[61]),"+f"(d[62]),"+f"(d[63])
        : "r"(alo), "r"(ahi), "r"(blo), "r"(bhi));
}
__device__ __forceinline__ void wg_ss128_z(float (&d)[64], uint32_t alo, uint32_t ahi, uint32_t blo, uint32_t bhi) {
    asm volatile("{\n.reg .b64 da, db;\nmov.b64 da, {%64, %65};\nmov.b64 db, {%66, %67};\n"
        "wgmma.mma_async.sync.aligned.m64n128k16.f32.bf16.bf16 {%0,%1,%2,%3,%4,%5,%6,%7,%8,%9,%10,%11,%12,%13,%14,%15,%16,%17,%18,%19,%20,%21,%22,%23,%24,%25,%26,%27,%28,%29,%30,%31,%32,%33,%34,%35,%36,%37,%38,%39,%40,%41,%42,%43,%44,%45,%46,%47,%48,%49,%50,%51,%52,%53,%54,%55,%56,%57,%58,%59,%60,%61,%62,%63}, da, db, 0, 1, 1, 0, 1;\n}\n"
        : "=f"(d[0]),"=f"(d[1]),"=f"(d[2]),"=f"(d[3]),"=f"(d[4]),"=f"(d[5]),"=f"(d[6]),"=f"(d[7]),"=f"(d[8]),"=f"(d[9]),"=f"(d[10]),"=f"(d[11]),"=f"(d[12]),"=f"(d[13]),"=f"(d[14]),"=f"(d[15]),"=f"(d[16]),"=f"(d[17]),"=f"(d[18]),"=f"(d[19]),"=f"(d[20]),"=f"(d[21]),"=f"(d[22]),"=f"(d[23]),"=f"(d[24]),"=f"(d[25]),"=f"(d[26]),"=f"(d[27]),"=f"(d[28]),"=f"(d[29]),"=f"(d[30]),"=f"(d[31]),"=f"(d[32]),"=f"(d[33]),"=f"(d[34]),"=f"(d[35]),"=f"(d[36]),"=f"(d[37]),"=f"(d[38]),"=f"(d[39]),"=f"(d[40]),"=f"(d[41]),"=f"(d[42]),"=f"(d[43]),"=f"(d[44]),"=f"(d[45]),"=f"(d[46]),"=f"(d[47]),"=f"(d[48]),"=f"(d[49]),"=f"(d[50]),"=f"(d[51]),"=f"(d[52]),"=f"(d[53]),"=f"(d[54]),"=f"(d[55]),"=f"(d[56]),"=f"(d[57]),"=f"(d[58]),"=f"(d[59]),"=f"(d[60]),"=f"(d[61]),"=f"(d[62]),"=f"(d[63])
        : "r"(alo), "r"(ahi), "r"(blo), "r"(bhi));
}
__device__ __forceinline__ void wg_ss64(float (&d)[32], uint32_t alo, uint32_t ahi, uint32_t blo, uint32_t bhi) {
    asm volatile("{\n.reg .b64 da, db;\nmov.b64 da, {%32, %33};\nmov.b64 db, {%34, %35};\n"
        "wgmma.mma_async.sync.aligned.m64n64k16.f32.bf16.bf16 {%0,%1,%2,%3,%4,%5,%6,%7,%8,%9,%10,%11,%12,%13,%14,%15,%16,%17,%18,%19,%20,%21,%22,%23,%24,%25,%26,%27,%28,%29,%30,%31}, da, db, 1, 1, 1, 0, 1;\n}\n"
        : "+f"(d[0]),"+f"(d[1]),"+f"(d[2]),"+f"(d[3]),"+f"(d[4]),"+f"(d[5]),"+f"(d[6]),"+f"(d[7]),"+f"(d[8]),"+f"(d[9]),"+f"(d[10]),"+f"(d[11]),"+f"(d[12]),"+f"(d[13]),"+f"(d[14]),"+f"(d[15]),"+f"(d[16]),"+f"(d[17]),"+f"(d[18]),"+f"(d[19]),"+f"(d[20]),"+f"(d[21]),"+f"(d[22]),"+f"(d[23]),"+f"(d[24]),"+f"(d[25]),"+f"(d[26]),"+f"(d[27]),"+f"(d[28]),"+f"(d[29]),"+f"(d[30]),"+f"(d[31])
        : "r"(alo), "r"(ahi), "r"(blo), "r"(bhi));
}
__device__ __forceinline__ void wg_ss64_z(float (&d)[32], uint32_t alo, uint32_t ahi, uint32_t blo, uint32_t bhi) {
    asm volatile("{\n.reg .b64 da, db;\nmov.b64 da, {%32, %33};\nmov.b64 db, {%34, %35};\n"
        "wgmma.mma_async.sync.aligned.m64n64k16.f32.bf16.bf16 {%0,%1,%2,%3,%4,%5,%6,%7,%8,%9,%10,%11,%12,%13,%14,%15,%16,%17,%18,%19,%20,%21,%22,%23,%24,%25,%26,%27,%28,%29,%30,%31}, da, db, 0, 1, 1, 0, 1;\n}\n"
        : "=f"(d[0]),"=f"(d[1]),"=f"(d[2]),"=f"(d[3]),"=f"(d[4]),"=f"(d[5]),"=f"(d[6]),"=f"(d[7]),"=f"(d[8]),"=f"(d[9]),"=f"(d[10]),"=f"(d[11]),"=f"(d[12]),"=f"(d[13]),"=f"(d[14]),"=f"(d[15]),"=f"(d[16]),"=f"(d[17]),"=f"(d[18]),"=f"(d[19]),"=f"(d[20]),"=f"(d[21]),"=f"(d[22]),"=f"(d[23]),"=f"(d[24]),"=f"(d[25]),"=f"(d[26]),"=f"(d[27]),"=f"(d[28]),"=f"(d[29]),"=f"(d[30]),"=f"(d[31])
        : "r"(alo), "r"(ahi), "r"(blo), "r"(bhi));
}

constexpr uint32_t DH128 = 64u | 0x40000000u;
constexpr uint32_t DH64 = 32u | 0x80000000u;
constexpr uint32_t LBO4K = (4096u >> 4) << 16, LBO8K = (8192u >> 4) << 16, LBO1 = 1u << 16;

template <bool SW64, bool FIRST> __device__ __forceinline__ void g1_issue(float (&acc)[64], uint32_t alo, uint32_t blo) {
    wg_fence();
#pragma unroll
    for (int k = 0; k < 4; k++) {
        if (FIRST && k == 0) wg_ss128_z(acc, alo, DH128, blo, SW64 ? DH64 : DH128);
        else wg_ss128(acc, alo + 2 * k, DH128, blo + (SW64 ? 64 * k : (k >> 1) * 512 + (k & 1) * 128), SW64 ? DH64 : DH128);
    }
    wg_commit();
}

template <int N> __device__ __forceinline__ void stash(uint32_t base, uint32_t sw, const uint32_t (&f)[N]) {
#pragma unroll
    for (int t = 0; t < N / 4; t++) stsm4(base + ((sw ^ (2 * t)) << 4), f[4 * t], f[4 * t + 1], f[4 * t + 2], f[4 * t + 3]);
}

template <int V0, int V1, int N> __device__ __forceinline__ void send_frag(const uint32_t (&f)[N], uint4* p, uint32_t tag) {
#pragma unroll
    for (int v = V0; v < V1; v++) st_pkt(p + (v & 3) * 32, (f[4 * v] & ~1u) | tag, f[4 * v + 1], f[4 * v + 2], f[4 * v + 3]);
}
template <int N> __device__ __forceinline__ void pack_acc(uint32_t (&f)[N], const float (&acc)[2 * N]) {
#pragma unroll
    for (int i = 0; i < N; i++) f[i] = pack2(acc[2 * i], acc[2 * i + 1]);
}
template <int N> __device__ __forceinline__ void recv_issue(uint32_t (&q)[N], const uint4* p) {
#pragma unroll
    for (int v = 0; v < N / 4; v++) ld_pkt(p + v * 32, q[4 * v], q[4 * v + 1], q[4 * v + 2], q[4 * v + 3]);
}
template <int N> __device__ __forceinline__ void recv_check(uint32_t (&q)[N], const uint4* p, uint32_t tag) {
    uint32_t it = 0;
    while (true) {
        uint32_t bad = 0;
#pragma unroll
        for (int v = 0; v < N / 4; v++) bad |= q[4 * v] ^ tag;
        if (__all_sync(0xffffffffu, (bad & 1u) == 0) || ++it > SPIN_GLOBAL) break;
        recv_issue(q, p);
    }
}
template <bool FIRST> __device__ __forceinline__ void accum(const uint32_t (&q)[16], float (&sum)[32]) {
#pragma unroll
    for (int i = 0; i < 16; i++) {
        if (FIRST) { sum[2 * i] = bf_lo(q[i]); sum[2 * i + 1] = bf_hi(q[i]); }
        else { sum[2 * i] += bf_lo(q[i]); sum[2 * i + 1] += bf_hi(q[i]); }
    }
}

}

__global__ void __launch_bounds__(384, 1)
fused_kernel(const __grid_constant__ Maps maps, const __nv_bfloat16* __restrict__ gate_w,
             const char* __restrict__ pf_qkv, const char* __restrict__ pf_g, const char* __restrict__ pf_u,
             const char* __restrict__ pf_d, const char* __restrict__ pf_o, __nv_bfloat16* __restrict__ out) {
    extern __shared__ __align__(1024) uint8_t smem_raw[];
    const uint32_t sb = (uint32_t)__cvta_generic_to_shared(smem_raw);
    const int tid = threadIdx.x, lane = tid & 31;
    const int warp = __shfl_sync(0xffffffffu, tid >> 5, 0);
    const int j = (blockIdx.x >> 1) & 7;
    const int r = ((blockIdx.x >> 4) << 1) | (blockIdx.x & 1);
    const uint32_t rank = blockIdx.x & 1;

    if (warp == 0) { TSG(0, 30); TS(0, 0); }
    if (warp == 9 && lane < 7) asm volatile("prefetch.tensormap [%0];" :: "l"(&maps.x + lane) : "memory");
    if (tid == 256) {
        for (int i = 0; i < 5; i++) { mbar_init(sb + B_FULL + 8 * i, 1); mbar_init(sb + B_EMPTY + 8 * i, MC ? 4 : 2); }
        for (int i = 0; i < 8; i++) mbar_init(sb + B_XFULL + 8 * i, 1);
        mbar_init(sb + B_GRDY, 3); mbar_init(sb + B_STGFULL, 4); mbar_init(sb + B_STGFREE, 2); mbar_init(sb + B_KVRDY, 2);
        asm volatile("fence.mbarrier_init.release.cluster;" ::: "memory");
        asm volatile("fence.proxy.async.shared::cta;" ::: "memory");
        mbar_expect(sb + B_XFULL, 16384);
        tma2(sb + OFF_X, &maps.x, 0, r * 128, sb + B_XFULL);
    }
    __syncthreads();

    if (warp >= 8) {
        asm volatile("setmaxnreg.dec.sync.aligned.u32 56;");
        if (warp == 8) {
            if (lane == 0) {
                int slot = 0, ph = 1;
                for (int s = 0; s < 16; s++) {
                    const uint32_t full = sb + B_FULL + 8 * slot, dst = sb + OFF_RING + slot * 16384;
                    mbar_wait(sb + B_EMPTY + 8 * slot, ph);
                    mbar_expect(full, 16384);
                    if (!MC || rank == 0) tmaw3(dst, &maps.gu, 224 * j, 32 * s, 0, full);
                    if (!MC || rank == 1) tmaw3(dst + 8192, &maps.kv, 64 * j, 32 * s, 1, full);
                    int xb = (s == 1) ? 1 : (s == 3) ? 2 : (s == 4) ? 3 : ((s & 1) && s >= 5 && s <= 11) ? (s + 3) / 2 : 0;
                    if (xb) { mbar_expect(sb + B_XFULL + 8 * xb, 16384); tma2(sb + OFF_X + xb * 16384, &maps.x, 64 * xb, r * 128, sb + B_XFULL + 8 * xb); }
                    if (++slot == 5) { slot = 0; ph ^= 1; }
                }
                for (int s = 0; s < 24; s++) {
                    const uint32_t full = sb + B_FULL + 8 * slot, dst = sb + OFF_RING + slot * 16384;
                    const int k0 = (s & 7) * 64;
                    mbar_wait(sb + B_EMPTY + 8 * slot, ph);
                    mbar_expect(full, 16384);
                    if (s < 8) {
                        if (!MC || rank == 0) tmaw3(dst, &maps.q64, 0, k0, 2 * j, full);
                        if (!MC || rank == 1) tmaw3(dst + 8192, &maps.gu64, 224 * j + 192, k0, 0, full);
                    } else {
                        const int c0 = 224 * j + 64 * (s >> 3);
                        if (!MC || rank == 0) tmaw3(dst, &maps.gu, c0, k0, 0, full);
                        if (!MC || rank == 1) tmaw3(dst + 8192, &maps.gu, c0, k0 + 32, 0, full);
                    }
                    if (++slot == 5) { slot = 0; ph ^= 1; }
                }
                const int p = j >> 1, cb = (j & 1) * 256, jo = j ^ 1;
                for (int t = 0; t < 19; t++) {
                    const uint32_t full = sb + B_FULL + 8 * slot, dst = sb + OFF_RING + slot * 16384;
                    mbar_wait(sb + B_EMPTY + 8 * slot, ph);
                    const bool wide = t < 9;
                    const int u = wide ? t : (t - 9) % 5;
                    const int nb = (!wide && u == 4) ? 2 : 4;
                    mbar_expect(full, nb * 4096);
                    for (int bx = 0; bx < nb; bx++) {
                        if (MC && (bx >> 1) != (int)rank && nb == 4) continue;
                        if (MC && nb == 2 && bx != (int)rank) continue;
                        const int kblk = wide ? u : 2 * u + (bx >> 1), half = bx & 1;
                        const int col = cb + 64 * ((wide ? p + 1 + (bx >> 1) : t < 14 ? p + 3 : p) & 3);
                        const bool is_o = kblk == 5 || kblk == 6;
                        int row;
                        if (kblk == 4) row = 224 * (half ? jo : j) + 192;
                        else if (is_o) row = 64 * (kblk == 5 ? j : jo) + 32 * half;
                        else row = 224 * ((kblk == 2 || kblk == 3 || kblk == 8) ? jo : j) + (kblk >= 7 ? 128 : 64 * (kblk & 1)) + 32 * half;
                        tmaw2(dst + bx * 4096, is_o ? &maps.wo : &maps.wd, col, row, full);
                    }
                    if (++slot == 5) { slot = 0; ph ^= 1; }
                }
            }
        } else if (warp < 11) {
            const int hx = warp - 9;
            {
                float s[16];
#pragma unroll
                for (int i = 0; i < 16; i++) s[i] = 0.f;
                const uint32_t xa = sb + OFF_X + (hx * 64 + (lane >> 3)) * 128;
                const uint32_t sw0 = ((lane & 7) ^ (lane >> 3)) << 4;
#pragma unroll 1
                for (int kb = 0; kb < 8; kb++) {
                    const uint4 wv = __ldg((const uint4*)gate_w + kb * 8 + (lane & 7));
                    const float w0 = bf_lo(wv.x), w1 = bf_hi(wv.x), w2 = bf_lo(wv.y), w3 = bf_hi(wv.y);
                    const float w4 = bf_lo(wv.z), w5 = bf_hi(wv.z), w6 = bf_lo(wv.w), w7 = bf_hi(wv.w);
                    mbar_wait(sb + B_XFULL + 8 * kb, 0);
#pragma unroll
                    for (int i = 0; i < 16; i++) {
                        uint4 v;
                        asm volatile("ld.shared.v4.u32 {%0,%1,%2,%3}, [%4];" : "=r"(v.x), "=r"(v.y), "=r"(v.z), "=r"(v.w)
                                     : "r"(xa + kb * 16384 + i * 512 + (sw0 ^ ((i & 1) << 6))));
                        float t0 = fmaf(bf_lo(v.x), w0, s[i]), t1 = bf_hi(v.x) * w1;
                        t0 = fmaf(bf_lo(v.y), w2, t0); t1 = fmaf(bf_hi(v.y), w3, t1);
                        t0 = fmaf(bf_lo(v.z), w4, t0); t1 = fmaf(bf_hi(v.z), w5, t1);
                        t0 = fmaf(bf_lo(v.w), w6, t0); t1 = fmaf(bf_hi(v.w), w7, t1);
                        s[i] = t0 + t1;
                    }
                }
#pragma unroll
                for (int i = 0; i < 16; i++) {
                    s[i] += __shfl_xor_sync(0xffffffffu, s[i], 1);
                    s[i] += __shfl_xor_sync(0xffffffffu, s[i], 2);
                    s[i] += __shfl_xor_sync(0xffffffffu, s[i], 4);
                    if ((lane & 7) == (i & 7))
                        asm volatile("st.shared.f32 [%0], %1;" :: "r"(sb + OFF_G + (hx * 64 + i * 4 + (lane >> 3)) * 4), "f"(1.f / (1.f + __expf(-s[i]))) : "memory");
                }
                __syncwarp();
                if (lane == 0) mbar_arrive(sb + B_GRDY);
            }
            TS(2 + hx, 1);
            float d[2][2][4], z[2][2];
#pragma unroll
            for (int h = 0; h < 2; h++)
#pragma unroll
                for (int n = 0; n < 2; n++) { d[h][n][0] = d[h][n][1] = d[h][n][2] = d[h][n][3] = 0.f; z[h][n] = 0.f; }
            {
                const uint32_t ka = sb + OFF_STG + ((lane & 7) + 8 * ((lane >> 3) & 1)) * 128, ksw = (lane >> 4) ^ (lane & 7);
                const uint32_t va = sb + OFF_STG + 8192 + ((lane & 7) + 8 * (lane >> 4)) * 128, vsw = ((lane >> 3) & 1) ^ (lane & 7);
#pragma unroll 1
                for (int rnd = 0; rnd < 2; rnd++) {
                    mbar_wait(sb + B_STGFULL, rnd);
#pragma unroll
                    for (int sl = 0; sl < 4; sl++) {
#pragma unroll
                        for (int h = 0; h < 2; h++) {
                            uint32_t a[4], b[4];
                            const uint32_t cs = (uint32_t)(4 * hx + 2 * h);
                            ldsm4t(a, va + sl * 2048 + ((vsw ^ cs) << 4));
                            ldsm4t(b, ka + sl * 2048 + ((ksw ^ cs) << 4));
                            mma16816(d[h][0], a[0], a[1], a[2], a[3], b[0], b[1]);
                            mma16816(d[h][1], a[0], a[1], a[2], a[3], b[2], b[3]);
                            z[h][0] += (bf_lo(b[0]) + bf_hi(b[0])) + (bf_lo(b[1]) + bf_hi(b[1]));
                            z[h][1] += (bf_lo(b[2]) + bf_hi(b[2])) + (bf_lo(b[3]) + bf_hi(b[3]));
                        }
                    }
                    __syncwarp();
                    if (rnd == 0 && lane == 0) mbar_arrive(sb + B_STGFREE);
                    TS(2 + hx, 5 + rnd);
                }
            }
            mbar_wait(sb + B_GRDY, 0);
            uint32_t epoch;
            asm volatile("ld.shared.u32 %0, [%1];" : "=r"(epoch) : "r"(sb + OFF_EPOCH) : "memory");
            float* accp = g_kvacc + (((epoch & 1) * 8 + j) * 4 + 2 * hx) * 272;
#pragma unroll
            for (int h = 0; h < 2; h++) {
#pragma unroll
                for (int n = 0; n < 2; n++) {
                    asm volatile("red.global.add.v4.f32 [%0], {%1,%2,%3,%4};" :: "l"(accp + h * 272 + n * 128 + lane * 4),
                                 "f"(d[h][n][0]), "f"(d[h][n][1]), "f"(d[h][n][2]), "f"(d[h][n][3]) : "memory");
                    float zz = z[h][n];
                    zz += __shfl_xor_sync(0xffffffffu, zz, 1);
                    zz += __shfl_xor_sync(0xffffffffu, zz, 2);
                    if ((lane & 3) == 0) asm volatile("red.global.add.f32 [%0], %1;" :: "l"(accp + h * 272 + 256 + n * 8 + (lane >> 2)), "f"(zz) : "memory");
                }
            }
            TS(2 + hx, 7);
            __threadfence();
            __syncwarp();
            unsigned* cnt = g_kvcnt + j * 32;
            if (lane == 0) asm volatile("red.release.gpu.global.add.u32 [%0], 1;" :: "l"(cnt) : "memory");
            TS(2 + hx, 2);
            {
                const unsigned target = 32u * (epoch + 1);
                uint32_t it = 0, v;
                do {
                    asm volatile("ld.acquire.gpu.global.u32 %0, [%1];" : "=r"(v) : "l"(cnt) : "memory");
                } while ((int)(v - target) < 0 && ++it < SPIN_GLOBAL);
            }
            TS(2 + hx, 3);
#pragma unroll
            for (int h = 0; h < 2; h++) {
                const float4 d0 = __ldcg((const float4*)(accp + h * 272) + lane);
                const float4 d1 = __ldcg((const float4*)(accp + h * 272 + 128) + lane);
                const float2 z0 = __ldcg((const float2*)(accp + h * 272 + 256) + (lane & 3));
                const float2 z1 = __ldcg((const float2*)(accp + h * 272 + 264) + (lane & 3));
                asm volatile("st.shared.v4.u32 [%0], {%1,%2,%3,%4};" :: "r"(sb + OFF_KVF + (2 * hx + h) * 512 + lane * 16),
                             "r"(pack2(d0.x, d0.y)), "r"(pack2(d1.x, d1.y)), "r"(pack2(d0.z, d0.w)), "r"(pack2(d1.z, d1.w)) : "memory");
                if (lane < 4) asm volatile("st.shared.v2.u32 [%0], {%1,%2};" :: "r"(sb + OFF_ZF + (2 * hx + h) * 32 + lane * 8), "r"(pack2(z0.x, z0.y)), "r"(pack2(z1.x, z1.y)) : "memory");
            }
            __syncwarp();
            if (lane == 0) mbar_arrive(sb + B_KVRDY);
            TS(2 + hx, 4);
        } else {
            uint32_t epoch = 0;
            if (lane == 0) {
                asm volatile("ld.relaxed.gpu.global.u32 %0, [%1];" : "=r"(epoch) : "l"(g_epoch + blockIdx.x) : "memory");
                asm volatile("st.shared.u32 [%0], %1;" :: "r"(sb + OFF_EPOCH), "r"(epoch) : "memory");
                mbar_arrive(sb + B_GRDY);
                g_epoch[blockIdx.x] = epoch + 1;
            }
            epoch = __shfl_sync(0xffffffffu, epoch, 0);
            if (r == 0) {
                float4* zp = (float4*)(g_kvacc + (((epoch & 1) ^ 1) * 8 + j) * 4 * 272);
                for (int i = lane; i < 272; i += 32) zp[i] = make_float4(0.f, 0.f, 0.f, 0.f);
            }
            mbar_wait(sb + B_XFULL, 0);
            const int b = blockIdx.x;
            if (lane == 0) l2_prefetch(pf_qkv + b * 12288, 12288);
            if (lane == 1) l2_prefetch(pf_g + b * 14336, 14336);
            if (lane == 2) l2_prefetch(pf_u + b * 14336, 14336);
            mbar_wait(sb + B_XFULL + 8 * 7, 0);
            if (lane == 0) l2_prefetch(pf_d + b * 14336, 14336);
            if (lane == 1) l2_prefetch(pf_o + b * 4096, 4096);
        }
    } else {
        asm volatile("setmaxnreg.inc.sync.aligned.u32 224;");
        const int wg = warp >> 2;
        const bool elect = (tid & 127) == 0;
        float a0[128];
        const uint32_t xlo = ((sb + OFF_X + wg * 8192) >> 4) | LBO1;
        const uint32_t ringlo = (sb + OFF_RING) >> 4;
        int slot = 0, ph = 0, prev = 0;
        auto release = [&](int s) {
            if (elect) {
                mbar_arrive(sb + B_EMPTY + 8 * s);
            }
        };
        auto adv = [&]() { prev = slot; if (++slot == 5) { slot = 0; ph ^= 1; } };

        mbar_wait(sb + B_XFULL, 0);
        mbar_wait(sb + B_FULL, 0);
        if ((warp & 3) == 0) TS(wg, 1);
        wg_fence();
        wg_ss256_z(a0, xlo, DH128, ringlo | LBO4K, DH128);
        wg_ss256(a0, xlo + 2, DH128, (ringlo | LBO4K) + 128, DH128);
        wg_commit();
        adv();
#pragma unroll 1
        for (int s = 1; s < 16; s++) {
            if (!(s & 1)) mbar_wait(sb + B_XFULL + 4 * s, 0);
            mbar_wait(sb + B_FULL + 8 * slot, ph);
            const uint32_t blo = (ringlo + slot * 1024) | LBO4K, alo = xlo + (s >> 1) * 1024 + 4 * (s & 1);
            wg_fence();
            wg_ss256(a0, alo, DH128, blo, DH128);
            wg_ss256(a0, alo + 2, DH128, blo + 128, DH128);
            wg_commit();
            wg_wait<1>();
            release(prev);
            adv();
        }
        mbar_wait(sb + B_GRDY, 0);
        float g_lo, g_hi;
        uint32_t tag;
        {
            const uint32_t ga = sb + OFF_G + (warp * 16 + (lane >> 2)) * 4;
            asm volatile("ld.shared.f32 %0, [%1];" : "=f"(g_lo) : "r"(ga) : "memory");
            asm volatile("ld.shared.f32 %0, [%1];" : "=f"(g_hi) : "r"(ga + 32) : "memory");
            asm volatile("ld.shared.u32 %0, [%1];" : "=r"(tag) : "r"(sb + OFF_EPOCH) : "memory");
            tag = (tag + 1) & 1;
        }
        const float m_lo = 1.f - g_lo, m_hi = 1.f - g_hi;
        wg_wait<0>();
        pin(a0);
        release(prev);
        if ((warp & 3) == 0) TS(wg, 2);

        uint32_t fh0[16], fh1[16], fh2[16], fh3[8], fo[16];
#define H_EPI(acc, F, N, OG, OU) _Pragma("unroll") for (int i = 0; i < (N); i++) { \
            const float m_ = (i & 1) ? m_hi : m_lo; \
            F[i] = pack2(acc[(OG) + 2 * i] * acc[(OU) + 2 * i] * m_, acc[(OG) + 2 * i + 1] * acc[(OU) + 2 * i + 1] * m_); }
        H_EPI(a0, fh0, 16, 0, 32);

        const uint32_t srow = ((warp & 3) * 16 + (lane & 7) + 8 * ((lane >> 3) & 1)) * 128;
        const uint32_t ssw = (lane >> 4) ^ (lane & 7);

#define G1_STAGE(acc, SW, KB, FIRST) do { mbar_wait(sb + B_FULL + 8 * slot, ph); \
            g1_issue<SW, FIRST>(acc, xlo + (KB) * 1024, (ringlo + slot * 1024) | LBO4K); } while (0)
#define G1_RETIRE() do { wg_wait<1>(); release(prev); adv(); } while (0)

        float a1[64], a2_[64], a3[64];
        G1_STAGE(a1, true, 0, 1); adv();
        G1_STAGE(a1, true, 1, 0);
        uint4* const hsend = g_hx + (size_t)((r * 8 + j) * 5) * 1024 + warp * 128 + lane;
        const uint4* const hrecv = g_hx + (size_t)((r * 8 + (j ^ 1)) * 5) * 1024 + warp * 128 + lane;
        {
            uint32_t pk[16], pv[16];
#pragma unroll
            for (int i = 0; i < 16; i++) {
                pk[i] = pack2(phi(a0[64 + 2 * i]), phi(a0[64 + 2 * i + 1]));
                pv[i] = pack2(a0[96 + 2 * i], a0[96 + 2 * i + 1]);
            }
            if (wg == 0) {
                stash<16>(sb + OFF_STG + srow, ssw, pk); stash<16>(sb + OFF_STG + 8192 + srow, ssw, pv);
                __syncwarp();
                if (lane == 0) mbar_arrive(sb + B_STGFULL);
            }
            G1_RETIRE();
            G1_STAGE(a1, true, 2, 0);
            send_frag<0, 4>(fh0, hsend, tag);
            G1_RETIRE();
            G1_STAGE(a1, true, 3, 0);
            if (wg == 1) {
                mbar_wait(sb + B_STGFREE, 0);
                stash<16>(sb + OFF_STG + srow, ssw, pk); stash<16>(sb + OFF_STG + 8192 + srow, ssw, pv);
                __syncwarp();
                if (lane == 0) mbar_arrive(sb + B_STGFULL);
            }
            G1_RETIRE();
        }
#pragma unroll 1
        for (int kb = 4; kb < 8; kb++) { G1_STAGE(a1, true, kb, 0); G1_RETIRE(); }
        if ((warp & 3) == 0) TS(wg, 3);

        G1_STAGE(a2_, false, 0, 1); G1_RETIRE();
        pin(a1);
        G1_STAGE(a2_, false, 1, 0);
#pragma unroll
        for (int i = 0; i < 16; i++) fo[i] = pack2(phi(a1[2 * i]), phi(a1[2 * i + 1]));
        H_EPI(a1, fh3, 8, 32, 48);
        send_frag<0, 2>(fh3, hsend + 4 * 1024, tag);
        G1_RETIRE();
#pragma unroll 1
        for (int kb = 2; kb < 8; kb++) { G1_STAGE(a2_, false, kb, 0); G1_RETIRE(); }
        if ((warp & 3) == 0) TS(wg, 4);

        const uint32_t a2 = sb + OFF_X + wg * 8192 + srow;
        uint32_t qa[16], qb[16], qh[8];
        G1_STAGE(a3, false, 0, 1); G1_RETIRE();
        pin(a2_);
        G1_STAGE(a3, false, 1, 0);
        H_EPI(a2_, fh1, 16, 0, 32);
        send_frag<0, 4>(fh1, hsend + 1024, tag);
        recv_issue(qa, hrecv); recv_issue(qh, hrecv + 4 * 1024);
        G1_RETIRE();
        G1_STAGE(a3, false, 2, 0); stash<16>(a2, ssw, fh0); G1_RETIRE();
        G1_STAGE(a3, false, 3, 0); stash<16>(a2 + 16384, ssw, fh1); recv_issue(qb, hrecv + 1024); G1_RETIRE();
        G1_STAGE(a3, false, 4, 0); recv_check(qa, hrecv, tag); stash<16>(a2 + 2 * 16384, ssw, qa); G1_RETIRE();
        G1_STAGE(a3, false, 5, 0); recv_check(qb, hrecv + 1024, tag); stash<16>(a2 + 3 * 16384, ssw, qb); G1_RETIRE();
        G1_STAGE(a3, false, 6, 0);
        recv_check(qh, hrecv + 4 * 1024, tag);
        stash<8>(a2 + 4 * 16384, ssw, fh3); stash<8>(a2 + 4 * 16384, ssw ^ 4, qh);
        if ((warp & 3) == 0) TS(wg, 5);
        mbar_wait(sb + B_KVRDY, 0);
        if ((warp & 3) == 0) TS(wg, 6);
#pragma unroll
        for (int h = 0; h < 4; h++) {
            uint32_t b0, b1, b2, b3, z0, z1;
            asm volatile("ld.shared.v4.u32 {%0,%1,%2,%3}, [%4];" : "=r"(b0), "=r"(b1), "=r"(b2), "=r"(b3) : "r"(sb + OFF_KVF + h * 512 + lane * 16) : "memory");
            asm volatile("ld.shared.v2.u32 {%0,%1}, [%2];" : "=r"(z0), "=r"(z1) : "r"(sb + OFF_ZF + h * 32 + (lane & 3) * 8) : "memory");
            float n0[4] = {0.f, 0.f, 0.f, 0.f}, n1[4] = {0.f, 0.f, 0.f, 0.f}, dn[4] = {0.f, 0.f, 0.f, 0.f};
            mma16816(dn, fo[4 * h], fo[4 * h + 1], fo[4 * h + 2], fo[4 * h + 3], z0, z1);
            mma16816(n0, fo[4 * h], fo[4 * h + 1], fo[4 * h + 2], fo[4 * h + 3], b0, b1);
            mma16816(n1, fo[4 * h], fo[4 * h + 1], fo[4 * h + 2], fo[4 * h + 3], b2, b3);
            const float s_lo = __fdividef(g_lo, dn[0] + 1e-6f), s_hi = __fdividef(g_hi, dn[2] + 1e-6f);
            fo[4 * h] = pack2(n0[0] * s_lo, n0[1] * s_lo); fo[4 * h + 1] = pack2(n0[2] * s_hi, n0[3] * s_hi);
            fo[4 * h + 2] = pack2(n1[0] * s_lo, n1[1] * s_lo); fo[4 * h + 3] = pack2(n1[2] * s_hi, n1[3] * s_hi);
        }
        send_frag<0, 4>(fo, hsend + 3 * 1024, tag);
        G1_RETIRE();
        G1_STAGE(a3, false, 7, 0);
        stash<16>(a2 + 5 * 16384, ssw, fo);
#define A2_SYNC() do { asm volatile("fence.proxy.async.shared::cta;" ::: "memory"); asm volatile("bar.sync %0, 128;" :: "r"(wg + 1) : "memory"); } while (0)
        G1_RETIRE();
        A2_SYNC();
        if ((warp & 3) == 0) TS(wg, 7);

        const uint32_t slo = ((sb + OFF_STG + wg * 8192) >> 4) | LBO1;
#define G2_A(K) ((K) < 8 ? xlo + (K) * 1024 : slo)
#define G2_B(T) (ringlo + ((T) % 5) * 1024)
#define G2_WAIT(T) mbar_wait(sb + B_FULL + 8 * ((T) % 5), ((T) / 5) & 1)
#define G2_REL(T) do { if ((T) < 14) release((T) % 5); } while (0)
#define G2_W(T, acc) do { G2_WAIT(T); wg_fence(); _Pragma("unroll") for (int k = 0; k < 4; k++) { \
            if ((T) == 0 && k == 0) wg_ss128_z(acc, G2_A(T), DH128, G2_B(T) | LBO8K, DH128); \
            else wg_ss128(acc, G2_A(T) + 2 * k, DH128, (G2_B(T) | LBO8K) + 128 * k, DH128); } wg_commit(); } while (0)
#define G2_N(T, acc, U) do { G2_WAIT(T); wg_fence(); _Pragma("unroll") for (int k = 0; k < ((U) == 4 ? 4 : 8); k++) { \
            if ((U) == 0 && k == 0) wg_ss64_z(acc, G2_A(0), DH128, G2_B(T) | LBO1, DH128); \
            else wg_ss64(acc, G2_A(2 * (U) + (k >> 2)) + 2 * (k & 3), DH128, (G2_B(T) | LBO1) + 128 * k, DH128); } wg_commit(); } while (0)

        const int p = j >> 1;
        uint4* const pbase = g_part + (size_t)(r * 2 + (j & 1)) * 16384 + warp * 128 + lane;
        auto sendp = [&](int d) { return pbase + ((((p + d) & 3) * 4 + p) << 10); };
        auto recvp = [&](int d) { return pbase + ((p * 4 + ((p - d) & 3)) << 10); };

        float p1[64], p2[32], p3[32];
        G2_W(0, p1);
        wg_wait<1>();
        release(prev);
        pin(a3);
        G2_W(1, p1);
        H_EPI(a3, fh2, 16, 0, 32);
        send_frag<0, 4>(fh2, hsend + 2 * 1024, tag);
        recv_issue(qa, hrecv + 3 * 1024);
        stash<16>(a2 + 7 * 16384, ssw, fh2);
        wg_wait<1>(); G2_REL(0);
        G2_W(2, p1); wg_wait<1>(); G2_REL(1);
        G2_W(3, p1);
        recv_check(qa, hrecv + 3 * 1024, tag); stash<16>(a2 + 6 * 16384, ssw, qa);
        wg_wait<1>(); G2_REL(2);
        G2_W(4, p1);
        recv_issue(qb, hrecv + 2 * 1024);
        wg_wait<1>(); G2_REL(3);
        A2_SYNC();
        G2_W(5, p1); wg_wait<1>(); G2_REL(4);
        G2_W(6, p1);
        recv_check(qb, hrecv + 2 * 1024, tag); stash<16>(sb + OFF_STG + wg * 8192 + srow, ssw, qb);
        wg_wait<1>(); G2_REL(5);
        G2_W(7, p1); wg_wait<1>(); G2_REL(6);
        A2_SYNC();
        G2_W(8, p1); wg_wait<1>(); G2_REL(7);
        if ((warp & 3) == 0) TS(wg, 8);
        uint32_t sp[32];
        G2_N(9, p2, 0); wg_wait<1>(); G2_REL(8);
        pin(p1);
        pack_acc(sp, p1);
        G2_N(10, p2, 1); send_frag<0, 2>(sp, sendp(1), tag); wg_wait<1>(); G2_REL(9);
        G2_N(11, p2, 2); send_frag<2, 4>(sp, sendp(1), tag); wg_wait<1>(); G2_REL(10);
        G2_N(12, p2, 3); send_frag<4, 6>(sp, sendp(2), tag); wg_wait<1>(); G2_REL(11);
        G2_N(13, p2, 4); send_frag<6, 8>(sp, sendp(2), tag); wg_wait<1>(); G2_REL(12);
        if ((warp & 3) == 0) TS(wg, 9);
        float sum[32];
        uint32_t qc[16];
        G2_N(14, p3, 0); wg_wait<1>(); G2_REL(13);
        pin(p2);
        pack_acc(qc, p2);
        send_frag<0, 4>(qc, sendp(3), tag);
        G2_N(15, p3, 1);
        recv_issue(qa, recvp(1)); recv_issue(qb, recvp(2));
        G2_N(16, p3, 2);
        G2_N(17, p3, 3);
        recv_issue(qc, recvp(3));
        G2_N(18, p3, 4);
        if ((warp & 3) == 0) TS(wg, 10);
        recv_check(qa, recvp(1), tag); accum<true>(qa, sum);
        recv_check(qb, recvp(2), tag); accum<false>(qb, sum);
        if ((warp & 3) == 0) TS(wg, 12);
        recv_check(qc, recvp(3), tag); accum<false>(qc, sum);
        if ((warp & 3) == 0) TS(wg, 13);
        wg_wait<0>();
        pin(p3);
        {
            uint32_t f[16];
#pragma unroll
            for (int i = 0; i < 16; i++) f[i] = pack2(p3[2 * i] + sum[2 * i], p3[2 * i + 1] + sum[2 * i + 1]);
            const uint32_t slab = sb + OFF_X + wg * 8192;
            stash<16>(slab + srow, ssw, f);
            __syncwarp();
            __nv_bfloat16* op = out + (size_t)(r * 128 + warp * 16 + (lane >> 3)) * kD + (j & 1) * 256 + p * 64 + (lane & 7) * 8;
#pragma unroll
            for (int i = 0; i < 4; i++) {
                const int row = i * 4 + (lane >> 3);
                uint4 v;
                asm volatile("ld.shared.v4.u32 {%0,%1,%2,%3}, [%4];" : "=r"(v.x), "=r"(v.y), "=r"(v.z), "=r"(v.w)
                             : "r"(slab + ((warp & 3) * 16 + row) * 128 + (((lane & 7) ^ (row & 7)) << 4)) : "memory");
                *(uint4*)(op + i * 4 * kD) = v;
            }
        }
        if ((warp & 3) == 0) { TS(wg, 14); TSG(wg, 31); }
    }
}

typedef CUresult (*EncodeFn)(CUtensorMap*, CUtensorMapDataType, cuuint32_t, void*, const cuuint64_t*, const cuuint64_t*, const cuuint32_t*,
                             const cuuint32_t*, CUtensorMapInterleave, CUtensorMapSwizzle, CUtensorMapL2promotion, CUtensorMapFloatOOBfill);

static void encode(EncodeFn fn, CUtensorMap* m, int rank, const void* base, uint64_t d0, uint64_t d1, uint64_t d2, uint64_t s1, uint64_t s2,
                   uint32_t b0, uint32_t b1, uint32_t b2, CUtensorMapSwizzle sw) {
    cuuint64_t gd[3] = {d0, d1, d2}, gs[2] = {s1, s2};
    cuuint32_t bd[3] = {b0, b1, b2}, es[3] = {1, 1, 1};
    fn(m, CU_TENSOR_MAP_DATA_TYPE_BFLOAT16, rank, const_cast<void*>(base), gd, gs, bd, es, CU_TENSOR_MAP_INTERLEAVE_NONE, sw,
       CU_TENSOR_MAP_L2_PROMOTION_L2_128B, CU_TENSOR_MAP_FLOAT_OOB_FILL_NONE);
}

extern "C" void kernel_launch(void* const* d_in, const int* in_sizes, int n_in, void* d_out, int out_size) {
    const char* x = (const char*)d_in[0];
    const char* wqkv = (const char*)d_in[1];
    const char* wo = (const char*)d_in[2];
    const char* wg = (const char*)d_in[4];
    const char* wu = (const char*)d_in[5];
    const char* wd = (const char*)d_in[6];
    void* fnp = nullptr;
    cudaDriverEntryPointQueryResult qr;
    cudaGetDriverEntryPoint("cuTensorMapEncodeTiled", &fnp, cudaEnableDefault, &qr);
    EncodeFn fn = (EncodeFn)fnp;
    Maps maps;
    const char* lo = wg < wu ? wg : wu;
    const uint64_t diff = wg < wu ? (uint64_t)(wu - wg) : (uint64_t)(wg - wu);
    encode(fn, &maps.x, 2, x, kD, 2048, 1, kD * 2, 0, 64, 128, 1, CU_TENSOR_MAP_SWIZZLE_128B);
    encode(fn, &maps.gu, 3, lo, kF, kD, 2, kF * 2, diff, 64, 32, 2, CU_TENSOR_MAP_SWIZZLE_128B);
    encode(fn, &maps.kv, 3, wqkv, kD, kD, 3, 3 * kD * 2, kD * 2, 64, 32, 2, CU_TENSOR_MAP_SWIZZLE_128B);
    encode(fn, &maps.q64, 3, wqkv, 32, kD, 48, 3 * kD * 2, 64, 32, 64, 2, CU_TENSOR_MAP_SWIZZLE_64B);
    encode(fn, &maps.gu64, 3, lo, kF, kD, 2, kF * 2, diff, 32, 64, 2, CU_TENSOR_MAP_SWIZZLE_64B);
    encode(fn, &maps.wd, 2, wd, kD, kF, 1, kD * 2, 0, 64, 32, 1, CU_TENSOR_MAP_SWIZZLE_128B);
    encode(fn, &maps.wo, 2, wo, kD, kD, 1, kD * 2, 0, 64, 32, 1, CU_TENSOR_MAP_SWIZZLE_128B);
    cudaFuncSetAttribute(fused_kernel, cudaFuncAttributeMaxDynamicSharedMemorySize, SMEM_BYTES);
    cudaLaunchConfig_t cfg = {};
    cfg.gridDim = dim3(128);
    cfg.blockDim = dim3(384);
    cfg.dynamicSmemBytes = SMEM_BYTES;
    cfg.stream = cudaStreamPerThread;
    cudaLaunchAttribute at[1];
    at[0].id = cudaLaunchAttributeClusterDimension;
    at[0].val.clusterDim.x = 2; at[0].val.clusterDim.y = 1; at[0].val.clusterDim.z = 1;
    cfg.attrs = at;
    cfg.numAttrs = MC ? 1 : 0;
    cudaLaunchKernelEx(&cfg, fused_kernel, maps, (const __nv_bfloat16*)d_in[7], wqkv, wg, wu, wd, wo, (__nv_bfloat16*)d_out);
}
```

```cpp
#include <cuda_runtime.h>
#include <cuda.h>
#include <cuda_bf16.h>
#include <stdint.h>

#define MC 0
#define PROF 0

namespace {

constexpr int kD = 512;
constexpr uint32_t OFF_X = 0, OFF_STG = 131072, OFF_RING = 147456, OFF_MISC = 229376;
constexpr uint32_t B_FULL = OFF_MISC, B_EMPTY = OFF_MISC + 64, B_XFULL = OFF_MISC + 128;
constexpr uint32_t B_GRDY = OFF_MISC + 192, B_KVDONE = OFF_MISC + 200, B_KVRDY = OFF_MISC + 208;
constexpr uint32_t OFF_EPOCH = OFF_MISC + 240, OFF_G = OFF_MISC + 256;
constexpr uint32_t OFF_KVF = OFF_MISC + 768, OFF_ZF = OFF_KVF + 2048;
constexpr uint32_t OFF_ONES = OFF_ZF + 128;
constexpr uint32_t SMEM_BYTES = OFF_ONES + 128;
constexpr uint32_t SPIN_MBAR = 1u << 16, SPIN_GLOBAL = 1u << 14;

struct alignas(64) Maps { CUtensorMap x, gu, kv, q64, gu64, wdw, wdx, wow, wdn128, wdn96, won128; };

}

__device__ uint4 g_part[16 * 2 * 4 * 4 * 1024];
__device__ uint4 g_hx[16 * 8 * 5 * 1024];
__device__ float g_kvacc[2 * 8 * 4 * 272];
__device__ unsigned g_kvcnt[8 * 32];
__device__ unsigned g_epoch[128];
#define TS(role, idx)
#define TS2(idx)
#define TSG(role, idx)

namespace {

__device__ __forceinline__ void mbar_init(uint32_t bar, uint32_t cnt) { asm volatile("mbarrier.init.shared::cta.b64 [%0], %1;" :: "r"(bar), "r"(cnt) : "memory"); }
__device__ __forceinline__ void mbar_expect(uint32_t bar, uint32_t bytes) { asm volatile("mbarrier.arrive.expect_tx.shared::cta.b64 _, [%0], %1;" :: "r"(bar), "r"(bytes) : "memory"); }
__device__ __forceinline__ void mbar_arrive(uint32_t bar) { asm volatile("mbarrier.arrive.shared::cta.b64 _, [%0];" :: "r"(bar) : "memory"); }
__device__ __forceinline__ void mbar_arrive_cta(uint32_t bar, uint32_t cta) {
    asm volatile("{\n.reg .b32 ra;\nmapa.shared::cluster.u32 ra, %0, %1;\nmbarrier.arrive.shared::cluster.b64 _, [ra];\n}" :: "r"(bar), "r"(cta) : "memory");
}
__device__ __forceinline__ void mbar_wait(uint32_t bar, uint32_t parity) {
    uint32_t ok, it = 0;
    do {
        asm volatile("{\n.reg .pred p;\nmbarrier.try_wait.parity.shared::cta.b64 p, [%1], %2;\nselp.u32 %0, 1, 0, p;\n}" : "=r"(ok) : "r"(bar), "r"(parity) : "memory");
    } while (!ok && ++it < SPIN_MBAR);
}
__device__ __forceinline__ void tma2(uint32_t dst, const CUtensorMap* m, int c0, int c1, uint32_t bar) {
    asm volatile("cp.async.bulk.tensor.2d.shared::cluster.global.mbarrier::complete_tx::bytes [%0], [%1, {%3, %4}], [%2];"
        :: "r"(dst), "l"(m), "r"(bar), "r"(c0), "r"(c1) : "memory");
}
__device__ __forceinline__ void tmaw2(uint32_t dst, const CUtensorMap* m, int c0, int c1, uint32_t bar) {
    tma2(dst, m, c0, c1, bar);
}
__device__ __forceinline__ void tmaw3(uint32_t dst, const CUtensorMap* m, int c0, int c1, int c2, uint32_t bar) {
    asm volatile("cp.async.bulk.tensor.3d.shared::cluster.global.mbarrier::complete_tx::bytes [%0], [%1, {%3, %4, %5}], [%2];"
        :: "r"(dst), "l"(m), "r"(bar), "r"(c0), "r"(c1), "r"(c2) : "memory");
}
__device__ __forceinline__ void tmaw4(uint32_t dst, const CUtensorMap* m, int c0, int c1, int c2, int c3, uint32_t bar) {
    asm volatile("cp.async.bulk.tensor.4d.shared::cluster.global.mbarrier::complete_tx::bytes [%0], [%1, {%3, %4, %5, %6}], [%2];"
        :: "r"(dst), "l"(m), "r"(bar), "r"(c0), "r"(c1), "r"(c2), "r"(c3) : "memory");
}
__device__ __forceinline__ void l2_prefetch(const void* p, uint32_t bytes) { asm volatile("cp.async.bulk.prefetch.L2.global [%0], %1;" :: "l"(p), "r"(bytes) : "memory"); }
__device__ __forceinline__ void wg_fence() { asm volatile("wgmma.fence.sync.aligned;" ::: "memory"); }
__device__ __forceinline__ void wg_commit() { asm volatile("wgmma.commit_group.sync.aligned;" ::: "memory"); }
template <int N> __device__ __forceinline__ void wg_wait() { asm volatile("wgmma.wait_group.sync.aligned %0;" :: "n"(N) : "memory"); }
template <int N> __device__ __forceinline__ void pin(float (&d)[N]) {
#pragma unroll
    for (int i = 0; i < N; i++) asm volatile("" : "+f"(d[i]) :: "memory");
}
__device__ __forceinline__ uint32_t pack2(float lo, float hi) { uint32_t r; asm("cvt.rn.bf16x2.f32 %0, %1, %2;" : "=r"(r) : "f"(hi), "f"(lo)); return r; }
__device__ __forceinline__ float phi(float t) {
    float e;
    asm("ex2.approx.ftz.f32 %0, %1;" : "=f"(e) : "f"(fminf(t * 1.4426950408889634f, 0.f)));
    return e + (fmaxf(t, 0.f) + 1e-6f);
}
__device__ __forceinline__ void stsm4(uint32_t a, uint32_t r0, uint32_t r1, uint32_t r2, uint32_t r3) {
    asm volatile("stmatrix.sync.aligned.m8n8.x4.shared.b16 [%0], {%1,%2,%3,%4};" :: "r"(a), "r"(r0), "r"(r1), "r"(r2), "r"(r3) : "memory");
}
__device__ __forceinline__ void mma16816(float (&c)[4], uint32_t a0, uint32_t a1, uint32_t a2, uint32_t a3, uint32_t b0, uint32_t b1) {
    asm volatile("mma.sync.aligned.m16n8k16.row.col.f32.bf16.bf16.f32 {%0,%1,%2,%3}, {%4,%5,%6,%7}, {%8,%9}, {%0,%1,%2,%3};"
        : "+f"(c[0]), "+f"(c[1]), "+f"(c[2]), "+f"(c[3]) : "r"(a0), "r"(a1), "r"(a2), "r"(a3), "r"(b0), "r"(b1));
}
__device__ __forceinline__ float bf_lo(uint32_t w) { return __uint_as_float(w << 16); }
__device__ __forceinline__ float bf_hi(uint32_t w) { return __uint_as_float(w & 0xffff0000u); }
__device__ __forceinline__ void st_pkt(uint4* p, uint32_t w0, uint32_t w1, uint32_t w2, uint32_t w3) {
    asm volatile("{\n.reg .b64 lo, hi;\n.reg .b128 v;\nmov.b64 lo, {%1, %2};\nmov.b64 hi, {%3, %4};\nmov.b128 v, {lo, hi};\nst.relaxed.gpu.global.b128 [%0], v;\n}"
        :: "l"(p), "r"(w0), "r"(w1), "r"(w2), "r"(w3) : "memory");
}
__device__ __forceinline__ void ld_pkt(const uint4* p, uint32_t& w0, uint32_t& w1, uint32_t& w2, uint32_t& w3) {
    asm volatile("{\n.reg .b64 lo, hi;\n.reg .b128 v;\nld.relaxed.gpu.global.b128 v, [%4];\nmov.b128 {lo, hi}, v;\nmov.b64 {%0, %1}, lo;\nmov.b64 {%2, %3}, hi;\n}"
        : "=r"(w0), "=r"(w1), "=r"(w2), "=r"(w3) : "l"(p) : "memory");
}

__device__ __forceinline__ void wg_ss128(float (&d)[64], uint32_t alo, uint32_t ahi, uint32_t blo, uint32_t bhi) {
    asm volatile("{\n.reg .b64 da, db;\nmov.b64 da, {%64, %65};\nmov.b64 db, {%66, %67};\n"
        "wgmma.mma_async.sync.aligned.m64n128k16.f32.bf16.bf16 {%0,%1,%2,%3,%4,%5,%6,%7,%8,%9,%10,%11,%12,%13,%14,%15,%16,%17,%18,%19,%20,%21,%22,%23,%24,%25,%26,%27,%28,%29,%30,%31,%32,%33,%34,%35,%36,%37,%38,%39,%40,%41,%42,%43,%44,%45,%46,%47,%48,%49,%50,%51,%52,%53,%54,%55,%56,%57,%58,%59,%60,%61,%62,%63}, da, db, 1, 1, 1, 0, 1;\n}\n"
        : "+f"(d[0]),"+f"(d[1]),"+f"(d[2]),"+f"(d[3]),"+f"(d[4]),"+f"(d[5]),"+f"(d[6]),"+f"(d[7]),"+f"(d[8]),"+f"(d[9]),"+f"(d[10]),"+f"(d[11]),"+f"(d[12]),"+f"(d[13]),"+f"(d[14]),"+f"(d[15]),"+f"(d[16]),"+f"(d[17]),"+f"(d[18]),"+f"(d[19]),"+f"(d[20]),"+f"(d[21]),"+f"(d[22]),"+f"(d[23]),"+f"(d[24]),"+f"(d[25]),"+f"(d[26]),"+f"(d[27]),"+f"(d[28]),"+f"(d[29]),"+f"(d[30]),"+f"(d[31]),"+f"(d[32]),"+f"(d[33]),"+f"(d[34]),"+f"(d[35]),"+f"(d[36]),"+f"(d[37]),"+f"(d[38]),"+f"(d[39]),"+f"(d[40]),"+f"(d[41]),"+f"(d[42]),"+f"(d[43]),"+f"(d[44]),"+f"(d[45]),"+f"(d[46]),"+f"(d[47]),"+f"(d[48]),"+f"(d[49]),"+f"(d[50]),"+f"(d[51]),"+f"(d[52]),"+f"(d[53]),"+f"(d[54]),"+f"(d[55]),"+f"(d[56]),"+f"(d[57]),"+f"(d[58]),"+f"(d[59]),"+f"(d[60]),"+f"(d[61]),"+f"(d[62]),"+f"(d[63])
        : "r"(alo), "r"(ahi), "r"(blo), "r"(bhi));
}
__device__ __forceinline__ void wg_ss128_z(float (&d)[64], uint32_t alo, uint32_t ahi, uint32_t blo, uint32_t bhi) {
    asm volatile("{\n.reg .b64 da, db;\nmov.b64 da, {%64, %65};\nmov.b64 db, {%66, %67};\n"
        "wgmma.mma_async.sync.aligned.m64n128k16.f32.bf16.bf16 {%0,%1,%2,%3,%4,%5,%6,%7,%8,%9,%10,%11,%12,%13,%14,%15,%16,%17,%18,%19,%20,%21,%22,%23,%24,%25,%26,%27,%28,%29,%30,%31,%32,%33,%34,%35,%36,%37,%38,%39,%40,%41,%42,%43,%44,%45,%46,%47,%48,%49,%50,%51,%52,%53,%54,%55,%56,%57,%58,%59,%60,%61,%62,%63}, da, db, 0, 1, 1, 0, 1;\n}\n"
        : "=f"(d[0]),"=f"(d[1]),"=f"(d[2]),"=f"(d[3]),"=f"(d[4]),"=f"(d[5]),"=f"(d[6]),"=f"(d[7]),"=f"(d[8]),"=f"(d[9]),"=f"(d[10]),"=f"(d[11]),"=f"(d[12]),"=f"(d[13]),"=f"(d[14]),"=f"(d[15]),"=f"(d[16]),"=f"(d[17]),"=f"(d[18]),"=f"(d[19]),"=f"(d[20]),"=f"(d[21]),"=f"(d[22]),"=f"(d[23]),"=f"(d[24]),"=f"(d[25]),"=f"(d[26]),"=f"(d[27]),"=f"(d[28]),"=f"(d[29]),"=f"(d[30]),"=f"(d[31]),"=f"(d[32]),"=f"(d[33]),"=f"(d[34]),"=f"(d[35]),"=f"(d[36]),"=f"(d[37]),"=f"(d[38]),"=f"(d[39]),"=f"(d[40]),"=f"(d[41]),"=f"(d[42]),"=f"(d[43]),"=f"(d[44]),"=f"(d[45]),"=f"(d[46]),"=f"(d[47]),"=f"(d[48]),"=f"(d[49]),"=f"(d[50]),"=f"(d[51]),"=f"(d[52]),"=f"(d[53]),"=f"(d[54]),"=f"(d[55]),"=f"(d[56]),"=f"(d[57]),"=f"(d[58]),"=f"(d[59]),"=f"(d[60]),"=f"(d[61]),"=f"(d[62]),"=f"(d[63])
        : "r"(alo), "r"(ahi), "r"(blo), "r"(bhi));
}
__device__ __forceinline__ void wg_ss64(float (&d)[32], uint32_t alo, uint32_t ahi, uint32_t blo, uint32_t bhi) {
    asm volatile("{\n.reg .b64 da, db;\nmov.b64 da, {%32, %33};\nmov.b64 db, {%34, %35};\n"
        "wgmma.mma_async.sync.aligned.m64n64k16.f32.bf16.bf16 {%0,%1,%2,%3,%4,%5,%6,%7,%8,%9,%10,%11,%12,%13,%14,%15,%16,%17,%18,%19,%20,%21,%22,%23,%24,%25,%26,%27,%28,%29,%30,%31}, da, db, 1, 1, 1, 0, 1;\n}\n"
        : "+f"(d[0]),"+f"(d[1]),"+f"(d[2]),"+f"(d[3]),"+f"(d[4]),"+f"(d[5]),"+f"(d[6]),"+f"(d[7]),"+f"(d[8]),"+f"(d[9]),"+f"(d[10]),"+f"(d[11]),"+f"(d[12]),"+f"(d[13]),"+f"(d[14]),"+f"(d[15]),"+f"(d[16]),"+f"(d[17]),"+f"(d[18]),"+f"(d[19]),"+f"(d[20]),"+f"(d[21]),"+f"(d[22]),"+f"(d[23]),"+f"(d[24]),"+f"(d[25]),"+f"(d[26]),"+f"(d[27]),"+f"(d[28]),"+f"(d[29]),"+f"(d[30]),"+f"(d[31])
        : "r"(alo), "r"(ahi), "r"(blo), "r"(bhi));
}
__device__ __forceinline__ void wg_ss64_z(float (&d)[32], uint32_t alo, uint32_t ahi, uint32_t blo, uint32_t bhi) {
    asm volatile("{\n.reg .b64 da, db;\nmov.b64 da, {%32, %33};\nmov.b64 db, {%34, %35};\n"
        "wgmma.mma_async.sync.aligned.m64n64k16.f32.bf16.bf16 {%0,%1,%2,%3,%4,%5,%6,%7,%8,%9,%10,%11,%12,%13,%14,%15,%16,%17,%18,%19,%20,%21,%22,%23,%24,%25,%26,%27,%28,%29,%30,%31}, da, db, 0, 1, 1, 0, 1;\n}\n"
        : "=f"(d[0]),"=f"(d[1]),"=f"(d[2]),"=f"(d[3]),"=f"(d[4]),"=f"(d[5]),"=f"(d[6]),"=f"(d[7]),"=f"(d[8]),"=f"(d[9]),"=f"(d[10]),"=f"(d[11]),"=f"(d[12]),"=f"(d[13]),"=f"(d[14]),"=f"(d[15]),"=f"(d[16]),"=f"(d[17]),"=f"(d[18]),"=f"(d[19]),"=f"(d[20]),"=f"(d[21]),"=f"(d[22]),"=f"(d[23]),"=f"(d[24]),"=f"(d[25]),"=f"(d[26]),"=f"(d[27]),"=f"(d[28]),"=f"(d[29]),"=f"(d[30]),"=f"(d[31])
        : "r"(alo), "r"(ahi), "r"(blo), "r"(bhi));
}
__device__ __forceinline__ void wg_ss64t(float (&d)[32], uint32_t alo, uint32_t ahi, uint32_t blo, uint32_t bhi) {
    asm volatile("{\n.reg .b64 da, db;\nmov.b64 da, {%32, %33};\nmov.b64 db, {%34, %35};\n"
        "wgmma.mma_async.sync.aligned.m64n64k16.f32.bf16.bf16 {%0,%1,%2,%3,%4,%5,%6,%7,%8,%9,%10,%11,%12,%13,%14,%15,%16,%17,%18,%19,%20,%21,%22,%23,%24,%25,%26,%27,%28,%29,%30,%31}, da, db, 1, 1, 1, 1, 1;\n}\n"
        : "+f"(d[0]),"+f"(d[1]),"+f"(d[2]),"+f"(d[3]),"+f"(d[4]),"+f"(d[5]),"+f"(d[6]),"+f"(d[7]),"+f"(d[8]),"+f"(d[9]),"+f"(d[10]),"+f"(d[11]),"+f"(d[12]),"+f"(d[13]),"+f"(d[14]),"+f"(d[15]),"+f"(d[16]),"+f"(d[17]),"+f"(d[18]),"+f"(d[19]),"+f"(d[20]),"+f"(d[21]),"+f"(d[22]),"+f"(d[23]),"+f"(d[24]),"+f"(d[25]),"+f"(d[26]),"+f"(d[27]),"+f"(d[28]),"+f"(d[29]),"+f"(d[30]),"+f"(d[31])
        : "r"(alo), "r"(ahi), "r"(blo), "r"(bhi));
}
__device__ __forceinline__ void wg_ss64t_z(float (&d)[32], uint32_t alo, uint32_t ahi, uint32_t blo, uint32_t bhi) {
    asm volatile("{\n.reg .b64 da, db;\nmov.b64 da, {%32, %33};\nmov.b64 db, {%34, %35};\n"
        "wgmma.mma_async.sync.aligned.m64n64k16.f32.bf16.bf16 {%0,%1,%2,%3,%4,%5,%6,%7,%8,%9,%10,%11,%12,%13,%14,%15,%16,%17,%18,%19,%20,%21,%22,%23,%24,%25,%26,%27,%28,%29,%30,%31}, da, db, 0, 1, 1, 1, 1;\n}\n"
        : "=f"(d[0]),"=f"(d[1]),"=f"(d[2]),"=f"(d[3]),"=f"(d[4]),"=f"(d[5]),"=f"(d[6]),"=f"(d[7]),"=f"(d[8]),"=f"(d[9]),"=f"(d[10]),"=f"(d[11]),"=f"(d[12]),"=f"(d[13]),"=f"(d[14]),"=f"(d[15]),"=f"(d[16]),"=f"(d[17]),"=f"(d[18]),"=f"(d[19]),"=f"(d[20]),"=f"(d[21]),"=f"(d[22]),"=f"(d[23]),"=f"(d[24]),"=f"(d[25]),"=f"(d[26]),"=f"(d[27]),"=f"(d[28]),"=f"(d[29]),"=f"(d[30]),"=f"(d[31])
        : "r"(alo), "r"(ahi), "r"(blo), "r"(bhi));
}
__device__ __forceinline__ void wg_ss8t(float (&d)[4], uint32_t alo, uint32_t ahi, uint32_t blo, uint32_t bhi) {
    asm volatile("{\n.reg .b64 da, db;\nmov.b64 da, {%4, %5};\nmov.b64 db, {%6, %7};\n"
        "wgmma.mma_async.sync.aligned.m64n8k16.f32.bf16.bf16 {%0,%1,%2,%3}, da, db, 1, 1, 1, 1, 0;\n}\n"
        : "+f"(d[0]),"+f"(d[1]),"+f"(d[2]),"+f"(d[3])
        : "r"(alo), "r"(ahi), "r"(blo), "r"(bhi));
}
__device__ __forceinline__ void wg_ss8t_z(float (&d)[4], uint32_t alo, uint32_t ahi, uint32_t blo, uint32_t bhi) {
    asm volatile("{\n.reg .b64 da, db;\nmov.b64 da, {%4, %5};\nmov.b64 db, {%6, %7};\n"
        "wgmma.mma_async.sync.aligned.m64n8k16.f32.bf16.bf16 {%0,%1,%2,%3}, da, db, 0, 1, 1, 1, 0;\n}\n"
        : "=f"(d[0]),"=f"(d[1]),"=f"(d[2]),"=f"(d[3])
        : "r"(alo), "r"(ahi), "r"(blo), "r"(bhi));
}

constexpr uint32_t DH128 = 64u | 0x40000000u;
constexpr uint32_t DH64 = 32u | 0x80000000u;
constexpr uint32_t LBO4K = (4096u >> 4) << 16, LBO8K = (8192u >> 4) << 16, LBO1 = 1u << 16;

template <bool SW64, bool FIRST> __device__ __forceinline__ void g1_issue(float (&acc)[64], uint32_t alo, uint32_t blo) {
    wg_fence();
#pragma unroll
    for (int k = 0; k < 4; k++) {
        if (FIRST && k == 0) wg_ss128_z(acc, alo, DH128, blo, SW64 ? DH64 : DH128);
        else wg_ss128(acc, alo + 2 * k, DH128, blo + (SW64 ? 64 * k : 128 * k), SW64 ? DH64 : DH128);
    }
    wg_commit();
}

template <int N> __device__ __forceinline__ void stash(uint32_t base, uint32_t sw, const uint32_t (&f)[N]) {
#pragma unroll
    for (int t = 0; t < N / 4; t++) stsm4(base + ((sw ^ (2 * t)) << 4), f[4 * t], f[4 * t + 1], f[4 * t + 2], f[4 * t + 3]);
}

template <int V0, int V1, int N> __device__ __forceinline__ void send_frag(const uint32_t (&f)[N], uint4* p, uint32_t tag) {
#pragma unroll
    for (int v = V0; v < V1; v++) st_pkt(p + (v & 3) * 32, (f[4 * v] & ~1u) | tag, f[4 * v + 1], f[4 * v + 2], f[4 * v + 3]);
}
template <int N> __device__ __forceinline__ void pack_acc(uint32_t (&f)[N], const float (&acc)[2 * N]) {
#pragma unroll
    for (int i = 0; i < N; i++) f[i] = pack2(acc[2 * i], acc[2 * i + 1]);
}
template <int N> __device__ __forceinline__ void recv_issue(uint32_t (&q)[N], const uint4* p) {
#pragma unroll
    for (int v = 0; v < N / 4; v++) ld_pkt(p + v * 32, q[4 * v], q[4 * v + 1], q[4 * v + 2], q[4 * v + 3]);
}
template <int N> __device__ __forceinline__ void recv_check(uint32_t (&q)[N], const uint4* p, uint32_t tag) {
    uint32_t it = 0;
    while (true) {
        uint32_t bad = 0;
#pragma unroll
        for (int v = 0; v < N / 4; v++) bad |= q[4 * v] ^ tag;
        if (__all_sync(0xffffffffu, (bad & 1u) == 0) || ++it > SPIN_GLOBAL) break;
        recv_issue(q, p);
    }
}
template <bool FIRST> __device__ __forceinline__ void accum(const uint32_t (&q)[16], float (&sum)[32]) {
#pragma unroll
    for (int i = 0; i < 16; i++) {
        if (FIRST) { sum[2 * i] = bf_lo(q[i]); sum[2 * i + 1] = bf_hi(q[i]); }
        else { sum[2 * i] += bf_lo(q[i]); sum[2 * i + 1] += bf_hi(q[i]); }
    }
}

}

__global__ void __launch_bounds__(384, 1)
fused_kernel(const __grid_constant__ Maps maps, const __nv_bfloat16* __restrict__ gate_w,
             const char* __restrict__ pf_qkv, const char* __restrict__ pf_g, const char* __restrict__ pf_u,
             const char* __restrict__ pf_d, const char* __restrict__ pf_o, __nv_bfloat16* __restrict__ out) {
    extern __shared__ __align__(1024) uint8_t smem_raw[];
    const uint32_t sb = (uint32_t)__cvta_generic_to_shared(smem_raw);
    const int tid = threadIdx.x, lane = tid & 31;
    const int warp = __shfl_sync(0xffffffffu, tid >> 5, 0);
    const int j = (blockIdx.x >> 1) & 7;
    const int r = ((blockIdx.x >> 4) << 1) | (blockIdx.x & 1);
    const uint32_t rank = blockIdx.x & 1;

    if (warp == 0) { TSG(0, 30); TS(0, 0); }
    if (warp == 9 && lane < 11) asm volatile("prefetch.tensormap [%0];" :: "l"(&maps.x + lane) : "memory");
    if (tid == 256) {
        for (int i = 0; i < 5; i++) { mbar_init(sb + B_FULL + 8 * i, 1); mbar_init(sb + B_EMPTY + 8 * i, MC ? 4 : 2); }
        for (int i = 0; i < 8; i++) mbar_init(sb + B_XFULL + 8 * i, 1);
        mbar_init(sb + B_GRDY, 3); mbar_init(sb + B_KVDONE, 8); mbar_init(sb + B_KVRDY, 2);
        asm volatile("fence.mbarrier_init.release.cluster;" ::: "memory");
        asm volatile("fence.proxy.async.shared::cta;" ::: "memory");
        mbar_expect(sb + B_XFULL, 16384);
        tma2(sb + OFF_X, &maps.x, 0, r * 128, sb + B_XFULL);
    }
    __syncthreads();

    if (warp >= 8) {
        asm volatile("setmaxnreg.dec.sync.aligned.u32 56;");
        if (warp == 8) {
            if (lane == 0) {
                int slot = 0, ph = 1;
                uint32_t full, dst;
#define P_BEGIN(S, BYTES) full = sb + B_FULL + 8 * slot; dst = sb + OFF_RING + slot * 16384; \
                mbar_wait(sb + B_EMPTY + 8 * slot, ph); TS2(S); mbar_expect(full, BYTES); if (!MC || (((S) ^ rank) & 1) == 0)
#define P_END() if (++slot == 5) { slot = 0; ph ^= 1; }
                for (int s = 0; s < 16; s++) {
                    P_BEGIN(s, 16384) {
                        if (s & 1) tmaw3(dst, &maps.kv, 64 * j, 32 * (s - 1), 1, full);
                        else tmaw3(dst, &maps.gu, 224 * j, 32 * s, 0, full);
                    }
                    const int xb = (s == 4) ? 3 : !(s & 1) ? 0 : (s < 5) ? (s + 1) / 2 : (s <= 11) ? (s + 3) / 2 : 0;
                    if (xb) { mbar_expect(sb + B_XFULL + 8 * xb, 16384); tma2(sb + OFF_X + xb * 16384, &maps.x, 64 * xb, r * 128, sb + B_XFULL + 8 * xb); }
                    P_END()
                }
                for (int s = 0; s < 8; s++) {
                    P_BEGIN(16 + s, 16384) {
                        tmaw3(dst, &maps.q64, 0, 64 * s, 2 * j, full);
                        tmaw3(dst + 8192, &maps.gu64, 224 * j + 192, 64 * s, 0, full);
                    }
                    P_END()
                }
                for (int s = 0; s < 16; s++) {
                    P_BEGIN(24 + s, 16384) tmaw3(dst, &maps.gu, 224 * j + 64 + 64 * (s >> 3), 64 * (s & 7), 0, full);
                    P_END()
                }
                const int p = j >> 1, ro = 224 * j, rp = 224 * (j ^ 1);
                const int cw = (j & 1) * 4 + 2 * ((p >> 1) ^ 1);
                P_BEGIN(40, 16384) tmaw3(dst, &maps.wdw, 0, ro, cw, full); P_END()
                P_BEGIN(41, 16384) tmaw3(dst, &maps.wdw, 0, ro + 64, cw, full); P_END()
                P_BEGIN(42, 16384) tmaw3(dst, &maps.wdw, 0, rp, cw, full); P_END()
                P_BEGIN(43, 16384) tmaw3(dst, &maps.wdw, 0, rp + 64, cw, full); P_END()
                P_BEGIN(44, 16384) tmaw4(dst, &maps.wdx, 0, 448 * p + 192, 0, cw, full); P_END()
                P_BEGIN(45, 16384) tmaw3(dst, &maps.wow, 0, 128 * p, cw, full); P_END()
                P_BEGIN(46, 16384) tmaw3(dst, &maps.wow, 0, 128 * p + 64, cw, full); P_END()
                P_BEGIN(47, 16384) tmaw3(dst, &maps.wdw, 0, ro + 128, cw, full); P_END()
                P_BEGIN(48, 16384) tmaw3(dst, &maps.wdw, 0, rp + 128, cw, full); P_END()
                for (int q = 0; q < 2; q++) {
                    const int cn = (j & 1) * 256 + 64 * (p ^ (q ^ 1));
                    P_BEGIN(49 + 5 * q, 16384) tmaw2(dst, &maps.wdn128, cn, ro, full); P_END()
                    P_BEGIN(50 + 5 * q, 16384) tmaw2(dst, &maps.wdn128, cn, rp, full); P_END()
                    P_BEGIN(51 + 5 * q, 16384) tmaw2(dst, &maps.won128, cn, 128 * p, full); P_END()
                    P_BEGIN(52 + 5 * q, 12288) tmaw2(dst, &maps.wdn96, cn, ro + 128, full); P_END()
                    P_BEGIN(53 + 5 * q, 12288) tmaw2(dst, &maps.wdn96, cn, rp + 128, full); P_END()
                }
            }
        } else if (warp < 11) {
            const int hx = warp - 9;
            {
                float s[16];
#pragma unroll
                for (int i = 0; i < 16; i++) s[i] = 0.f;
                const uint32_t xa = sb + OFF_X + (hx * 64 + (lane >> 3)) * 128;
                const uint32_t sw0 = ((lane & 7) ^ (lane >> 3)) << 4;
                const uint32_t gws = sb + OFF_KVF + hx * 1024;
                {
                    const uint4 t0 = __ldg((const uint4*)gate_w + lane), t1 = __ldg((const uint4*)gate_w + 32 + lane);
                    asm volatile("st.shared.v4.u32 [%0], {%1,%2,%3,%4};" :: "r"(gws + lane * 16), "r"(t0.x), "r"(t0.y), "r"(t0.z), "r"(t0.w) : "memory");
                    asm volatile("st.shared.v4.u32 [%0], {%1,%2,%3,%4};" :: "r"(gws + 512 + lane * 16), "r"(t1.x), "r"(t1.y), "r"(t1.z), "r"(t1.w) : "memory");
                    __syncwarp();
                }
#pragma unroll 1
                for (int kb = 0; kb < 8; kb++) {
                    uint4 wv;
                    asm volatile("ld.shared.v4.u32 {%0,%1,%2,%3}, [%4];" : "=r"(wv.x), "=r"(wv.y), "=r"(wv.z), "=r"(wv.w) : "r"(gws + kb * 128 + (lane & 7) * 16) : "memory");
                    const float w0 = bf_lo(wv.x), w1 = bf_hi(wv.x), w2 = bf_lo(wv.y), w3 = bf_hi(wv.y);
                    const float w4 = bf_lo(wv.z), w5 = bf_hi(wv.z), w6 = bf_lo(wv.w), w7 = bf_hi(wv.w);
                    mbar_wait(sb + B_XFULL + 8 * kb, 0);
#pragma unroll
                    for (int i = 0; i < 16; i++) {
                        uint4 v;
                        asm volatile("ld.shared.v4.u32 {%0,%1,%2,%3}, [%4];" : "=r"(v.x), "=r"(v.y), "=r"(v.z), "=r"(v.w)
                                     : "r"(xa + kb * 16384 + i * 512 + (sw0 ^ ((i & 1) << 6))));
                        float t0 = fmaf(bf_lo(v.x), w0, s[i]), t1 = bf_hi(v.x) * w1;
                        t0 = fmaf(bf_lo(v.y), w2, t0); t1 = fmaf(bf_hi(v.y), w3, t1);
                        t0 = fmaf(bf_lo(v.z), w4, t0); t1 = fmaf(bf_hi(v.z), w5, t1);
                        t0 = fmaf(bf_lo(v.w), w6, t0); t1 = fmaf(bf_hi(v.w), w7, t1);
                        s[i] = t0 + t1;
                    }
                }
#pragma unroll
                for (int i = 0; i < 16; i++) {
                    s[i] += __shfl_xor_sync(0xffffffffu, s[i], 1);
                    s[i] += __shfl_xor_sync(0xffffffffu, s[i], 2);
                    s[i] += __shfl_xor_sync(0xffffffffu, s[i], 4);
                    if ((lane & 7) == (i & 7))
                        asm volatile("st.shared.f32 [%0], %1;" :: "r"(sb + OFF_G + (hx * 64 + i * 4 + (lane >> 3)) * 4), "f"(1.f / (1.f + __expf(-s[i]))) : "memory");
                }
                __syncwarp();
                if (lane == 0) mbar_arrive(sb + B_GRDY);
            }
            TS(2 + hx, 1);
            mbar_wait(sb + B_GRDY, 0);
            uint32_t epoch;
            asm volatile("ld.shared.u32 %0, [%1];" : "=r"(epoch) : "r"(sb + OFF_EPOCH) : "memory");
            const float* accp = g_kvacc + (((epoch & 1) * 8 + j) * 4 + 2 * hx) * 272;
            unsigned* cnt = g_kvcnt + j * 32;
            if (hx == 0) {
                mbar_wait(sb + B_KVDONE, 0);
                TS(2, 5);
                if (lane == 0) asm volatile("red.release.gpu.global.add.u32 [%0], 1;" :: "l"(cnt) : "memory");
                __syncwarp();
            }
            TS(2 + hx, 2);
            {
                const unsigned target = 16u * (epoch + 1);
                uint32_t it = 0, v;
                do {
                    asm volatile("ld.acquire.gpu.global.u32 %0, [%1];" : "=r"(v) : "l"(cnt) : "memory");
                } while ((int)(v - target) < 0 && ++it < SPIN_GLOBAL);
            }
            TS(2 + hx, 3);
#pragma unroll
            for (int h = 0; h < 2; h++) {
                const float4 d0 = __ldcg((const float4*)(accp + h * 272) + lane);
                const float4 d1 = __ldcg((const float4*)(accp + h * 272 + 128) + lane);
                const float2 z0 = __ldcg((const float2*)(accp + h * 272 + 256) + (lane & 3));
                const float2 z1 = __ldcg((const float2*)(accp + h * 272 + 264) + (lane & 3));
                asm volatile("st.shared.v4.u32 [%0], {%1,%2,%3,%4};" :: "r"(sb + OFF_KVF + (2 * hx + h) * 512 + lane * 16),
                             "r"(pack2(d0.x, d0.y)), "r"(pack2(d1.x, d1.y)), "r"(pack2(d0.z, d0.w)), "r"(pack2(d1.z, d1.w)) : "memory");
                if (lane < 4) asm volatile("st.shared.v2.u32 [%0], {%1,%2};" :: "r"(sb + OFF_ZF + (2 * hx + h) * 32 + lane * 8), "r"(pack2(z0.x, z0.y)), "r"(pack2(z1.x, z1.y)) : "memory");
            }
            __syncwarp();
            if (lane == 0) mbar_arrive(sb + B_KVRDY);
            TS(2 + hx, 4);
        } else {
            uint32_t epoch = 0;
            asm volatile("st.shared.u32 [%0], %1;" :: "r"(sb + OFF_ONES + lane * 4), "r"(0x3f803f80u) : "memory");
            asm volatile("fence.proxy.async.shared::cta;" ::: "memory");
            __syncwarp();
            if (lane == 0) {
                asm volatile("ld.relaxed.gpu.global.u32 %0, [%1];" : "=r"(epoch) : "l"(g_epoch + blockIdx.x) : "memory");
                asm volatile("st.shared.u32 [%0], %1;" :: "r"(sb + OFF_EPOCH), "r"(epoch) : "memory");
                mbar_arrive(sb + B_GRDY);
                g_epoch[blockIdx.x] = epoch + 1;
            }
            epoch = __shfl_sync(0xffffffffu, epoch, 0);
            if (r == 0) {
                float4* zp = (float4*)(g_kvacc + (((epoch & 1) ^ 1) * 8 + j) * 4 * 272);
                for (int i = lane; i < 272; i += 32) zp[i] = make_float4(0.f, 0.f, 0.f, 0.f);
            }
            mbar_wait(sb + B_XFULL, 0);
            const int b = blockIdx.x;
            if (lane == 0) l2_prefetch(pf_qkv + b * 12288, 12288);
            if (lane == 1) l2_prefetch(pf_g + b * 14336, 14336);
            if (lane == 2) l2_prefetch(pf_u + b * 14336, 14336);
            mbar_wait(sb + B_XFULL + 8 * 7, 0);
            if (lane == 0) l2_prefetch(pf_d + b * 14336, 14336);
            if (lane == 1) l2_prefetch(pf_o + b * 4096, 4096);
        }
    } else {
        asm volatile("setmaxnreg.inc.sync.aligned.u32 224;");
        const int wg = warp >> 2;
        const bool elect = (tid & 127) == 0;
        const uint32_t xlo = ((sb + OFF_X + wg * 8192) >> 4) | LBO1;
        const uint32_t ringlo = (sb + OFF_RING) >> 4;
        int slot = 0, ph = 0, prev = 0;
        auto release = [&](int s) {
            if (elect) {
                mbar_arrive(sb + B_EMPTY + 8 * s);
            }
        };
        auto adv = [&]() { prev = slot; if (++slot == 5) { slot = 0; ph ^= 1; } };

        int pidx = 64;
#define G1_STAGE(acc, SW, KB, FIRST) do { mbar_wait(sb + B_FULL + 8 * slot, ph); if (PROF) { if (tid == 0) TS2(pidx); pidx++; } \
            g1_issue<SW, FIRST>(acc, xlo + (KB) * 1024, (ringlo + slot * 1024) | (SW ? LBO4K : LBO8K)); } while (0)
#define G1_RETIRE() do { wg_wait<1>(); release(prev); adv(); } while (0)
#define A2_SYNC() do { asm volatile("fence.proxy.async.shared::cta;" ::: "memory"); asm volatile("bar.sync %0, 128;" :: "r"(wg + 1) : "memory"); } while (0)
#define H_EPI(acc, F, N, OG, OU) _Pragma("unroll") for (int i = 0; i < (N); i++) { \
            const float m_ = (i & 1) ? m_hi : m_lo; \
            F[i] = pack2(acc[(OG) + 2 * i] * acc[(OU) + 2 * i] * m_, acc[(OG) + 2 * i + 1] * acc[(OU) + 2 * i + 1] * m_); }

        float a0[64], b0[64], a1[64], a2_[64], a3[64];
        mbar_wait(sb + B_XFULL, 0);
        G1_STAGE(a0, false, 0, 1); adv();
        if ((warp & 3) == 0) TS(wg, 1);
        G1_STAGE(b0, false, 0, 1); G1_RETIRE();
#pragma unroll 1
        for (int kb = 1; kb < 8; kb++) {
            mbar_wait(sb + B_XFULL + 8 * kb, 0);
            if (PROF && tid == 0) TS2(128 + kb);
            G1_STAGE(a0, false, kb, 0); G1_RETIRE();
            G1_STAGE(b0, false, kb, 0); G1_RETIRE();
        }
        pin(a0);
        mbar_wait(sb + B_GRDY, 0);
        float g_lo, g_hi;
        uint32_t tag;
        {
            const uint32_t ga = sb + OFF_G + (warp * 16 + (lane >> 2)) * 4;
            asm volatile("ld.shared.f32 %0, [%1];" : "=f"(g_lo) : "r"(ga) : "memory");
            asm volatile("ld.shared.f32 %0, [%1];" : "=f"(g_hi) : "r"(ga + 32) : "memory");
            asm volatile("ld.shared.u32 %0, [%1];" : "=r"(tag) : "r"(sb + OFF_EPOCH) : "memory");
        }
        float* const kvp = g_kvacc + (((tag & 1) * 8 + j) * 4 + (warp & 3)) * 272;
        tag = (tag + 1) & 1;
        const float m_lo = 1.f - g_lo, m_hi = 1.f - g_hi;
        if ((warp & 3) == 0) TS(wg, 2);
        uint32_t fh0[16], fh1[16], fh2[16], fh3[8], fo[16];
        H_EPI(a0, fh0, 16, 0, 32);

        const uint32_t lrow = ((lane & 7) + 8 * ((lane >> 3) & 1)) * 128;
        const uint32_t srow = (warp & 3) * 2048 + lrow;
        const uint32_t ssw = (lane >> 4) ^ (lane & 7);
        uint4* const hsend = g_hx + (size_t)((r * 8 + j) * 5) * 1024 + warp * 128 + lane;
        const uint4* const hrecv = g_hx + (size_t)((r * 8 + (j ^ 1)) * 5) * 1024 + warp * 128 + lane;

        {
            uint32_t pk[16], pv[16];
            float kv[32], zs[4];
            const uint32_t stg = sb + OFF_STG + wg * 8192;
            const uint32_t klo = (stg >> 4) | LBO1, vlo = klo + 256, olo = (sb + OFF_ONES) >> 4;
            G1_STAGE(a1, true, 0, 1); G1_RETIRE();
            pin(b0);
            G1_STAGE(a1, true, 1, 0);
#pragma unroll
            for (int i = 0; i < 8; i++) pk[i] = pack2(phi(b0[2 * i]), phi(b0[2 * i + 1]));
            send_frag<0, 4>(fh0, hsend, tag);
            G1_RETIRE();
            G1_STAGE(a1, true, 2, 0);
#pragma unroll
            for (int i = 8; i < 16; i++) pk[i] = pack2(phi(b0[2 * i]), phi(b0[2 * i + 1]));
#pragma unroll
            for (int i = 0; i < 16; i++) pv[i] = pack2(b0[32 + 2 * i], b0[32 + 2 * i + 1]);
            if (!(warp & 2)) { stash<16>(stg + (warp & 1) * 2048 + lrow, ssw, pk); stash<16>(stg + 4096 + (warp & 1) * 2048 + lrow, ssw, pv); }
            G1_RETIRE();
            A2_SYNC();
            wg_fence();
            wg_ss64t_z(kv, vlo, DH128, klo, DH128); wg_ss64t(kv, vlo + 128, DH128, klo + 128, DH128);
            wg_ss8t_z(zs, klo, DH128, olo, 0); wg_ss8t(zs, klo + 128, DH128, olo, 0);
            wg_commit();
            G1_STAGE(a1, true, 3, 0); G1_RETIRE();
            if (warp & 2) { stash<16>(stg + (warp & 1) * 2048 + lrow, ssw, pk); stash<16>(stg + 4096 + (warp & 1) * 2048 + lrow, ssw, pv); }
            A2_SYNC();
            wg_fence();
            wg_ss64t(kv, vlo, DH128, klo, DH128); wg_ss64t(kv, vlo + 128, DH128, klo + 128, DH128);
            wg_ss8t(zs, klo, DH128, olo, 0); wg_ss8t(zs, klo + 128, DH128, olo, 0);
            wg_commit();
            G1_STAGE(a1, true, 4, 0); G1_RETIRE();
            pin(kv); pin(zs);
            G1_STAGE(a1, true, 5, 0);
#define KV_RED(W) do { asm volatile("red.global.add.v4.f32 [%0], {%1,%2,%3,%4};" :: "l"(kvp + lane * 4), "f"(kv[8 * W]), "f"(kv[8 * W + 1]), "f"(kv[8 * W + 2]), "f"(kv[8 * W + 3]) : "memory"); \
                       asm volatile("red.global.add.v4.f32 [%0], {%1,%2,%3,%4};" :: "l"(kvp + 128 + lane * 4), "f"(kv[8 * W + 4]), "f"(kv[8 * W + 5]), "f"(kv[8 * W + 6]), "f"(kv[8 * W + 7]) : "memory"); } while (0)
            if ((warp & 3) == 0) KV_RED(0); else if ((warp & 3) == 1) KV_RED(1); else if ((warp & 3) == 2) KV_RED(2); else KV_RED(3);
            if ((lane & 3) == 0) {
                asm volatile("red.global.add.f32 [%0], %1;" :: "l"(kvp + 256 + (lane >> 2)), "f"(zs[0]) : "memory");
                asm volatile("red.global.add.f32 [%0], %1;" :: "l"(kvp + 264 + (lane >> 2)), "f"(zs[2]) : "memory");
            }
            __syncwarp();
            if (lane == 0) mbar_arrive(sb + B_KVDONE);
            G1_RETIRE();
        }
        G1_STAGE(a1, true, 6, 0); G1_RETIRE();
        G1_STAGE(a1, true, 7, 0); G1_RETIRE();
        if ((warp & 3) == 0) TS(wg, 3);

        G1_STAGE(a2_, false, 0, 1); G1_RETIRE();
        pin(a1);
        G1_STAGE(a2_, false, 1, 0);
#pragma unroll
        for (int i = 0; i < 8; i++) fo[i] = pack2(phi(a1[2 * i]), phi(a1[2 * i + 1]));
        G1_RETIRE();
        G1_STAGE(a2_, false, 2, 0);
#pragma unroll
        for (int i = 8; i < 16; i++) fo[i] = pack2(phi(a1[2 * i]), phi(a1[2 * i + 1]));
        G1_RETIRE();
        G1_STAGE(a2_, false, 3, 0);
        H_EPI(a1, fh3, 8, 32, 48);
        send_frag<0, 2>(fh3, hsend + 4 * 1024, tag);
        G1_RETIRE();
#pragma unroll 1
        for (int kb = 4; kb < 8; kb++) { G1_STAGE(a2_, false, kb, 0); G1_RETIRE(); }
        if ((warp & 3) == 0) TS(wg, 4);

        const uint32_t odd = j & 1;
        const uint32_t a2 = sb + OFF_X + wg * 8192 + srow;
        uint32_t qa[16], qb[16], qh[8];
        G1_STAGE(a3, false, 0, 1); G1_RETIRE();
        pin(a2_);
        G1_STAGE(a3, false, 1, 0);
        H_EPI(a2_, fh1, 16, 0, 32);
        send_frag<0, 4>(fh1, hsend + 1024, tag);
        recv_issue(qa, hrecv); recv_issue(qh, hrecv + 4 * 1024);
        G1_RETIRE();
        G1_STAGE(a3, false, 2, 0); stash<16>(a2, ssw, fh0); G1_RETIRE();
        G1_STAGE(a3, false, 3, 0); stash<16>(a2 + 16384, ssw, fh1); recv_issue(qb, hrecv + 1024); G1_RETIRE();
        G1_STAGE(a3, false, 4, 0); recv_check(qa, hrecv, tag); stash<16>(a2 + 2 * 16384, ssw, qa); G1_RETIRE();
        G1_STAGE(a3, false, 5, 0); recv_check(qb, hrecv + 1024, tag); stash<16>(a2 + 3 * 16384, ssw, qb); G1_RETIRE();
        G1_STAGE(a3, false, 6, 0);
        recv_check(qh, hrecv + 4 * 1024, tag);
        stash<8>(a2 + 4 * 16384, ssw ^ (odd << 2), fh3); stash<8>(a2 + 4 * 16384, ssw ^ (odd << 2) ^ 4, qh);
        if ((warp & 3) == 0) TS(wg, 5);
        mbar_wait(sb + B_KVRDY, 0);
        if ((warp & 3) == 0) TS(wg, 6);
#pragma unroll
        for (int h = 0; h < 4; h++) {
            uint32_t b0, b1, b2, b3, z0, z1;
            asm volatile("ld.shared.v4.u32 {%0,%1,%2,%3}, [%4];" : "=r"(b0), "=r"(b1), "=r"(b2), "=r"(b3) : "r"(sb + OFF_KVF + h * 512 + lane * 16) : "memory");
            asm volatile("ld.shared.v2.u32 {%0,%1}, [%2];" : "=r"(z0), "=r"(z1) : "r"(sb + OFF_ZF + h * 32 + (lane & 3) * 8) : "memory");
            float n0[4] = {0.f, 0.f, 0.f, 0.f}, n1[4] = {0.f, 0.f, 0.f, 0.f}, dn[4] = {0.f, 0.f, 0.f, 0.f};
            mma16816(dn, fo[4 * h], fo[4 * h + 1], fo[4 * h + 2], fo[4 * h + 3], z0, z1);
            mma16816(n0, fo[4 * h], fo[4 * h + 1], fo[4 * h + 2], fo[4 * h + 3], b0, b1);
            mma16816(n1, fo[4 * h], fo[4 * h + 1], fo[4 * h + 2], fo[4 * h + 3], b2, b3);
            const float s_lo = __fdividef(g_lo, dn[0] + 1e-6f), s_hi = __fdividef(g_hi, dn[2] + 1e-6f);
            fo[4 * h] = pack2(n0[0] * s_lo, n0[1] * s_lo); fo[4 * h + 1] = pack2(n0[2] * s_hi, n0[3] * s_hi);
            fo[4 * h + 2] = pack2(n1[0] * s_lo, n1[1] * s_lo); fo[4 * h + 3] = pack2(n1[2] * s_hi, n1[3] * s_hi);
        }
        send_frag<0, 4>(fo, hsend + 3 * 1024, tag);
        G1_RETIRE();
        G1_STAGE(a3, false, 7, 0);
        G1_RETIRE();
        A2_SYNC();
        if ((warp & 3) == 0) TS(wg, 7);

        const uint32_t slo = ((sb + OFF_STG + wg * 8192) >> 4) | LBO1;
#define G2_A(K) ((K) < 8 ? xlo + (K) * 1024 : slo)
#define G2_B(T) (ringlo + ((T) % 5) * 1024)
#define G2_WAIT(T) do { mbar_wait(sb + B_FULL + 8 * ((T) % 5), ((T) / 5) & 1); if (PROF && tid == 0) TS2(64 + 40 + (T)); } while (0)
#define G2_REL(T) do { if ((T) < 14) release((T) % 5); } while (0)
#define G2_W(T, acc) do { G2_WAIT(T); wg_fence(); _Pragma("unroll") for (int k = 0; k < 4; k++) { \
            if ((T) == 0 && k == 0) wg_ss128_z(acc, G2_A(T), DH128, G2_B(T) | LBO8K, DH128); \
            else wg_ss128(acc, G2_A(T) + 2 * k, DH128, (G2_B(T) | LBO8K) + 128 * k, DH128); } wg_commit(); } while (0)
        const uint32_t h3o = xlo + 4 * 1024 + 4 * odd, h3p = xlo + 4 * 1024 + 4 * (odd ^ 1);
#define G2_NA(U, k) ((U) < 2 ? G2_A(2 * (U) + ((k) >> 2)) + 2 * ((k) & 3) : (U) == 2 ? G2_A(5 + ((k) >> 2)) + 2 * ((k) & 3) : \
                     (k) < 4 ? G2_A((U) + 4) + 2 * (k) : ((U) == 3 ? h3o : h3p) + 2 * ((k) & 3))
#define G2_N(T, acc, U) do { G2_WAIT(T); wg_fence(); _Pragma("unroll") for (int k = 0; k < ((U) >= 3 ? 6 : 8); k++) { \
            if ((U) == 0 && k == 0) wg_ss64_z(acc, G2_A(0), DH128, G2_B(T) | LBO1, DH128); \
            else wg_ss64(acc, G2_NA(U, k), DH128, (G2_B(T) | LBO1) + 128 * k, DH128); } wg_commit(); } while (0)

        const int p = j >> 1;
        uint4* const pbase = g_part + (size_t)(r * 2 + (j & 1)) * 16384 + warp * 128 + lane;
        const int pw = (p & 2) ^ 2;
        auto other = [&](int d) { return d == 3 ? p ^ 1 : pw + d - 1; };
        auto sendp = [&](int d) { return pbase + ((other(d) * 4 + p) << 10); };
        auto recvp = [&](int d) { return pbase + ((p * 4 + other(d)) << 10); };

        float p1[64], p2[32], p3[32];
        G2_W(0, p1);
        wg_wait<1>();
        release(prev);
        pin(a3);
        G2_W(1, p1);
        H_EPI(a3, fh2, 16, 0, 32);
        send_frag<0, 4>(fh2, hsend + 2 * 1024, tag);
        recv_issue(qa, hrecv + 3 * 1024);
        stash<16>(a2 + 7 * 16384, ssw, fh2); stash<16>(a2 + (5 + odd) * 16384, ssw, fo);
        wg_wait<1>(); G2_REL(0);
        G2_W(2, p1); wg_wait<1>(); G2_REL(1);
        G2_W(3, p1);
        recv_check(qa, hrecv + 3 * 1024, tag); stash<16>(a2 + (6 - odd) * 16384, ssw, qa);
        wg_wait<1>(); G2_REL(2);
        G2_W(4, p1);
        recv_issue(qb, hrecv + 2 * 1024);
        wg_wait<1>(); G2_REL(3);
        A2_SYNC();
        G2_W(5, p1); wg_wait<1>(); G2_REL(4);
        G2_W(6, p1);
        recv_check(qb, hrecv + 2 * 1024, tag); stash<16>(sb + OFF_STG + wg * 8192 + srow, ssw, qb);
        wg_wait<1>(); G2_REL(5);
        G2_W(7, p1); wg_wait<1>(); G2_REL(6);
        A2_SYNC();
        G2_W(8, p1); wg_wait<1>(); G2_REL(7);
        if ((warp & 3) == 0) TS(wg, 8);
        uint32_t sp[32];
        G2_N(9, p2, 0); wg_wait<1>(); G2_REL(8);
        pin(p1);
        pack_acc(sp, p1);
        G2_N(10, p2, 1); send_frag<0, 2>(sp, sendp(1), tag); wg_wait<1>(); G2_REL(9);
        G2_N(11, p2, 2); send_frag<2, 4>(sp, sendp(1), tag); wg_wait<1>(); G2_REL(10);
        G2_N(12, p2, 3); send_frag<4, 6>(sp, sendp(2), tag); wg_wait<1>(); G2_REL(11);
        G2_N(13, p2, 4); send_frag<6, 8>(sp, sendp(2), tag); wg_wait<1>(); G2_REL(12);
        if ((warp & 3) == 0) TS(wg, 9);
        float sum[32];
        uint32_t qc[16];
        G2_N(14, p3, 0); wg_wait<1>(); G2_REL(13);
        pin(p2);
        pack_acc(qc, p2);
        send_frag<0, 4>(qc, sendp(3), tag);
        G2_N(15, p3, 1);
        recv_issue(qa, recvp(1)); recv_issue(qb, recvp(2));
        G2_N(16, p3, 2);
        G2_N(17, p3, 3);
        recv_issue(qc, recvp(3));
        G2_N(18, p3, 4);
        if ((warp & 3) == 0) TS(wg, 10);
        recv_check(qa, recvp(1), tag); accum<true>(qa, sum);
        recv_check(qb, recvp(2), tag); accum<false>(qb, sum);
        if ((warp & 3) == 0) TS(wg, 12);
        recv_check(qc, recvp(3), tag); accum<false>(qc, sum);
        if ((warp & 3) == 0) TS(wg, 13);
        wg_wait<0>();
        pin(p3);
        {
            uint32_t f[16];
#pragma unroll
            for (int i = 0; i < 16; i++) f[i] = pack2(p3[2 * i] + sum[2 * i], p3[2 * i + 1] + sum[2 * i + 1]);
            const uint32_t slab = sb + OFF_X + wg * 8192;
            stash<16>(slab + srow, ssw, f);
            __syncwarp();
            __nv_bfloat16* op = out + (size_t)(r * 128 + warp * 16 + (lane >> 3)) * kD + (j & 1) * 256 + p * 64 + (lane & 7) * 8;
#pragma unroll
            for (int i = 0; i < 4; i++) {
                const int row = i * 4 + (lane >> 3);
                uint4 v;
                asm volatile("ld.shared.v4.u32 {%0,%1,%2,%3}, [%4];" : "=r"(v.x), "=r"(v.y), "=r"(v.z), "=r"(v.w)
                             : "r"(slab + ((warp & 3) * 16 + row) * 128 + (((lane & 7) ^ (row & 7)) << 4)) : "memory");
                *(uint4*)(op + i * 4 * kD) = v;
            }
        }
        if ((warp & 3) == 0) { TS(wg, 14); TSG(wg, 31); }
    }
}

typedef CUresult (*EncodeFn)(CUtensorMap*, CUtensorMapDataType, cuuint32_t, void*, const cuuint64_t*, const cuuint64_t*, const cuuint32_t*,
                             const cuuint32_t*, CUtensorMapInterleave, CUtensorMapSwizzle, CUtensorMapL2promotion, CUtensorMapFloatOOBfill);

static void encode(EncodeFn fn, CUtensorMap* m, int rank, const void* base, const cuuint64_t (&gd)[4], const cuuint64_t (&gs)[3],
                   const cuuint32_t (&bd)[4], CUtensorMapSwizzle sw) {
    cuuint32_t es[4] = {1, 1, 1, 1};
    fn(m, CU_TENSOR_MAP_DATA_TYPE_BFLOAT16, rank, const_cast<void*>(base), gd, gs, bd, es, CU_TENSOR_MAP_INTERLEAVE_NONE, sw,
       CU_TENSOR_MAP_L2_PROMOTION_L2_128B, CU_TENSOR_MAP_FLOAT_OOB_FILL_NONE);
}

extern "C" void kernel_launch(void* const* d_in, const int* in_sizes, int n_in, void* d_out, int out_size) {
    const char* x = (const char*)d_in[0];
    const char* wqkv = (const char*)d_in[1];
    const char* wo = (const char*)d_in[2];
    const char* wg = (const char*)d_in[4];
    const char* wu = (const char*)d_in[5];
    const char* wd = (const char*)d_in[6];
    void* fnp = nullptr;
    cudaDriverEntryPointQueryResult qr;
    cudaGetDriverEntryPoint("cuTensorMapEncodeTiled", &fnp, cudaEnableDefault, &qr);
    EncodeFn fn = (EncodeFn)fnp;
    Maps maps;
    const char* lo = wg < wu ? wg : wu;
    const uint64_t diff = wg < wu ? (uint64_t)(wu - wg) : (uint64_t)(wg - wu);
    const CUtensorMapSwizzle S128 = CU_TENSOR_MAP_SWIZZLE_128B, S64 = CU_TENSOR_MAP_SWIZZLE_64B;
    encode(fn, &maps.x, 2, x, {512, 2048, 1, 1}, {1024, 0, 0}, {64, 128, 1, 1}, S128);
    encode(fn, &maps.gu, 3, lo, {1792, 512, 2, 1}, {3584, diff, 0}, {64, 64, 2, 1}, S128);
    encode(fn, &maps.kv, 3, wqkv, {512, 512, 3, 1}, {3072, 1024, 0}, {64, 64, 2, 1}, S128);
    encode(fn, &maps.q64, 3, wqkv, {32, 512, 48, 1}, {3072, 64, 0}, {32, 64, 2, 1}, S64);
    encode(fn, &maps.gu64, 3, lo, {1792, 512, 2, 1}, {3584, diff, 0}, {32, 64, 2, 1}, S64);
    encode(fn, &maps.wdw, 3, wd, {64, 1792, 8, 1}, {1024, 128, 0}, {64, 64, 2, 1}, S128);
    encode(fn, &maps.wdx, 4, wd, {64, 1568, 2, 8}, {1024, 224 * 1024, 128}, {64, 32, 2, 2}, S128);
    encode(fn, &maps.wow, 3, wo, {64, 512, 8, 1}, {1024, 128, 0}, {64, 64, 2, 1}, S128);
    encode(fn, &maps.wdn128, 2, wd, {512, 1792, 1, 1}, {1024, 0, 0}, {64, 128, 1, 1}, S128);
    encode(fn, &maps.wdn96, 2, wd, {512, 1792, 1, 1}, {1024, 0, 0}, {64, 96, 1, 1}, S128);
    encode(fn, &maps.won128, 2, wo, {512, 512, 1, 1}, {1024, 0, 0}, {64, 128, 1, 1}, S128);
    cudaFuncSetAttribute(fused_kernel, cudaFuncAttributeMaxDynamicSharedMemorySize, SMEM_BYTES);
    cudaLaunchConfig_t cfg = {};
    cfg.gridDim = dim3(128);
    cfg.blockDim = dim3(384);
    cfg.dynamicSmemBytes = SMEM_BYTES;
    cfg.stream = cudaStreamPerThread;
    cudaLaunchAttribute at[1];
    at[0].id = cudaLaunchAttributeClusterDimension;
    at[0].val.clusterDim.x = 2; at[0].val.clusterDim.y = 1; at[0].val.clusterDim.z = 1;
    cfg.attrs = at;
    cfg.numAttrs = MC ? 1 : 0;
    cudaLaunchKernelEx(&cfg, fused_kernel, maps, (const __nv_bfloat16*)d_in[7], wqkv, wg, wu, wd, wo, (__nv_bfloat16*)d_out);
}
```

```cpp
#include <cuda_runtime.h>
#include <cuda.h>
#include <cuda_bf16.h>
#include <stdint.h>

#define MC 0
#define PROF 0

namespace {

constexpr int kD = 512;
constexpr uint32_t OFF_X = 0, OFF_STG = 131072, OFF_RING = 147456, OFF_MISC = 229376;
constexpr uint32_t B_FULL = OFF_MISC, B_EMPTY = OFF_MISC + 64, B_XFULL = OFF_MISC + 128;
constexpr uint32_t B_GRDY = OFF_MISC + 192, B_KVDONE = OFF_MISC + 200, B_KVRDY = OFF_MISC + 208;
constexpr uint32_t OFF_EPOCH = OFF_MISC + 240, OFF_G = OFF_MISC + 256;
constexpr uint32_t OFF_KVF = OFF_MISC + 768, OFF_ZF = OFF_KVF + 2048;
constexpr uint32_t OFF_ONES = OFF_ZF + 128;
constexpr uint32_t SMEM_BYTES = OFF_ONES + 128;
constexpr uint32_t SPIN_MBAR = 1u << 16, SPIN_GLOBAL = 1u << 14;

struct alignas(64) Maps { CUtensorMap x, gu, kv, q64, gu64, wdw, wdx, wow, wdn128, wdn96, won128; };

}

__device__ uint4 g_part[16 * 2 * 4 * 4 * 1024];
__device__ uint4 g_hx[16 * 8 * 5 * 1024];
__device__ uint4 g_gx[16 * 32];
__device__ float g_kvacc[2 * 8 * 4 * 272];
__device__ unsigned g_kvcnt[8 * 32];
__device__ unsigned g_epoch[128];
#define TS(role, idx)
#define TS2(idx)
#define TSG(role, idx)

namespace {

__device__ __forceinline__ void mbar_init(uint32_t bar, uint32_t cnt) { asm volatile("mbarrier.init.shared::cta.b64 [%0], %1;" :: "r"(bar), "r"(cnt) : "memory"); }
__device__ __forceinline__ void mbar_expect(uint32_t bar, uint32_t bytes) { asm volatile("mbarrier.arrive.expect_tx.shared::cta.b64 _, [%0], %1;" :: "r"(bar), "r"(bytes) : "memory"); }
__device__ __forceinline__ void mbar_arrive(uint32_t bar) { asm volatile("mbarrier.arrive.shared::cta.b64 _, [%0];" :: "r"(bar) : "memory"); }
__device__ __forceinline__ void mbar_arrive_cta(uint32_t bar, uint32_t cta) {
    asm volatile("{\n.reg .b32 ra;\nmapa.shared::cluster.u32 ra, %0, %1;\nmbarrier.arrive.shared::cluster.b64 _, [ra];\n}" :: "r"(bar), "r"(cta) : "memory");
}
__device__ __forceinline__ void mbar_wait(uint32_t bar, uint32_t parity) {
    uint32_t ok, it = 0;
    do {
        asm volatile("{\n.reg .pred p;\nmbarrier.try_wait.parity.shared::cta.b64 p, [%1], %2;\nselp.u32 %0, 1, 0, p;\n}" : "=r"(ok) : "r"(bar), "r"(parity) : "memory");
    } while (!ok && ++it < SPIN_MBAR);
}
__device__ __forceinline__ void tma2(uint32_t dst, const CUtensorMap* m, int c0, int c1, uint32_t bar) {
    asm volatile("cp.async.bulk.tensor.2d.shared::cluster.global.mbarrier::complete_tx::bytes [%0], [%1, {%3, %4}], [%2];"
        :: "r"(dst), "l"(m), "r"(bar), "r"(c0), "r"(c1) : "memory");
}
__device__ __forceinline__ void tmaw2(uint32_t dst, const CUtensorMap* m, int c0, int c1, uint32_t bar) {
    tma2(dst, m, c0, c1, bar);
}
__device__ __forceinline__ void tmaw3(uint32_t dst, const CUtensorMap* m, int c0, int c1, int c2, uint32_t bar) {
    asm volatile("cp.async.bulk.tensor.3d.shared::cluster.global.mbarrier::complete_tx::bytes [%0], [%1, {%3, %4, %5}], [%2];"
        :: "r"(dst), "l"(m), "r"(bar), "r"(c0), "r"(c1), "r"(c2) : "memory");
}
__device__ __forceinline__ void tmaw4(uint32_t dst, const CUtensorMap* m, int c0, int c1, int c2, int c3, uint32_t bar) {
    asm volatile("cp.async.bulk.tensor.4d.shared::cluster.global.mbarrier::complete_tx::bytes [%0], [%1, {%3, %4, %5, %6}], [%2];"
        :: "r"(dst), "l"(m), "r"(bar), "r"(c0), "r"(c1), "r"(c2), "r"(c3) : "memory");
}
__device__ __forceinline__ void l2_prefetch(const void* p, uint32_t bytes) { asm volatile("cp.async.bulk.prefetch.L2.global [%0], %1;" :: "l"(p), "r"(bytes) : "memory"); }
__device__ __forceinline__ void wg_fence() { asm volatile("wgmma.fence.sync.aligned;" ::: "memory"); }
__device__ __forceinline__ void wg_commit() { asm volatile("wgmma.commit_group.sync.aligned;" ::: "memory"); }
template <int N> __device__ __forceinline__ void wg_wait() { asm volatile("wgmma.wait_group.sync.aligned %0;" :: "n"(N) : "memory"); }
template <int N> __device__ __forceinline__ void pin(float (&d)[N]) {
#pragma unroll
    for (int i = 0; i < N; i++) asm volatile("" : "+f"(d[i]) :: "memory");
}
__device__ __forceinline__ uint32_t pack2(float lo, float hi) { uint32_t r; asm("cvt.rn.bf16x2.f32 %0, %1, %2;" : "=r"(r) : "f"(hi), "f"(lo)); return r; }
__device__ __forceinline__ float phi(float t) {
    float e;
    asm("ex2.approx.ftz.f32 %0, %1;" : "=f"(e) : "f"(fminf(t * 1.4426950408889634f, 0.f)));
    return e + (fmaxf(t, 0.f) + 1e-6f);
}
__device__ __forceinline__ void stsm4(uint32_t a, uint32_t r0, uint32_t r1, uint32_t r2, uint32_t r3) {
    asm volatile("stmatrix.sync.aligned.m8n8.x4.shared.b16 [%0], {%1,%2,%3,%4};" :: "r"(a), "r"(r0), "r"(r1), "r"(r2), "r"(r3) : "memory");
}
__device__ __forceinline__ void mma16816(float (&c)[4], uint32_t a0, uint32_t a1, uint32_t a2, uint32_t a3, uint32_t b0, uint32_t b1) {
    asm volatile("mma.sync.aligned.m16n8k16.row.col.f32.bf16.bf16.f32 {%0,%1,%2,%3}, {%4,%5,%6,%7}, {%8,%9}, {%0,%1,%2,%3};"
        : "+f"(c[0]), "+f"(c[1]), "+f"(c[2]), "+f"(c[3]) : "r"(a0), "r"(a1), "r"(a2), "r"(a3), "r"(b0), "r"(b1));
}
__device__ __forceinline__ float bf_lo(uint32_t w) { return __uint_as_float(w << 16); }
__device__ __forceinline__ float bf_hi(uint32_t w) { return __uint_as_float(w & 0xffff0000u); }
__device__ __forceinline__ void st_pkt(uint4* p, uint32_t w0, uint32_t w1, uint32_t w2, uint32_t w3) {
    asm volatile("{\n.reg .b64 lo, hi;\n.reg .b128 v;\nmov.b64 lo, {%1, %2};\nmov.b64 hi, {%3, %4};\nmov.b128 v, {lo, hi};\nst.relaxed.gpu.global.b128 [%0], v;\n}"
        :: "l"(p), "r"(w0), "r"(w1), "r"(w2), "r"(w3) : "memory");
}
__device__ __forceinline__ void ld_pkt(const uint4* p, uint32_t& w0, uint32_t& w1, uint32_t& w2, uint32_t& w3) {
    asm volatile("{\n.reg .b64 lo, hi;\n.reg .b128 v;\nld.relaxed.gpu.global.b128 v, [%4];\nmov.b128 {lo, hi}, v;\nmov.b64 {%0, %1}, lo;\nmov.b64 {%2, %3}, hi;\n}"
        : "=r"(w0), "=r"(w1), "=r"(w2), "=r"(w3) : "l"(p) : "memory");
}

__device__ __forceinline__ void wg_ss128(float (&d)[64], uint32_t alo, uint32_t ahi, uint32_t blo, uint32_t bhi) {
    asm volatile("{\n.reg .b64 da, db;\nmov.b64 da, {%64, %65};\nmov.b64 db, {%66, %67};\n"
        "wgmma.mma_async.sync.aligned.m64n128k16.f32.bf16.bf16 {%0,%1,%2,%3,%4,%5,%6,%7,%8,%9,%10,%11,%12,%13,%14,%15,%16,%17,%18,%19,%20,%21,%22,%23,%24,%25,%26,%27,%28,%29,%30,%31,%32,%33,%34,%35,%36,%37,%38,%39,%40,%41,%42,%43,%44,%45,%46,%47,%48,%49,%50,%51,%52,%53,%54,%55,%56,%57,%58,%59,%60,%61,%62,%63}, da, db, 1, 1, 1, 0, 1;\n}\n"
        : "+f"(d[0]),"+f"(d[1]),"+f"(d[2]),"+f"(d[3]),"+f"(d[4]),"+f"(d[5]),"+f"(d[6]),"+f"(d[7]),"+f"(d[8]),"+f"(d[9]),"+f"(d[10]),"+f"(d[11]),"+f"(d[12]),"+f"(d[13]),"+f"(d[14]),"+f"(d[15]),"+f"(d[16]),"+f"(d[17]),"+f"(d[18]),"+f"(d[19]),"+f"(d[20]),"+f"(d[21]),"+f"(d[22]),"+f"(d[23]),"+f"(d[24]),"+f"(d[25]),"+f"(d[26]),"+f"(d[27]),"+f"(d[28]),"+f"(d[29]),"+f"(d[30]),"+f"(d[31]),"+f"(d[32]),"+f"(d[33]),"+f"(d[34]),"+f"(d[35]),"+f"(d[36]),"+f"(d[37]),"+f"(d[38]),"+f"(d[39]),"+f"(d[40]),"+f"(d[41]),"+f"(d[42]),"+f"(d[43]),"+f"(d[44]),"+f"(d[45]),"+f"(d[46]),"+f"(d[47]),"+f"(d[48]),"+f"(d[49]),"+f"(d[50]),"+f"(d[51]),"+f"(d[52]),"+f"(d[53]),"+f"(d[54]),"+f"(d[55]),"+f"(d[56]),"+f"(d[57]),"+f"(d[58]),"+f"(d[59]),"+f"(d[60]),"+f"(d[61]),"+f"(d[62]),"+f"(d[63])
        : "r"(alo), "r"(ahi), "r"(blo), "r"(bhi));
}
__device__ __forceinline__ void wg_ss128_z(float (&d)[64], uint32_t alo, uint32_t ahi, uint32_t blo, uint32_t bhi) {
    asm volatile("{\n.reg .b64 da, db;\nmov.b64 da, {%64, %65};\nmov.b64 db, {%66, %67};\n"
        "wgmma.mma_async.sync.aligned.m64n128k16.f32.bf16.bf16 {%0,%1,%2,%3,%4,%5,%6,%7,%8,%9,%10,%11,%12,%13,%14,%15,%16,%17,%18,%19,%20,%21,%22,%23,%24,%25,%26,%27,%28,%29,%30,%31,%32,%33,%34,%35,%36,%37,%38,%39,%40,%41,%42,%43,%44,%45,%46,%47,%48,%49,%50,%51,%52,%53,%54,%55,%56,%57,%58,%59,%60,%61,%62,%63}, da, db, 0, 1, 1, 0, 1;\n}\n"
        : "=f"(d[0]),"=f"(d[1]),"=f"(d[2]),"=f"(d[3]),"=f"(d[4]),"=f"(d[5]),"=f"(d[6]),"=f"(d[7]),"=f"(d[8]),"=f"(d[9]),"=f"(d[10]),"=f"(d[11]),"=f"(d[12]),"=f"(d[13]),"=f"(d[14]),"=f"(d[15]),"=f"(d[16]),"=f"(d[17]),"=f"(d[18]),"=f"(d[19]),"=f"(d[20]),"=f"(d[21]),"=f"(d[22]),"=f"(d[23]),"=f"(d[24]),"=f"(d[25]),"=f"(d[26]),"=f"(d[27]),"=f"(d[28]),"=f"(d[29]),"=f"(d[30]),"=f"(d[31]),"=f"(d[32]),"=f"(d[33]),"=f"(d[34]),"=f"(d[35]),"=f"(d[36]),"=f"(d[37]),"=f"(d[38]),"=f"(d[39]),"=f"(d[40]),"=f"(d[41]),"=f"(d[42]),"=f"(d[43]),"=f"(d[44]),"=f"(d[45]),"=f"(d[46]),"=f"(d[47]),"=f"(d[48]),"=f"(d[49]),"=f"(d[50]),"=f"(d[51]),"=f"(d[52]),"=f"(d[53]),"=f"(d[54]),"=f"(d[55]),"=f"(d[56]),"=f"(d[57]),"=f"(d[58]),"=f"(d[59]),"=f"(d[60]),"=f"(d[61]),"=f"(d[62]),"=f"(d[63])
        : "r"(alo), "r"(ahi), "r"(blo), "r"(bhi));
}
__device__ __forceinline__ void wg_ss64(float (&d)[32], uint32_t alo, uint32_t ahi, uint32_t blo, uint32_t bhi) {
    asm volatile("{\n.reg .b64 da, db;\nmov.b64 da, {%32, %33};\nmov.b64 db, {%34, %35};\n"
        "wgmma.mma_async.sync.aligned.m64n64k16.f32.bf16.bf16 {%0,%1,%2,%3,%4,%5,%6,%7,%8,%9,%10,%11,%12,%13,%14,%15,%16,%17,%18,%19,%20,%21,%22,%23,%24,%25,%26,%27,%28,%29,%30,%31}, da, db, 1, 1, 1, 0, 1;\n}\n"
        : "+f"(d[0]),"+f"(d[1]),"+f"(d[2]),"+f"(d[3]),"+f"(d[4]),"+f"(d[5]),"+f"(d[6]),"+f"(d[7]),"+f"(d[8]),"+f"(d[9]),"+f"(d[10]),"+f"(d[11]),"+f"(d[12]),"+f"(d[13]),"+f"(d[14]),"+f"(d[15]),"+f"(d[16]),"+f"(d[17]),"+f"(d[18]),"+f"(d[19]),"+f"(d[20]),"+f"(d[21]),"+f"(d[22]),"+f"(d[23]),"+f"(d[24]),"+f"(d[25]),"+f"(d[26]),"+f"(d[27]),"+f"(d[28]),"+f"(d[29]),"+f"(d[30]),"+f"(d[31])
        : "r"(alo), "r"(ahi), "r"(blo), "r"(bhi));
}
__device__ __forceinline__ void wg_ss64_z(float (&d)[32], uint32_t alo, uint32_t ahi, uint32_t blo, uint32_t bhi) {
    asm volatile("{\n.reg .b64 da, db;\nmov.b64 da, {%32, %33};\nmov.b64 db, {%34, %35};\n"
        "wgmma.mma_async.sync.aligned.m64n64k16.f32.bf16.bf16 {%0,%1,%2,%3,%4,%5,%6,%7,%8,%9,%10,%11,%12,%13,%14,%15,%16,%17,%18,%19,%20,%21,%22,%23,%24,%25,%26,%27,%28,%29,%30,%31}, da, db, 0, 1, 1, 0, 1;\n}\n"
        : "=f"(d[0]),"=f"(d[1]),"=f"(d[2]),"=f"(d[3]),"=f"(d[4]),"=f"(d[5]),"=f"(d[6]),"=f"(d[7]),"=f"(d[8]),"=f"(d[9]),"=f"(d[10]),"=f"(d[11]),"=f"(d[12]),"=f"(d[13]),"=f"(d[14]),"=f"(d[15]),"=f"(d[16]),"=f"(d[17]),"=f"(d[18]),"=f"(d[19]),"=f"(d[20]),"=f"(d[21]),"=f"(d[22]),"=f"(d[23]),"=f"(d[24]),"=f"(d[25]),"=f"(d[26]),"=f"(d[27]),"=f"(d[28]),"=f"(d[29]),"=f"(d[30]),"=f"(d[31])
        : "r"(alo), "r"(ahi), "r"(blo), "r"(bhi));
}
__device__ __forceinline__ void wg_ss64t(float (&d)[32], uint32_t alo, uint32_t ahi, uint32_t blo, uint32_t bhi) {
    asm volatile("{\n.reg .b64 da, db;\nmov.b64 da, {%32, %33};\nmov.b64 db, {%34, %35};\n"
        "wgmma.mma_async.sync.aligned.m64n64k16.f32.bf16.bf16 {%0,%1,%2,%3,%4,%5,%6,%7,%8,%9,%10,%11,%12,%13,%14,%15,%16,%17,%18,%19,%20,%21,%22,%23,%24,%25,%26,%27,%28,%29,%30,%31}, da, db, 1, 1, 1, 1, 1;\n}\n"
        : "+f"(d[0]),"+f"(d[1]),"+f"(d[2]),"+f"(d[3]),"+f"(d[4]),"+f"(d[5]),"+f"(d[6]),"+f"(d[7]),"+f"(d[8]),"+f"(d[9]),"+f"(d[10]),"+f"(d[11]),"+f"(d[12]),"+f"(d[13]),"+f"(d[14]),"+f"(d[15]),"+f"(d[16]),"+f"(d[17]),"+f"(d[18]),"+f"(d[19]),"+f"(d[20]),"+f"(d[21]),"+f"(d[22]),"+f"(d[23]),"+f"(d[24]),"+f"(d[25]),"+f"(d[26]),"+f"(d[27]),"+f"(d[28]),"+f"(d[29]),"+f"(d[30]),"+f"(d[31])
        : "r"(alo), "r"(ahi), "r"(blo), "r"(bhi));
}
__device__ __forceinline__ void wg_ss64t_z(float (&d)[32], uint32_t alo, uint32_t ahi, uint32_t blo, uint32_t bhi) {
    asm volatile("{\n.reg .b64 da, db;\nmov.b64 da, {%32, %33};\nmov.b64 db, {%34, %35};\n"
        "wgmma.mma_async.sync.aligned.m64n64k16.f32.bf16.bf16 {%0,%1,%2,%3,%4,%5,%6,%7,%8,%9,%10,%11,%12,%13,%14,%15,%16,%17,%18,%19,%20,%21,%22,%23,%24,%25,%26,%27,%28,%29,%30,%31}, da, db, 0, 1, 1, 1, 1;\n}\n"
        : "=f"(d[0]),"=f"(d[1]),"=f"(d[2]),"=f"(d[3]),"=f"(d[4]),"=f"(d[5]),"=f"(d[6]),"=f"(d[7]),"=f"(d[8]),"=f"(d[9]),"=f"(d[10]),"=f"(d[11]),"=f"(d[12]),"=f"(d[13]),"=f"(d[14]),"=f"(d[15]),"=f"(d[16]),"=f"(d[17]),"=f"(d[18]),"=f"(d[19]),"=f"(d[20]),"=f"(d[21]),"=f"(d[22]),"=f"(d[23]),"=f"(d[24]),"=f"(d[25]),"=f"(d[26]),"=f"(d[27]),"=f"(d[28]),"=f"(d[29]),"=f"(d[30]),"=f"(d[31])
        : "r"(alo), "r"(ahi), "r"(blo), "r"(bhi));
}
__device__ __forceinline__ void wg_ss8t(float (&d)[4], uint32_t alo, uint32_t ahi, uint32_t blo, uint32_t bhi) {
    asm volatile("{\n.reg .b64 da, db;\nmov.b64 da, {%4, %5};\nmov.b64 db, {%6, %7};\n"
        "wgmma.mma_async.sync.aligned.m64n8k16.f32.bf16.bf16 {%0,%1,%2,%3}, da, db, 1, 1, 1, 1, 0;\n}\n"
        : "+f"(d[0]),"+f"(d[1]),"+f"(d[2]),"+f"(d[3])
        : "r"(alo), "r"(ahi), "r"(blo), "r"(bhi));
}
__device__ __forceinline__ void wg_ss8t_z(float (&d)[4], uint32_t alo, uint32_t ahi, uint32_t blo, uint32_t bhi) {
    asm volatile("{\n.reg .b64 da, db;\nmov.b64 da, {%4, %5};\nmov.b64 db, {%6, %7};\n"
        "wgmma.mma_async.sync.aligned.m64n8k16.f32.bf16.bf16 {%0,%1,%2,%3}, da, db, 0, 1, 1, 1, 0;\n}\n"
        : "=f"(d[0]),"=f"(d[1]),"=f"(d[2]),"=f"(d[3])
        : "r"(alo), "r"(ahi), "r"(blo), "r"(bhi));
}

constexpr uint32_t DH128 = 64u | 0x40000000u;
constexpr uint32_t DH64 = 32u | 0x80000000u;
constexpr uint32_t LBO4K = (4096u >> 4) << 16, LBO8K = (8192u >> 4) << 16, LBO1 = 1u << 16;

template <bool SW64, bool FIRST> __device__ __forceinline__ void g1_issue(float (&acc)[64], uint32_t alo, uint32_t blo) {
    wg_fence();
#pragma unroll
    for (int k = 0; k < 4; k++) {
        if (FIRST && k == 0) wg_ss128_z(acc, alo, DH128, blo, SW64 ? DH64 : DH128);
        else wg_ss128(acc, alo + 2 * k, DH128, blo + (SW64 ? 64 * k : 128 * k), SW64 ? DH64 : DH128);
    }
    wg_commit();
}

template <int N> __device__ __forceinline__ void stash(uint32_t base, uint32_t sw, const uint32_t (&f)[N]) {
#pragma unroll
    for (int t = 0; t < N / 4; t++) stsm4(base + ((sw ^ (2 * t)) << 4), f[4 * t], f[4 * t + 1], f[4 * t + 2], f[4 * t + 3]);
}

template <int V0, int V1, int N> __device__ __forceinline__ void send_frag(const uint32_t (&f)[N], uint4* p, uint32_t tag) {
#pragma unroll
    for (int v = V0; v < V1; v++) st_pkt(p + (v & 3) * 32, (f[4 * v] & ~1u) | tag, f[4 * v + 1], f[4 * v + 2], f[4 * v + 3]);
}
template <int N> __device__ __forceinline__ void pack_acc(uint32_t (&f)[N], const float (&acc)[2 * N]) {
#pragma unroll
    for (int i = 0; i < N; i++) f[i] = pack2(acc[2 * i], acc[2 * i + 1]);
}
template <int N> __device__ __forceinline__ void recv_issue(uint32_t (&q)[N], const uint4* p) {
#pragma unroll
    for (int v = 0; v < N / 4; v++) ld_pkt(p + v * 32, q[4 * v], q[4 * v + 1], q[4 * v + 2], q[4 * v + 3]);
}
template <int N> __device__ __forceinline__ void recv_check(uint32_t (&q)[N], const uint4* p, uint32_t tag) {
    uint32_t it = 0;
    while (true) {
        uint32_t bad = 0;
#pragma unroll
        for (int v = 0; v < N / 4; v++) bad |= q[4 * v] ^ tag;
        if (__all_sync(0xffffffffu, (bad & 1u) == 0) || ++it > SPIN_GLOBAL) break;
        recv_issue(q, p);
    }
}
template <bool FIRST> __device__ __forceinline__ void accum(const uint32_t (&q)[16], float (&sum)[32]) {
#pragma unroll
    for (int i = 0; i < 16; i++) {
        if (FIRST) { sum[2 * i] = bf_lo(q[i]); sum[2 * i + 1] = bf_hi(q[i]); }
        else { sum[2 * i] += bf_lo(q[i]); sum[2 * i + 1] += bf_hi(q[i]); }
    }
}

}

__global__ void __launch_bounds__(384, 1)
fused_kernel(const __grid_constant__ Maps maps, const __nv_bfloat16* __restrict__ xg, const __nv_bfloat16* __restrict__ gate_w,
             const char* __restrict__ pf_qkv, const char* __restrict__ pf_g, const char* __restrict__ pf_u,
             const char* __restrict__ pf_d, const char* __restrict__ pf_o, __nv_bfloat16* __restrict__ out) {
    extern __shared__ __align__(1024) uint8_t smem_raw[];
    const uint32_t sb = (uint32_t)__cvta_generic_to_shared(smem_raw);
    const int tid = threadIdx.x, lane = tid & 31;
    const int warp = __shfl_sync(0xffffffffu, tid >> 5, 0);
    const int j = (blockIdx.x >> 1) & 7;
    const int r = ((blockIdx.x >> 4) << 1) | (blockIdx.x & 1);
    const uint32_t rank = blockIdx.x & 1;

    if (warp == 0) { TSG(0, 30); TS(0, 0); }
    if (warp == 9 && lane < 11) asm volatile("prefetch.tensormap [%0];" :: "l"(&maps.x + lane) : "memory");
    if (tid == 256) {
        for (int i = 0; i < 5; i++) { mbar_init(sb + B_FULL + 8 * i, 1); mbar_init(sb + B_EMPTY + 8 * i, MC ? 4 : 2); }
        for (int i = 0; i < 8; i++) mbar_init(sb + B_XFULL + 8 * i, 1);
        mbar_init(sb + B_GRDY, 1); mbar_init(sb + B_KVDONE, 8); mbar_init(sb + B_KVRDY, 2);
        asm volatile("fence.mbarrier_init.release.cluster;" ::: "memory");
        asm volatile("fence.proxy.async.shared::cta;" ::: "memory");
        mbar_expect(sb + B_XFULL, 16384);
        tma2(sb + OFF_X, &maps.x, 0, r * 128, sb + B_XFULL);
    }
    __syncthreads();

    if (warp >= 8) {
        asm volatile("setmaxnreg.dec.sync.aligned.u32 72;");
        if (warp == 8) {
            if (lane == 0) {
                int slot = 0, ph = 1;
                uint32_t full, dst;
#define P_BEGIN(S, BYTES) full = sb + B_FULL + 8 * slot; dst = sb + OFF_RING + slot * 16384; \
                mbar_wait(sb + B_EMPTY + 8 * slot, ph); TS2(S); mbar_expect(full, BYTES); if (!MC || (((S) ^ rank) & 1) == 0)
#define P_END() if (++slot == 5) { slot = 0; ph ^= 1; }
                for (int s = 0; s < 16; s++) {
                    P_BEGIN(s, 16384) {
                        if (s & 1) tmaw3(dst, &maps.kv, 64 * j, 32 * (s - 1), 1, full);
                        else tmaw3(dst, &maps.gu, 224 * j, 32 * s, 0, full);
                    }
                    const int xb = (s == 4) ? 3 : !(s & 1) ? 0 : (s < 5) ? (s + 1) / 2 : (s <= 11) ? (s + 3) / 2 : 0;
                    if (xb) { mbar_expect(sb + B_XFULL + 8 * xb, 16384); tma2(sb + OFF_X + xb * 16384, &maps.x, 64 * xb, r * 128, sb + B_XFULL + 8 * xb); }
                    P_END()
                }
                for (int s = 0; s < 8; s++) {
                    P_BEGIN(16 + s, 16384) {
                        tmaw3(dst, &maps.q64, 0, 64 * s, 2 * j, full);
                        tmaw3(dst + 8192, &maps.gu64, 224 * j + 192, 64 * s, 0, full);
                    }
                    P_END()
                }
                for (int s = 0; s < 16; s++) {
                    P_BEGIN(24 + s, 16384) tmaw3(dst, &maps.gu, 224 * j + 64 + 64 * (s >> 3), 64 * (s & 7), 0, full);
                    P_END()
                }
                const int p = j >> 1, ro = 224 * j, rp = 224 * (j ^ 1);
                const int cw = (j & 1) * 4 + 2 * ((p >> 1) ^ 1);
                P_BEGIN(40, 16384) tmaw3(dst, &maps.wdw, 0, ro, cw, full); P_END()
                P_BEGIN(41, 16384) tmaw3(dst, &maps.wdw, 0, ro + 64, cw, full); P_END()
                P_BEGIN(42, 16384) tmaw3(dst, &maps.wdw, 0, rp, cw, full); P_END()
                P_BEGIN(43, 16384) tmaw3(dst, &maps.wdw, 0, rp + 64, cw, full); P_END()
                P_BEGIN(44, 16384) tmaw4(dst, &maps.wdx, 0, 448 * p + 192, 0, cw, full); P_END()
                P_BEGIN(45, 16384) tmaw3(dst, &maps.wow, 0, 128 * p, cw, full); P_END()
                P_BEGIN(46, 16384) tmaw3(dst, &maps.wow, 0, 128 * p + 64, cw, full); P_END()
                P_BEGIN(47, 16384) tmaw3(dst, &maps.wdw, 0, ro + 128, cw, full); P_END()
                P_BEGIN(48, 16384) tmaw3(dst, &maps.wdw, 0, rp + 128, cw, full); P_END()
                for (int q = 0; q < 2; q++) {
                    const int cn = (j & 1) * 256 + 64 * (p ^ (q ^ 1));
                    P_BEGIN(49 + 5 * q, 16384) tmaw2(dst, &maps.wdn128, cn, ro, full); P_END()
                    P_BEGIN(50 + 5 * q, 16384) tmaw2(dst, &maps.wdn128, cn, rp, full); P_END()
                    P_BEGIN(51 + 5 * q, 16384) tmaw2(dst, &maps.won128, cn, 128 * p, full); P_END()
                    P_BEGIN(52 + 5 * q, 12288) tmaw2(dst, &maps.wdn96, cn, ro + 128, full); P_END()
                    P_BEGIN(53 + 5 * q, 12288) tmaw2(dst, &maps.wdn96, cn, rp + 128, full); P_END()
                }
            }
        } else if (warp < 11) {
            const int hx = warp - 9;
            uint32_t epoch;
            asm volatile("ld.relaxed.gpu.global.u32 %0, [%1];" : "=r"(epoch) : "l"(g_epoch + blockIdx.x) : "memory");
            {
                const uint4* xr = (const uint4*)(xg + (size_t)(r * 128 + j * 16 + hx * 8) * kD) + lane;
                const uint4 wa = __ldg((const uint4*)gate_w + lane), wb = __ldg((const uint4*)gate_w + 32 + lane);
                float s[8];
#pragma unroll
                for (int i0 = 0; i0 < 8; i0 += 4) {
                    uint4 va[4], vb[4];
#pragma unroll
                    for (int i = 0; i < 4; i++) { va[i] = __ldg(xr + (i0 + i) * 64); vb[i] = __ldg(xr + (i0 + i) * 64 + 32); }
#pragma unroll
                    for (int i = 0; i < 4; i++) {
                        float t0 = bf_lo(va[i].x) * bf_lo(wa.x), t1 = bf_hi(va[i].x) * bf_hi(wa.x);
                        t0 = fmaf(bf_lo(va[i].y), bf_lo(wa.y), t0); t1 = fmaf(bf_hi(va[i].y), bf_hi(wa.y), t1);
                        t0 = fmaf(bf_lo(va[i].z), bf_lo(wa.z), t0); t1 = fmaf(bf_hi(va[i].z), bf_hi(wa.z), t1);
                        t0 = fmaf(bf_lo(va[i].w), bf_lo(wa.w), t0); t1 = fmaf(bf_hi(va[i].w), bf_hi(wa.w), t1);
                        t0 = fmaf(bf_lo(vb[i].x), bf_lo(wb.x), t0); t1 = fmaf(bf_hi(vb[i].x), bf_hi(wb.x), t1);
                        t0 = fmaf(bf_lo(vb[i].y), bf_lo(wb.y), t0); t1 = fmaf(bf_hi(vb[i].y), bf_hi(wb.y), t1);
                        t0 = fmaf(bf_lo(vb[i].z), bf_lo(wb.z), t0); t1 = fmaf(bf_hi(vb[i].z), bf_hi(wb.z), t1);
                        t0 = fmaf(bf_lo(vb[i].w), bf_lo(wb.w), t0); t1 = fmaf(bf_hi(vb[i].w), bf_hi(wb.w), t1);
                        s[i0 + i] = t0 + t1;
                    }
                }
#pragma unroll
                for (int i = 0; i < 8; i++) {
#pragma unroll
                    for (int o = 16; o; o >>= 1) s[i] += __shfl_xor_sync(0xffffffffu, s[i], o);
                    s[i] = 1.f / (1.f + __expf(-s[i]));
                }
                const uint32_t tag = (epoch + 1) & 1;
                uint4* gp = g_gx + r * 32;
                if (lane < 2) {
                    const float v0 = lane ? s[4] : s[0], v1 = lane ? s[5] : s[1], v2 = lane ? s[6] : s[2], v3 = lane ? s[7] : s[3];
                    st_pkt(gp + j * 4 + hx * 2 + lane, (__float_as_uint(v0) & ~1u) | tag, __float_as_uint(v1), __float_as_uint(v2), __float_as_uint(v3));
                }
                if (hx == 1) {
                    asm volatile("st.shared.u32 [%0], %1;" :: "r"(sb + OFF_ONES + lane * 4), "r"(0x3f803f80u) : "memory");
                    asm volatile("fence.proxy.async.shared::cta;" ::: "memory");
                }
                asm volatile("bar.sync 3, 64;" ::: "memory");
                if (hx == 0) {
                    uint32_t q[4];
                    recv_issue(q, gp + lane);
                    recv_check(q, gp + lane, tag);
                    asm volatile("st.shared.v4.u32 [%0], {%1,%2,%3,%4};" :: "r"(sb + OFF_G + lane * 16), "r"(q[0]), "r"(q[1]), "r"(q[2]), "r"(q[3]) : "memory");
                    if (lane == 0) {
                        asm volatile("st.shared.u32 [%0], %1;" :: "r"(sb + OFF_EPOCH), "r"(epoch) : "memory");
                        g_epoch[blockIdx.x] = epoch + 1;
                    }
                    __syncwarp();
                    if (lane == 0) mbar_arrive(sb + B_GRDY);
                } else {
                    if (r == 0) {
                        float4* zp = (float4*)(g_kvacc + (((epoch & 1) ^ 1) * 8 + j) * 4 * 272);
                        for (int i = lane; i < 272; i += 32) zp[i] = make_float4(0.f, 0.f, 0.f, 0.f);
                    }
                }
            }
            TS(2 + hx, 1);
            const float* accp = g_kvacc + (((epoch & 1) * 8 + j) * 4 + 2 * hx) * 272;
            unsigned* cnt = g_kvcnt + j * 32;
            if (hx == 0) {
                mbar_wait(sb + B_KVDONE, 0);
                TS(2, 5);
                if (lane == 0) asm volatile("red.release.gpu.global.add.u32 [%0], 1;" :: "l"(cnt) : "memory");
                __syncwarp();
            }
            TS(2 + hx, 2);
            {
                const unsigned target = 16u * (epoch + 1);
                uint32_t it = 0, v;
                do {
                    asm volatile("ld.acquire.gpu.global.u32 %0, [%1];" : "=r"(v) : "l"(cnt) : "memory");
                } while ((int)(v - target) < 0 && ++it < SPIN_GLOBAL);
            }
            TS(2 + hx, 3);
#pragma unroll
            for (int h = 0; h < 2; h++) {
                const float4 d0 = __ldcg((const float4*)(accp + h * 272) + lane);
                const float4 d1 = __ldcg((const float4*)(accp + h * 272 + 128) + lane);
                const float2 z0 = __ldcg((const float2*)(accp + h * 272 + 256) + (lane & 3));
                const float2 z1 = __ldcg((const float2*)(accp + h * 272 + 264) + (lane & 3));
                asm volatile("st.shared.v4.u32 [%0], {%1,%2,%3,%4};" :: "r"(sb + OFF_KVF + (2 * hx + h) * 512 + lane * 16),
                             "r"(pack2(d0.x, d0.y)), "r"(pack2(d1.x, d1.y)), "r"(pack2(d0.z, d0.w)), "r"(pack2(d1.z, d1.w)) : "memory");
                if (lane < 4) asm volatile("st.shared.v2.u32 [%0], {%1,%2};" :: "r"(sb + OFF_ZF + (2 * hx + h) * 32 + lane * 8), "r"(pack2(z0.x, z0.y)), "r"(pack2(z1.x, z1.y)) : "memory");
            }
            __syncwarp();
            if (lane == 0) mbar_arrive(sb + B_KVRDY);
            TS(2 + hx, 4);
        } else {
            mbar_wait(sb + B_XFULL, 0);
            const int b = blockIdx.x;
            if (lane == 0) l2_prefetch(pf_qkv + b * 12288, 12288);
            if (lane == 1) l2_prefetch(pf_g + b * 14336, 14336);
            if (lane == 2) l2_prefetch(pf_u + b * 14336, 14336);
            mbar_wait(sb + B_XFULL + 8 * 7, 0);
            if (lane == 0) l2_prefetch(pf_d + b * 14336, 14336);
            if (lane == 1) l2_prefetch(pf_o + b * 4096, 4096);
        }
    } else {
        asm volatile("setmaxnreg.inc.sync.aligned.u32 216;");
        const int wg = warp >> 2;
        const bool elect = (tid & 127) == 0;
        const uint32_t xlo = ((sb + OFF_X + wg * 8192) >> 4) | LBO1;
        const uint32_t ringlo = (sb + OFF_RING) >> 4;
        int slot = 0, ph = 0, prev = 0;
        auto release = [&](int s) {
            if (elect) {
                mbar_arrive(sb + B_EMPTY + 8 * s);
            }
        };
        auto adv = [&]() { prev = slot; if (++slot == 5) { slot = 0; ph ^= 1; } };

        int pidx = 64;
#define G1_STAGE(acc, SW, KB, FIRST) do { mbar_wait(sb + B_FULL + 8 * slot, ph); if (PROF) { if (tid == 0) TS2(pidx); pidx++; } \
            g1_issue<SW, FIRST>(acc, xlo + (KB) * 1024, (ringlo + slot * 1024) | (SW ? LBO4K : LBO8K)); } while (0)
#define G1_RETIRE() do { wg_wait<1>(); release(prev); adv(); } while (0)
#define A2_SYNC() do { asm volatile("fence.proxy.async.shared::cta;" ::: "memory"); asm volatile("bar.sync %0, 128;" :: "r"(wg + 1) : "memory"); } while (0)
#define H_EPI(acc, F, N, OG, OU) _Pragma("unroll") for (int i = 0; i < (N); i++) { \
            const float m_ = (i & 1) ? m_hi : m_lo; \
            F[i] = pack2(acc[(OG) + 2 * i] * acc[(OU) + 2 * i] * m_, acc[(OG) + 2 * i + 1] * acc[(OU) + 2 * i + 1] * m_); }

        float a0[64], b0[64], a1[64], a2_[64], a3[64];
        mbar_wait(sb + B_XFULL, 0);
        G1_STAGE(a0, false, 0, 1); adv();
        if ((warp & 3) == 0) TS(wg, 1);
        G1_STAGE(b0, false, 0, 1); G1_RETIRE();
#pragma unroll 1
        for (int kb = 1; kb < 8; kb++) {
            mbar_wait(sb + B_XFULL + 8 * kb, 0);
            if (PROF && tid == 0) TS2(128 + kb);
            G1_STAGE(a0, false, kb, 0); G1_RETIRE();
            G1_STAGE(b0, false, kb, 0); G1_RETIRE();
        }
        pin(a0);
        mbar_wait(sb + B_GRDY, 0);
        float g_lo, g_hi;
        uint32_t tag;
        {
            const uint32_t ga = sb + OFF_G + (warp * 16 + (lane >> 2)) * 4;
            asm volatile("ld.shared.f32 %0, [%1];" : "=f"(g_lo) : "r"(ga) : "memory");
            asm volatile("ld.shared.f32 %0, [%1];" : "=f"(g_hi) : "r"(ga + 32) : "memory");
            asm volatile("ld.shared.u32 %0, [%1];" : "=r"(tag) : "r"(sb + OFF_EPOCH) : "memory");
        }
        float* const kvp = g_kvacc + (((tag & 1) * 8 + j) * 4 + (warp & 3)) * 272;
        tag = (tag + 1) & 1;
        const float m_lo = 1.f - g_lo, m_hi = 1.f - g_hi;
        if ((warp & 3) == 0) TS(wg, 2);
        uint32_t fh0[16], fh1[16], fh2[16], fh3[8], fo[16];
        H_EPI(a0, fh0, 16, 0, 32);

        const uint32_t lrow = ((lane & 7) + 8 * ((lane >> 3) & 1)) * 128;
        const uint32_t srow = (warp & 3) * 2048 + lrow;
        const uint32_t ssw = (lane >> 4) ^ (lane & 7);
        uint4* const hsend = g_hx + (size_t)((r * 8 + j) * 5) * 1024 + warp * 128 + lane;
        const uint4* const hrecv = g_hx + (size_t)((r * 8 + (j ^ 1)) * 5) * 1024 + warp * 128 + lane;

        {
            uint32_t pk[16], pv[16];
            float kv[32], zs[4];
            const uint32_t stg = sb + OFF_STG + wg * 8192;
            const uint32_t klo = (stg >> 4) | LBO1, vlo = klo + 256, olo = (sb + OFF_ONES) >> 4;
            G1_STAGE(a1, true, 0, 1); G1_RETIRE();
            pin(b0);
            G1_STAGE(a1, true, 1, 0);
#pragma unroll
            for (int i = 0; i < 8; i++) pk[i] = pack2(phi(b0[2 * i]), phi(b0[2 * i + 1]));
            send_frag<0, 4>(fh0, hsend, tag);
            G1_RETIRE();
            G1_STAGE(a1, true, 2, 0);
#pragma unroll
            for (int i = 8; i < 16; i++) pk[i] = pack2(phi(b0[2 * i]), phi(b0[2 * i + 1]));
#pragma unroll
            for (int i = 0; i < 16; i++) pv[i] = pack2(b0[32 + 2 * i], b0[32 + 2 * i + 1]);
            if (!(warp & 2)) { stash<16>(stg + (warp & 1) * 2048 + lrow, ssw, pk); stash<16>(stg + 4096 + (warp & 1) * 2048 + lrow, ssw, pv); }
            G1_RETIRE();
            A2_SYNC();
            wg_fence();
            wg_ss64t_z(kv, vlo, DH128, klo, DH128); wg_ss64t(kv, vlo + 128, DH128, klo + 128, DH128);
            wg_ss8t_z(zs, klo, DH128, olo, 0); wg_ss8t(zs, klo + 128, DH128, olo, 0);
            wg_commit();
            G1_STAGE(a1, true, 3, 0); G1_RETIRE();
            if (warp & 2) { stash<16>(stg + (warp & 1) * 2048 + lrow, ssw, pk); stash<16>(stg + 4096 + (warp & 1) * 2048 + lrow, ssw, pv); }
            A2_SYNC();
            wg_fence();
            wg_ss64t(kv, vlo, DH128, klo, DH128); wg_ss64t(kv, vlo + 128, DH128, klo + 128, DH128);
            wg_ss8t(zs, klo, DH128, olo, 0); wg_ss8t(zs, klo + 128, DH128, olo, 0);
            wg_commit();
            G1_STAGE(a1, true, 4, 0); G1_RETIRE();
            pin(kv); pin(zs);
            G1_STAGE(a1, true, 5, 0);
#define KV_RED(W) do { asm volatile("red.global.add.v4.f32 [%0], {%1,%2,%3,%4};" :: "l"(kvp + lane * 4), "f"(kv[8 * W]), "f"(kv[8 * W + 1]), "f"(kv[8 * W + 2]), "f"(kv[8 * W + 3]) : "memory"); \
                       asm volatile("red.global.add.v4.f32 [%0], {%1,%2,%3,%4};" :: "l"(kvp + 128 + lane * 4), "f"(kv[8 * W + 4]), "f"(kv[8 * W + 5]), "f"(kv[8 * W + 6]), "f"(kv[8 * W + 7]) : "memory"); } while (0)
            if ((warp & 3) == 0) KV_RED(0); else if ((warp & 3) == 1) KV_RED(1); else if ((warp & 3) == 2) KV_RED(2); else KV_RED(3);
            if ((lane & 3) == 0) {
                asm volatile("red.global.add.f32 [%0], %1;" :: "l"(kvp + 256 + (lane >> 2)), "f"(zs[0]) : "memory");
                asm volatile("red.global.add.f32 [%0], %1;" :: "l"(kvp + 264 + (lane >> 2)), "f"(zs[2]) : "memory");
            }
            __syncwarp();
            if (lane == 0) mbar_arrive(sb + B_KVDONE);
            G1_RETIRE();
        }
        G1_STAGE(a1, true, 6, 0); G1_RETIRE();
        G1_STAGE(a1, true, 7, 0); G1_RETIRE();
        if ((warp & 3) == 0) TS(wg, 3);

        G1_STAGE(a2_, false, 0, 1); G1_RETIRE();
        pin(a1);
        G1_STAGE(a2_, false, 1, 0);
#pragma unroll
        for (int i = 0; i < 8; i++) fo[i] = pack2(phi(a1[2 * i]), phi(a1[2 * i + 1]));
        G1_RETIRE();
        G1_STAGE(a2_, false, 2, 0);
#pragma unroll
        for (int i = 8; i < 16; i++) fo[i] = pack2(phi(a1[2 * i]), phi(a1[2 * i + 1]));
        G1_RETIRE();
        G1_STAGE(a2_, false, 3, 0);
        H_EPI(a1, fh3, 8, 32, 48);
        send_frag<0, 2>(fh3, hsend + 4 * 1024, tag);
        G1_RETIRE();
#pragma unroll 1
        for (int kb = 4; kb < 8; kb++) { G1_STAGE(a2_, false, kb, 0); G1_RETIRE(); }
        if ((warp & 3) == 0) TS(wg, 4);

        const uint32_t odd = j & 1;
        const uint32_t a2 = sb + OFF_X + wg * 8192 + srow;
        uint32_t qa[16], qb[16], qh[8];
        G1_STAGE(a3, false, 0, 1); G1_RETIRE();
        pin(a2_);
        G1_STAGE(a3, false, 1, 0);
        H_EPI(a2_, fh1, 16, 0, 32);
        send_frag<0, 4>(fh1, hsend + 1024, tag);
        recv_issue(qa, hrecv); recv_issue(qh, hrecv + 4 * 1024);
        G1_RETIRE();
        G1_STAGE(a3, false, 2, 0); stash<16>(a2, ssw, fh0); G1_RETIRE();
        G1_STAGE(a3, false, 3, 0); stash<16>(a2 + 16384, ssw, fh1); recv_issue(qb, hrecv + 1024); G1_RETIRE();
        G1_STAGE(a3, false, 4, 0); recv_check(qa, hrecv, tag); stash<16>(a2 + 2 * 16384, ssw, qa); G1_RETIRE();
        G1_STAGE(a3, false, 5, 0); recv_check(qb, hrecv + 1024, tag); stash<16>(a2 + 3 * 16384, ssw, qb); G1_RETIRE();
        G1_STAGE(a3, false, 6, 0);
        recv_check(qh, hrecv + 4 * 1024, tag);
        stash<8>(a2 + 4 * 16384, ssw ^ (odd << 2), fh3); stash<8>(a2 + 4 * 16384, ssw ^ (odd << 2) ^ 4, qh);
        if ((warp & 3) == 0) TS(wg, 5);
        mbar_wait(sb + B_KVRDY, 0);
        if ((warp & 3) == 0) TS(wg, 6);
#pragma unroll
        for (int h = 0; h < 4; h++) {
            uint32_t b0, b1, b2, b3, z0, z1;
            asm volatile("ld.shared.v4.u32 {%0,%1,%2,%3}, [%4];" : "=r"(b0), "=r"(b1), "=r"(b2), "=r"(b3) : "r"(sb + OFF_KVF + h * 512 + lane * 16) : "memory");
            asm volatile("ld.shared.v2.u32 {%0,%1}, [%2];" : "=r"(z0), "=r"(z1) : "r"(sb + OFF_ZF + h * 32 + (lane & 3) * 8) : "memory");
            float n0[4] = {0.f, 0.f, 0.f, 0.f}, n1[4] = {0.f, 0.f, 0.f, 0.f}, dn[4] = {0.f, 0.f, 0.f, 0.f};
            mma16816(dn, fo[4 * h], fo[4 * h + 1], fo[4 * h + 2], fo[4 * h + 3], z0, z1);
            mma16816(n0, fo[4 * h], fo[4 * h + 1], fo[4 * h + 2], fo[4 * h + 3], b0, b1);
            mma16816(n1, fo[4 * h], fo[4 * h + 1], fo[4 * h + 2], fo[4 * h + 3], b2, b3);
            const float s_lo = __fdividef(g_lo, dn[0] + 1e-6f), s_hi = __fdividef(g_hi, dn[2] + 1e-6f);
            fo[4 * h] = pack2(n0[0] * s_lo, n0[1] * s_lo); fo[4 * h + 1] = pack2(n0[2] * s_hi, n0[3] * s_hi);
            fo[4 * h + 2] = pack2(n1[0] * s_lo, n1[1] * s_lo); fo[4 * h + 3] = pack2(n1[2] * s_hi, n1[3] * s_hi);
        }
        send_frag<0, 4>(fo, hsend + 3 * 1024, tag);
        G1_RETIRE();
        G1_STAGE(a3, false, 7, 0);
        G1_RETIRE();
        A2_SYNC();
        if ((warp & 3) == 0) TS(wg, 7);

        const uint32_t slo = ((sb + OFF_STG + wg * 8192) >> 4) | LBO1;
#define G2_A(K) ((K) < 8 ? xlo + (K) * 1024 : slo)
#define G2_B(T) (ringlo + ((T) % 5) * 1024)
#define G2_WAIT(T) do { mbar_wait(sb + B_FULL + 8 * ((T) % 5), ((T) / 5) & 1); if (PROF && tid == 0) TS2(64 + 40 + (T)); } while (0)
#define G2_REL(T) do { if ((T) < 14) release((T) % 5); } while (0)
#define G2_W(T, acc) do { G2_WAIT(T); wg_fence(); _Pragma("unroll") for (int k = 0; k < 4; k++) { \
            if ((T) == 0 && k == 0) wg_ss128_z(acc, G2_A(T), DH128, G2_B(T) | LBO8K, DH128); \
            else wg_ss128(acc, G2_A(T) + 2 * k, DH128, (G2_B(T) | LBO8K) + 128 * k, DH128); } wg_commit(); } while (0)
        const uint32_t h3o = xlo + 4 * 1024 + 4 * odd, h3p = xlo + 4 * 1024 + 4 * (odd ^ 1);
#define G2_NA(U, k) ((U) < 2 ? G2_A(2 * (U) + ((k) >> 2)) + 2 * ((k) & 3) : (U) == 2 ? G2_A(5 + ((k) >> 2)) + 2 * ((k) & 3) : \
                     (k) < 4 ? G2_A((U) + 4) + 2 * (k) : ((U) == 3 ? h3o : h3p) + 2 * ((k) & 3))
#define G2_N(T, acc, U) do { G2_WAIT(T); wg_fence(); _Pragma("unroll") for (int k = 0; k < ((U) >= 3 ? 6 : 8); k++) { \
            if ((U) == 0 && k == 0) wg_ss64_z(acc, G2_A(0), DH128, G2_B(T) | LBO1, DH128); \
            else wg_ss64(acc, G2_NA(U, k), DH128, (G2_B(T) | LBO1) + 128 * k, DH128); } wg_commit(); } while (0)

        const int p = j >> 1;
        uint4* const pbase = g_part + (size_t)(r * 2 + (j & 1)) * 16384 + warp * 128 + lane;
        const int pw = (p & 2) ^ 2;
        auto other = [&](int d) { return d == 3 ? p ^ 1 : pw + d - 1; };
        auto sendp = [&](int d) { return pbase + ((other(d) * 4 + p) << 10); };
        auto recvp = [&](int d) { return pbase + ((p * 4 + other(d)) << 10); };

        float p1[64], p2[32], p3[32];
        G2_W(0, p1);
        wg_wait<1>();
        release(prev);
        pin(a3);
        G2_W(1, p1);
        H_EPI(a3, fh2, 16, 0, 32);
        send_frag<0, 4>(fh2, hsend + 2 * 1024, tag);
        recv_issue(qa, hrecv + 3 * 1024);
        stash<16>(a2 + 7 * 16384, ssw, fh2); stash<16>(a2 + (5 + odd) * 16384, ssw, fo);
        wg_wait<1>(); G2_REL(0);
        G2_W(2, p1); wg_wait<1>(); G2_REL(1);
        G2_W(3, p1);
        recv_check(qa, hrecv + 3 * 1024, tag); stash<16>(a2 + (6 - odd) * 16384, ssw, qa);
        wg_wait<1>(); G2_REL(2);
        G2_W(4, p1);
        recv_issue(qb, hrecv + 2 * 1024);
        wg_wait<1>(); G2_REL(3);
        A2_SYNC();
        G2_W(5, p1); wg_wait<1>(); G2_REL(4);
        G2_W(6, p1);
        recv_check(qb, hrecv + 2 * 1024, tag); stash<16>(sb + OFF_STG + wg * 8192 + srow, ssw, qb);
        wg_wait<1>(); G2_REL(5);
        G2_W(7, p1); wg_wait<1>(); G2_REL(6);
        A2_SYNC();
        G2_W(8, p1); wg_wait<1>(); G2_REL(7);
        if ((warp & 3) == 0) TS(wg, 8);
        uint32_t sp[32];
        G2_N(9, p2, 0); wg_wait<1>(); G2_REL(8);
        pin(p1);
        pack_acc(sp, p1);
        G2_N(10, p2, 1); send_frag<0, 2>(sp, sendp(1), tag); wg_wait<1>(); G2_REL(9);
        G2_N(11, p2, 2); send_frag<2, 4>(sp, sendp(1), tag); wg_wait<1>(); G2_REL(10);
        G2_N(12, p2, 3); send_frag<4, 6>(sp, sendp(2), tag); wg_wait<1>(); G2_REL(11);
        G2_N(13, p2, 4); send_frag<6, 8>(sp, sendp(2), tag); wg_wait<1>(); G2_REL(12);
        if ((warp & 3) == 0) TS(wg, 9);
        float sum[32];
        uint32_t qc[16];
        G2_N(14, p3, 0); wg_wait<1>(); G2_REL(13);
        pin(p2);
        pack_acc(qc, p2);
        send_frag<0, 4>(qc, sendp(3), tag);
        G2_N(15, p3, 1);
        recv_issue(qa, recvp(1)); recv_issue(qb, recvp(2));
        G2_N(16, p3, 2);
        G2_N(17, p3, 3);
        recv_issue(qc, recvp(3));
        G2_N(18, p3, 4);
        if ((warp & 3) == 0) TS(wg, 10);
        recv_check(qa, recvp(1), tag); accum<true>(qa, sum);
        recv_check(qb, recvp(2), tag); accum<false>(qb, sum);
        if ((warp & 3) == 0) TS(wg, 12);
        recv_check(qc, recvp(3), tag); accum<false>(qc, sum);
        if ((warp & 3) == 0) TS(wg, 13);
        wg_wait<0>();
        pin(p3);
        {
            uint32_t f[16];
#pragma unroll
            for (int i = 0; i < 16; i++) f[i] = pack2(p3[2 * i] + sum[2 * i], p3[2 * i + 1] + sum[2 * i + 1]);
            const uint32_t slab = sb + OFF_X + wg * 8192;
            stash<16>(slab + srow, ssw, f);
            __syncwarp();
            __nv_bfloat16* op = out + (size_t)(r * 128 + warp * 16 + (lane >> 3)) * kD + (j & 1) * 256 + p * 64 + (lane & 7) * 8;
#pragma unroll
            for (int i = 0; i < 4; i++) {
                const int row = i * 4 + (lane >> 3);
                uint4 v;
                asm volatile("ld.shared.v4.u32 {%0,%1,%2,%3}, [%4];" : "=r"(v.x), "=r"(v.y), "=r"(v.z), "=r"(v.w)
                             : "r"(slab + ((warp & 3) * 16 + row) * 128 + (((lane & 7) ^ (row & 7)) << 4)) : "memory");
                *(uint4*)(op + i * 4 * kD) = v;
            }
        }
        if ((warp & 3) == 0) { TS(wg, 14); TSG(wg, 31); }
    }
}

typedef CUresult (*EncodeFn)(CUtensorMap*, CUtensorMapDataType, cuuint32_t, void*, const cuuint64_t*, const cuuint64_t*, const cuuint32_t*,
                             const cuuint32_t*, CUtensorMapInterleave, CUtensorMapSwizzle, CUtensorMapL2promotion, CUtensorMapFloatOOBfill);

static void encode(EncodeFn fn, CUtensorMap* m, int rank, const void* base, const cuuint64_t (&gd)[4], const cuuint64_t (&gs)[3],
                   const cuuint32_t (&bd)[4], CUtensorMapSwizzle sw) {
    cuuint32_t es[4] = {1, 1, 1, 1};
    fn(m, CU_TENSOR_MAP_DATA_TYPE_BFLOAT16, rank, const_cast<void*>(base), gd, gs, bd, es, CU_TENSOR_MAP_INTERLEAVE_NONE, sw,
       CU_TENSOR_MAP_L2_PROMOTION_L2_128B, CU_TENSOR_MAP_FLOAT_OOB_FILL_NONE);
}

extern "C" void kernel_launch(void* const* d_in, const int* in_sizes, int n_in, void* d_out, int out_size) {
    const char* x = (const char*)d_in[0];
    const char* wqkv = (const char*)d_in[1];
    const char* wo = (const char*)d_in[2];
    const char* wg = (const char*)d_in[4];
    const char* wu = (const char*)d_in[5];
    const char* wd = (const char*)d_in[6];
    void* fnp = nullptr;
    cudaDriverEntryPointQueryResult qr;
    cudaGetDriverEntryPoint("cuTensorMapEncodeTiled", &fnp, cudaEnableDefault, &qr);
    EncodeFn fn = (EncodeFn)fnp;
    Maps maps;
    const char* lo = wg < wu ? wg : wu;
    const uint64_t diff = wg < wu ? (uint64_t)(wu - wg) : (uint64_t)(wg - wu);
    const CUtensorMapSwizzle S128 = CU_TENSOR_MAP_SWIZZLE_128B, S64 = CU_TENSOR_MAP_SWIZZLE_64B;
    encode(fn, &maps.x, 2, x, {512, 2048, 1, 1}, {1024, 0, 0}, {64, 128, 1, 1}, S128);
    encode(fn, &maps.gu, 3, lo, {1792, 512, 2, 1}, {3584, diff, 0}, {64, 64, 2, 1}, S128);
    encode(fn, &maps.kv, 3, wqkv, {512, 512, 3, 1}, {3072, 1024, 0}, {64, 64, 2, 1}, S128);
    encode(fn, &maps.q64, 3, wqkv, {32, 512, 48, 1}, {3072, 64, 0}, {32, 64, 2, 1}, S64);
    encode(fn, &maps.gu64, 3, lo, {1792, 512, 2, 1}, {3584, diff, 0}, {32, 64, 2, 1}, S64);
    encode(fn, &maps.wdw, 3, wd, {64, 1792, 8, 1}, {1024, 128, 0}, {64, 64, 2, 1}, S128);
    encode(fn, &maps.wdx, 4, wd, {64, 1568, 2, 8}, {1024, 224 * 1024, 128}, {64, 32, 2, 2}, S128);
    encode(fn, &maps.wow, 3, wo, {64, 512, 8, 1}, {1024, 128, 0}, {64, 64, 2, 1}, S128);
    encode(fn, &maps.wdn128, 2, wd, {512, 1792, 1, 1}, {1024, 0, 0}, {64, 128, 1, 1}, S128);
    encode(fn, &maps.wdn96, 2, wd, {512, 1792, 1, 1}, {1024, 0, 0}, {64, 96, 1, 1}, S128);
    encode(fn, &maps.won128, 2, wo, {512, 512, 1, 1}, {1024, 0, 0}, {64, 128, 1, 1}, S128);
    cudaFuncSetAttribute(fused_kernel, cudaFuncAttributeMaxDynamicSharedMemorySize, SMEM_BYTES);
    cudaLaunchConfig_t cfg = {};
    cfg.gridDim = dim3(128);
    cfg.blockDim = dim3(384);
    cfg.dynamicSmemBytes = SMEM_BYTES;
    cfg.stream = cudaStreamPerThread;
    cudaLaunchAttribute at[1];
    at[0].id = cudaLaunchAttributeClusterDimension;
    at[0].val.clusterDim.x = 2; at[0].val.clusterDim.y = 1; at[0].val.clusterDim.z = 1;
    cfg.attrs = at;
    cfg.numAttrs = MC ? 1 : 0;
    cudaLaunchKernelEx(&cfg, fused_kernel, maps, (const __nv_bfloat16*)d_in[0], (const __nv_bfloat16*)d_in[7], wqkv, wg, wu, wd, wo, (__nv_bfloat16*)d_out);
}
```

```cpp
#include <cuda_runtime.h>
#include <cuda.h>
#include <cuda_bf16.h>
#include <stdint.h>

#define MC 0
#define PROF 0

namespace {

constexpr int kD = 512;
constexpr uint32_t OFF_X = 0, OFF_STG = 131072, OFF_RING = 147456, OFF_MISC = 229376;
constexpr uint32_t B_FULL = OFF_MISC, B_EMPTY = OFF_MISC + 40, B_XFULL = OFF_MISC + 80;
constexpr uint32_t B_GRDY = OFF_MISC + 152, B_KVDONE = OFF_MISC + 160, B_KVRDY = OFF_MISC + 168;
constexpr uint32_t B_HSENT = OFF_MISC + 176, B_XFREE = OFF_MISC + 216;
constexpr uint32_t OFF_EPOCH = OFF_MISC + 240, OFF_G = OFF_MISC + 256;
constexpr uint32_t OFF_KVF = OFF_MISC + 768, OFF_ZF = OFF_KVF + 2048;
constexpr uint32_t OFF_ONES = OFF_ZF + 128;
constexpr uint32_t SMEM_BYTES = OFF_ONES + 128;
constexpr uint32_t SPIN_MBAR = 1u << 16, SPIN_GLOBAL = 1u << 14;

struct alignas(64) Maps { CUtensorMap x, gu, kv, q64, gu64, wdw, wdh, wow, wdp, wdph, wop, hx, hxh; };

}

__device__ uint4 g_part[16 * 2 * 4 * 4 * 1024];
__device__ uint4 g_hx[16 * 8 * 5 * 1024];
__device__ unsigned g_hflag[128 * 8];
__device__ uint4 g_gx[16 * 32];
__device__ float g_kvacc[2 * 8 * 4 * 272];
__device__ unsigned g_kvcnt[8 * 32];
__device__ unsigned g_epoch[128];
#define TS(role, idx)
#define TS2(idx)
#define TSG(role, idx)

namespace {

__device__ __forceinline__ void mbar_init(uint32_t bar, uint32_t cnt) { asm volatile("mbarrier.init.shared::cta.b64 [%0], %1;" :: "r"(bar), "r"(cnt) : "memory"); }
__device__ __forceinline__ void mbar_expect(uint32_t bar, uint32_t bytes) { asm volatile("mbarrier.arrive.expect_tx.shared::cta.b64 _, [%0], %1;" :: "r"(bar), "r"(bytes) : "memory"); }
__device__ __forceinline__ void mbar_arrive(uint32_t bar) { asm volatile("mbarrier.arrive.shared::cta.b64 _, [%0];" :: "r"(bar) : "memory"); }
__device__ __forceinline__ void mbar_arrive_cta(uint32_t bar, uint32_t cta) {
    asm volatile("{\n.reg .b32 ra;\nmapa.shared::cluster.u32 ra, %0, %1;\nmbarrier.arrive.shared::cluster.b64 _, [ra];\n}" :: "r"(bar), "r"(cta) : "memory");
}
__device__ __forceinline__ void mbar_wait(uint32_t bar, uint32_t parity) {
    uint32_t ok, it = 0;
    do {
        asm volatile("{\n.reg .pred p;\nmbarrier.try_wait.parity.shared::cta.b64 p, [%1], %2;\nselp.u32 %0, 1, 0, p;\n}" : "=r"(ok) : "r"(bar), "r"(parity) : "memory");
    } while (!ok && ++it < SPIN_MBAR);
}
__device__ __forceinline__ void tma2(uint32_t dst, const CUtensorMap* m, int c0, int c1, uint32_t bar) {
    asm volatile("cp.async.bulk.tensor.2d.shared::cluster.global.mbarrier::complete_tx::bytes [%0], [%1, {%3, %4}], [%2];"
        :: "r"(dst), "l"(m), "r"(bar), "r"(c0), "r"(c1) : "memory");
}
__device__ __forceinline__ void tmaw2(uint32_t dst, const CUtensorMap* m, int c0, int c1, uint32_t bar) {
    tma2(dst, m, c0, c1, bar);
}
__device__ __forceinline__ void tmaw3(uint32_t dst, const CUtensorMap* m, int c0, int c1, int c2, uint32_t bar) {
    asm volatile("cp.async.bulk.tensor.3d.shared::cluster.global.mbarrier::complete_tx::bytes [%0], [%1, {%3, %4, %5}], [%2];"
        :: "r"(dst), "l"(m), "r"(bar), "r"(c0), "r"(c1), "r"(c2) : "memory");
}
__device__ __forceinline__ void tmaw5(uint32_t dst, const CUtensorMap* m, int c0, int c4, uint32_t bar) {
    asm volatile("cp.async.bulk.tensor.5d.shared::cluster.global.mbarrier::complete_tx::bytes [%0], [%1, {%3, %5, %5, %5, %4}], [%2];"
        :: "r"(dst), "l"(m), "r"(bar), "r"(c0), "r"(c4), "r"(0) : "memory");
}
__device__ __forceinline__ void l2_prefetch(const void* p, uint32_t bytes) { asm volatile("cp.async.bulk.prefetch.L2.global [%0], %1;" :: "l"(p), "r"(bytes) : "memory"); }
__device__ __forceinline__ void wg_fence() { asm volatile("wgmma.fence.sync.aligned;" ::: "memory"); }
__device__ __forceinline__ void wg_commit() { asm volatile("wgmma.commit_group.sync.aligned;" ::: "memory"); }
template <int N> __device__ __forceinline__ void wg_wait() { asm volatile("wgmma.wait_group.sync.aligned %0;" :: "n"(N) : "memory"); }
template <int N> __device__ __forceinline__ void pin(float (&d)[N]) {
#pragma unroll
    for (int i = 0; i < N; i++) asm volatile("" : "+f"(d[i]) :: "memory");
}
__device__ __forceinline__ uint32_t pack2(float lo, float hi) { uint32_t r; asm("cvt.rn.bf16x2.f32 %0, %1, %2;" : "=r"(r) : "f"(hi), "f"(lo)); return r; }
__device__ __forceinline__ float phi(float t) {
    float e;
    asm("ex2.approx.ftz.f32 %0, %1;" : "=f"(e) : "f"(fminf(t * 1.4426950408889634f, 0.f)));
    return e + (fmaxf(t, 0.f) + 1e-6f);
}
__device__ __forceinline__ void stsm4(uint32_t a, uint32_t r0, uint32_t r1, uint32_t r2, uint32_t r3) {
    asm volatile("stmatrix.sync.aligned.m8n8.x4.shared.b16 [%0], {%1,%2,%3,%4};" :: "r"(a), "r"(r0), "r"(r1), "r"(r2), "r"(r3) : "memory");
}
__device__ __forceinline__ void mma16816(float (&c)[4], uint32_t a0, uint32_t a1, uint32_t a2, uint32_t a3, uint32_t b0, uint32_t b1) {
    asm volatile("mma.sync.aligned.m16n8k16.row.col.f32.bf16.bf16.f32 {%0,%1,%2,%3}, {%4,%5,%6,%7}, {%8,%9}, {%0,%1,%2,%3};"
        : "+f"(c[0]), "+f"(c[1]), "+f"(c[2]), "+f"(c[3]) : "r"(a0), "r"(a1), "r"(a2), "r"(a3), "r"(b0), "r"(b1));
}
__device__ __forceinline__ float bf_lo(uint32_t w) { return __uint_as_float(w << 16); }
__device__ __forceinline__ float bf_hi(uint32_t w) { return __uint_as_float(w & 0xffff0000u); }
__device__ __forceinline__ void st_pkt(uint4* p, uint32_t w0, uint32_t w1, uint32_t w2, uint32_t w3) {
    asm volatile("{\n.reg .b64 lo, hi;\n.reg .b128 v;\nmov.b64 lo, {%1, %2};\nmov.b64 hi, {%3, %4};\nmov.b128 v, {lo, hi};\nst.relaxed.gpu.global.b128 [%0], v;\n}"
        :: "l"(p), "r"(w0), "r"(w1), "r"(w2), "r"(w3) : "memory");
}
__device__ __forceinline__ void ld_pkt(const uint4* p, uint32_t& w0, uint32_t& w1, uint32_t& w2, uint32_t& w3) {
    asm volatile("{\n.reg .b64 lo, hi;\n.reg .b128 v;\nld.relaxed.gpu.global.b128 v, [%4];\nmov.b128 {lo, hi}, v;\nmov.b64 {%0, %1}, lo;\nmov.b64 {%2, %3}, hi;\n}"
        : "=r"(w0), "=r"(w1), "=r"(w2), "=r"(w3) : "l"(p) : "memory");
}

__device__ __forceinline__ void wg_ss128(float (&d)[64], uint32_t alo, uint32_t ahi, uint32_t blo, uint32_t bhi) {
    asm volatile("{\n.reg .b64 da, db;\nmov.b64 da, {%64, %65};\nmov.b64 db, {%66, %67};\n"
        "wgmma.mma_async.sync.aligned.m64n128k16.f32.bf16.bf16 {%0,%1,%2,%3,%4,%5,%6,%7,%8,%9,%10,%11,%12,%13,%14,%15,%16,%17,%18,%19,%20,%21,%22,%23,%24,%25,%26,%27,%28,%29,%30,%31,%32,%33,%34,%35,%36,%37,%38,%39,%40,%41,%42,%43,%44,%45,%46,%47,%48,%49,%50,%51,%52,%53,%54,%55,%56,%57,%58,%59,%60,%61,%62,%63}, da, db, 1, 1, 1, 0, 1;\n}\n"
        : "+f"(d[0]),"+f"(d[1]),"+f"(d[2]),"+f"(d[3]),"+f"(d[4]),"+f"(d[5]),"+f"(d[6]),"+f"(d[7]),"+f"(d[8]),"+f"(d[9]),"+f"(d[10]),"+f"(d[11]),"+f"(d[12]),"+f"(d[13]),"+f"(d[14]),"+f"(d[15]),"+f"(d[16]),"+f"(d[17]),"+f"(d[18]),"+f"(d[19]),"+f"(d[20]),"+f"(d[21]),"+f"(d[22]),"+f"(d[23]),"+f"(d[24]),"+f"(d[25]),"+f"(d[26]),"+f"(d[27]),"+f"(d[28]),"+f"(d[29]),"+f"(d[30]),"+f"(d[31]),"+f"(d[32]),"+f"(d[33]),"+f"(d[34]),"+f"(d[35]),"+f"(d[36]),"+f"(d[37]),"+f"(d[38]),"+f"(d[39]),"+f"(d[40]),"+f"(d[41]),"+f"(d[42]),"+f"(d[43]),"+f"(d[44]),"+f"(d[45]),"+f"(d[46]),"+f"(d[47]),"+f"(d[48]),"+f"(d[49]),"+f"(d[50]),"+f"(d[51]),"+f"(d[52]),"+f"(d[53]),"+f"(d[54]),"+f"(d[55]),"+f"(d[56]),"+f"(d[57]),"+f"(d[58]),"+f"(d[59]),"+f"(d[60]),"+f"(d[61]),"+f"(d[62]),"+f"(d[63])
        : "r"(alo), "r"(ahi), "r"(blo), "r"(bhi));
}
__device__ __forceinline__ void wg_ss128_z(float (&d)[64], uint32_t alo, uint32_t ahi, uint32_t blo, uint32_t bhi) {
    asm volatile("{\n.reg .b64 da, db;\nmov.b64 da, {%64, %65};\nmov.b64 db, {%66, %67};\n"
        "wgmma.mma_async.sync.aligned.m64n128k16.f32.bf16.bf16 {%0,%1,%2,%3,%4,%5,%6,%7,%8,%9,%10,%11,%12,%13,%14,%15,%16,%17,%18,%19,%20,%21,%22,%23,%24,%25,%26,%27,%28,%29,%30,%31,%32,%33,%34,%35,%36,%37,%38,%39,%40,%41,%42,%43,%44,%45,%46,%47,%48,%49,%50,%51,%52,%53,%54,%55,%56,%57,%58,%59,%60,%61,%62,%63}, da, db, 0, 1, 1, 0, 1;\n}\n"
        : "=f"(d[0]),"=f"(d[1]),"=f"(d[2]),"=f"(d[3]),"=f"(d[4]),"=f"(d[5]),"=f"(d[6]),"=f"(d[7]),"=f"(d[8]),"=f"(d[9]),"=f"(d[10]),"=f"(d[11]),"=f"(d[12]),"=f"(d[13]),"=f"(d[14]),"=f"(d[15]),"=f"(d[16]),"=f"(d[17]),"=f"(d[18]),"=f"(d[19]),"=f"(d[20]),"=f"(d[21]),"=f"(d[22]),"=f"(d[23]),"=f"(d[24]),"=f"(d[25]),"=f"(d[26]),"=f"(d[27]),"=f"(d[28]),"=f"(d[29]),"=f"(d[30]),"=f"(d[31]),"=f"(d[32]),"=f"(d[33]),"=f"(d[34]),"=f"(d[35]),"=f"(d[36]),"=f"(d[37]),"=f"(d[38]),"=f"(d[39]),"=f"(d[40]),"=f"(d[41]),"=f"(d[42]),"=f"(d[43]),"=f"(d[44]),"=f"(d[45]),"=f"(d[46]),"=f"(d[47]),"=f"(d[48]),"=f"(d[49]),"=f"(d[50]),"=f"(d[51]),"=f"(d[52]),"=f"(d[53]),"=f"(d[54]),"=f"(d[55]),"=f"(d[56]),"=f"(d[57]),"=f"(d[58]),"=f"(d[59]),"=f"(d[60]),"=f"(d[61]),"=f"(d[62]),"=f"(d[63])
        : "r"(alo), "r"(ahi), "r"(blo), "r"(bhi));
}
__device__ __forceinline__ void wg_ss64(float (&d)[32], uint32_t alo, uint32_t ahi, uint32_t blo, uint32_t bhi) {
    asm volatile("{\n.reg .b64 da, db;\nmov.b64 da, {%32, %33};\nmov.b64 db, {%34, %35};\n"
        "wgmma.mma_async.sync.aligned.m64n64k16.f32.bf16.bf16 {%0,%1,%2,%3,%4,%5,%6,%7,%8,%9,%10,%11,%12,%13,%14,%15,%16,%17,%18,%19,%20,%21,%22,%23,%24,%25,%26,%27,%28,%29,%30,%31}, da, db, 1, 1, 1, 0, 1;\n}\n"
        : "+f"(d[0]),"+f"(d[1]),"+f"(d[2]),"+f"(d[3]),"+f"(d[4]),"+f"(d[5]),"+f"(d[6]),"+f"(d[7]),"+f"(d[8]),"+f"(d[9]),"+f"(d[10]),"+f"(d[11]),"+f"(d[12]),"+f"(d[13]),"+f"(d[14]),"+f"(d[15]),"+f"(d[16]),"+f"(d[17]),"+f"(d[18]),"+f"(d[19]),"+f"(d[20]),"+f"(d[21]),"+f"(d[22]),"+f"(d[23]),"+f"(d[24]),"+f"(d[25]),"+f"(d[26]),"+f"(d[27]),"+f"(d[28]),"+f"(d[29]),"+f"(d[30]),"+f"(d[31])
        : "r"(alo), "r"(ahi), "r"(blo), "r"(bhi));
}
__device__ __forceinline__ void wg_ss64_z(float (&d)[32], uint32_t alo, uint32_t ahi, uint32_t blo, uint32_t bhi) {
    asm volatile("{\n.reg .b64 da, db;\nmov.b64 da, {%32, %33};\nmov.b64 db, {%34, %35};\n"
        "wgmma.mma_async.sync.aligned.m64n64k16.f32.bf16.bf16 {%0,%1,%2,%3,%4,%5,%6,%7,%8,%9,%10,%11,%12,%13,%14,%15,%16,%17,%18,%19,%20,%21,%22,%23,%24,%25,%26,%27,%28,%29,%30,%31}, da, db, 0, 1, 1, 0, 1;\n}\n"
        : "=f"(d[0]),"=f"(d[1]),"=f"(d[2]),"=f"(d[3]),"=f"(d[4]),"=f"(d[5]),"=f"(d[6]),"=f"(d[7]),"=f"(d[8]),"=f"(d[9]),"=f"(d[10]),"=f"(d[11]),"=f"(d[12]),"=f"(d[13]),"=f"(d[14]),"=f"(d[15]),"=f"(d[16]),"=f"(d[17]),"=f"(d[18]),"=f"(d[19]),"=f"(d[20]),"=f"(d[21]),"=f"(d[22]),"=f"(d[23]),"=f"(d[24]),"=f"(d[25]),"=f"(d[26]),"=f"(d[27]),"=f"(d[28]),"=f"(d[29]),"=f"(d[30]),"=f"(d[31])
        : "r"(alo), "r"(ahi), "r"(blo), "r"(bhi));
}
__device__ __forceinline__ void wg_ss64t(float (&d)[32], uint32_t alo, uint32_t ahi, uint32_t blo, uint32_t bhi) {
    asm volatile("{\n.reg .b64 da, db;\nmov.b64 da, {%32, %33};\nmov.b64 db, {%34, %35};\n"
        "wgmma.mma_async.sync.aligned.m64n64k16.f32.bf16.bf16 {%0,%1,%2,%3,%4,%5,%6,%7,%8,%9,%10,%11,%12,%13,%14,%15,%16,%17,%18,%19,%20,%21,%22,%23,%24,%25,%26,%27,%28,%29,%30,%31}, da, db, 1, 1, 1, 1, 1;\n}\n"
        : "+f"(d[0]),"+f"(d[1]),"+f"(d[2]),"+f"(d[3]),"+f"(d[4]),"+f"(d[5]),"+f"(d[6]),"+f"(d[7]),"+f"(d[8]),"+f"(d[9]),"+f"(d[10]),"+f"(d[11]),"+f"(d[12]),"+f"(d[13]),"+f"(d[14]),"+f"(d[15]),"+f"(d[16]),"+f"(d[17]),"+f"(d[18]),"+f"(d[19]),"+f"(d[20]),"+f"(d[21]),"+f"(d[22]),"+f"(d[23]),"+f"(d[24]),"+f"(d[25]),"+f"(d[26]),"+f"(d[27]),"+f"(d[28]),"+f"(d[29]),"+f"(d[30]),"+f"(d[31])
        : "r"(alo), "r"(ahi), "r"(blo), "r"(bhi));
}
__device__ __forceinline__ void wg_ss64t_z(float (&d)[32], uint32_t alo, uint32_t ahi, uint32_t blo, uint32_t bhi) {
    asm volatile("{\n.reg .b64 da, db;\nmov.b64 da, {%32, %33};\nmov.b64 db, {%34, %35};\n"
        "wgmma.mma_async.sync.aligned.m64n64k16.f32.bf16.bf16 {%0,%1,%2,%3,%4,%5,%6,%7,%8,%9,%10,%11,%12,%13,%14,%15,%16,%17,%18,%19,%20,%21,%22,%23,%24,%25,%26,%27,%28,%29,%30,%31}, da, db, 0, 1, 1, 1, 1;\n}\n"
        : "=f"(d[0]),"=f"(d[1]),"=f"(d[2]),"=f"(d[3]),"=f"(d[4]),"=f"(d[5]),"=f"(d[6]),"=f"(d[7]),"=f"(d[8]),"=f"(d[9]),"=f"(d[10]),"=f"(d[11]),"=f"(d[12]),"=f"(d[13]),"=f"(d[14]),"=f"(d[15]),"=f"(d[16]),"=f"(d[17]),"=f"(d[18]),"=f"(d[19]),"=f"(d[20]),"=f"(d[21]),"=f"(d[22]),"=f"(d[23]),"=f"(d[24]),"=f"(d[25]),"=f"(d[26]),"=f"(d[27]),"=f"(d[28]),"=f"(d[29]),"=f"(d[30]),"=f"(d[31])
        : "r"(alo), "r"(ahi), "r"(blo), "r"(bhi));
}
__device__ __forceinline__ void wg_ss8t(float (&d)[4], uint32_t alo, uint32_t ahi, uint32_t blo, uint32_t bhi) {
    asm volatile("{\n.reg .b64 da, db;\nmov.b64 da, {%4, %5};\nmov.b64 db, {%6, %7};\n"
        "wgmma.mma_async.sync.aligned.m64n8k16.f32.bf16.bf16 {%0,%1,%2,%3}, da, db, 1, 1, 1, 1, 0;\n}\n"
        : "+f"(d[0]),"+f"(d[1]),"+f"(d[2]),"+f"(d[3])
        : "r"(alo), "r"(ahi), "r"(blo), "r"(bhi));
}
__device__ __forceinline__ void wg_ss8t_z(float (&d)[4], uint32_t alo, uint32_t ahi, uint32_t blo, uint32_t bhi) {
    asm volatile("{\n.reg .b64 da, db;\nmov.b64 da, {%4, %5};\nmov.b64 db, {%6, %7};\n"
        "wgmma.mma_async.sync.aligned.m64n8k16.f32.bf16.bf16 {%0,%1,%2,%3}, da, db, 0, 1, 1, 1, 0;\n}\n"
        : "=f"(d[0]),"=f"(d[1]),"=f"(d[2]),"=f"(d[3])
        : "r"(alo), "r"(ahi), "r"(blo), "r"(bhi));
}

constexpr uint32_t DH128 = 64u | 0x40000000u;
constexpr uint32_t DH64 = 32u | 0x80000000u;
constexpr uint32_t LBO4K = (4096u >> 4) << 16, LBO8K = (8192u >> 4) << 16, LBO1 = 1u << 16;

template <bool SW64, bool FIRST> __device__ __forceinline__ void g1_issue(float (&acc)[64], uint32_t alo, uint32_t blo) {
    wg_fence();
#pragma unroll
    for (int k = 0; k < 4; k++) {
        if (FIRST && k == 0) wg_ss128_z(acc, alo, DH128, blo, SW64 ? DH64 : DH128);
        else wg_ss128(acc, alo + 2 * k, DH128, blo + (SW64 ? 64 * k : 128 * k), SW64 ? DH64 : DH128);
    }
    wg_commit();
}

template <int N> __device__ __forceinline__ void stash(uint32_t base, uint32_t sw, const uint32_t (&f)[N]) {
#pragma unroll
    for (int t = 0; t < N / 4; t++) stsm4(base + ((sw ^ (2 * t)) << 4), f[4 * t], f[4 * t + 1], f[4 * t + 2], f[4 * t + 3]);
}

template <int V0, int V1, int N> __device__ __forceinline__ void send_frag(const uint32_t (&f)[N], uint4* p, uint32_t tag) {
#pragma unroll
    for (int v = V0; v < V1; v++) st_pkt(p + (v & 3) * 32, (f[4 * v] & ~1u) | tag, f[4 * v + 1], f[4 * v + 2], f[4 * v + 3]);
}
template <int N> __device__ __forceinline__ void send_h(const uint32_t (&f)[N], uint4* p) {
#pragma unroll
    for (int h = 0; h < N / 8; h++) {
        p[4 * h] = make_uint4(f[8 * h], f[8 * h + 2], f[8 * h + 4], f[8 * h + 6]);
        p[4 * h + 64] = make_uint4(f[8 * h + 1], f[8 * h + 3], f[8 * h + 5], f[8 * h + 7]);
    }
}
template <int O, int N, int M> __device__ __forceinline__ void pack_sub(uint32_t (&f)[N], const float (&acc)[M]) {
#pragma unroll
    for (int i = 0; i < N; i++) f[i] = pack2(acc[O + 2 * i], acc[O + 2 * i + 1]);
}
template <int N> __device__ __forceinline__ void pack_acc(uint32_t (&f)[N], const float (&acc)[2 * N]) {
#pragma unroll
    for (int i = 0; i < N; i++) f[i] = pack2(acc[2 * i], acc[2 * i + 1]);
}
template <int N> __device__ __forceinline__ void recv_issue(uint32_t (&q)[N], const uint4* p) {
#pragma unroll
    for (int v = 0; v < N / 4; v++) ld_pkt(p + v * 32, q[4 * v], q[4 * v + 1], q[4 * v + 2], q[4 * v + 3]);
}
template <int N> __device__ __forceinline__ void recv_check(uint32_t (&q)[N], const uint4* p, uint32_t tag) {
    uint32_t it = 0;
    while (true) {
        uint32_t bad = 0;
#pragma unroll
        for (int v = 0; v < N / 4; v++) bad |= q[4 * v] ^ tag;
        if (__all_sync(0xffffffffu, (bad & 1u) == 0) || ++it > SPIN_GLOBAL) break;
        recv_issue(q, p);
    }
}
template <bool FIRST> __device__ __forceinline__ void accum(const uint32_t (&q)[16], float (&sum)[32]) {
#pragma unroll
    for (int i = 0; i < 16; i++) {
        if (FIRST) { sum[2 * i] = bf_lo(q[i]); sum[2 * i + 1] = bf_hi(q[i]); }
        else { sum[2 * i] += bf_lo(q[i]); sum[2 * i + 1] += bf_hi(q[i]); }
    }
}

}

__global__ void __launch_bounds__(384, 1)
fused_kernel(const __grid_constant__ Maps maps, const __nv_bfloat16* __restrict__ xg, const __nv_bfloat16* __restrict__ gate_w,
             const char* __restrict__ pf_qkv, const char* __restrict__ pf_g, const char* __restrict__ pf_u,
             const char* __restrict__ pf_d, const char* __restrict__ pf_o, __nv_bfloat16* __restrict__ out) {
    extern __shared__ __align__(1024) uint8_t smem_raw[];
    const uint32_t sb = (uint32_t)__cvta_generic_to_shared(smem_raw);
    const int tid = threadIdx.x, lane = tid & 31;
    const int warp = __shfl_sync(0xffffffffu, tid >> 5, 0);
    const int j = (blockIdx.x >> 1) & 7;
    const int r = ((blockIdx.x >> 4) << 1) | (blockIdx.x & 1);
    const uint32_t rank = blockIdx.x & 1;

    if (warp == 0) { TSG(0, 30); TS(0, 0); }
    if (warp == 9 && lane < 13) asm volatile("prefetch.tensormap [%0];" :: "l"(&maps.x + lane) : "memory");
    if (tid == 256) {
        for (int i = 0; i < 5; i++) { mbar_init(sb + B_FULL + 8 * i, 1); mbar_init(sb + B_EMPTY + 8 * i, MC ? 4 : 2); }
        for (int i = 0; i < 9; i++) mbar_init(sb + B_XFULL + 8 * i, 1);
        for (int i = 0; i < 5; i++) mbar_init(sb + B_HSENT + 8 * i, 8);
        mbar_init(sb + B_XFREE, 2); mbar_init(sb + B_XFREE + 8, 2);
        mbar_init(sb + B_GRDY, 1); mbar_init(sb + B_KVDONE, 8); mbar_init(sb + B_KVRDY, 1);
        asm volatile("fence.mbarrier_init.release.cluster;" ::: "memory");
        asm volatile("fence.proxy.async.shared::cta;" ::: "memory");
        mbar_expect(sb + B_XFULL, 16384);
        tma2(sb + OFF_X, &maps.x, 0, r * 128, sb + B_XFULL);
    }
    __syncthreads();

    if (warp >= 8) {
        asm volatile("setmaxnreg.dec.sync.aligned.u32 72;");
        if (warp == 8) {
            if (lane == 0) {
                int slot = 0, ph = 1;
                uint32_t full, dst;
#define P_BEGIN(S, BYTES) full = sb + B_FULL + 8 * slot; dst = sb + OFF_RING + slot * 16384; \
                mbar_wait(sb + B_EMPTY + 8 * slot, ph); TS2(S); mbar_expect(full, BYTES); if (!MC || (((S) ^ rank) & 1) == 0)
#define P_END() if (++slot == 5) { slot = 0; ph ^= 1; }
                for (int s = 0; s < 16; s++) {
                    P_BEGIN(s, 16384) {
                        if (s & 1) tmaw3(dst, &maps.kv, 64 * j, 32 * (s - 1), 1, full);
                        else tmaw3(dst, &maps.gu, 224 * j, 32 * s, 0, full);
                    }
                    const int xb = (s == 4) ? 3 : !(s & 1) ? 0 : (s < 5) ? (s + 1) / 2 : (s <= 11) ? (s + 3) / 2 : 0;
                    if (xb) { mbar_expect(sb + B_XFULL + 8 * xb, 16384); tma2(sb + OFF_X + xb * 16384, &maps.x, 64 * xb, r * 128, sb + B_XFULL + 8 * xb); }
                    P_END()
                }
                for (int s = 0; s < 8; s++) {
                    P_BEGIN(16 + s, 16384) {
                        tmaw3(dst, &maps.q64, 0, 64 * s, 2 * j, full);
                        tmaw3(dst + 8192, &maps.gu64, 224 * j + 192, 64 * s, 0, full);
                    }
                    P_END()
                }
                for (int s = 0; s < 16; s++) {
                    P_BEGIN(24 + s, 16384) tmaw3(dst, &maps.gu, 224 * j + 64 + 64 * (s >> 3), 64 * (s & 7), 0, full);
                    P_END()
                }
                const int p = j >> 1, ro = 224 * j, gp = 7 * (j ^ 1);
                for (int q = 0; q < 2; q++) {
                    const int cw = (j & 1) * 4 + ((p & 2) ^ (q ? 0 : 2)), cc = 64 * cw, t = 40 + 9 * q;
                    P_BEGIN(t, 16384) tmaw3(dst, &maps.wdw, 0, ro, cw, full); P_END()
                    P_BEGIN(t + 1, 16384) tmaw3(dst, &maps.wdw, 0, ro + 64, cw, full); P_END()
                    P_BEGIN(t + 2, 16384) { tmaw5(dst, &maps.wdp, cc, gp, full); tmaw5(dst + 8192, &maps.wdp, cc + 64, gp, full); } P_END()
                    P_BEGIN(t + 3, 16384) { tmaw5(dst, &maps.wdp, cc, gp + 2, full); tmaw5(dst + 8192, &maps.wdp, cc + 64, gp + 2, full); } P_END()
                    P_BEGIN(t + 4, 16384) {
                        tmaw5(dst, &maps.wdph, cc, gp + 6, full); tmaw5(dst + 4096, &maps.wdph, cc + 64, gp + 6, full);
                        tmaw3(dst + 8192, &maps.wdh, 0, ro + 192, cw, full);
                    } P_END()
                    P_BEGIN(t + 5, 16384) tmaw3(dst, &maps.wow, 0, 64 * j, cw, full); P_END()
                    P_BEGIN(t + 6, 16384) tmaw3(dst, &maps.wdw, 0, ro + 128, cw, full); P_END()
                    P_BEGIN(t + 7, 16384) { tmaw5(dst, &maps.wop, cc, 2 * (j ^ 1), full); tmaw5(dst + 8192, &maps.wop, cc + 64, 2 * (j ^ 1), full); } P_END()
                    P_BEGIN(t + 8, 16384) { tmaw5(dst, &maps.wdp, cc, gp + 4, full); tmaw5(dst + 8192, &maps.wdp, cc + 64, gp + 4, full); } P_END()
                }
            }
        } else if (warp < 11) {
            const int hx = warp - 9;
            uint32_t epoch;
            asm volatile("ld.relaxed.gpu.global.u32 %0, [%1];" : "=r"(epoch) : "l"(g_epoch + blockIdx.x) : "memory");
            {
                const uint4* xr = (const uint4*)(xg + (size_t)(r * 128 + j * 16 + hx * 8) * kD) + lane;
                const uint4 wa = __ldg((const uint4*)gate_w + lane), wb = __ldg((const uint4*)gate_w + 32 + lane);
                float s[8];
#pragma unroll
                for (int i0 = 0; i0 < 8; i0 += 4) {
                    uint4 va[4], vb[4];
#pragma unroll
                    for (int i = 0; i < 4; i++) { va[i] = __ldg(xr + (i0 + i) * 64); vb[i] = __ldg(xr + (i0 + i) * 64 + 32); }
#pragma unroll
                    for (int i = 0; i < 4; i++) {
                        float t0 = bf_lo(va[i].x) * bf_lo(wa.x), t1 = bf_hi(va[i].x) * bf_hi(wa.x);
                        t0 = fmaf(bf_lo(va[i].y), bf_lo(wa.y), t0); t1 = fmaf(bf_hi(va[i].y), bf_hi(wa.y), t1);
                        t0 = fmaf(bf_lo(va[i].z), bf_lo(wa.z), t0); t1 = fmaf(bf_hi(va[i].z), bf_hi(wa.z), t1);
                        t0 = fmaf(bf_lo(va[i].w), bf_lo(wa.w), t0); t1 = fmaf(bf_hi(va[i].w), bf_hi(wa.w), t1);
                        t0 = fmaf(bf_lo(vb[i].x), bf_lo(wb.x), t0); t1 = fmaf(bf_hi(vb[i].x), bf_hi(wb.x), t1);
                        t0 = fmaf(bf_lo(vb[i].y), bf_lo(wb.y), t0); t1 = fmaf(bf_hi(vb[i].y), bf_hi(wb.y), t1);
                        t0 = fmaf(bf_lo(vb[i].z), bf_lo(wb.z), t0); t1 = fmaf(bf_hi(vb[i].z), bf_hi(wb.z), t1);
                        t0 = fmaf(bf_lo(vb[i].w), bf_lo(wb.w), t0); t1 = fmaf(bf_hi(vb[i].w), bf_hi(wb.w), t1);
                        s[i0 + i] = t0 + t1;
                    }
                }
#pragma unroll
                for (int i = 0; i < 8; i++) {
#pragma unroll
                    for (int o = 16; o; o >>= 1) s[i] += __shfl_xor_sync(0xffffffffu, s[i], o);
                    s[i] = 1.f / (1.f + __expf(-s[i]));
                }
                const uint32_t tag = (epoch + 1) & 1;
                uint4* gp = g_gx + r * 32;
                if (lane < 2) {
                    const float v0 = lane ? s[4] : s[0], v1 = lane ? s[5] : s[1], v2 = lane ? s[6] : s[2], v3 = lane ? s[7] : s[3];
                    st_pkt(gp + j * 4 + hx * 2 + lane, (__float_as_uint(v0) & ~1u) | tag, __float_as_uint(v1), __float_as_uint(v2), __float_as_uint(v3));
                }
                if (hx == 1) {
                    asm volatile("st.shared.u32 [%0], %1;" :: "r"(sb + OFF_ONES + lane * 4), "r"(0x3f803f80u) : "memory");
                    asm volatile("fence.proxy.async.shared::cta;" ::: "memory");
                }
                asm volatile("bar.sync 3, 64;" ::: "memory");
                if (hx == 0) {
                    uint32_t q[4];
                    recv_issue(q, gp + lane);
                    recv_check(q, gp + lane, tag);
                    asm volatile("st.shared.v4.u32 [%0], {%1,%2,%3,%4};" :: "r"(sb + OFF_G + lane * 16), "r"(q[0]), "r"(q[1]), "r"(q[2]), "r"(q[3]) : "memory");
                    if (lane == 0) {
                        asm volatile("st.shared.u32 [%0], %1;" :: "r"(sb + OFF_EPOCH), "r"(epoch) : "memory");
                        g_epoch[blockIdx.x] = epoch + 1;
                    }
                    __syncwarp();
                    if (lane == 0) mbar_arrive(sb + B_GRDY);
                } else {
                    if (r == 0) {
                        float4* zp = (float4*)(g_kvacc + (((epoch & 1) ^ 1) * 8 + j) * 4 * 272);
                        for (int i = lane; i < 272; i += 32) zp[i] = make_float4(0.f, 0.f, 0.f, 0.f);
                    }
                }
            }
            TS(2 + hx, 1);
            if (hx == 1) {
#pragma unroll 1
                for (int b = 0; b < 5; b++) {
                    mbar_wait(sb + B_HSENT + 8 * b, 0);
                    if (lane == 0) asm volatile("st.release.gpu.global.u32 [%0], %1;" :: "l"(g_hflag + (r * 8 + j) * 8 + b), "r"(epoch + 1) : "memory");
                    __syncwarp();
                    TS(3, 5 + b);
                }
            } else {
                const float* accp = g_kvacc + ((epoch & 1) * 8 + j) * 4 * 272;
                unsigned* cnt = g_kvcnt + j * 32;
                mbar_wait(sb + B_KVDONE, 0);
                TS(2, 5);
                if (lane == 0) asm volatile("red.release.gpu.global.add.u32 [%0], 1;" :: "l"(cnt) : "memory");
                __syncwarp();
                TS(2, 2);
                {
                    const unsigned target = 16u * (epoch + 1);
                    uint32_t it = 0, v;
                    do {
                        asm volatile("ld.acquire.gpu.global.u32 %0, [%1];" : "=r"(v) : "l"(cnt) : "memory");
                    } while ((int)(v - target) < 0 && ++it < SPIN_GLOBAL);
                }
                TS(2, 3);
#pragma unroll
                for (int h = 0; h < 4; h++) {
                    const float4 d0 = __ldcg((const float4*)(accp + h * 272) + lane);
                    const float4 d1 = __ldcg((const float4*)(accp + h * 272 + 128) + lane);
                    const float2 z0 = __ldcg((const float2*)(accp + h * 272 + 256) + (lane & 3));
                    const float2 z1 = __ldcg((const float2*)(accp + h * 272 + 264) + (lane & 3));
                    asm volatile("st.shared.v4.u32 [%0], {%1,%2,%3,%4};" :: "r"(sb + OFF_KVF + h * 512 + lane * 16),
                                 "r"(pack2(d0.x, d0.y)), "r"(pack2(d1.x, d1.y)), "r"(pack2(d0.z, d0.w)), "r"(pack2(d1.z, d1.w)) : "memory");
                    if (lane < 4) asm volatile("st.shared.v2.u32 [%0], {%1,%2};" :: "r"(sb + OFF_ZF + h * 32 + lane * 8), "r"(pack2(z0.x, z0.y)), "r"(pack2(z1.x, z1.y)) : "memory");
                }
                __syncwarp();
                if (lane == 0) mbar_arrive(sb + B_KVRDY);
                TS(2, 4);
            }
        } else {
            mbar_wait(sb + B_XFULL, 0);
            const int b = blockIdx.x;
            if (lane == 0) l2_prefetch(pf_qkv + b * 12288, 12288);
            if (lane == 1) l2_prefetch(pf_g + b * 14336, 14336);
            if (lane == 2) l2_prefetch(pf_u + b * 14336, 14336);
            mbar_wait(sb + B_XFULL + 8 * 7, 0);
            if (lane == 0) l2_prefetch(pf_d + b * 14336, 14336);
            if (lane == 1) l2_prefetch(pf_o + b * 4096, 4096);
            if (lane == 0) {
                mbar_wait(sb + B_GRDY, 0);
                uint32_t want;
                asm volatile("ld.shared.u32 %0, [%1];" : "=r"(want) : "r"(sb + OFF_EPOCH) : "memory");
                want += 1;
                const unsigned* fl = g_hflag + (r * 8 + (j ^ 1)) * 8;
                const int hrow = (r * 8 + (j ^ 1)) * 5 * 128;
#pragma unroll 1
                for (int i = 0; i < 5; i++) {
                    const int blk = i == 1 ? 2 : i == 2 ? 1 : i;
                    const int piece = i == 4 ? 8 : i + 2;
                    if (i == 0) mbar_wait(sb + B_XFREE, 0);
                    if (i == 2) mbar_wait(sb + B_XFREE + 8, 0);
                    uint32_t it = 0, v;
                    do {
                        asm volatile("ld.acquire.gpu.global.u32 %0, [%1];" : "=r"(v) : "l"(fl + blk) : "memory");
                    } while (v != want && ++it < SPIN_GLOBAL);
                    asm volatile("fence.proxy.async;" ::: "memory");
                    TS2(140 + i);
                    mbar_expect(sb + B_XFULL + 8 * piece, i == 2 ? 8192 : 16384);
                    tma2(sb + OFF_X + piece * 16384, i == 2 ? &maps.hxh : &maps.hx, 0, hrow + blk * 128, sb + B_XFULL + 8 * piece);
                }
            }
        }
    } else {
        asm volatile("setmaxnreg.inc.sync.aligned.u32 216;");
        const int wg = warp >> 2;
        const bool elect = (tid & 127) == 0;
        const uint32_t xlo = ((sb + OFF_X + wg * 8192) >> 4) | LBO1;
        const uint32_t ringlo = (sb + OFF_RING) >> 4;
        int slot = 0, ph = 0, prev = 0;
        auto release = [&](int s) {
            if (elect) {
                mbar_arrive(sb + B_EMPTY + 8 * s);
            }
        };
        auto adv = [&]() { prev = slot; if (++slot == 5) { slot = 0; ph ^= 1; } };

        int pidx = 64;
#define G1_STAGE(acc, SW, KB, FIRST) do { mbar_wait(sb + B_FULL + 8 * slot, ph); if (PROF) { if (tid == 0) TS2(pidx); pidx++; } \
            g1_issue<SW, FIRST>(acc, xlo + (KB) * 1024, (ringlo + slot * 1024) | (SW ? LBO4K : LBO8K)); } while (0)
#define G1_RETIRE() do { wg_wait<1>(); release(prev); adv(); } while (0)
#define A2_SYNC() do { asm volatile("fence.proxy.async.shared::cta;" ::: "memory"); asm volatile("bar.sync %0, 128;" :: "r"(wg + 1) : "memory"); } while (0)
#define H_EPI(acc, F, N, OG, OU) _Pragma("unroll") for (int i = 0; i < (N); i++) { \
            const float m_ = (i & 1) ? m_hi : m_lo; \
            F[i] = pack2(acc[(OG) + 2 * i] * acc[(OU) + 2 * i] * m_, acc[(OG) + 2 * i + 1] * acc[(OU) + 2 * i + 1] * m_); }

        float a0[64], b0[64], a1[64], a2_[64], a3[64];
        mbar_wait(sb + B_XFULL, 0);
        G1_STAGE(a0, false, 0, 1); adv();
        if ((warp & 3) == 0) TS(wg, 1);
        G1_STAGE(b0, false, 0, 1); G1_RETIRE();
#pragma unroll 1
        for (int kb = 1; kb < 8; kb++) {
            mbar_wait(sb + B_XFULL + 8 * kb, 0);
            if (PROF && tid == 0) TS2(128 + kb);
            G1_STAGE(a0, false, kb, 0); G1_RETIRE();
            G1_STAGE(b0, false, kb, 0); G1_RETIRE();
        }
        pin(a0);
        mbar_wait(sb + B_GRDY, 0);
        float g_lo, g_hi;
        uint32_t tag;
        {
            const uint32_t ga = sb + OFF_G + (warp * 16 + (lane >> 2)) * 4;
            asm volatile("ld.shared.f32 %0, [%1];" : "=f"(g_lo) : "r"(ga) : "memory");
            asm volatile("ld.shared.f32 %0, [%1];" : "=f"(g_hi) : "r"(ga + 32) : "memory");
            asm volatile("ld.shared.u32 %0, [%1];" : "=r"(tag) : "r"(sb + OFF_EPOCH) : "memory");
        }
        float* const kvp = g_kvacc + (((tag & 1) * 8 + j) * 4 + (warp & 3)) * 272;
        tag = (tag + 1) & 1;
        const float m_lo = 1.f - g_lo, m_hi = 1.f - g_hi;
        if ((warp & 3) == 0) TS(wg, 2);
        uint32_t fh0[16], fh1[16], fh2[16], fh3[8], fo[16];
        H_EPI(a0, fh0, 16, 0, 32);

        const uint32_t lrow = ((lane & 7) + 8 * ((lane >> 3) & 1)) * 128;
        const uint32_t srow = (warp & 3) * 2048 + lrow;
        const uint32_t ssw = (lane >> 4) ^ (lane & 7);
        uint4* const hsend = g_hx + (size_t)((r * 8 + j) * 5) * 1024 + warp * 128 + (lane >> 2) * 8 + (lane & 3);
#define SEND_H(F, B) do { send_h(F, hsend + (B) * 1024); __syncwarp(); if (lane == 0) mbar_arrive(sb + B_HSENT + 8 * (B)); } while (0)

        float kv[32], zs[4];
        {
            uint32_t pk[16], pv[16];
            const uint32_t stg = sb + OFF_STG + wg * 8192;
            const uint32_t klo = (stg >> 4) | LBO1, vlo = klo + 256, olo = (sb + OFF_ONES) >> 4;
            G1_STAGE(a1, true, 0, 1); G1_RETIRE();
            pin(b0);
            G1_STAGE(a1, true, 1, 0);
#pragma unroll
            for (int i = 0; i < 8; i++) pk[i] = pack2(phi(b0[2 * i]), phi(b0[2 * i + 1]));
            SEND_H(fh0, 0);
            G1_RETIRE();
            G1_STAGE(a1, true, 2, 0);
#pragma unroll
            for (int i = 8; i < 16; i++) pk[i] = pack2(phi(b0[2 * i]), phi(b0[2 * i + 1]));
#pragma unroll
            for (int i = 0; i < 16; i++) pv[i] = pack2(b0[32 + 2 * i], b0[32 + 2 * i + 1]);
            if (!(warp & 2)) { stash<16>(stg + (warp & 1) * 2048 + lrow, ssw, pk); stash<16>(stg + 4096 + (warp & 1) * 2048 + lrow, ssw, pv); }
            G1_RETIRE();
            G1_STAGE(a1, true, 3, 0); G1_RETIRE();
            A2_SYNC();
            wg_fence();
            wg_ss64t_z(kv, vlo, DH128, klo, DH128); wg_ss64t(kv, vlo + 128, DH128, klo + 128, DH128);
            wg_ss8t_z(zs, klo, DH128, olo, 0); wg_ss8t(zs, klo + 128, DH128, olo, 0);
            wg_commit();
            G1_STAGE(a1, true, 4, 0); G1_RETIRE();
            G1_STAGE(a1, true, 5, 0);
            if (warp & 2) { stash<16>(stg + (warp & 1) * 2048 + lrow, ssw, pk); stash<16>(stg + 4096 + (warp & 1) * 2048 + lrow, ssw, pv); }
            G1_RETIRE();
            G1_STAGE(a1, true, 6, 0); G1_RETIRE();
            A2_SYNC();
            wg_fence();
            wg_ss64t(kv, vlo, DH128, klo, DH128); wg_ss64t(kv, vlo + 128, DH128, klo + 128, DH128);
            wg_ss8t(zs, klo, DH128, olo, 0); wg_ss8t(zs, klo + 128, DH128, olo, 0);
            wg_commit();
            G1_STAGE(a1, true, 7, 0); G1_RETIRE();
        }
        if ((warp & 3) == 0) TS(wg, 3);

        G1_STAGE(a2_, false, 0, 1);
        pin(kv); pin(zs);
#define KV_RED(W) do { asm volatile("red.global.add.v4.f32 [%0], {%1,%2,%3,%4};" :: "l"(kvp + lane * 4), "f"(kv[8 * W]), "f"(kv[8 * W + 1]), "f"(kv[8 * W + 2]), "f"(kv[8 * W + 3]) : "memory"); \
                       asm volatile("red.global.add.v4.f32 [%0], {%1,%2,%3,%4};" :: "l"(kvp + 128 + lane * 4), "f"(kv[8 * W + 4]), "f"(kv[8 * W + 5]), "f"(kv[8 * W + 6]), "f"(kv[8 * W + 7]) : "memory"); } while (0)
        if ((warp & 3) == 0) KV_RED(0); else if ((warp & 3) == 1) KV_RED(1); else if ((warp & 3) == 2) KV_RED(2); else KV_RED(3);
        if ((lane & 3) == 0) {
            asm volatile("red.global.add.f32 [%0], %1;" :: "l"(kvp + 256 + (lane >> 2)), "f"(zs[0]) : "memory");
            asm volatile("red.global.add.f32 [%0], %1;" :: "l"(kvp + 264 + (lane >> 2)), "f"(zs[2]) : "memory");
        }
        __syncwarp();
        if (lane == 0) mbar_arrive(sb + B_KVDONE);
        G1_RETIRE();
        pin(a1);
        G1_STAGE(a2_, false, 1, 0);
#pragma unroll
        for (int i = 0; i < 8; i++) fo[i] = pack2(phi(a1[2 * i]), phi(a1[2 * i + 1]));
        G1_RETIRE();
        G1_STAGE(a2_, false, 2, 0);
#pragma unroll
        for (int i = 8; i < 16; i++) fo[i] = pack2(phi(a1[2 * i]), phi(a1[2 * i + 1]));
        G1_RETIRE();
        G1_STAGE(a2_, false, 3, 0);
        H_EPI(a1, fh3, 8, 32, 48);
        SEND_H(fh3, 1);
        G1_RETIRE();
#pragma unroll 1
        for (int kb = 4; kb < 8; kb++) { G1_STAGE(a2_, false, kb, 0); G1_RETIRE(); }
        if ((warp & 3) == 0) TS(wg, 4);

        const uint32_t a2 = sb + OFF_X + wg * 8192 + srow;
        G1_STAGE(a3, false, 0, 1); G1_RETIRE();
        pin(a2_);
        G1_STAGE(a3, false, 1, 0);
        H_EPI(a2_, fh1, 16, 0, 32);
        SEND_H(fh1, 2);
        G1_RETIRE();
        G1_STAGE(a3, false, 2, 0); stash<16>(a2, ssw, fh0); G1_RETIRE();
        G1_STAGE(a3, false, 3, 0); stash<16>(a2 + 16384, ssw, fh1); G1_RETIRE();
        G1_STAGE(a3, false, 4, 0); G1_RETIRE();
        if (elect) mbar_arrive(sb + B_XFREE);
        G1_STAGE(a3, false, 5, 0);
        if ((warp & 3) == 0) TS(wg, 5);
        mbar_wait(sb + B_KVRDY, 0);
        if ((warp & 3) == 0) TS(wg, 6);
#pragma unroll
        for (int h = 0; h < 4; h++) {
            uint32_t b0, b1, b2, b3, z0, z1;
            asm volatile("ld.shared.v4.u32 {%0,%1,%2,%3}, [%4];" : "=r"(b0), "=r"(b1), "=r"(b2), "=r"(b3) : "r"(sb + OFF_KVF + h * 512 + lane * 16) : "memory");
            asm volatile("ld.shared.v2.u32 {%0,%1}, [%2];" : "=r"(z0), "=r"(z1) : "r"(sb + OFF_ZF + h * 32 + (lane & 3) * 8) : "memory");
            float n0[4] = {0.f, 0.f, 0.f, 0.f}, n1[4] = {0.f, 0.f, 0.f, 0.f}, dn[4] = {0.f, 0.f, 0.f, 0.f};
            mma16816(dn, fo[4 * h], fo[4 * h + 1], fo[4 * h + 2], fo[4 * h + 3], z0, z1);
            mma16816(n0, fo[4 * h], fo[4 * h + 1], fo[4 * h + 2], fo[4 * h + 3], b0, b1);
            mma16816(n1, fo[4 * h], fo[4 * h + 1], fo[4 * h + 2], fo[4 * h + 3], b2, b3);
            const float s_lo = __fdividef(g_lo, dn[0] + 1e-6f), s_hi = __fdividef(g_hi, dn[2] + 1e-6f);
            fo[4 * h] = pack2(n0[0] * s_lo, n0[1] * s_lo); fo[4 * h + 1] = pack2(n0[2] * s_hi, n0[3] * s_hi);
            fo[4 * h + 2] = pack2(n1[0] * s_lo, n1[1] * s_lo); fo[4 * h + 3] = pack2(n1[2] * s_hi, n1[3] * s_hi);
        }
        SEND_H(fo, 3);
        G1_RETIRE();
        G1_STAGE(a3, false, 6, 0);
        stash<8>(a2 + 4 * 16384, ssw ^ 4, fh3);
        G1_RETIRE();
        if (elect) mbar_arrive(sb + B_XFREE + 8);
        G1_STAGE(a3, false, 7, 0);
        G1_RETIRE();
        A2_SYNC();
        if ((warp & 3) == 0) TS(wg, 7);

#define G2_PIECE(U) ((U) < 5 ? (U) : (U) == 5 ? 6 : (U) == 6 ? 7 : (U) == 7 ? 5 : 8)
#define G2_B(T) (ringlo + ((T) % 5) * 1024)
#define G2_WAIT(T) do { mbar_wait(sb + B_FULL + 8 * ((T) % 5), ((T) / 5) & 1); if (PROF && tid == 0) TS2(64 + 40 + (T)); } while (0)
#define G2_REL(T) do { if ((T) < 13) release((T) % 5); } while (0)
#define G2_W(T, acc) do { G2_WAIT(T); wg_fence(); _Pragma("unroll") for (int k = 0; k < 4; k++) { \
            if ((T) % 9 == 0 && k == 0) wg_ss128_z(acc, xlo, DH128, G2_B(T) | LBO8K, DH128); \
            else if ((T) % 9 == 4) wg_ss128(acc, xlo + 4096 + 2 * k, DH128, (G2_B(T) | LBO4K) + (k >> 1) * 512 + (k & 1) * 128, DH128); \
            else wg_ss128(acc, xlo + G2_PIECE((T) % 9) * 1024 + 2 * k, DH128, (G2_B(T) | LBO8K) + 128 * k, DH128); } wg_commit(); } while (0)
#define H_WAIT(P) do { mbar_wait(sb + B_XFULL + 8 * (P), (P) < 8); if (PROF && tid == 0) TS2(150 + (P)); } while (0)

        const int p = j >> 1;
        uint4* const pbase = g_part + (size_t)(r * 2 + (j & 1)) * 16384 + warp * 128 + lane;
        const int pw = (p & 2) ^ 2;
        auto other = [&](int d) { return d == 3 ? p ^ 1 : pw + d - 1; };
        auto sendp = [&](int d) { return pbase + ((other(d) * 4 + p) << 10); };
        auto recvp = [&](int d) { return pbase + ((p * 4 + other(d)) << 10); };

        float p1[64], p2[64];
        G2_W(0, p1);
        wg_wait<1>();
        release(prev);
        pin(a3);
        G2_W(1, p1);
        H_EPI(a3, fh2, 16, 0, 32);
        SEND_H(fh2, 4);
        wg_wait<1>(); G2_REL(0);
        H_WAIT(2); G2_W(2, p1);
        stash<16>(a2 + 6 * 16384, ssw, fo); stash<16>(a2 + 7 * 16384, ssw, fh2);
        wg_wait<1>(); G2_REL(1);
        H_WAIT(3); G2_W(3, p1); wg_wait<1>(); G2_REL(2);
        H_WAIT(4); G2_W(4, p1); wg_wait<1>(); G2_REL(3);
        A2_SYNC();
        G2_W(5, p1); wg_wait<1>(); G2_REL(4);
        G2_W(6, p1); wg_wait<1>(); G2_REL(5);
        H_WAIT(5); G2_W(7, p1); wg_wait<1>(); G2_REL(6);
        H_WAIT(8); G2_W(8, p1); wg_wait<1>(); G2_REL(7);
        if ((warp & 3) == 0) TS(wg, 8);
        uint32_t sp[32], qa[16], qb[16];
        float sum[32];
        G2_W(9, p2); wg_wait<1>(); G2_REL(8);
        pin(p1);
        G2_W(10, p2); pack_acc(sp, p1); send_frag<0, 2>(sp, sendp(1), tag); wg_wait<1>(); G2_REL(9);
        G2_W(11, p2); send_frag<2, 4>(sp, sendp(1), tag); wg_wait<1>(); G2_REL(10);
        G2_W(12, p2); send_frag<4, 6>(sp, sendp(2), tag); wg_wait<1>(); G2_REL(11);
        G2_W(13, p2); send_frag<6, 8>(sp, sendp(2), tag); wg_wait<1>(); G2_REL(12);
        G2_W(14, p2); wg_wait<1>();
        G2_W(15, p2); recv_issue(qa, recvp(1)); wg_wait<1>();
        G2_W(16, p2); recv_issue(qb, recvp(2)); wg_wait<1>();
        G2_W(17, p2);
        if ((warp & 3) == 0) TS(wg, 9);
        recv_check(qa, recvp(1), tag); accum<true>(qa, sum);
        recv_check(qb, recvp(2), tag); accum<false>(qb, sum);
        if ((warp & 3) == 0) TS(wg, 10);
        wg_wait<0>();
        pin(p2);
        if ((warp & 3) == 0) TS(wg, 11);
        if (p & 1) pack_sub<0>(qa, p2); else pack_sub<32>(qa, p2);
        send_frag<0, 4>(qa, sendp(3), tag);
        recv_issue(qb, recvp(3));
        if (p & 1) {
#pragma unroll
            for (int i = 0; i < 32; i++) sum[i] += p2[32 + i];
        } else {
#pragma unroll
            for (int i = 0; i < 32; i++) sum[i] += p2[i];
        }
        if ((warp & 3) == 0) TS(wg, 12);
        recv_check(qb, recvp(3), tag); accum<false>(qb, sum);
        if ((warp & 3) == 0) TS(wg, 13);
        {
            uint32_t f[16];
            pack_acc(f, sum);
            const uint32_t slab = sb + OFF_X + wg * 8192;
            stash<16>(slab + srow, ssw, f);
            __syncwarp();
            __nv_bfloat16* op = out + (size_t)(r * 128 + warp * 16 + (lane >> 3)) * kD + (j & 1) * 256 + p * 64 + (lane & 7) * 8;
#pragma unroll
            for (int i = 0; i < 4; i++) {
                const int row = i * 4 + (lane >> 3);
                uint4 v;
                asm volatile("ld.shared.v4.u32 {%0,%1,%2,%3}, [%4];" : "=r"(v.x), "=r"(v.y), "=r"(v.z), "=r"(v.w)
                             : "r"(slab + ((warp & 3) * 16 + row) * 128 + (((lane & 7) ^ (row & 7)) << 4)) : "memory");
                *(uint4*)(op + i * 4 * kD) = v;
            }
        }
        if ((warp & 3) == 0) { TS(wg, 14); TSG(wg, 31); }
    }
}

typedef CUresult (*EncodeFn)(CUtensorMap*, CUtensorMapDataType, cuuint32_t, void*, const cuuint64_t*, const cuuint64_t*, const cuuint32_t*,
                             const cuuint32_t*, CUtensorMapInterleave, CUtensorMapSwizzle, CUtensorMapL2promotion, CUtensorMapFloatOOBfill);

static void encode(EncodeFn fn, CUtensorMap* m, int rank, const void* base, const cuuint64_t (&gd)[5], const cuuint64_t (&gs)[4],
                   const cuuint32_t (&bd)[5], CUtensorMapSwizzle sw) {
    cuuint32_t es[5] = {1, 1, 1, 1, 1};
    fn(m, CU_TENSOR_MAP_DATA_TYPE_BFLOAT16, rank, const_cast<void*>(base), gd, gs, bd, es, CU_TENSOR_MAP_INTERLEAVE_NONE, sw,
       CU_TENSOR_MAP_L2_PROMOTION_L2_128B, CU_TENSOR_MAP_FLOAT_OOB_FILL_NONE);
}

extern "C" void kernel_launch(void* const* d_in, const int* in_sizes, int n_in, void* d_out, int out_size) {
    const char* x = (const char*)d_in[0];
    const char* wqkv = (const char*)d_in[1];
    const char* wo = (const char*)d_in[2];
    const char* wg = (const char*)d_in[4];
    const char* wu = (const char*)d_in[5];
    const char* wd = (const char*)d_in[6];
    void* fnp = nullptr;
    cudaDriverEntryPointQueryResult qr;
    cudaGetDriverEntryPoint("cuTensorMapEncodeTiled", &fnp, cudaEnableDefault, &qr);
    EncodeFn fn = (EncodeFn)fnp;
    Maps maps;
    const char* lo = wg < wu ? wg : wu;
    const uint64_t diff = wg < wu ? (uint64_t)(wu - wg) : (uint64_t)(wg - wu);
    const CUtensorMapSwizzle S128 = CU_TENSOR_MAP_SWIZZLE_128B, S64 = CU_TENSOR_MAP_SWIZZLE_64B;
    encode(fn, &maps.x, 2, x, {512, 2048, 1, 1}, {1024, 0, 0}, {64, 128, 1, 1}, S128);
    encode(fn, &maps.gu, 3, lo, {1792, 512, 2, 1}, {3584, diff, 0}, {64, 64, 2, 1}, S128);
    encode(fn, &maps.kv, 3, wqkv, {512, 512, 3, 1}, {3072, 1024, 0}, {64, 64, 2, 1}, S128);
    encode(fn, &maps.q64, 3, wqkv, {32, 512, 48, 1}, {3072, 64, 0}, {32, 64, 2, 1}, S64);
    encode(fn, &maps.gu64, 3, lo, {1792, 512, 2, 1}, {3584, diff, 0}, {32, 64, 2, 1}, S64);
    encode(fn, &maps.wdw, 3, wd, {64, 1792, 8, 1}, {1024, 128, 0}, {64, 64, 2, 1}, S128);
    encode(fn, &maps.wdh, 3, wd, {64, 1792, 8}, {1024, 128}, {64, 32, 2}, S128);
    encode(fn, &maps.wow, 3, wo, {64, 512, 8}, {1024, 128}, {64, 64, 2}, S128);
    encode(fn, &maps.wdp, 5, wd, {512, 2, 4, 4, 56}, {1024, 8192, 2048, 32768}, {64, 2, 4, 4, 2}, S128);
    encode(fn, &maps.wdph, 5, wd, {512, 2, 4, 4, 56}, {1024, 8192, 2048, 32768}, {64, 2, 4, 4, 1}, S128);
    encode(fn, &maps.wop, 5, wo, {512, 2, 4, 4, 16}, {1024, 8192, 2048, 32768}, {64, 2, 4, 4, 2}, S128);
    void* hx = nullptr;
    cudaGetSymbolAddress(&hx, g_hx);
    encode(fn, &maps.hx, 2, hx, {64, 16 * 8 * 5 * 128}, {128}, {64, 128}, S128);
    encode(fn, &maps.hxh, 2, hx, {64, 16 * 8 * 5 * 128}, {128}, {32, 128}, S128);
    cudaFuncSetAttribute(fused_kernel, cudaFuncAttributeMaxDynamicSharedMemorySize, SMEM_BYTES);
    cudaLaunchConfig_t cfg = {};
    cfg.gridDim = dim3(128);
    cfg.blockDim = dim3(384);
    cfg.dynamicSmemBytes = SMEM_BYTES;
    cfg.stream = cudaStreamPerThread;
    cudaLaunchAttribute at[1];
    at[0].id = cudaLaunchAttributeClusterDimension;
    at[0].val.clusterDim.x = 2; at[0].val.clusterDim.y = 1; at[0].val.clusterDim.z = 1;
    cfg.attrs = at;
    cfg.numAttrs = MC ? 1 : 0;
    cudaLaunchKernelEx(&cfg, fused_kernel, maps, (const __nv_bfloat16*)d_in[0], (const __nv_bfloat16*)d_in[7], wqkv, wg, wu, wd, wo, (__nv_bfloat16*)d_out);
}
```

```cpp
#include <cuda_runtime.h>
#include <cuda.h>
#include <cuda_bf16.h>
#include <stdint.h>

#define MC 0
#define PROF 0

namespace {

constexpr int kD = 512;
constexpr uint32_t OFF_X = 0, OFF_STG = 131072, OFF_RING = 147456, OFF_MISC = 229376;
constexpr uint32_t B_FULL = OFF_MISC, B_EMPTY = OFF_MISC + 40, B_XFULL = OFF_MISC + 80;
constexpr uint32_t B_GRDY = OFF_MISC + 152, B_KVDONE = OFF_MISC + 160, B_KVRDY = OFF_MISC + 168;
constexpr uint32_t B_HSENT = OFF_MISC + 176, B_XFREE = OFF_MISC + 216;
constexpr uint32_t OFF_EPOCH = OFF_MISC + 240, OFF_G = OFF_MISC + 256;
constexpr uint32_t OFF_KVF = OFF_MISC + 768, OFF_ZF = OFF_KVF + 2048;
constexpr uint32_t OFF_ONES = OFF_ZF + 128;
constexpr uint32_t SMEM_BYTES = OFF_ONES + 128;
constexpr uint32_t SPIN_MBAR = 1u << 16, SPIN_GLOBAL = 1u << 14;

struct alignas(64) Maps { CUtensorMap x, gu, kv, q64, gu64, wdw, wdh, wow, wdp, wdph, wop, hx, hxh; };

}

__device__ uint4 g_part[16 * 2 * 4 * 4 * 1024];
__device__ uint4 g_hx[16 * 8 * 5 * 1024];
__device__ unsigned g_hflag[128 * 8];
__device__ uint4 g_gx[16 * 32];
__device__ float g_kvacc[2 * 8 * 4 * 272];
__device__ unsigned g_kvcnt[8 * 32];
__device__ unsigned g_epoch[128];
#define TS(role, idx)
#define TS2(idx)
#define TSG(role, idx)

namespace {

__device__ __forceinline__ void mbar_init(uint32_t bar, uint32_t cnt) { asm volatile("mbarrier.init.shared::cta.b64 [%0], %1;" :: "r"(bar), "r"(cnt) : "memory"); }
__device__ __forceinline__ void mbar_expect(uint32_t bar, uint32_t bytes) { asm volatile("mbarrier.arrive.expect_tx.shared::cta.b64 _, [%0], %1;" :: "r"(bar), "r"(bytes) : "memory"); }
__device__ __forceinline__ void mbar_arrive(uint32_t bar) { asm volatile("mbarrier.arrive.shared::cta.b64 _, [%0];" :: "r"(bar) : "memory"); }
__device__ __forceinline__ void mbar_arrive_cta(uint32_t bar, uint32_t cta) {
    asm volatile("{\n.reg .b32 ra;\nmapa.shared::cluster.u32 ra, %0, %1;\nmbarrier.arrive.shared::cluster.b64 _, [ra];\n}" :: "r"(bar), "r"(cta) : "memory");
}
__device__ __forceinline__ void mbar_wait(uint32_t bar, uint32_t parity) {
    uint32_t ok, it = 0;
    do {
        asm volatile("{\n.reg .pred p;\nmbarrier.try_wait.parity.shared::cta.b64 p, [%1], %2;\nselp.u32 %0, 1, 0, p;\n}" : "=r"(ok) : "r"(bar), "r"(parity) : "memory");
    } while (!ok && ++it < SPIN_MBAR);
}
__device__ __forceinline__ void tma2(uint32_t dst, const CUtensorMap* m, int c0, int c1, uint32_t bar) {
    asm volatile("cp.async.bulk.tensor.2d.shared::cluster.global.mbarrier::complete_tx::bytes [%0], [%1, {%3, %4}], [%2];"
        :: "r"(dst), "l"(m), "r"(bar), "r"(c0), "r"(c1) : "memory");
}
__device__ __forceinline__ void tmaw2(uint32_t dst, const CUtensorMap* m, int c0, int c1, uint32_t bar) {
    tma2(dst, m, c0, c1, bar);
}
__device__ __forceinline__ void tmaw3(uint32_t dst, const CUtensorMap* m, int c0, int c1, int c2, uint32_t bar) {
    asm volatile("cp.async.bulk.tensor.3d.shared::cluster.global.mbarrier::complete_tx::bytes [%0], [%1, {%3, %4, %5}], [%2];"
        :: "r"(dst), "l"(m), "r"(bar), "r"(c0), "r"(c1), "r"(c2) : "memory");
}
__device__ __forceinline__ void tmaw5(uint32_t dst, const CUtensorMap* m, int c0, int c4, uint32_t bar) {
    asm volatile("cp.async.bulk.tensor.5d.shared::cluster.global.mbarrier::complete_tx::bytes [%0], [%1, {%3, %5, %5, %5, %4}], [%2];"
        :: "r"(dst), "l"(m), "r"(bar), "r"(c0), "r"(c4), "r"(0) : "memory");
}
__device__ __forceinline__ void l2_prefetch(const void* p, uint32_t bytes) { asm volatile("cp.async.bulk.prefetch.L2.global [%0], %1;" :: "l"(p), "r"(bytes) : "memory"); }
__device__ __forceinline__ void wg_fence() { asm volatile("wgmma.fence.sync.aligned;" ::: "memory"); }
__device__ __forceinline__ void wg_commit() { asm volatile("wgmma.commit_group.sync.aligned;" ::: "memory"); }
template <int N> __device__ __forceinline__ void wg_wait() { asm volatile("wgmma.wait_group.sync.aligned %0;" :: "n"(N) : "memory"); }
template <int N> __device__ __forceinline__ void pin(float (&d)[N]) {
#pragma unroll
    for (int i = 0; i < N; i++) asm volatile("" : "+f"(d[i]) :: "memory");
}
__device__ __forceinline__ uint32_t pack2(float lo, float hi) { uint32_t r; asm("cvt.rn.bf16x2.f32 %0, %1, %2;" : "=r"(r) : "f"(hi), "f"(lo)); return r; }
__device__ __forceinline__ float phi(float t) {
    float e;
    asm("ex2.approx.ftz.f32 %0, %1;" : "=f"(e) : "f"(fminf(t * 1.4426950408889634f, 0.f)));
    return e + (fmaxf(t, 0.f) + 1e-6f);
}
__device__ __forceinline__ void stsm4(uint32_t a, uint32_t r0, uint32_t r1, uint32_t r2, uint32_t r3) {
    asm volatile("stmatrix.sync.aligned.m8n8.x4.shared.b16 [%0], {%1,%2,%3,%4};" :: "r"(a), "r"(r0), "r"(r1), "r"(r2), "r"(r3) : "memory");
}
__device__ __forceinline__ void mma16816(float (&c)[4], uint32_t a0, uint32_t a1, uint32_t a2, uint32_t a3, uint32_t b0, uint32_t b1) {
    asm volatile("mma.sync.aligned.m16n8k16.row.col.f32.bf16.bf16.f32 {%0,%1,%2,%3}, {%4,%5,%6,%7}, {%8,%9}, {%0,%1,%2,%3};"
        : "+f"(c[0]), "+f"(c[1]), "+f"(c[2]), "+f"(c[3]) : "r"(a0), "r"(a1), "r"(a2), "r"(a3), "r"(b0), "r"(b1));
}
__device__ __forceinline__ float bf_lo(uint32_t w) { return __uint_as_float(w << 16); }
__device__ __forceinline__ float bf_hi(uint32_t w) { return __uint_as_float(w & 0xffff0000u); }
__device__ __forceinline__ void st_pkt(uint4* p, uint32_t w0, uint32_t w1, uint32_t w2, uint32_t w3) {
    asm volatile("{\n.reg .b64 lo, hi;\n.reg .b128 v;\nmov.b64 lo, {%1, %2};\nmov.b64 hi, {%3, %4};\nmov.b128 v, {lo, hi};\nst.relaxed.gpu.global.b128 [%0], v;\n}"
        :: "l"(p), "r"(w0), "r"(w1), "r"(w2), "r"(w3) : "memory");
}
__device__ __forceinline__ void ld_pkt(const uint4* p, uint32_t& w0, uint32_t& w1, uint32_t& w2, uint32_t& w3) {
    asm volatile("{\n.reg .b64 lo, hi;\n.reg .b128 v;\nld.relaxed.gpu.global.b128 v, [%4];\nmov.b128 {lo, hi}, v;\nmov.b64 {%0, %1}, lo;\nmov.b64 {%2, %3}, hi;\n}"
        : "=r"(w0), "=r"(w1), "=r"(w2), "=r"(w3) : "l"(p) : "memory");
}

__device__ __forceinline__ void wg_ss128(float (&d)[64], uint32_t alo, uint32_t ahi, uint32_t blo, uint32_t bhi) {
    asm volatile("{\n.reg .b64 da, db;\nmov.b64 da, {%64, %65};\nmov.b64 db, {%66, %67};\n"
        "wgmma.mma_async.sync.aligned.m64n128k16.f32.bf16.bf16 {%0,%1,%2,%3,%4,%5,%6,%7,%8,%9,%10,%11,%12,%13,%14,%15,%16,%17,%18,%19,%20,%21,%22,%23,%24,%25,%26,%27,%28,%29,%30,%31,%32,%33,%34,%35,%36,%37,%38,%39,%40,%41,%42,%43,%44,%45,%46,%47,%48,%49,%50,%51,%52,%53,%54,%55,%56,%57,%58,%59,%60,%61,%62,%63}, da, db, 1, 1, 1, 0, 1;\n}\n"
        : "+f"(d[0]),"+f"(d[1]),"+f"(d[2]),"+f"(d[3]),"+f"(d[4]),"+f"(d[5]),"+f"(d[6]),"+f"(d[7]),"+f"(d[8]),"+f"(d[9]),"+f"(d[10]),"+f"(d[11]),"+f"(d[12]),"+f"(d[13]),"+f"(d[14]),"+f"(d[15]),"+f"(d[16]),"+f"(d[17]),"+f"(d[18]),"+f"(d[19]),"+f"(d[20]),"+f"(d[21]),"+f"(d[22]),"+f"(d[23]),"+f"(d[24]),"+f"(d[25]),"+f"(d[26]),"+f"(d[27]),"+f"(d[28]),"+f"(d[29]),"+f"(d[30]),"+f"(d[31]),"+f"(d[32]),"+f"(d[33]),"+f"(d[34]),"+f"(d[35]),"+f"(d[36]),"+f"(d[37]),"+f"(d[38]),"+f"(d[39]),"+f"(d[40]),"+f"(d[41]),"+f"(d[42]),"+f"(d[43]),"+f"(d[44]),"+f"(d[45]),"+f"(d[46]),"+f"(d[47]),"+f"(d[48]),"+f"(d[49]),"+f"(d[50]),"+f"(d[51]),"+f"(d[52]),"+f"(d[53]),"+f"(d[54]),"+f"(d[55]),"+f"(d[56]),"+f"(d[57]),"+f"(d[58]),"+f"(d[59]),"+f"(d[60]),"+f"(d[61]),"+f"(d[62]),"+f"(d[63])
        : "r"(alo), "r"(ahi), "r"(blo), "r"(bhi));
}
__device__ __forceinline__ void wg_ss128_z(float (&d)[64], uint32_t alo, uint32_t ahi, uint32_t blo, uint32_t bhi) {
    asm volatile("{\n.reg .b64 da, db;\nmov.b64 da, {%64, %65};\nmov.b64 db, {%66, %67};\n"
        "wgmma.mma_async.sync.aligned.m64n128k16.f32.bf16.bf16 {%0,%1,%2,%3,%4,%5,%6,%7,%8,%9,%10,%11,%12,%13,%14,%15,%16,%17,%18,%19,%20,%21,%22,%23,%24,%25,%26,%27,%28,%29,%30,%31,%32,%33,%34,%35,%36,%37,%38,%39,%40,%41,%42,%43,%44,%45,%46,%47,%48,%49,%50,%51,%52,%53,%54,%55,%56,%57,%58,%59,%60,%61,%62,%63}, da, db, 0, 1, 1, 0, 1;\n}\n"
        : "=f"(d[0]),"=f"(d[1]),"=f"(d[2]),"=f"(d[3]),"=f"(d[4]),"=f"(d[5]),"=f"(d[6]),"=f"(d[7]),"=f"(d[8]),"=f"(d[9]),"=f"(d[10]),"=f"(d[11]),"=f"(d[12]),"=f"(d[13]),"=f"(d[14]),"=f"(d[15]),"=f"(d[16]),"=f"(d[17]),"=f"(d[18]),"=f"(d[19]),"=f"(d[20]),"=f"(d[21]),"=f"(d[22]),"=f"(d[23]),"=f"(d[24]),"=f"(d[25]),"=f"(d[26]),"=f"(d[27]),"=f"(d[28]),"=f"(d[29]),"=f"(d[30]),"=f"(d[31]),"=f"(d[32]),"=f"(d[33]),"=f"(d[34]),"=f"(d[35]),"=f"(d[36]),"=f"(d[37]),"=f"(d[38]),"=f"(d[39]),"=f"(d[40]),"=f"(d[41]),"=f"(d[42]),"=f"(d[43]),"=f"(d[44]),"=f"(d[45]),"=f"(d[46]),"=f"(d[47]),"=f"(d[48]),"=f"(d[49]),"=f"(d[50]),"=f"(d[51]),"=f"(d[52]),"=f"(d[53]),"=f"(d[54]),"=f"(d[55]),"=f"(d[56]),"=f"(d[57]),"=f"(d[58]),"=f"(d[59]),"=f"(d[60]),"=f"(d[61]),"=f"(d[62]),"=f"(d[63])
        : "r"(alo), "r"(ahi), "r"(blo), "r"(bhi));
}
__device__ __forceinline__ void wg_ss64(float (&d)[32], uint32_t alo, uint32_t ahi, uint32_t blo, uint32_t bhi) {
    asm volatile("{\n.reg .b64 da, db;\nmov.b64 da, {%32, %33};\nmov.b64 db, {%34, %35};\n"
        "wgmma.mma_async.sync.aligned.m64n64k16.f32.bf16.bf16 {%0,%1,%2,%3,%4,%5,%6,%7,%8,%9,%10,%11,%12,%13,%14,%15,%16,%17,%18,%19,%20,%21,%22,%23,%24,%25,%26,%27,%28,%29,%30,%31}, da, db, 1, 1, 1, 0, 1;\n}\n"
        : "+f"(d[0]),"+f"(d[1]),"+f"(d[2]),"+f"(d[3]),"+f"(d[4]),"+f"(d[5]),"+f"(d[6]),"+f"(d[7]),"+f"(d[8]),"+f"(d[9]),"+f"(d[10]),"+f"(d[11]),"+f"(d[12]),"+f"(d[13]),"+f"(d[14]),"+f"(d[15]),"+f"(d[16]),"+f"(d[17]),"+f"(d[18]),"+f"(d[19]),"+f"(d[20]),"+f"(d[21]),"+f"(d[22]),"+f"(d[23]),"+f"(d[24]),"+f"(d[25]),"+f"(d[26]),"+f"(d[27]),"+f"(d[28]),"+f"(d[29]),"+f"(d[30]),"+f"(d[31])
        : "r"(alo), "r"(ahi), "r"(blo), "r"(bhi));
}
__device__ __forceinline__ void wg_ss64_z(float (&d)[32], uint32_t alo, uint32_t ahi, uint32_t blo, uint32_t bhi) {
    asm volatile("{\n.reg .b64 da, db;\nmov.b64 da, {%32, %33};\nmov.b64 db, {%34, %35};\n"
        "wgmma.mma_async.sync.aligned.m64n64k16.f32.bf16.bf16 {%0,%1,%2,%3,%4,%5,%6,%7,%8,%9,%10,%11,%12,%13,%14,%15,%16,%17,%18,%19,%20,%21,%22,%23,%24,%25,%26,%27,%28,%29,%30,%31}, da, db, 0, 1, 1, 0, 1;\n}\n"
        : "=f"(d[0]),"=f"(d[1]),"=f"(d[2]),"=f"(d[3]),"=f"(d[4]),"=f"(d[5]),"=f"(d[6]),"=f"(d[7]),"=f"(d[8]),"=f"(d[9]),"=f"(d[10]),"=f"(d[11]),"=f"(d[12]),"=f"(d[13]),"=f"(d[14]),"=f"(d[15]),"=f"(d[16]),"=f"(d[17]),"=f"(d[18]),"=f"(d[19]),"=f"(d[20]),"=f"(d[21]),"=f"(d[22]),"=f"(d[23]),"=f"(d[24]),"=f"(d[25]),"=f"(d[26]),"=f"(d[27]),"=f"(d[28]),"=f"(d[29]),"=f"(d[30]),"=f"(d[31])
        : "r"(alo), "r"(ahi), "r"(blo), "r"(bhi));
}
__device__ __forceinline__ void wg_ss64t(float (&d)[32], uint32_t alo, uint32_t ahi, uint32_t blo, uint32_t bhi) {
    asm volatile("{\n.reg .b64 da, db;\nmov.b64 da, {%32, %33};\nmov.b64 db, {%34, %35};\n"
        "wgmma.mma_async.sync.aligned.m64n64k16.f32.bf16.bf16 {%0,%1,%2,%3,%4,%5,%6,%7,%8,%9,%10,%11,%12,%13,%14,%15,%16,%17,%18,%19,%20,%21,%22,%23,%24,%25,%26,%27,%28,%29,%30,%31}, da, db, 1, 1, 1, 1, 1;\n}\n"
        : "+f"(d[0]),"+f"(d[1]),"+f"(d[2]),"+f"(d[3]),"+f"(d[4]),"+f"(d[5]),"+f"(d[6]),"+f"(d[7]),"+f"(d[8]),"+f"(d[9]),"+f"(d[10]),"+f"(d[11]),"+f"(d[12]),"+f"(d[13]),"+f"(d[14]),"+f"(d[15]),"+f"(d[16]),"+f"(d[17]),"+f"(d[18]),"+f"(d[19]),"+f"(d[20]),"+f"(d[21]),"+f"(d[22]),"+f"(d[23]),"+f"(d[24]),"+f"(d[25]),"+f"(d[26]),"+f"(d[27]),"+f"(d[28]),"+f"(d[29]),"+f"(d[30]),"+f"(d[31])
        : "r"(alo), "r"(ahi), "r"(blo), "r"(bhi));
}
__device__ __forceinline__ void wg_ss64t_z(float (&d)[32], uint32_t alo, uint32_t ahi, uint32_t blo, uint32_t bhi) {
    asm volatile("{\n.reg .b64 da, db;\nmov.b64 da, {%32, %33};\nmov.b64 db, {%34, %35};\n"
        "wgmma.mma_async.sync.aligned.m64n64k16.f32.bf16.bf16 {%0,%1,%2,%3,%4,%5,%6,%7,%8,%9,%10,%11,%12,%13,%14,%15,%16,%17,%18,%19,%20,%21,%22,%23,%24,%25,%26,%27,%28,%29,%30,%31}, da, db, 0, 1, 1, 1, 1;\n}\n"
        : "=f"(d[0]),"=f"(d[1]),"=f"(d[2]),"=f"(d[3]),"=f"(d[4]),"=f"(d[5]),"=f"(d[6]),"=f"(d[7]),"=f"(d[8]),"=f"(d[9]),"=f"(d[10]),"=f"(d[11]),"=f"(d[12]),"=f"(d[13]),"=f"(d[14]),"=f"(d[15]),"=f"(d[16]),"=f"(d[17]),"=f"(d[18]),"=f"(d[19]),"=f"(d[20]),"=f"(d[21]),"=f"(d[22]),"=f"(d[23]),"=f"(d[24]),"=f"(d[25]),"=f"(d[26]),"=f"(d[27]),"=f"(d[28]),"=f"(d[29]),"=f"(d[30]),"=f"(d[31])
        : "r"(alo), "r"(ahi), "r"(blo), "r"(bhi));
}
__device__ __forceinline__ void wg_ss8t(float (&d)[4], uint32_t alo, uint32_t ahi, uint32_t blo, uint32_t bhi) {
    asm volatile("{\n.reg .b64 da, db;\nmov.b64 da, {%4, %5};\nmov.b64 db, {%6, %7};\n"
        "wgmma.mma_async.sync.aligned.m64n8k16.f32.bf16.bf16 {%0,%1,%2,%3}, da, db, 1, 1, 1, 1, 0;\n}\n"
        : "+f"(d[0]),"+f"(d[1]),"+f"(d[2]),"+f"(d[3])
        : "r"(alo), "r"(ahi), "r"(blo), "r"(bhi));
}
__device__ __forceinline__ void wg_ss8t_z(float (&d)[4], uint32_t alo, uint32_t ahi, uint32_t blo, uint32_t bhi) {
    asm volatile("{\n.reg .b64 da, db;\nmov.b64 da, {%4, %5};\nmov.b64 db, {%6, %7};\n"
        "wgmma.mma_async.sync.aligned.m64n8k16.f32.bf16.bf16 {%0,%1,%2,%3}, da, db, 0, 1, 1, 1, 0;\n}\n"
        : "=f"(d[0]),"=f"(d[1]),"=f"(d[2]),"=f"(d[3])
        : "r"(alo), "r"(ahi), "r"(blo), "r"(bhi));
}

constexpr uint32_t DH128 = 64u | 0x40000000u;
constexpr uint32_t DH64 = 32u | 0x80000000u;
constexpr uint32_t LBO4K = (4096u >> 4) << 16, LBO8K = (8192u >> 4) << 16, LBO1 = 1u << 16;

template <bool SW64, bool FIRST> __device__ __forceinline__ void g1_issue(float (&acc)[64], uint32_t alo, uint32_t blo) {
    wg_fence();
#pragma unroll
    for (int k = 0; k < 4; k++) {
        if (FIRST && k == 0) wg_ss128_z(acc, alo, DH128, blo, SW64 ? DH64 : DH128);
        else wg_ss128(acc, alo + 2 * k, DH128, blo + (SW64 ? 64 * k : 128 * k), SW64 ? DH64 : DH128);
    }
    wg_commit();
}

template <int N> __device__ __forceinline__ void stash(uint32_t base, uint32_t sw, const uint32_t (&f)[N]) {
#pragma unroll
    for (int t = 0; t < N / 4; t++) stsm4(base + ((sw ^ (2 * t)) << 4), f[4 * t], f[4 * t + 1], f[4 * t + 2], f[4 * t + 3]);
}

template <int V0, int V1, int N> __device__ __forceinline__ void send_frag(const uint32_t (&f)[N], uint4* p, uint32_t tag) {
#pragma unroll
    for (int v = V0; v < V1; v++) st_pkt(p + (v & 3) * 32, (f[4 * v] & ~1u) | tag, f[4 * v + 1], f[4 * v + 2], f[4 * v + 3]);
}
template <int N> __device__ __forceinline__ void send_h(const uint32_t (&f)[N], uint4* p) {
#pragma unroll
    for (int h = 0; h < N / 8; h++) {
        p[4 * h] = make_uint4(f[8 * h], f[8 * h + 2], f[8 * h + 4], f[8 * h + 6]);
        p[4 * h + 64] = make_uint4(f[8 * h + 1], f[8 * h + 3], f[8 * h + 5], f[8 * h + 7]);
    }
}
template <int O, int N, int M> __device__ __forceinline__ void pack_sub(uint32_t (&f)[N], const float (&acc)[M]) {
#pragma unroll
    for (int i = 0; i < N; i++) f[i] = pack2(acc[O + 2 * i], acc[O + 2 * i + 1]);
}
template <int N> __device__ __forceinline__ void pack_acc(uint32_t (&f)[N], const float (&acc)[2 * N]) {
#pragma unroll
    for (int i = 0; i < N; i++) f[i] = pack2(acc[2 * i], acc[2 * i + 1]);
}
template <int N> __device__ __forceinline__ void recv_issue(uint32_t (&q)[N], const uint4* p) {
#pragma unroll
    for (int v = 0; v < N / 4; v++) ld_pkt(p + v * 32, q[4 * v], q[4 * v + 1], q[4 * v + 2], q[4 * v + 3]);
}
template <int N> __device__ __forceinline__ void recv_check(uint32_t (&q)[N], const uint4* p, uint32_t tag) {
    uint32_t it = 0;
    while (true) {
        uint32_t bad = 0;
#pragma unroll
        for (int v = 0; v < N / 4; v++) bad |= q[4 * v] ^ tag;
        if (__all_sync(0xffffffffu, (bad & 1u) == 0) || ++it > SPIN_GLOBAL) break;
        recv_issue(q, p);
    }
}
template <bool FIRST> __device__ __forceinline__ void accum(const uint32_t (&q)[16], float (&sum)[32]) {
#pragma unroll
    for (int i = 0; i < 16; i++) {
        if (FIRST) { sum[2 * i] = bf_lo(q[i]); sum[2 * i + 1] = bf_hi(q[i]); }
        else { sum[2 * i] += bf_lo(q[i]); sum[2 * i + 1] += bf_hi(q[i]); }
    }
}

}

__global__ void __launch_bounds__(384, 1)
fused_kernel(const __grid_constant__ Maps maps, const __nv_bfloat16* __restrict__ xg, const __nv_bfloat16* __restrict__ gate_w,
             const char* __restrict__ pf_qkv, const char* __restrict__ pf_g, const char* __restrict__ pf_u,
             const char* __restrict__ pf_d, const char* __restrict__ pf_o, __nv_bfloat16* __restrict__ out) {
    extern __shared__ __align__(1024) uint8_t smem_raw[];
    const uint32_t sb = (uint32_t)__cvta_generic_to_shared(smem_raw);
    const int tid = threadIdx.x, lane = tid & 31;
    const int warp = __shfl_sync(0xffffffffu, tid >> 5, 0);
    const int j = (blockIdx.x >> 1) & 7;
    const int r = ((blockIdx.x >> 4) << 1) | (blockIdx.x & 1);
    const uint32_t rank = blockIdx.x & 1;

    if (warp == 0) { TSG(0, 30); TS(0, 0); }
    if (tid == 256) {
        for (int i = 0; i < 5; i++) { mbar_init(sb + B_FULL + 8 * i, 1); mbar_init(sb + B_EMPTY + 8 * i, MC ? 4 : 2); }
        for (int i = 0; i < 9; i++) mbar_init(sb + B_XFULL + 8 * i, 1);
        asm volatile("fence.mbarrier_init.release.cluster;" ::: "memory");
        mbar_expect(sb + B_XFULL, 16384);
        tma2(sb + OFF_X, &maps.x, 0, r * 128, sb + B_XFULL);
        TS2(0);
        mbar_expect(sb + B_FULL, 16384);
        tmaw3(sb + OFF_RING, &maps.gu, 224 * j, 0, 0, sb + B_FULL);
        TS2(1);
        mbar_expect(sb + B_FULL + 8, 16384);
        tmaw3(sb + OFF_RING + 16384, &maps.kv, 64 * j, 0, 1, sb + B_FULL + 8);
    } else if (tid == 288) {
        for (int i = 0; i < 5; i++) mbar_init(sb + B_HSENT + 8 * i, 8);
        mbar_init(sb + B_XFREE, 2); mbar_init(sb + B_XFREE + 8, 2);
        mbar_init(sb + B_GRDY, 1); mbar_init(sb + B_KVDONE, 8); mbar_init(sb + B_KVRDY, 1);
        asm volatile("fence.mbarrier_init.release.cluster;" ::: "memory");
    } else if (warp == 10 && lane < 12) {
        asm volatile("prefetch.tensormap [%0];" :: "l"(&maps.gu + lane) : "memory");
    }
    __syncthreads();

    if (warp >= 8) {
        asm volatile("setmaxnreg.dec.sync.aligned.u32 72;");
        if (warp == 8) {
            if (lane == 0) {
                int slot = MC ? 0 : 2, ph = 1;
                uint32_t full, dst;
                if (!MC) { mbar_expect(sb + B_XFULL + 8, 16384); tma2(sb + OFF_X + 16384, &maps.x, 64, r * 128, sb + B_XFULL + 8); }
#define P_BEGIN(S, BYTES) full = sb + B_FULL + 8 * slot; dst = sb + OFF_RING + slot * 16384; \
                mbar_wait(sb + B_EMPTY + 8 * slot, ph); TS2(S); mbar_expect(full, BYTES); if (!MC || (((S) ^ rank) & 1) == 0)
#define P_END() if (++slot == 5) { slot = 0; ph ^= 1; }
                for (int s = MC ? 0 : 2; s < 16; s++) {
                    P_BEGIN(s, 16384) {
                        if (s & 1) tmaw3(dst, &maps.kv, 64 * j, 32 * (s - 1), 1, full);
                        else tmaw3(dst, &maps.gu, 224 * j, 32 * s, 0, full);
                    }
                    const int xb = (s == 4) ? 3 : !(s & 1) ? 0 : (s < 5) ? (s + 1) / 2 : (s <= 11) ? (s + 3) / 2 : 0;
                    if (xb) { mbar_expect(sb + B_XFULL + 8 * xb, 16384); tma2(sb + OFF_X + xb * 16384, &maps.x, 64 * xb, r * 128, sb + B_XFULL + 8 * xb); }
                    P_END()
                }
                for (int s = 0; s < 8; s++) {
                    P_BEGIN(16 + s, 16384) {
                        tmaw3(dst, &maps.q64, 0, 64 * s, 2 * j, full);
                        tmaw3(dst + 8192, &maps.gu64, 224 * j + 192, 64 * s, 0, full);
                    }
                    P_END()
                }
                for (int s = 0; s < 16; s++) {
                    P_BEGIN(24 + s, 16384) tmaw3(dst, &maps.gu, 224 * j + 64 + 64 * (s >> 3), 64 * (s & 7), 0, full);
                    P_END()
                }
                const int p = j >> 1, ro = 224 * j, gp = 7 * (j ^ 1);
#pragma unroll 1
                for (int t = 0; t < 18; t++) {
                    const int q = (t >= 7 && t != 9 && t != 10), u = t < 7 ? t : t < 9 ? t - 7 : t < 11 ? t - 2 : t - 9;
                    const int cw = (j & 1) * 4 + ((p & 2) ^ (q ? 0 : 2)), cc = 64 * cw;
                    P_BEGIN(40 + t, 16384) {
                        if (u == 4) {
                            tmaw5(dst, &maps.wdph, cc, gp + 6, full); tmaw5(dst + 4096, &maps.wdph, cc + 64, gp + 6, full);
                            tmaw3(dst + 8192, &maps.wdh, 0, ro + 192, cw, full);
                        } else if (u == 2 || u == 3 || u >= 7) {
                            const CUtensorMap* m = u == 7 ? &maps.wop : &maps.wdp;
                            const int g = u == 7 ? 2 * (j ^ 1) : u == 8 ? gp + 4 : gp + 2 * (u - 2);
                            tmaw5(dst, m, cc, g, full); tmaw5(dst + 8192, m, cc + 64, g, full);
                        } else {
                            tmaw3(dst, u == 5 ? &maps.wow : &maps.wdw, 0, u == 5 ? 64 * j : u == 6 ? ro + 128 : ro + 64 * u, cw, full);
                        }
                    }
                    P_END()
                }
            }
        } else if (warp < 11) {
            const int hx = warp - 9;
            uint32_t epoch;
            asm volatile("ld.relaxed.gpu.global.u32 %0, [%1];" : "=r"(epoch) : "l"(g_epoch + blockIdx.x) : "memory");
            {
                const uint4* xr = (const uint4*)(xg + (size_t)(r * 128 + j * 16 + hx * 8) * kD) + lane;
                const uint4 wa = __ldg((const uint4*)gate_w + lane), wb = __ldg((const uint4*)gate_w + 32 + lane);
                const uint32_t tag = (epoch + 1) & 1;
                uint4* gp = g_gx + r * 32;
                if (lane < 2) st_pkt(gp + j * 4 + hx * 2 + lane, tag ^ 1, 0, 0, 0);
                float s[8];
#pragma unroll
                for (int i0 = 0; i0 < 8; i0 += 4) {
                    uint4 va[4], vb[4];
#pragma unroll
                    for (int i = 0; i < 4; i++) { va[i] = __ldg(xr + (i0 + i) * 64); vb[i] = __ldg(xr + (i0 + i) * 64 + 32); }
#pragma unroll
                    for (int i = 0; i < 4; i++) {
                        float t0 = bf_lo(va[i].x) * bf_lo(wa.x), t1 = bf_hi(va[i].x) * bf_hi(wa.x);
                        t0 = fmaf(bf_lo(va[i].y), bf_lo(wa.y), t0); t1 = fmaf(bf_hi(va[i].y), bf_hi(wa.y), t1);
                        t0 = fmaf(bf_lo(va[i].z), bf_lo(wa.z), t0); t1 = fmaf(bf_hi(va[i].z), bf_hi(wa.z), t1);
                        t0 = fmaf(bf_lo(va[i].w), bf_lo(wa.w), t0); t1 = fmaf(bf_hi(va[i].w), bf_hi(wa.w), t1);
                        t0 = fmaf(bf_lo(vb[i].x), bf_lo(wb.x), t0); t1 = fmaf(bf_hi(vb[i].x), bf_hi(wb.x), t1);
                        t0 = fmaf(bf_lo(vb[i].y), bf_lo(wb.y), t0); t1 = fmaf(bf_hi(vb[i].y), bf_hi(wb.y), t1);
                        t0 = fmaf(bf_lo(vb[i].z), bf_lo(wb.z), t0); t1 = fmaf(bf_hi(vb[i].z), bf_hi(wb.z), t1);
                        t0 = fmaf(bf_lo(vb[i].w), bf_lo(wb.w), t0); t1 = fmaf(bf_hi(vb[i].w), bf_hi(wb.w), t1);
                        s[i0 + i] = t0 + t1;
                    }
                }
#pragma unroll
                for (int i = 0; i < 8; i++) {
#pragma unroll
                    for (int o = 16; o; o >>= 1) s[i] += __shfl_xor_sync(0xffffffffu, s[i], o);
                    s[i] = 1.f / (1.f + __expf(-s[i]));
                }
                if (lane < 2) {
                    const float v0 = lane ? s[4] : s[0], v1 = lane ? s[5] : s[1], v2 = lane ? s[6] : s[2], v3 = lane ? s[7] : s[3];
                    st_pkt(gp + j * 4 + hx * 2 + lane, (__float_as_uint(v0) & ~1u) | tag, __float_as_uint(v1), __float_as_uint(v2), __float_as_uint(v3));
                }
                if (hx == 1) {
                    asm volatile("st.shared.u32 [%0], %1;" :: "r"(sb + OFF_ONES + lane * 4), "r"(0x3f803f80u) : "memory");
                    asm volatile("fence.proxy.async.shared::cta;" ::: "memory");
                }
                asm volatile("bar.sync 3, 64;" ::: "memory");
                if (hx == 0) {
                    uint32_t q[4];
                    recv_issue(q, gp + lane);
                    recv_check(q, gp + lane, tag);
                    asm volatile("st.shared.v4.u32 [%0], {%1,%2,%3,%4};" :: "r"(sb + OFF_G + lane * 16), "r"(q[0]), "r"(q[1]), "r"(q[2]), "r"(q[3]) : "memory");
                    if (lane == 0) {
                        asm volatile("st.shared.u32 [%0], %1;" :: "r"(sb + OFF_EPOCH), "r"(epoch) : "memory");
                        g_epoch[blockIdx.x] = epoch + 1;
                    }
                    __syncwarp();
                    if (lane == 0) mbar_arrive(sb + B_GRDY);
                } else {
                    if (r == 0) {
                        float4* zp = (float4*)(g_kvacc + (((epoch & 1) ^ 1) * 8 + j) * 4 * 272);
                        for (int i = lane; i < 272; i += 32) zp[i] = make_float4(0.f, 0.f, 0.f, 0.f);
                    }
                }
            }
            TS(2 + hx, 1);
#define PUBLISH_H(B) do { mbar_wait(sb + B_HSENT + 8 * (B), 0); if (lane == 0) { asm volatile("fence.proxy.async;" ::: "memory"); \
                asm volatile("st.release.gpu.global.u32 [%0], %1;" :: "l"(g_hflag + (r * 8 + j) * 8 + (B)), "r"(epoch + 1) : "memory"); } __syncwarp(); } while (0)
            if (hx == 1) {
#pragma unroll 1
                for (int b = 0; b < 4; b++) { PUBLISH_H(b); TS(3, 5 + b); }
            } else {
                const float* accp = g_kvacc + ((epoch & 1) * 8 + j) * 4 * 272;
                unsigned* cnt = g_kvcnt + j * 32;
                mbar_wait(sb + B_KVDONE, 0);
                TS(2, 5);
                if (lane == 0) asm volatile("red.release.gpu.global.add.u32 [%0], 1;" :: "l"(cnt) : "memory");
                __syncwarp();
                TS(2, 2);
                {
                    const unsigned target = 16u * (epoch + 1);
                    uint32_t it = 0, v;
                    do {
                        asm volatile("ld.acquire.gpu.global.u32 %0, [%1];" : "=r"(v) : "l"(cnt) : "memory");
                    } while ((int)(v - target) < 0 && ++it < SPIN_GLOBAL);
                }
                TS(2, 3);
#pragma unroll
                for (int h = 0; h < 4; h++) {
                    const float4 d0 = __ldcg((const float4*)(accp + h * 272) + lane);
                    const float4 d1 = __ldcg((const float4*)(accp + h * 272 + 128) + lane);
                    const float2 z0 = __ldcg((const float2*)(accp + h * 272 + 256) + (lane & 3));
                    const float2 z1 = __ldcg((const float2*)(accp + h * 272 + 264) + (lane & 3));
                    asm volatile("st.shared.v4.u32 [%0], {%1,%2,%3,%4};" :: "r"(sb + OFF_KVF + h * 512 + lane * 16),
                                 "r"(pack2(d0.x, d0.y)), "r"(pack2(d1.x, d1.y)), "r"(pack2(d0.z, d0.w)), "r"(pack2(d1.z, d1.w)) : "memory");
                    if (lane < 4) asm volatile("st.shared.v2.u32 [%0], {%1,%2};" :: "r"(sb + OFF_ZF + h * 32 + lane * 8), "r"(pack2(z0.x, z0.y)), "r"(pack2(z1.x, z1.y)) : "memory");
                }
                __syncwarp();
                if (lane == 0) mbar_arrive(sb + B_KVRDY);
                TS(2, 4);
                PUBLISH_H(4);
                TS(3, 9);
            }
        } else {
            mbar_wait(sb + B_XFULL, 0);
            const int b = blockIdx.x;
            if (lane == 0) l2_prefetch(pf_qkv + b * 12288, 12288);
            if (lane == 1) l2_prefetch(pf_g + b * 14336, 14336);
            if (lane == 2) l2_prefetch(pf_u + b * 14336, 14336);
            mbar_wait(sb + B_XFULL + 8 * 7, 0);
            if (lane == 0) l2_prefetch(pf_d + b * 14336, 14336);
            if (lane == 1) l2_prefetch(pf_o + b * 4096, 4096);
            if (lane == 0) {
                mbar_wait(sb + B_GRDY, 0);
                uint32_t want;
                asm volatile("ld.shared.u32 %0, [%1];" : "=r"(want) : "r"(sb + OFF_EPOCH) : "memory");
                want += 1;
                const unsigned* fl = g_hflag + (r * 8 + (j ^ 1)) * 8;
                const int hrow = (r * 8 + (j ^ 1)) * 5 * 128;
#pragma unroll 1
                for (int i = 0; i < 5; i++) {
                    const int blk = i == 1 ? 2 : i == 2 ? 1 : i;
                    const int piece = i == 4 ? 8 : i + 2;
                    uint32_t it = 0, v;
                    do {
                        asm volatile("ld.acquire.gpu.global.u32 %0, [%1];" : "=r"(v) : "l"(fl + blk) : "memory");
                    } while (v != want && ++it < SPIN_GLOBAL);
                    if (i == 0) mbar_wait(sb + B_XFREE, 0);
                    if (i == 2) mbar_wait(sb + B_XFREE + 8, 0);
                    TS2(140 + i);
                    mbar_expect(sb + B_XFULL + 8 * piece, i == 2 ? 8192 : 16384);
                    tma2(sb + OFF_X + piece * 16384, i == 2 ? &maps.hxh : &maps.hx, 0, hrow + blk * 128, sb + B_XFULL + 8 * piece);
                }
            }
        }
    } else {
        asm volatile("setmaxnreg.inc.sync.aligned.u32 216;");
        const int wg = warp >> 2;
        const bool elect = (tid & 127) == 0;
        const uint32_t xlo = ((sb + OFF_X + wg * 8192) >> 4) | LBO1;
        const uint32_t ringlo = (sb + OFF_RING) >> 4;
        int slot = 0, ph = 0, prev = 0;
        auto release = [&](int s) {
            if (elect) {
                mbar_arrive(sb + B_EMPTY + 8 * s);
            }
        };
        auto adv = [&]() { prev = slot; if (++slot == 5) { slot = 0; ph ^= 1; } };

        int pidx = 64;
#define G1_STAGE(acc, SW, KB, FIRST) do { mbar_wait(sb + B_FULL + 8 * slot, ph); if (PROF) { if (tid == 0) TS2(pidx); pidx++; } \
            g1_issue<SW, FIRST>(acc, xlo + (KB) * 1024, (ringlo + slot * 1024) | (SW ? LBO4K : LBO8K)); } while (0)
#define FENCE_SCHED() mbar_wait(sb + B_XFULL, 0)
#define G1_RETIRE() do { wg_wait<1>(); release(prev); adv(); } while (0)
#define A2_SYNC() do { asm volatile("fence.proxy.async.shared::cta;" ::: "memory"); asm volatile("bar.sync %0, 128;" :: "r"(wg + 1) : "memory"); } while (0)
#define H_EPI(acc, F, N, OG, OU) _Pragma("unroll") for (int i = 0; i < (N); i++) { \
            const float m_ = (i & 1) ? m_hi : m_lo; \
            F[i] = pack2(acc[(OG) + 2 * i] * acc[(OU) + 2 * i] * m_, acc[(OG) + 2 * i + 1] * acc[(OU) + 2 * i + 1] * m_); }

        float a0[64], b0[64], a1[64], a2_[64], a3[64];
        mbar_wait(sb + B_XFULL, 0);
        G1_STAGE(a0, false, 0, 1); adv();
        if ((warp & 3) == 0) TS(wg, 1);
        G1_STAGE(b0, false, 0, 1); G1_RETIRE();
#pragma unroll 1
        for (int kb = 1; kb < 8; kb++) {
            mbar_wait(sb + B_XFULL + 8 * kb, 0);
            if (PROF && tid == 0) TS2(128 + kb);
            G1_STAGE(a0, false, kb, 0); G1_RETIRE();
            G1_STAGE(b0, false, kb, 0); G1_RETIRE();
        }
        pin(a0);
        mbar_wait(sb + B_GRDY, 0);
        float g_lo, g_hi;
        uint32_t tag;
        {
            const uint32_t ga = sb + OFF_G + (warp * 16 + (lane >> 2)) * 4;
            asm volatile("ld.shared.f32 %0, [%1];" : "=f"(g_lo) : "r"(ga) : "memory");
            asm volatile("ld.shared.f32 %0, [%1];" : "=f"(g_hi) : "r"(ga + 32) : "memory");
            asm volatile("ld.shared.u32 %0, [%1];" : "=r"(tag) : "r"(sb + OFF_EPOCH) : "memory");
        }
        float* const kvp = g_kvacc + (((tag & 1) * 8 + j) * 4 + (warp & 3)) * 272;
        tag = (tag + 1) & 1;
        const float m_lo = 1.f - g_lo, m_hi = 1.f - g_hi;
        if ((warp & 3) == 0) TS(wg, 2);
        uint32_t fh0[16], fh1[16], fh2[16], fh3[8], fo[16];
        H_EPI(a0, fh0, 16, 0, 32);

        const uint32_t lrow = ((lane & 7) + 8 * ((lane >> 3) & 1)) * 128;
        const uint32_t srow = (warp & 3) * 2048 + lrow;
        const uint32_t ssw = (lane >> 4) ^ (lane & 7);
        uint4* const hsend = g_hx + (size_t)((r * 8 + j) * 5) * 1024 + warp * 128 + (lane >> 2) * 8 + (lane & 3);
#define SEND_H(F, B) do { send_h(F, hsend + (B) * 1024); __syncwarp(); if (lane == 0) mbar_arrive(sb + B_HSENT + 8 * (B)); } while (0)

        float kv[32], zs[4];
        {
            uint32_t pk[16], pv[16];
            const uint32_t stg = sb + OFF_STG + wg * 8192;
            const uint32_t klo = (stg >> 4) | LBO1, vlo = klo + 256, olo = (sb + OFF_ONES) >> 4;
            G1_STAGE(a1, true, 0, 1); G1_RETIRE();
            pin(b0);
            G1_STAGE(a1, true, 1, 0); FENCE_SCHED();
#pragma unroll
            for (int i = 0; i < 8; i++) pk[i] = pack2(phi(b0[2 * i]), phi(b0[2 * i + 1]));
            SEND_H(fh0, 0);
            G1_RETIRE();
            G1_STAGE(a1, true, 2, 0); FENCE_SCHED();
#pragma unroll
            for (int i = 8; i < 16; i++) pk[i] = pack2(phi(b0[2 * i]), phi(b0[2 * i + 1]));
#pragma unroll
            for (int i = 0; i < 16; i++) pv[i] = pack2(b0[32 + 2 * i], b0[32 + 2 * i + 1]);
            if (!(warp & 2)) { stash<16>(stg + (warp & 1) * 2048 + lrow, ssw, pk); stash<16>(stg + 4096 + (warp & 1) * 2048 + lrow, ssw, pv); }
            G1_RETIRE();
            G1_STAGE(a1, true, 3, 0); G1_RETIRE();
            A2_SYNC();
            wg_fence();
            wg_ss64t_z(kv, vlo, DH128, klo, DH128); wg_ss64t(kv, vlo + 128, DH128, klo + 128, DH128);
            wg_ss8t_z(zs, klo, DH128, olo, 0); wg_ss8t(zs, klo + 128, DH128, olo, 0);
            wg_commit();
            G1_STAGE(a1, true, 4, 0); G1_RETIRE();
            G1_STAGE(a1, true, 5, 0); FENCE_SCHED();
            if (warp & 2) { stash<16>(stg + (warp & 1) * 2048 + lrow, ssw, pk); stash<16>(stg + 4096 + (warp & 1) * 2048 + lrow, ssw, pv); }
            G1_RETIRE();
            G1_STAGE(a1, true, 6, 0); G1_RETIRE();
            A2_SYNC();
            wg_fence();
            wg_ss64t(kv, vlo, DH128, klo, DH128); wg_ss64t(kv, vlo + 128, DH128, klo + 128, DH128);
            wg_ss8t(zs, klo, DH128, olo, 0); wg_ss8t(zs, klo + 128, DH128, olo, 0);
            wg_commit();
            G1_STAGE(a1, true, 7, 0); G1_RETIRE();
        }
        if ((warp & 3) == 0) TS(wg, 3);

        G1_STAGE(a2_, false, 0, 1); FENCE_SCHED();
        pin(kv); pin(zs);
#define KV_RED(W) do { asm volatile("red.global.add.v4.f32 [%0], {%1,%2,%3,%4};" :: "l"(kvp + lane * 4), "f"(kv[8 * W]), "f"(kv[8 * W + 1]), "f"(kv[8 * W + 2]), "f"(kv[8 * W + 3]) : "memory"); \
                       asm volatile("red.global.add.v4.f32 [%0], {%1,%2,%3,%4};" :: "l"(kvp + 128 + lane * 4), "f"(kv[8 * W + 4]), "f"(kv[8 * W + 5]), "f"(kv[8 * W + 6]), "f"(kv[8 * W + 7]) : "memory"); } while (0)
        if ((warp & 3) == 0) KV_RED(0); else if ((warp & 3) == 1) KV_RED(1); else if ((warp & 3) == 2) KV_RED(2); else KV_RED(3);
        if ((lane & 3) == 0) {
            asm volatile("red.global.add.f32 [%0], %1;" :: "l"(kvp + 256 + (lane >> 2)), "f"(zs[0]) : "memory");
            asm volatile("red.global.add.f32 [%0], %1;" :: "l"(kvp + 264 + (lane >> 2)), "f"(zs[2]) : "memory");
        }
        __syncwarp();
        if (lane == 0) mbar_arrive(sb + B_KVDONE);
        G1_RETIRE();
        pin(a1);
        G1_STAGE(a2_, false, 1, 0); FENCE_SCHED();
#pragma unroll
        for (int i = 0; i < 8; i++) fo[i] = pack2(phi(a1[2 * i]), phi(a1[2 * i + 1]));
        G1_RETIRE();
        G1_STAGE(a2_, false, 2, 0); FENCE_SCHED();
#pragma unroll
        for (int i = 8; i < 16; i++) fo[i] = pack2(phi(a1[2 * i]), phi(a1[2 * i + 1]));
        G1_RETIRE();
        G1_STAGE(a2_, false, 3, 0); FENCE_SCHED();
        H_EPI(a1, fh3, 8, 32, 48);
        SEND_H(fh3, 1);
        G1_RETIRE();
        const int p = j >> 1;
        uint4* const pbase = g_part + (size_t)(r * 2 + (j & 1)) * 16384 + warp * 128 + lane;
        const int pw = (p & 2) ^ 2;
        auto other = [&](int d) { return d == 3 ? p ^ 1 : pw + d - 1; };
        auto sendp = [&](int d) { return pbase + ((other(d) * 4 + p) << 10); };
        auto recvp = [&](int d) { return pbase + ((p * 4 + other(d)) << 10); };
#pragma unroll 1
        for (int kb = 4; kb < 7; kb++) {
            G1_STAGE(a2_, false, kb, 0);
            uint4* mp = sendp(kb - 3);
#pragma unroll
            for (int v = 0; v < 4; v++) st_pkt(mp + v * 32, tag ^ 1, 0, 0, 0);
            G1_RETIRE();
        }
        G1_STAGE(a2_, false, 7, 0); G1_RETIRE();
        if ((warp & 3) == 0) TS(wg, 4);

        const uint32_t a2 = sb + OFF_X + wg * 8192 + srow;
        G1_STAGE(a3, false, 0, 1); G1_RETIRE();
        pin(a2_);
        G1_STAGE(a3, false, 1, 0); FENCE_SCHED();
        H_EPI(a2_, fh1, 16, 0, 32);
        SEND_H(fh1, 2);
        G1_RETIRE();
        G1_STAGE(a3, false, 2, 0); FENCE_SCHED(); stash<16>(a2, ssw, fh0); G1_RETIRE();
        G1_STAGE(a3, false, 3, 0); FENCE_SCHED(); stash<16>(a2 + 16384, ssw, fh1); G1_RETIRE();
        G1_STAGE(a3, false, 4, 0); G1_RETIRE();
        if (elect) mbar_arrive(sb + B_XFREE);
        G1_STAGE(a3, false, 5, 0);
        if ((warp & 3) == 0) TS(wg, 5);
        mbar_wait(sb + B_KVRDY, 0);
        if ((warp & 3) == 0) TS(wg, 6);
#pragma unroll
        for (int h = 0; h < 4; h++) {
            uint32_t b0, b1, b2, b3, z0, z1;
            asm volatile("ld.shared.v4.u32 {%0,%1,%2,%3}, [%4];" : "=r"(b0), "=r"(b1), "=r"(b2), "=r"(b3) : "r"(sb + OFF_KVF + h * 512 + lane * 16) : "memory");
            asm volatile("ld.shared.v2.u32 {%0,%1}, [%2];" : "=r"(z0), "=r"(z1) : "r"(sb + OFF_ZF + h * 32 + (lane & 3) * 8) : "memory");
            float n0[4] = {0.f, 0.f, 0.f, 0.f}, n1[4] = {0.f, 0.f, 0.f, 0.f}, dn[4] = {0.f, 0.f, 0.f, 0.f};
            mma16816(dn, fo[4 * h], fo[4 * h + 1], fo[4 * h + 2], fo[4 * h + 3], z0, z1);
            mma16816(n0, fo[4 * h], fo[4 * h + 1], fo[4 * h + 2], fo[4 * h + 3], b0, b1);
            mma16816(n1, fo[4 * h], fo[4 * h + 1], fo[4 * h + 2], fo[4 * h + 3], b2, b3);
            const float s_lo = __fdividef(g_lo, dn[0] + 1e-6f), s_hi = __fdividef(g_hi, dn[2] + 1e-6f);
            fo[4 * h] = pack2(n0[0] * s_lo, n0[1] * s_lo); fo[4 * h + 1] = pack2(n0[2] * s_hi, n0[3] * s_hi);
            fo[4 * h + 2] = pack2(n1[0] * s_lo, n1[1] * s_lo); fo[4 * h + 3] = pack2(n1[2] * s_hi, n1[3] * s_hi);
        }
        SEND_H(fo, 3);
        G1_RETIRE();
        G1_STAGE(a3, false, 6, 0); FENCE_SCHED();
        stash<8>(a2 + 4 * 16384, ssw ^ 4, fh3);
        G1_RETIRE();
        if (elect) mbar_arrive(sb + B_XFREE + 8);
        G1_STAGE(a3, false, 7, 0);
        G1_RETIRE();
        A2_SYNC();
        if ((warp & 3) == 0) TS(wg, 7);

#define G2_PIECE(U) ((U) < 5 ? (U) : (U) == 5 ? 6 : (U) == 6 ? 7 : (U) == 7 ? 5 : 8)
#define G2_B(T) (ringlo + ((T) % 5) * 1024)
#define G2_WAIT(T) do { mbar_wait(sb + B_FULL + 8 * ((T) % 5), ((T) / 5) & 1); if (PROF && tid == 0) TS2(64 + 40 + (T)); } while (0)
#define G2_REL(T) do { if ((T) < 13) release((T) % 5); } while (0)
#define G2_W(T, acc, U) do { G2_WAIT(T); wg_fence(); _Pragma("unroll") for (int k = 0; k < 4; k++) { \
            if ((U) == 0 && k == 0) wg_ss128_z(acc, xlo, DH128, G2_B(T) | LBO8K, DH128); \
            else if ((U) == 4) wg_ss128(acc, xlo + 4096 + 2 * k, DH128, (G2_B(T) | LBO4K) + (k >> 1) * 512 + (k & 1) * 128, DH128); \
            else wg_ss128(acc, xlo + G2_PIECE(U) * 1024 + 2 * k, DH128, (G2_B(T) | LBO8K) + 128 * k, DH128); } wg_commit(); } while (0)
#define H_WAIT(P) do { mbar_wait(sb + B_XFULL + 8 * (P), (P) < 8); if (PROF && tid == 0) TS2(150 + (P)); } while (0)

        float p1[64], p2[64];
        G2_W(0, p1, 0);
        wg_wait<1>();
        release(prev);
        pin(a3);
        G2_W(1, p1, 1); FENCE_SCHED();
        H_EPI(a3, fh2, 16, 0, 32);
        SEND_H(fh2, 4);
        wg_wait<1>(); G2_REL(0);
        H_WAIT(2); G2_W(2, p1, 2); FENCE_SCHED();
        stash<16>(a2 + 6 * 16384, ssw, fo); stash<16>(a2 + 7 * 16384, ssw, fh2);
        wg_wait<1>(); G2_REL(1);
        H_WAIT(3); G2_W(3, p1, 3); wg_wait<1>(); G2_REL(2);
        H_WAIT(4); G2_W(4, p1, 4); wg_wait<1>(); G2_REL(3);
        A2_SYNC();
        G2_W(5, p1, 5); wg_wait<1>(); G2_REL(4);
        G2_W(6, p1, 6); wg_wait<1>(); G2_REL(5);
        G2_W(7, p2, 0); wg_wait<1>(); G2_REL(6);
        G2_W(8, p2, 1); wg_wait<1>(); G2_REL(7);
        H_WAIT(5); G2_W(9, p1, 7); wg_wait<1>(); G2_REL(8);
        H_WAIT(8); G2_W(10, p1, 8); wg_wait<1>(); G2_REL(9);
        if ((warp & 3) == 0) TS(wg, 8);
        uint32_t sp[32], qa[16], qb[16];
        float sum[32];
        G2_W(11, p2, 2); wg_wait<1>(); G2_REL(10);
        pin(p1);
        G2_W(12, p2, 3); FENCE_SCHED(); pack_acc(sp, p1); send_frag<0, 3>(sp, sendp(1), tag); wg_wait<1>(); G2_REL(11);
        G2_W(13, p2, 4); send_frag<3, 4>(sp, sendp(1), tag); send_frag<4, 6>(sp, sendp(2), tag); wg_wait<1>(); G2_REL(12);
        G2_W(14, p2, 5); send_frag<6, 8>(sp, sendp(2), tag); wg_wait<1>();
        G2_W(15, p2, 6); wg_wait<1>();
        G2_W(16, p2, 7); recv_issue(qa, recvp(1)); wg_wait<1>();
        G2_W(17, p2, 8); recv_issue(qb, recvp(2)); FENCE_SCHED();
        if ((warp & 3) == 0) TS(wg, 9);
        recv_check(qa, recvp(1), tag); accum<true>(qa, sum);
        recv_check(qb, recvp(2), tag); accum<false>(qb, sum);
        if ((warp & 3) == 0) TS(wg, 10);
        wg_wait<0>();
        pin(p2);
        if ((warp & 3) == 0) TS(wg, 11);
        if (p & 1) pack_sub<0>(qa, p2); else pack_sub<32>(qa, p2);
        send_frag<0, 4>(qa, sendp(3), tag);
        recv_issue(qb, recvp(3));
        if (p & 1) {
#pragma unroll
            for (int i = 0; i < 32; i++) sum[i] += p2[32 + i];
        } else {
#pragma unroll
            for (int i = 0; i < 32; i++) sum[i] += p2[i];
        }
        if ((warp & 3) == 0) TS(wg, 12);
        recv_check(qb, recvp(3), tag); accum<false>(qb, sum);
        if ((warp & 3) == 0) TS(wg, 13);
        {
            uint32_t f[16];
            pack_acc(f, sum);
            const uint32_t slab = sb + OFF_X + wg * 8192;
            stash<16>(slab + srow, ssw, f);
            __syncwarp();
            __nv_bfloat16* op = out + (size_t)(r * 128 + warp * 16 + (lane >> 3)) * kD + (j & 1) * 256 + p * 64 + (lane & 7) * 8;
#pragma unroll
            for (int i = 0; i < 4; i++) {
                const int row = i * 4 + (lane >> 3);
                uint4 v;
                asm volatile("ld.shared.v4.u32 {%0,%1,%2,%3}, [%4];" : "=r"(v.x), "=r"(v.y), "=r"(v.z), "=r"(v.w)
                             : "r"(slab + ((warp & 3) * 16 + row) * 128 + (((lane & 7) ^ (row & 7)) << 4)) : "memory");
                *(uint4*)(op + i * 4 * kD) = v;
            }
        }
        if ((warp & 3) == 0) { TS(wg, 14); TSG(wg, 31); }
    }
}

typedef CUresult (*EncodeFn)(CUtensorMap*, CUtensorMapDataType, cuuint32_t, void*, const cuuint64_t*, const cuuint64_t*, const cuuint32_t*,
                             const cuuint32_t*, CUtensorMapInterleave, CUtensorMapSwizzle, CUtensorMapL2promotion, CUtensorMapFloatOOBfill);

static void encode(EncodeFn fn, CUtensorMap* m, int rank, const void* base, const cuuint64_t (&gd)[5], const cuuint64_t (&gs)[4],
                   const cuuint32_t (&bd)[5], CUtensorMapSwizzle sw) {
    cuuint32_t es[5] = {1, 1, 1, 1, 1};
    fn(m, CU_TENSOR_MAP_DATA_TYPE_BFLOAT16, rank, const_cast<void*>(base), gd, gs, bd, es, CU_TENSOR_MAP_INTERLEAVE_NONE, sw,
       CU_TENSOR_MAP_L2_PROMOTION_L2_128B, CU_TENSOR_MAP_FLOAT_OOB_FILL_NONE);
}

extern "C" void kernel_launch(void* const* d_in, const int* in_sizes, int n_in, void* d_out, int out_size) {
    const char* x = (const char*)d_in[0];
    const char* wqkv = (const char*)d_in[1];
    const char* wo = (const char*)d_in[2];
    const char* wg = (const char*)d_in[4];
    const char* wu = (const char*)d_in[5];
    const char* wd = (const char*)d_in[6];
    void* fnp = nullptr;
    cudaDriverEntryPointQueryResult qr;
    cudaGetDriverEntryPoint("cuTensorMapEncodeTiled", &fnp, cudaEnableDefault, &qr);
    EncodeFn fn = (EncodeFn)fnp;
    Maps maps;
    const char* lo = wg < wu ? wg : wu;
    const uint64_t diff = wg < wu ? (uint64_t)(wu - wg) : (uint64_t)(wg - wu);
    const CUtensorMapSwizzle S128 = CU_TENSOR_MAP_SWIZZLE_128B, S64 = CU_TENSOR_MAP_SWIZZLE_64B;
    encode(fn, &maps.x, 2, x, {512, 2048, 1, 1}, {1024, 0, 0}, {64, 128, 1, 1}, S128);
    encode(fn, &maps.gu, 3, lo, {1792, 512, 2, 1}, {3584, diff, 0}, {64, 64, 2, 1}, S128);
    encode(fn, &maps.kv, 3, wqkv, {512, 512, 3, 1}, {3072, 1024, 0}, {64, 64, 2, 1}, S128);
    encode(fn, &maps.q64, 3, wqkv, {32, 512, 48, 1}, {3072, 64, 0}, {32, 64, 2, 1}, S64);
    encode(fn, &maps.gu64, 3, lo, {1792, 512, 2, 1}, {3584, diff, 0}, {32, 64, 2, 1}, S64);
    encode(fn, &maps.wdw, 3, wd, {64, 1792, 8, 1}, {1024, 128, 0}, {64, 64, 2, 1}, S128);
    encode(fn, &maps.wdh, 3, wd, {64, 1792, 8}, {1024, 128}, {64, 32, 2}, S128);
    encode(fn, &maps.wow, 3, wo, {64, 512, 8}, {1024, 128}, {64, 64, 2}, S128);
    encode(fn, &maps.wdp, 5, wd, {512, 2, 4, 4, 56}, {1024, 8192, 2048, 32768}, {64, 2, 4, 4, 2}, S128);
    encode(fn, &maps.wdph, 5, wd, {512, 2, 4, 4, 56}, {1024, 8192, 2048, 32768}, {64, 2, 4, 4, 1}, S128);
    encode(fn, &maps.wop, 5, wo, {512, 2, 4, 4, 16}, {1024, 8192, 2048, 32768}, {64, 2, 4, 4, 2}, S128);
    void* hx = nullptr;
    cudaGetSymbolAddress(&hx, g_hx);
    encode(fn, &maps.hx, 2, hx, {64, 16 * 8 * 5 * 128}, {128}, {64, 128}, S128);
    encode(fn, &maps.hxh, 2, hx, {64, 16 * 8 * 5 * 128}, {128}, {32, 128}, S128);
    cudaFuncSetAttribute(fused_kernel, cudaFuncAttributeMaxDynamicSharedMemorySize, SMEM_BYTES);
    cudaLaunchConfig_t cfg = {};
    cfg.gridDim = dim3(128);
    cfg.blockDim = dim3(384);
    cfg.dynamicSmemBytes = SMEM_BYTES;
    cfg.stream = cudaStreamPerThread;
    cudaLaunchAttribute at[1];
    at[0].id = cudaLaunchAttributeClusterDimension;
    at[0].val.clusterDim.x = 2; at[0].val.clusterDim.y = 1; at[0].val.clusterDim.z = 1;
    cfg.attrs = at;
    cfg.numAttrs = MC ? 1 : 0;
    cudaLaunchKernelEx(&cfg, fused_kernel, maps, (const __nv_bfloat16*)d_in[0], (const __nv_bfloat16*)d_in[7], wqkv, wg, wu, wd, wo, (__nv_bfloat16*)d_out);
}
```

```cpp
#include <cuda_runtime.h>
#include <cuda.h>
#include <cuda_bf16.h>
#include <stdint.h>

#define MC 0
#define PROF 0

namespace {

constexpr int kD = 512;
constexpr uint32_t OFF_X = 0, OFF_STG = 131072, OFF_RING = 147456, OFF_MISC = 229376;
constexpr uint32_t B_FULL = OFF_MISC, B_EMPTY = OFF_MISC + 40, B_XFULL = OFF_MISC + 80;
constexpr uint32_t B_GRDY = OFF_MISC + 152, B_KVDONE = OFF_MISC + 160, B_KVRDY = OFF_MISC + 168;
constexpr uint32_t B_HSENT = OFF_MISC + 176, B_XFREE = OFF_MISC + 216;
constexpr uint32_t OFF_EPOCH = OFF_MISC + 240, OFF_G = OFF_MISC + 256;
constexpr uint32_t OFF_KVF = OFF_MISC + 768, OFF_ZF = OFF_KVF + 2048;
constexpr uint32_t OFF_ONES = OFF_ZF + 128;
constexpr uint32_t SMEM_BYTES = OFF_ONES + 128;
constexpr uint32_t SPIN_GLOBAL = 1u << 14;

struct alignas(64) Maps { CUtensorMap x, gu, kv, q64, gu64, wdw, wdh, wow, wdp, wdph, wop, hx, hxh; };

}

__device__ uint4 g_part[16 * 2 * 4 * 4 * 1024];
__device__ uint4 g_hx[16 * 8 * 5 * 1024];
__device__ unsigned g_hflag[128 * 8];
__device__ uint4 g_gx[16 * 32];
__device__ float g_kvacc[2 * 8 * 4 * 272];
__device__ unsigned g_kvcnt[8 * 32];
__device__ unsigned g_epoch[128];
#define TS(role, idx)
#define TS2(idx)
#define TSG(role, idx)

namespace {

__device__ __forceinline__ void mbar_init(uint32_t bar, uint32_t cnt) { asm volatile("mbarrier.init.shared::cta.b64 [%0], %1;" :: "r"(bar), "r"(cnt) : "memory"); }
__device__ __forceinline__ void mbar_expect(uint32_t bar, uint32_t bytes) { asm volatile("mbarrier.arrive.expect_tx.shared::cta.b64 _, [%0], %1;" :: "r"(bar), "r"(bytes) : "memory"); }
__device__ __forceinline__ void mbar_arrive(uint32_t bar) { asm volatile("mbarrier.arrive.shared::cta.b64 _, [%0];" :: "r"(bar) : "memory"); }
__device__ __forceinline__ void mbar_arrive_cta(uint32_t bar, uint32_t cta) {
    asm volatile("{\n.reg .b32 ra;\nmapa.shared::cluster.u32 ra, %0, %1;\nmbarrier.arrive.shared::cluster.b64 _, [ra];\n}" :: "r"(bar), "r"(cta) : "memory");
}
__device__ __forceinline__ void mbar_wait(uint32_t bar, uint32_t parity) {
    asm volatile("{\n.reg .pred p;\n.reg .u32 c;\n"
                 "mbarrier.try_wait.parity.shared::cta.b64 p, [%0], %1;\n@p bra DONE;\n"
                 "mov.u32 c, 0;\nLAB_WAIT:\nmbarrier.try_wait.parity.shared::cta.b64 p, [%0], %1;\n@p bra DONE;\n"
                 "add.u32 c, c, 1;\nsetp.lt.u32 p, c, 65536;\n@p bra LAB_WAIT;\nDONE:\n}" :: "r"(bar), "r"(parity) : "memory");
}
__device__ __forceinline__ void tma2(uint32_t dst, const CUtensorMap* m, int c0, int c1, uint32_t bar) {
    asm volatile("cp.async.bulk.tensor.2d.shared::cluster.global.mbarrier::complete_tx::bytes [%0], [%1, {%3, %4}], [%2];"
        :: "r"(dst), "l"(m), "r"(bar), "r"(c0), "r"(c1) : "memory");
}
__device__ __forceinline__ void tmaw2(uint32_t dst, const CUtensorMap* m, int c0, int c1, uint32_t bar) {
    tma2(dst, m, c0, c1, bar);
}
__device__ __forceinline__ void tmaw3(uint32_t dst, const CUtensorMap* m, int c0, int c1, int c2, uint32_t bar) {
    asm volatile("cp.async.bulk.tensor.3d.shared::cluster.global.mbarrier::complete_tx::bytes [%0], [%1, {%3, %4, %5}], [%2];"
        :: "r"(dst), "l"(m), "r"(bar), "r"(c0), "r"(c1), "r"(c2) : "memory");
}
__device__ __forceinline__ void tmaw5(uint32_t dst, const CUtensorMap* m, int c0, int c4, uint32_t bar) {
    asm volatile("cp.async.bulk.tensor.5d.shared::cluster.global.mbarrier::complete_tx::bytes [%0], [%1, {%3, %5, %5, %5, %4}], [%2];"
        :: "r"(dst), "l"(m), "r"(bar), "r"(c0), "r"(c4), "r"(0) : "memory");
}
__device__ __forceinline__ void l2_prefetch(const void* p, uint32_t bytes) { asm volatile("cp.async.bulk.prefetch.L2.global [%0], %1;" :: "l"(p), "r"(bytes) : "memory"); }
__device__ __forceinline__ void wg_fence() { asm volatile("wgmma.fence.sync.aligned;" ::: "memory"); }
__device__ __forceinline__ void wg_commit() { asm volatile("wgmma.commit_group.sync.aligned;" ::: "memory"); }
template <int N> __device__ __forceinline__ void wg_wait() { asm volatile("wgmma.wait_group.sync.aligned %0;" :: "n"(N) : "memory"); }
template <int N> __device__ __forceinline__ void pin(float (&d)[N]) {
#pragma unroll
    for (int i = 0; i < N; i++) asm volatile("" : "+f"(d[i]) :: "memory");
}
__device__ __forceinline__ uint32_t pack2(float lo, float hi) { uint32_t r; asm("cvt.rn.bf16x2.f32 %0, %1, %2;" : "=r"(r) : "f"(hi), "f"(lo)); return r; }
__device__ __forceinline__ uint32_t hmul2(uint32_t a, uint32_t b) { uint32_t r; asm("mul.bf16x2 %0, %1, %2;" : "=r"(r) : "r"(a), "r"(b)); return r; }
__device__ __forceinline__ uint32_t phi2(float t0, float t1) {
    float e0, e1;
    asm("ex2.approx.ftz.f32 %0, %1;" : "=f"(e0) : "f"(t0 * 1.4426950408889634f));
    asm("ex2.approx.ftz.f32 %0, %1;" : "=f"(e1) : "f"(t1 * 1.4426950408889634f));
    uint32_t e = pack2(e0, e1), t = pack2(t0, t1), r;
    asm("min.bf16x2 %0, %0, %1;" : "+r"(e) : "r"(0x3f803f80u));
    asm("max.bf16x2 %0, %0, %1;" : "+r"(t) : "r"(0x35863586u));
    asm("add.bf16x2 %0, %1, %2;" : "=r"(r) : "r"(e), "r"(t));
    return r;
}
__device__ __forceinline__ void stsm4(uint32_t a, uint32_t r0, uint32_t r1, uint32_t r2, uint32_t r3) {
    asm volatile("stmatrix.sync.aligned.m8n8.x4.shared.b16 [%0], {%1,%2,%3,%4};" :: "r"(a), "r"(r0), "r"(r1), "r"(r2), "r"(r3) : "memory");
}
__device__ __forceinline__ void mma16816(float (&c)[4], uint32_t a0, uint32_t a1, uint32_t a2, uint32_t a3, uint32_t b0, uint32_t b1) {
    asm volatile("mma.sync.aligned.m16n8k16.row.col.f32.bf16.bf16.f32 {%0,%1,%2,%3}, {%4,%5,%6,%7}, {%8,%9}, {%10,%10,%10,%10};"
        : "=f"(c[0]), "=f"(c[1]), "=f"(c[2]), "=f"(c[3]) : "r"(a0), "r"(a1), "r"(a2), "r"(a3), "r"(b0), "r"(b1), "f"(0.f));
}
__device__ __forceinline__ float bf_lo(uint32_t w) { return __uint_as_float(w << 16); }
__device__ __forceinline__ float bf_hi(uint32_t w) { return __uint_as_float(w & 0xffff0000u); }
__device__ __forceinline__ void st_pkt(uint4* p, uint32_t w0, uint32_t w1, uint32_t w2, uint32_t w3) {
    asm volatile("{\n.reg .b64 lo, hi;\n.reg .b128 v;\nmov.b64 lo, {%1, %2};\nmov.b64 hi, {%3, %4};\nmov.b128 v, {lo, hi};\nst.relaxed.gpu.global.b128 [%0], v;\n}"
        :: "l"(p), "r"(w0), "r"(w1), "r"(w2), "r"(w3) : "memory");
}
__device__ __forceinline__ void ld_pkt(const uint4* p, uint32_t& w0, uint32_t& w1, uint32_t& w2, uint32_t& w3) {
    asm volatile("{\n.reg .b64 lo, hi;\n.reg .b128 v;\nld.relaxed.gpu.global.b128 v, [%4];\nmov.b128 {lo, hi}, v;\nmov.b64 {%0, %1}, lo;\nmov.b64 {%2, %3}, hi;\n}"
        : "=r"(w0), "=r"(w1), "=r"(w2), "=r"(w3) : "l"(p) : "memory");
}

__device__ __forceinline__ void wg_ss128(float (&d)[64], uint32_t alo, uint32_t ahi, uint32_t blo, uint32_t bhi) {
    asm volatile("{\n.reg .b64 da, db;\nmov.b64 da, {%64, %65};\nmov.b64 db, {%66, %67};\n"
        "wgmma.mma_async.sync.aligned.m64n128k16.f32.bf16.bf16 {%0,%1,%2,%3,%4,%5,%6,%7,%8,%9,%10,%11,%12,%13,%14,%15,%16,%17,%18,%19,%20,%21,%22,%23,%24,%25,%26,%27,%28,%29,%30,%31,%32,%33,%34,%35,%36,%37,%38,%39,%40,%41,%42,%43,%44,%45,%46,%47,%48,%49,%50,%51,%52,%53,%54,%55,%56,%57,%58,%59,%60,%61,%62,%63}, da, db, 1, 1, 1, 0, 1;\n}\n"
        : "+f"(d[0]),"+f"(d[1]),"+f"(d[2]),"+f"(d[3]),"+f"(d[4]),"+f"(d[5]),"+f"(d[6]),"+f"(d[7]),"+f"(d[8]),"+f"(d[9]),"+f"(d[10]),"+f"(d[11]),"+f"(d[12]),"+f"(d[13]),"+f"(d[14]),"+f"(d[15]),"+f"(d[16]),"+f"(d[17]),"+f"(d[18]),"+f"(d[19]),"+f"(d[20]),"+f"(d[21]),"+f"(d[22]),"+f"(d[23]),"+f"(d[24]),"+f"(d[25]),"+f"(d[26]),"+f"(d[27]),"+f"(d[28]),"+f"(d[29]),"+f"(d[30]),"+f"(d[31]),"+f"(d[32]),"+f"(d[33]),"+f"(d[34]),"+f"(d[35]),"+f"(d[36]),"+f"(d[37]),"+f"(d[38]),"+f"(d[39]),"+f"(d[40]),"+f"(d[41]),"+f"(d[42]),"+f"(d[43]),"+f"(d[44]),"+f"(d[45]),"+f"(d[46]),"+f"(d[47]),"+f"(d[48]),"+f"(d[49]),"+f"(d[50]),"+f"(d[51]),"+f"(d[52]),"+f"(d[53]),"+f"(d[54]),"+f"(d[55]),"+f"(d[56]),"+f"(d[57]),"+f"(d[58]),"+f"(d[59]),"+f"(d[60]),"+f"(d[61]),"+f"(d[62]),"+f"(d[63])
        : "r"(alo), "r"(ahi), "r"(blo), "r"(bhi));
}
__device__ __forceinline__ void wg_ss128_z(float (&d)[64], uint32_t alo, uint32_t ahi, uint32_t blo, uint32_t bhi) {
    asm volatile("{\n.reg .b64 da, db;\nmov.b64 da, {%64, %65};\nmov.b64 db, {%66, %67};\n"
        "wgmma.mma_async.sync.aligned.m64n128k16.f32.bf16.bf16 {%0,%1,%2,%3,%4,%5,%6,%7,%8,%9,%10,%11,%12,%13,%14,%15,%16,%17,%18,%19,%20,%21,%22,%23,%24,%25,%26,%27,%28,%29,%30,%31,%32,%33,%34,%35,%36,%37,%38,%39,%40,%41,%42,%43,%44,%45,%46,%47,%48,%49,%50,%51,%52,%53,%54,%55,%56,%57,%58,%59,%60,%61,%62,%63}, da, db, 0, 1, 1, 0, 1;\n}\n"
        : "=f"(d[0]),"=f"(d[1]),"=f"(d[2]),"=f"(d[3]),"=f"(d[4]),"=f"(d[5]),"=f"(d[6]),"=f"(d[7]),"=f"(d[8]),"=f"(d[9]),"=f"(d[10]),"=f"(d[11]),"=f"(d[12]),"=f"(d[13]),"=f"(d[14]),"=f"(d[15]),"=f"(d[16]),"=f"(d[17]),"=f"(d[18]),"=f"(d[19]),"=f"(d[20]),"=f"(d[21]),"=f"(d[22]),"=f"(d[23]),"=f"(d[24]),"=f"(d[25]),"=f"(d[26]),"=f"(d[27]),"=f"(d[28]),"=f"(d[29]),"=f"(d[30]),"=f"(d[31]),"=f"(d[32]),"=f"(d[33]),"=f"(d[34]),"=f"(d[35]),"=f"(d[36]),"=f"(d[37]),"=f"(d[38]),"=f"(d[39]),"=f"(d[40]),"=f"(d[41]),"=f"(d[42]),"=f"(d[43]),"=f"(d[44]),"=f"(d[45]),"=f"(d[46]),"=f"(d[47]),"=f"(d[48]),"=f"(d[49]),"=f"(d[50]),"=f"(d[51]),"=f"(d[52]),"=f"(d[53]),"=f"(d[54]),"=f"(d[55]),"=f"(d[56]),"=f"(d[57]),"=f"(d[58]),"=f"(d[59]),"=f"(d[60]),"=f"(d[61]),"=f"(d[62]),"=f"(d[63])
        : "r"(alo), "r"(ahi), "r"(blo), "r"(bhi));
}
__device__ __forceinline__ void wg_ss64(float (&d)[32], uint32_t alo, uint32_t ahi, uint32_t blo, uint32_t bhi) {
    asm volatile("{\n.reg .b64 da, db;\nmov.b64 da, {%32, %33};\nmov.b64 db, {%34, %35};\n"
        "wgmma.mma_async.sync.aligned.m64n64k16.f32.bf16.bf16 {%0,%1,%2,%3,%4,%5,%6,%7,%8,%9,%10,%11,%12,%13,%14,%15,%16,%17,%18,%19,%20,%21,%22,%23,%24,%25,%26,%27,%28,%29,%30,%31}, da, db, 1, 1, 1, 0, 1;\n}\n"
        : "+f"(d[0]),"+f"(d[1]),"+f"(d[2]),"+f"(d[3]),"+f"(d[4]),"+f"(d[5]),"+f"(d[6]),"+f"(d[7]),"+f"(d[8]),"+f"(d[9]),"+f"(d[10]),"+f"(d[11]),"+f"(d[12]),"+f"(d[13]),"+f"(d[14]),"+f"(d[15]),"+f"(d[16]),"+f"(d[17]),"+f"(d[18]),"+f"(d[19]),"+f"(d[20]),"+f"(d[21]),"+f"(d[22]),"+f"(d[23]),"+f"(d[24]),"+f"(d[25]),"+f"(d[26]),"+f"(d[27]),"+f"(d[28]),"+f"(d[29]),"+f"(d[30]),"+f"(d[31])
        : "r"(alo), "r"(ahi), "r"(blo), "r"(bhi));
}
__device__ __forceinline__ void wg_ss64_z(float (&d)[32], uint32_t alo, uint32_t ahi, uint32_t blo, uint32_t bhi) {
    asm volatile("{\n.reg .b64 da, db;\nmov.b64 da, {%32, %33};\nmov.b64 db, {%34, %35};\n"
        "wgmma.mma_async.sync.aligned.m64n64k16.f32.bf16.bf16 {%0,%1,%2,%3,%4,%5,%6,%7,%8,%9,%10,%11,%12,%13,%14,%15,%16,%17,%18,%19,%20,%21,%22,%23,%24,%25,%26,%27,%28,%29,%30,%31}, da, db, 0, 1, 1, 0, 1;\n}\n"
        : "=f"(d[0]),"=f"(d[1]),"=f"(d[2]),"=f"(d[3]),"=f"(d[4]),"=f"(d[5]),"=f"(d[6]),"=f"(d[7]),"=f"(d[8]),"=f"(d[9]),"=f"(d[10]),"=f"(d[11]),"=f"(d[12]),"=f"(d[13]),"=f"(d[14]),"=f"(d[15]),"=f"(d[16]),"=f"(d[17]),"=f"(d[18]),"=f"(d[19]),"=f"(d[20]),"=f"(d[21]),"=f"(d[22]),"=f"(d[23]),"=f"(d[24]),"=f"(d[25]),"=f"(d[26]),"=f"(d[27]),"=f"(d[28]),"=f"(d[29]),"=f"(d[30]),"=f"(d[31])
        : "r"(alo), "r"(ahi), "r"(blo), "r"(bhi));
}
__device__ __forceinline__ void wg_ss64t(float (&d)[32], uint32_t alo, uint32_t ahi, uint32_t blo, uint32_t bhi) {
    asm volatile("{\n.reg .b64 da, db;\nmov.b64 da, {%32, %33};\nmov.b64 db, {%34, %35};\n"
        "wgmma.mma_async.sync.aligned.m64n64k16.f32.bf16.bf16 {%0,%1,%2,%3,%4,%5,%6,%7,%8,%9,%10,%11,%12,%13,%14,%15,%16,%17,%18,%19,%20,%21,%22,%23,%24,%25,%26,%27,%28,%29,%30,%31}, da, db, 1, 1, 1, 1, 1;\n}\n"
        : "+f"(d[0]),"+f"(d[1]),"+f"(d[2]),"+f"(d[3]),"+f"(d[4]),"+f"(d[5]),"+f"(d[6]),"+f"(d[7]),"+f"(d[8]),"+f"(d[9]),"+f"(d[10]),"+f"(d[11]),"+f"(d[12]),"+f"(d[13]),"+f"(d[14]),"+f"(d[15]),"+f"(d[16]),"+f"(d[17]),"+f"(d[18]),"+f"(d[19]),"+f"(d[20]),"+f"(d[21]),"+f"(d[22]),"+f"(d[23]),"+f"(d[24]),"+f"(d[25]),"+f"(d[26]),"+f"(d[27]),"+f"(d[28]),"+f"(d[29]),"+f"(d[30]),"+f"(d[31])
        : "r"(alo), "r"(ahi), "r"(blo), "r"(bhi));
}
__device__ __forceinline__ void wg_ss64t_z(float (&d)[32], uint32_t alo, uint32_t ahi, uint32_t blo, uint32_t bhi) {
    asm volatile("{\n.reg .b64 da, db;\nmov.b64 da, {%32, %33};\nmov.b64 db, {%34, %35};\n"
        "wgmma.mma_async.sync.aligned.m64n64k16.f32.bf16.bf16 {%0,%1,%2,%3,%4,%5,%6,%7,%8,%9,%10,%11,%12,%13,%14,%15,%16,%17,%18,%19,%20,%21,%22,%23,%24,%25,%26,%27,%28,%29,%30,%31}, da, db, 0, 1, 1, 1, 1;\n}\n"
        : "=f"(d[0]),"=f"(d[1]),"=f"(d[2]),"=f"(d[3]),"=f"(d[4]),"=f"(d[5]),"=f"(d[6]),"=f"(d[7]),"=f"(d[8]),"=f"(d[9]),"=f"(d[10]),"=f"(d[11]),"=f"(d[12]),"=f"(d[13]),"=f"(d[14]),"=f"(d[15]),"=f"(d[16]),"=f"(d[17]),"=f"(d[18]),"=f"(d[19]),"=f"(d[20]),"=f"(d[21]),"=f"(d[22]),"=f"(d[23]),"=f"(d[24]),"=f"(d[25]),"=f"(d[26]),"=f"(d[27]),"=f"(d[28]),"=f"(d[29]),"=f"(d[30]),"=f"(d[31])
        : "r"(alo), "r"(ahi), "r"(blo), "r"(bhi));
}
__device__ __forceinline__ void wg_ss8t(float (&d)[4], uint32_t alo, uint32_t ahi, uint32_t blo, uint32_t bhi) {
    asm volatile("{\n.reg .b64 da, db;\nmov.b64 da, {%4, %5};\nmov.b64 db, {%6, %7};\n"
        "wgmma.mma_async.sync.aligned.m64n8k16.f32.bf16.bf16 {%0,%1,%2,%3}, da, db, 1, 1, 1, 1, 0;\n}\n"
        : "+f"(d[0]),"+f"(d[1]),"+f"(d[2]),"+f"(d[3])
        : "r"(alo), "r"(ahi), "r"(blo), "r"(bhi));
}
__device__ __forceinline__ void wg_ss8t_z(float (&d)[4], uint32_t alo, uint32_t ahi, uint32_t blo, uint32_t bhi) {
    asm volatile("{\n.reg .b64 da, db;\nmov.b64 da, {%4, %5};\nmov.b64 db, {%6, %7};\n"
        "wgmma.mma_async.sync.aligned.m64n8k16.f32.bf16.bf16 {%0,%1,%2,%3}, da, db, 0, 1, 1, 1, 0;\n}\n"
        : "=f"(d[0]),"=f"(d[1]),"=f"(d[2]),"=f"(d[3])
        : "r"(alo), "r"(ahi), "r"(blo), "r"(bhi));
}

constexpr uint32_t DH128 = 64u | 0x40000000u;
constexpr uint32_t DH64 = 32u | 0x80000000u;
constexpr uint32_t LBO4K = (4096u >> 4) << 16, LBO8K = (8192u >> 4) << 16, LBO1 = 1u << 16;

template <bool SW64, bool FIRST> __device__ __forceinline__ void g1_issue(float (&acc)[64], uint32_t alo, uint32_t blo) {
    wg_fence();
#pragma unroll
    for (int k = 0; k < 4; k++) {
        if (FIRST && k == 0) wg_ss128_z(acc, alo, DH128, blo, SW64 ? DH64 : DH128);
        else wg_ss128(acc, alo + 2 * k, DH128, blo + (SW64 ? 64 * k : 128 * k), SW64 ? DH64 : DH128);
    }
    wg_commit();
}

template <int N> __device__ __forceinline__ void stash(uint32_t base, uint32_t sw, const uint32_t (&f)[N]) {
#pragma unroll
    for (int t = 0; t < N / 4; t++) stsm4(base + ((sw ^ (2 * t)) << 4), f[4 * t], f[4 * t + 1], f[4 * t + 2], f[4 * t + 3]);
}

template <int V0, int V1, int N> __device__ __forceinline__ void send_frag(const uint32_t (&f)[N], uint4* p, uint32_t tag) {
#pragma unroll
    for (int v = V0; v < V1; v++) st_pkt(p + (v & 3) * 32, (f[4 * v] & ~1u) | tag, f[4 * v + 1], f[4 * v + 2], f[4 * v + 3]);
}
template <int H0, int H1, int N> __device__ __forceinline__ void send_h(const uint32_t (&f)[N], uint4* p) {
#pragma unroll
    for (int h = H0; h < H1; h++) {
        p[4 * h] = make_uint4(f[8 * h], f[8 * h + 2], f[8 * h + 4], f[8 * h + 6]);
        p[4 * h + 64] = make_uint4(f[8 * h + 1], f[8 * h + 3], f[8 * h + 5], f[8 * h + 7]);
    }
}
template <int O, int N, int M> __device__ __forceinline__ void pack_sub(uint32_t (&f)[N], const float (&acc)[M]) {
#pragma unroll
    for (int i = 0; i < N; i++) f[i] = pack2(acc[O + 2 * i], acc[O + 2 * i + 1]);
}
template <int N> __device__ __forceinline__ void recv_issue(uint32_t (&q)[N], const uint4* p) {
#pragma unroll
    for (int v = 0; v < N / 4; v++) ld_pkt(p + v * 32, q[4 * v], q[4 * v + 1], q[4 * v + 2], q[4 * v + 3]);
}
template <int N> __device__ __forceinline__ void recv_check(uint32_t (&q)[N], const uint4* p, uint32_t tag) {
    uint32_t it = 0;
    while (true) {
        uint32_t bad = 0;
#pragma unroll
        for (int v = 0; v < N / 4; v++) bad |= q[4 * v] ^ tag;
        if (__all_sync(0xffffffffu, (bad & 1u) == 0) || ++it > SPIN_GLOBAL) break;
        recv_issue(q, p);
    }
}
__device__ __forceinline__ void accum(const uint32_t (&q)[16], float (&sum)[32]) {
#pragma unroll
    for (int i = 0; i < 16; i++) { sum[2 * i] += bf_lo(q[i]); sum[2 * i + 1] += bf_hi(q[i]); }
}

}

__global__ void __launch_bounds__(384, 1)
fused_kernel(const __grid_constant__ Maps maps, const __nv_bfloat16* __restrict__ xg, const __nv_bfloat16* __restrict__ gate_w,
             const char* __restrict__ pf_qkv, const char* __restrict__ pf_g, const char* __restrict__ pf_u,
             const char* __restrict__ pf_d, const char* __restrict__ pf_o, __nv_bfloat16* __restrict__ out) {
    extern __shared__ __align__(1024) uint8_t smem_raw[];
    const uint32_t sb = (uint32_t)__cvta_generic_to_shared(smem_raw);
    const int tid = threadIdx.x, lane = tid & 31;
    const int warp = __shfl_sync(0xffffffffu, tid >> 5, 0);
    const int j = (blockIdx.x >> 1) & 7;
    const int r = ((blockIdx.x >> 4) << 1) | (blockIdx.x & 1);
    const uint32_t rank = blockIdx.x & 1;

    if (warp == 0) { TSG(0, 30); TS(0, 0); }
    if (tid == 256) {
        for (int i = 0; i < 5; i++) { mbar_init(sb + B_FULL + 8 * i, 1); mbar_init(sb + B_EMPTY + 8 * i, MC ? 4 : 2); }
        for (int i = 0; i < 9; i++) mbar_init(sb + B_XFULL + 8 * i, 1);
        asm volatile("fence.mbarrier_init.release.cluster;" ::: "memory");
        mbar_expect(sb + B_XFULL, 16384);
        tma2(sb + OFF_X, &maps.x, 0, r * 128, sb + B_XFULL);
        TS2(0);
        mbar_expect(sb + B_FULL, 16384);
        tmaw3(sb + OFF_RING, &maps.gu, 224 * j, 0, 0, sb + B_FULL);
        TS2(1);
        mbar_expect(sb + B_FULL + 8, 16384);
        tmaw3(sb + OFF_RING + 16384, &maps.kv, 64 * j, 0, 1, sb + B_FULL + 8);
    } else if (tid == 288) {
        for (int i = 0; i < 5; i++) mbar_init(sb + B_HSENT + 8 * i, 8);
        mbar_init(sb + B_XFREE, 2); mbar_init(sb + B_XFREE + 8, 2);
        mbar_init(sb + B_GRDY, 1); mbar_init(sb + B_KVDONE, 8); mbar_init(sb + B_KVRDY, 2);
        asm volatile("fence.mbarrier_init.release.cluster;" ::: "memory");
    } else if (warp == 10 && lane < 12) {
        asm volatile("prefetch.tensormap [%0];" :: "l"(&maps.gu + lane) : "memory");
    }
    __syncthreads();

    if (warp >= 8) {
        asm volatile("setmaxnreg.dec.sync.aligned.u32 72;");
        if (warp == 8) {
            if (lane == 0) {
                int slot = MC ? 0 : 2, ph = 1;
                uint32_t full, dst;
                if (!MC) { mbar_expect(sb + B_XFULL + 8, 16384); tma2(sb + OFF_X + 16384, &maps.x, 64, r * 128, sb + B_XFULL + 8); }
#define P_BEGIN(S, BYTES) full = sb + B_FULL + 8 * slot; dst = sb + OFF_RING + slot * 16384; \
                mbar_wait(sb + B_EMPTY + 8 * slot, ph); TS2(S); mbar_expect(full, BYTES); if (!MC || (((S) ^ rank) & 1) == 0)
#define P_END() if (++slot == 5) { slot = 0; ph ^= 1; }
                for (int s = MC ? 0 : 2; s < 16; s++) {
                    P_BEGIN(s, 16384) {
                        if (s & 1) tmaw3(dst, &maps.kv, 64 * j, 32 * (s - 1), 1, full);
                        else tmaw3(dst, &maps.gu, 224 * j, 32 * s, 0, full);
                    }
                    const int xb = (s == 4) ? 3 : !(s & 1) ? 0 : (s < 5) ? (s + 1) / 2 : (s <= 11) ? (s + 3) / 2 : 0;
                    if (xb) { mbar_expect(sb + B_XFULL + 8 * xb, 16384); tma2(sb + OFF_X + xb * 16384, &maps.x, 64 * xb, r * 128, sb + B_XFULL + 8 * xb); }
                    P_END()
                }
                for (int s = 0; s < 8; s++) {
                    P_BEGIN(16 + s, 16384) {
                        tmaw3(dst, &maps.q64, 0, 64 * s, 2 * j, full);
                        tmaw3(dst + 8192, &maps.gu64, 224 * j + 192, 64 * s, 0, full);
                    }
                    P_END()
                }
                for (int s = 0; s < 16; s++) {
                    P_BEGIN(24 + s, 16384) tmaw3(dst, &maps.gu, 224 * j + 64 + 64 * (s >> 3), 64 * (s & 7), 0, full);
                    P_END()
                }
                const int p = j >> 1, ro = 224 * j, gp = 7 * (j ^ 1);
#pragma unroll 1
                for (int t = 0; t < 18; t++) {
                    const int q = (t >= 7 && t != 9 && t != 10), u = t < 7 ? t : t < 9 ? t - 7 : t < 11 ? t - 2 : t - 9;
                    const int cw = (j & 1) * 4 + ((p & 2) ^ (q ? 0 : 2)), cc = 64 * cw;
                    P_BEGIN(40 + t, 16384) {
                        if (u == 4) {
                            tmaw5(dst, &maps.wdph, cc, gp + 6, full); tmaw5(dst + 4096, &maps.wdph, cc + 64, gp + 6, full);
                            tmaw3(dst + 8192, &maps.wdh, 0, ro + 192, cw, full);
                        } else if (u == 2 || u == 3 || u >= 7) {
                            const CUtensorMap* m = u == 7 ? &maps.wop : &maps.wdp;
                            const int g = u == 7 ? 2 * (j ^ 1) : u == 8 ? gp + 4 : gp + 2 * (u - 2);
                            tmaw5(dst, m, cc, g, full); tmaw5(dst + 8192, m, cc + 64, g, full);
                        } else {
                            tmaw3(dst, u == 5 ? &maps.wow : &maps.wdw, 0, u == 5 ? 64 * j : u == 6 ? ro + 128 : ro + 64 * u, cw, full);
                        }
                    }
                    P_END()
                }
            }
        } else if (warp < 11) {
            const int hx = warp - 9;
            uint32_t epoch;
            asm volatile("ld.relaxed.gpu.global.u32 %0, [%1];" : "=r"(epoch) : "l"(g_epoch + blockIdx.x) : "memory");
            {
                const uint4* xr = (const uint4*)(xg + (size_t)(r * 128 + j * 16 + hx * 8) * kD) + lane;
                const uint4 wa = __ldg((const uint4*)gate_w + lane), wb = __ldg((const uint4*)gate_w + 32 + lane);
                const uint32_t tag = (epoch + 1) & 1;
                uint4* gp = g_gx + r * 32;
                if (lane < 2) st_pkt(gp + j * 4 + hx * 2 + lane, tag ^ 1, 0, 0, 0);
                float s[8];
#pragma unroll
                for (int i0 = 0; i0 < 8; i0 += 4) {
                    uint4 va[4], vb[4];
#pragma unroll
                    for (int i = 0; i < 4; i++) { va[i] = __ldg(xr + (i0 + i) * 64); vb[i] = __ldg(xr + (i0 + i) * 64 + 32); }
#pragma unroll
                    for (int i = 0; i < 4; i++) {
                        float t0 = bf_lo(va[i].x) * bf_lo(wa.x), t1 = bf_hi(va[i].x) * bf_hi(wa.x);
                        t0 = fmaf(bf_lo(va[i].y), bf_lo(wa.y), t0); t1 = fmaf(bf_hi(va[i].y), bf_hi(wa.y), t1);
                        t0 = fmaf(bf_lo(va[i].z), bf_lo(wa.z), t0); t1 = fmaf(bf_hi(va[i].z), bf_hi(wa.z), t1);
                        t0 = fmaf(bf_lo(va[i].w), bf_lo(wa.w), t0); t1 = fmaf(bf_hi(va[i].w), bf_hi(wa.w), t1);
                        t0 = fmaf(bf_lo(vb[i].x), bf_lo(wb.x), t0); t1 = fmaf(bf_hi(vb[i].x), bf_hi(wb.x), t1);
                        t0 = fmaf(bf_lo(vb[i].y), bf_lo(wb.y), t0); t1 = fmaf(bf_hi(vb[i].y), bf_hi(wb.y), t1);
                        t0 = fmaf(bf_lo(vb[i].z), bf_lo(wb.z), t0); t1 = fmaf(bf_hi(vb[i].z), bf_hi(wb.z), t1);
                        t0 = fmaf(bf_lo(vb[i].w), bf_lo(wb.w), t0); t1 = fmaf(bf_hi(vb[i].w), bf_hi(wb.w), t1);
                        s[i0 + i] = t0 + t1;
                    }
                }
#pragma unroll
                for (int i = 0; i < 8; i++) {
#pragma unroll
                    for (int o = 16; o; o >>= 1) s[i] += __shfl_xor_sync(0xffffffffu, s[i], o);
                    s[i] = 1.f / (1.f + __expf(-s[i]));
                }
                if (lane < 2) {
                    const float v0 = lane ? s[4] : s[0], v1 = lane ? s[5] : s[1], v2 = lane ? s[6] : s[2], v3 = lane ? s[7] : s[3];
                    st_pkt(gp + j * 4 + hx * 2 + lane, (__float_as_uint(v0) & ~1u) | tag, __float_as_uint(v1), __float_as_uint(v2), __float_as_uint(v3));
                }
                if (hx == 1) {
                    asm volatile("st.shared.u32 [%0], %1;" :: "r"(sb + OFF_ONES + lane * 4), "r"(0x3f803f80u) : "memory");
                    asm volatile("fence.proxy.async.shared::cta;" ::: "memory");
                }
                asm volatile("bar.sync 3, 96;" ::: "memory");
                if (hx == 0) {
                    uint32_t q[4];
                    recv_issue(q, gp + lane);
                    recv_check(q, gp + lane, tag);
                    asm volatile("st.shared.v4.u32 [%0], {%1,%2,%3,%4};" :: "r"(sb + OFF_G + lane * 16), "r"(q[0]), "r"(q[1]), "r"(q[2]), "r"(q[3]) : "memory");
                    if (lane == 0) {
                        asm volatile("st.shared.u32 [%0], %1;" :: "r"(sb + OFF_EPOCH), "r"(epoch) : "memory");
                        g_epoch[blockIdx.x] = epoch + 1;
                    }
                    __syncwarp();
                    if (lane == 0) mbar_arrive(sb + B_GRDY);
                } else {
                    if (r == 0) {
                        float4* zp = (float4*)(g_kvacc + (((epoch & 1) ^ 1) * 8 + j) * 4 * 272);
                        for (int i = lane; i < 272; i += 32) zp[i] = make_float4(0.f, 0.f, 0.f, 0.f);
                    }
                }
            }
            TS(2 + hx, 1);
#define PUBLISH_H(B) do { mbar_wait(sb + B_HSENT + 8 * (B), 0); if (lane == 0) { asm volatile("fence.proxy.async;" ::: "memory"); \
                asm volatile("st.release.gpu.global.u32 [%0], %1;" :: "l"(g_hflag + (r * 8 + j) * 8 + (B)), "r"(epoch + 1) : "memory"); } __syncwarp(); } while (0)
            if (hx == 1) {
#pragma unroll 1
                for (int b = 0; b < 4; b++) { PUBLISH_H(b); TS(3, 5 + b); }
            } else {
                const float* accp = g_kvacc + ((epoch & 1) * 8 + j) * 4 * 272;
                unsigned* cnt = g_kvcnt + j * 32;
                mbar_wait(sb + B_KVDONE, 0);
                TS(2, 5);
                if (lane == 0) asm volatile("red.release.gpu.global.add.u32 [%0], 1;" :: "l"(cnt) : "memory");
                __syncwarp();
                TS(2, 2);
                {
                    const unsigned target = 16u * (epoch + 1);
                    uint32_t it = 0, v;
                    do {
                        asm volatile("ld.acquire.gpu.global.u32 %0, [%1];" : "=r"(v) : "l"(cnt) : "memory");
                    } while ((int)(v - target) < 0 && ++it < SPIN_GLOBAL);
                }
                TS(2, 3);
#pragma unroll
                for (int h = 0; h < 4; h++) {
                    const float4 d0 = __ldcg((const float4*)(accp + h * 272) + lane);
                    const float4 d1 = __ldcg((const float4*)(accp + h * 272 + 128) + lane);
                    const float2 z0 = __ldcg((const float2*)(accp + h * 272 + 256) + (lane & 3));
                    const float2 z1 = __ldcg((const float2*)(accp + h * 272 + 264) + (lane & 3));
                    asm volatile("st.shared.v4.u32 [%0], {%1,%2,%3,%4};" :: "r"(sb + OFF_KVF + h * 512 + lane * 16),
                                 "r"(pack2(d0.x, d0.y)), "r"(pack2(d1.x, d1.y)), "r"(pack2(d0.z, d0.w)), "r"(pack2(d1.z, d1.w)) : "memory");
                    if (lane < 4) asm volatile("st.shared.v2.u32 [%0], {%1,%2};" :: "r"(sb + OFF_ZF + h * 32 + lane * 8), "r"(pack2(z0.x, z0.y)), "r"(pack2(z1.x, z1.y)) : "memory");
                }
                __syncwarp();
                if (lane == 0) mbar_arrive(sb + B_KVRDY);
                TS(2, 4);
                PUBLISH_H(4);
                TS(3, 9);
            }
        } else {
            uint32_t epoch;
            asm volatile("ld.relaxed.gpu.global.u32 %0, [%1];" : "=r"(epoch) : "l"(g_epoch + blockIdx.x) : "memory");
            mbar_wait(sb + B_XFULL, 0);
            const int b = blockIdx.x;
            if (lane == 0) l2_prefetch(pf_qkv + b * 12288, 12288);
            if (lane == 1) l2_prefetch(pf_g + b * 14336, 14336);
            if (lane == 2) l2_prefetch(pf_u + b * 14336, 14336);
            asm volatile("bar.sync 3, 96;" :: "r"(epoch) : "memory");
            {
                const int p = j >> 1;
                uint4* mb = g_part + (size_t)(r * 2 + (j & 1)) * 16384 + p * 1024 + lane;
#pragma unroll 1
                for (int d = 1; d < 4; d++) {
#pragma unroll 8
                    for (int i = 0; i < 32; i++) st_pkt(mb + ((p ^ d) << 12) + i * 32, epoch & 1, 0, 0, 0);
                }
                __syncwarp();
                if (lane == 0) mbar_arrive(sb + B_KVRDY);
            }
            mbar_wait(sb + B_XFULL + 8 * 7, 0);
            if (lane == 0) l2_prefetch(pf_d + b * 14336, 14336);
            if (lane == 1) l2_prefetch(pf_o + b * 4096, 4096);
            if (lane == 0) {
                const uint32_t want = epoch + 1;
                const unsigned* fl = g_hflag + (r * 8 + (j ^ 1)) * 8;
                const int hrow = (r * 8 + (j ^ 1)) * 5 * 128;
#pragma unroll 1
                for (int i = 0; i < 5; i++) {
                    const int blk = i == 1 ? 2 : i == 2 ? 1 : i;
                    const int piece = i == 4 ? 8 : i + 2;
                    uint32_t it = 0, v;
                    do {
                        asm volatile("ld.acquire.gpu.global.u32 %0, [%1];" : "=r"(v) : "l"(fl + blk) : "memory");
                    } while (v != want && ++it < SPIN_GLOBAL);
                    if (i == 0) mbar_wait(sb + B_XFREE, 0);
                    if (i == 2) mbar_wait(sb + B_XFREE + 8, 0);
                    TS2(140 + i);
                    mbar_expect(sb + B_XFULL + 8 * piece, i == 2 ? 8192 : 16384);
                    tma2(sb + OFF_X + piece * 16384, i == 2 ? &maps.hxh : &maps.hx, 0, hrow + blk * 128, sb + B_XFULL + 8 * piece);
                }
            }
        }
    } else {
        asm volatile("setmaxnreg.inc.sync.aligned.u32 216;");
        const int wg = warp >> 2;
        const bool elect = (tid & 127) == 0;
        const uint32_t xlo = ((sb + OFF_X + wg * 8192) >> 4) | LBO1;
        const uint32_t ringlo = (sb + OFF_RING) >> 4;
        auto release = [&](int s) {
            if (elect) {
                mbar_arrive(sb + B_EMPTY + 8 * s);
            }
        };
#define S_WAIT(S) do { mbar_wait(sb + B_FULL + 8 * ((S) % 5), ((S) / 5) & 1); if (PROF && tid == 0) TS2(64 + (S)); } while (0)
#define S_B(S) (ringlo + ((S) % 5) * 1024)
#define G1(S, acc, SW, KB) do { S_WAIT(S); g1_issue<SW, (KB) == 0>(acc, xlo + (KB) * 1024, S_B(S) | (SW ? LBO4K : LBO8K)); } while (0)
#define RET(S) do { wg_wait<1>(); if ((S) - 1 < 53) release(((S) - 1) % 5); } while (0)
#define SCHED() mbar_wait(sb + B_XFULL, 0)
#define A2_SYNC() do { asm volatile("fence.proxy.async.shared::cta;" ::: "memory"); asm volatile("bar.sync %0, 128;" :: "r"(wg + 1) : "memory"); } while (0)
#define H_EPI(acc, F, I0, I1, OG, OU) _Pragma("unroll") for (int i = (I0); i < (I1); i++) \
            F[i] = hmul2(pack2(acc[(OG) + 2 * i] * acc[(OU) + 2 * i], acc[(OG) + 2 * i + 1] * acc[(OU) + 2 * i + 1]), (i & 1) ? m_hi : m_lo)
#define PHI(acc, F, I0, I1) _Pragma("unroll") for (int i = (I0); i < (I1); i++) F[i] = phi2(acc[2 * i], acc[2 * i + 1])

        float a0[64], b0[64], a1[64], a2_[64], a3[64];
        mbar_wait(sb + B_XFULL, 0);
        G1(0, a0, false, 0);
        if ((warp & 3) == 0) TS(wg, 1);
        G1(1, b0, false, 0); RET(1);
#define C0(KB) mbar_wait(sb + B_XFULL + 8 * (KB), 0); if (PROF && tid == 0) TS2(128 + (KB)); \
        G1(2 * (KB), a0, false, KB); RET(2 * (KB)); G1(2 * (KB) + 1, b0, false, KB); RET(2 * (KB) + 1)
        C0(1); C0(2); C0(3); C0(4); C0(5); C0(6);
        mbar_wait(sb + B_XFULL + 8 * 7, 0);
        G1(14, a0, false, 7); RET(14);
        G1(15, b0, false, 7);
        mbar_wait(sb + B_GRDY, 0);
        float g_lo, g_hi;
        uint32_t tag;
        {
            const uint32_t ga = sb + OFF_G + (warp * 16 + (lane >> 2)) * 4;
            asm volatile("ld.shared.f32 %0, [%1];" : "=f"(g_lo) : "r"(ga) : "memory");
            asm volatile("ld.shared.f32 %0, [%1];" : "=f"(g_hi) : "r"(ga + 32) : "memory");
            asm volatile("ld.shared.u32 %0, [%1];" : "=r"(tag) : "r"(sb + OFF_EPOCH) : "memory");
        }
        float* const kvp = g_kvacc + (((tag & 1) * 8 + j) * 4 + (warp & 3)) * 272;
        tag = (tag + 1) & 1;
        const uint32_t m_lo = pack2(1.f - g_lo, 1.f - g_lo), m_hi = pack2(1.f - g_hi, 1.f - g_hi);
        const uint32_t lrow = ((lane & 7) + 8 * ((lane >> 3) & 1)) * 128;
        const uint32_t srow = (warp & 3) * 2048 + lrow;
        const uint32_t ssw = (lane >> 4) ^ (lane & 7);
        uint4* const hsend = g_hx + (size_t)((r * 8 + j) * 5) * 1024 + warp * 128 + (lane >> 2) * 8 + (lane & 3);
#define SENT_H(B) do { __syncwarp(); if (lane == 0) mbar_arrive(sb + B_HSENT + 8 * (B)); } while (0)
        RET(15);
        pin(a0);
        if ((warp & 3) == 0) TS(wg, 2);
        uint32_t fh0[16], fh1[16], fh2[16], fh3[8], fo[16];
        H_EPI(a0, fh0, 0, 16, 0, 32);

        float kv[32], zs[4];
        {
            uint32_t pk[16], pv[16];
            const uint32_t stg = sb + OFF_STG + wg * 8192, stl = stg + (warp & 1) * 2048 + lrow;
            const uint32_t klo = (stg >> 4) | LBO1, vlo = klo + 256, olo = (sb + OFF_ONES) >> 4;
            G1(16, a1, true, 0); RET(16);
            pin(b0);
            G1(17, a1, true, 1); SCHED(); PHI(b0, pk, 0, 6); RET(17);
            G1(18, a1, true, 2); SCHED(); PHI(b0, pk, 6, 12); RET(18);
            G1(19, a1, true, 3); SCHED(); PHI(b0, pk, 12, 16); pack_sub<32>(pv, b0);
            if (!(warp & 2)) { stash<16>(stl, ssw, pk); stash<16>(stl + 4096, ssw, pv); }
            RET(19);
            G1(20, a1, true, 4); send_h<0, 1>(fh0, hsend); RET(20);
            A2_SYNC();
            wg_fence();
            wg_ss64t_z(kv, vlo, DH128, klo, DH128); wg_ss64t(kv, vlo + 128, DH128, klo + 128, DH128);
            wg_ss8t_z(zs, klo, DH128, olo, 0); wg_ss8t(zs, klo + 128, DH128, olo, 0);
            wg_commit();
            G1(21, a1, true, 5); send_h<1, 2>(fh0, hsend); SENT_H(0); RET(21);
            G1(22, a1, true, 6);
            if (warp & 2) { stash<16>(stl, ssw, pk); stash<16>(stl + 4096, ssw, pv); }
            RET(22);
            G1(23, a1, true, 7); RET(23);
            if ((warp & 3) == 0) TS(wg, 3);
            A2_SYNC();
            wg_fence();
            wg_ss64t(kv, vlo, DH128, klo, DH128); wg_ss64t(kv, vlo + 128, DH128, klo + 128, DH128);
            wg_ss8t(zs, klo, DH128, olo, 0); wg_ss8t(zs, klo + 128, DH128, olo, 0);
            wg_commit();
        }

        G1(24, a2_, false, 0); RET(24);
        pin(kv); pin(zs); pin(a1);
        G1(25, a2_, false, 1);
#define KV_RED(W) do { asm volatile("red.global.add.v4.f32 [%0], {%1,%2,%3,%4};" :: "l"(kvp + lane * 4), "f"(kv[8 * W]), "f"(kv[8 * W + 1]), "f"(kv[8 * W + 2]), "f"(kv[8 * W + 3]) : "memory"); \
                       asm volatile("red.global.add.v4.f32 [%0], {%1,%2,%3,%4};" :: "l"(kvp + 128 + lane * 4), "f"(kv[8 * W + 4]), "f"(kv[8 * W + 5]), "f"(kv[8 * W + 6]), "f"(kv[8 * W + 7]) : "memory"); } while (0)
        if ((warp & 3) == 0) KV_RED(0); else if ((warp & 3) == 1) KV_RED(1); else if ((warp & 3) == 2) KV_RED(2); else KV_RED(3);
        if ((lane & 3) == 0) {
            asm volatile("red.global.add.f32 [%0], %1;" :: "l"(kvp + 256 + (lane >> 2)), "f"(zs[0]) : "memory");
            asm volatile("red.global.add.f32 [%0], %1;" :: "l"(kvp + 264 + (lane >> 2)), "f"(zs[2]) : "memory");
        }
        __syncwarp();
        if (lane == 0) mbar_arrive(sb + B_KVDONE);
        RET(25);
        G1(26, a2_, false, 2); SCHED(); H_EPI(a1, fh3, 0, 8, 32, 48); send_h<0, 1>(fh3, hsend + 1024); SENT_H(1); RET(26);
        G1(27, a2_, false, 3); SCHED(); PHI(a1, fo, 0, 4); RET(27);
        G1(28, a2_, false, 4); SCHED(); PHI(a1, fo, 4, 8); RET(28);
        G1(29, a2_, false, 5); SCHED(); PHI(a1, fo, 8, 12); RET(29);
        G1(30, a2_, false, 6); SCHED(); PHI(a1, fo, 12, 16); RET(30);
        G1(31, a2_, false, 7); RET(31);
        if ((warp & 3) == 0) TS(wg, 4);

        const uint32_t a2 = sb + OFF_X + wg * 8192 + srow;
#define O_HEAD(h) do { uint32_t b0_, b1_, b2_, b3_, z0_, z1_; float n0[4], n1[4], dn[4]; \
            asm volatile("ld.shared.v4.u32 {%0,%1,%2,%3}, [%4];" : "=r"(b0_), "=r"(b1_), "=r"(b2_), "=r"(b3_) : "r"(sb + OFF_KVF + h * 512 + lane * 16) : "memory"); \
            asm volatile("ld.shared.v2.u32 {%0,%1}, [%2];" : "=r"(z0_), "=r"(z1_) : "r"(sb + OFF_ZF + h * 32 + (lane & 3) * 8) : "memory"); \
            mma16816(dn, fo[4 * h], fo[4 * h + 1], fo[4 * h + 2], fo[4 * h + 3], z0_, z1_); \
            mma16816(n0, fo[4 * h], fo[4 * h + 1], fo[4 * h + 2], fo[4 * h + 3], b0_, b1_); \
            mma16816(n1, fo[4 * h], fo[4 * h + 1], fo[4 * h + 2], fo[4 * h + 3], b2_, b3_); \
            const float s_lo = __fdividef(g_lo, dn[0] + 1e-6f), s_hi = __fdividef(g_hi, dn[2] + 1e-6f); \
            const uint32_t sl_ = pack2(s_lo, s_lo), sh_ = pack2(s_hi, s_hi); \
            fo[4 * h] = hmul2(pack2(n0[0], n0[1]), sl_); fo[4 * h + 1] = hmul2(pack2(n0[2], n0[3]), sh_); \
            fo[4 * h + 2] = hmul2(pack2(n1[0], n1[1]), sl_); fo[4 * h + 3] = hmul2(pack2(n1[2], n1[3]), sh_); } while (0)
        G1(32, a3, false, 0); RET(32);
        pin(a2_);
        G1(33, a3, false, 1); SCHED(); H_EPI(a2_, fh1, 0, 16, 0, 32); send_h<0, 1>(fh1, hsend + 2 * 1024); RET(33);
        G1(34, a3, false, 2); send_h<1, 2>(fh1, hsend + 2 * 1024); SENT_H(2); stash<16>(a2, ssw, fh0); RET(34);
        G1(35, a3, false, 3); stash<16>(a2 + 16384, ssw, fh1); RET(35);
        G1(36, a3, false, 4);
        if ((warp & 3) == 0) TS(wg, 5);
        mbar_wait(sb + B_KVRDY, 0);
        if ((warp & 3) == 0) TS(wg, 6);
        O_HEAD(0); O_HEAD(1);
        send_h<0, 1>(fo, hsend + 3 * 1024);
        RET(36);
        if (elect) mbar_arrive(sb + B_XFREE);
        G1(37, a3, false, 5); SCHED();
        O_HEAD(2); O_HEAD(3);
        send_h<1, 2>(fo, hsend + 3 * 1024); SENT_H(3);
        RET(37);
        G1(38, a3, false, 6); stash<8>(a2 + 4 * 16384, ssw ^ 4, fh3); RET(38);
        if (elect) mbar_arrive(sb + B_XFREE + 8);
        G1(39, a3, false, 7); RET(39);
        A2_SYNC();
        if ((warp & 3) == 0) TS(wg, 7);

#define G2_PIECE(U) ((U) < 5 ? (U) : (U) == 5 ? 6 : (U) == 6 ? 7 : (U) == 7 ? 5 : 8)
#define G2(S, acc, U) do { S_WAIT(S); wg_fence(); _Pragma("unroll") for (int k = 0; k < 4; k++) { \
            if ((U) == 0 && k == 0) wg_ss128_z(acc, xlo, DH128, S_B(S) | LBO8K, DH128); \
            else if ((U) == 4) wg_ss128(acc, xlo + 4096 + 2 * k, DH128, (S_B(S) | LBO4K) + (k >> 1) * 512 + (k & 1) * 128, DH128); \
            else wg_ss128(acc, xlo + G2_PIECE(U) * 1024 + 2 * k, DH128, (S_B(S) | LBO8K) + 128 * k, DH128); } wg_commit(); } while (0)
#define H_WAIT(P) do { mbar_wait(sb + B_XFULL + 8 * (P), (P) < 8); if (PROF && tid == 0) TS2(150 + (P)); } while (0)
        const int p = j >> 1;
        uint4* const pbase = g_part + (size_t)(r * 2 + (j & 1)) * 16384 + warp * 128 + lane;
        const int pw = (p & 2) ^ 2;
        auto other = [&](int d) { return d == 3 ? p ^ 1 : pw + d - 1; };
        auto sendp = [&](int d) { return pbase + ((other(d) * 4 + p) << 10); };
        auto recvp = [&](int d) { return pbase + ((p * 4 + other(d)) << 10); };

        float p1[64], p2[64];
        G2(40, p1, 0); RET(40);
        pin(a3);
        G2(41, p1, 1); SCHED(); H_EPI(a3, fh2, 0, 16, 0, 32); send_h<0, 2>(fh2, hsend + 4 * 1024); SENT_H(4); RET(41);
        H_WAIT(2); G2(42, p1, 2); stash<16>(a2 + 6 * 16384, ssw, fo); RET(42);
        H_WAIT(3); G2(43, p1, 3); stash<16>(a2 + 7 * 16384, ssw, fh2); RET(43);
        H_WAIT(4); G2(44, p1, 4); RET(44);
        A2_SYNC();
        G2(45, p1, 5); RET(45);
        G2(46, p1, 6); RET(46);
        G2(47, p2, 0); RET(47);
        G2(48, p2, 1); RET(48);
        H_WAIT(5); G2(49, p1, 7); RET(49);
        H_WAIT(8); G2(50, p1, 8); RET(50);
        if ((warp & 3) == 0) TS(wg, 8);
        uint32_t sa[16], sc[16], qa[16], qb[16];
        G2(51, p2, 2); RET(51);
        pin(p1);
        G2(52, p2, 3); SCHED(); pack_sub<0>(sa, p1); send_frag<0, 2>(sa, sendp(1), tag); RET(52);
        G2(53, p2, 4); SCHED(); pack_sub<32>(sc, p1); send_frag<2, 4>(sa, sendp(1), tag); RET(53);
        G2(54, p2, 5); send_frag<0, 2>(sc, sendp(2), tag); RET(54);
        G2(55, p2, 6); send_frag<2, 4>(sc, sendp(2), tag); RET(55);
        G2(56, p2, 7); RET(56);
        G2(57, p2, 8);
        recv_issue(qa, recvp(1)); recv_issue(qb, recvp(2));
        if ((warp & 3) == 0) TS(wg, 9);
        wg_wait<0>();
        pin(p2);
        if ((warp & 3) == 0) TS(wg, 11);
        float sum[32];
        if (p & 1) pack_sub<0>(sa, p2); else pack_sub<32>(sa, p2);
        send_frag<0, 4>(sa, sendp(3), tag);
        recv_issue(sc, recvp(3));
#pragma unroll
        for (int i = 0; i < 32; i++) sum[i] = (p & 1) ? p2[32 + i] : p2[i];
        recv_check(qa, recvp(1), tag); accum(qa, sum);
        recv_check(qb, recvp(2), tag); accum(qb, sum);
        if ((warp & 3) == 0) TS(wg, 12);
        recv_check(sc, recvp(3), tag); accum(sc, sum);
        if ((warp & 3) == 0) TS(wg, 13);
        {
            uint32_t f[16];
            pack_sub<0>(f, sum);
            const uint32_t slab = sb + OFF_X + wg * 8192;
            stash<16>(slab + srow, ssw, f);
            __syncwarp();
            __nv_bfloat16* op = out + (size_t)(r * 128 + warp * 16 + (lane >> 3)) * kD + (j & 1) * 256 + p * 64 + (lane & 7) * 8;
#pragma unroll
            for (int i = 0; i < 4; i++) {
                const int row = i * 4 + (lane >> 3);
                uint4 v;
                asm volatile("ld.shared.v4.u32 {%0,%1,%2,%3}, [%4];" : "=r"(v.x), "=r"(v.y), "=r"(v.z), "=r"(v.w)
                             : "r"(slab + ((warp & 3) * 16 + row) * 128 + (((lane & 7) ^ (row & 7)) << 4)) : "memory");
                *(uint4*)(op + i * 4 * kD) = v;
            }
        }
        if ((warp & 3) == 0) { TS(wg, 14); TSG(wg, 31); }
    }
}

typedef CUresult (*EncodeFn)(CUtensorMap*, CUtensorMapDataType, cuuint32_t, void*, const cuuint64_t*, const cuuint64_t*, const cuuint32_t*,
                             const cuuint32_t*, CUtensorMapInterleave, CUtensorMapSwizzle, CUtensorMapL2promotion, CUtensorMapFloatOOBfill);

static void encode(EncodeFn fn, CUtensorMap* m, int rank, const void* base, const cuuint64_t (&gd)[5], const cuuint64_t (&gs)[4],
                   const cuuint32_t (&bd)[5], CUtensorMapSwizzle sw) {
    cuuint32_t es[5] = {1, 1, 1, 1, 1};
    fn(m, CU_TENSOR_MAP_DATA_TYPE_BFLOAT16, rank, const_cast<void*>(base), gd, gs, bd, es, CU_TENSOR_MAP_INTERLEAVE_NONE, sw,
       CU_TENSOR_MAP_L2_PROMOTION_L2_128B, CU_TENSOR_MAP_FLOAT_OOB_FILL_NONE);
}

extern "C" void kernel_launch(void* const* d_in, const int* in_sizes, int n_in, void* d_out, int out_size) {
    const char* x = (const char*)d_in[0];
    const char* wqkv = (const char*)d_in[1];
    const char* wo = (const char*)d_in[2];
    const char* wg = (const char*)d_in[4];
    const char* wu = (const char*)d_in[5];
    const char* wd = (const char*)d_in[6];
    void* fnp = nullptr;
    cudaDriverEntryPointQueryResult qr;
    cudaGetDriverEntryPoint("cuTensorMapEncodeTiled", &fnp, cudaEnableDefault, &qr);
    EncodeFn fn = (EncodeFn)fnp;
    Maps maps;
    const char* lo = wg < wu ? wg : wu;
    const uint64_t diff = wg < wu ? (uint64_t)(wu - wg) : (uint64_t)(wg - wu);
    const CUtensorMapSwizzle S128 = CU_TENSOR_MAP_SWIZZLE_128B, S64 = CU_TENSOR_MAP_SWIZZLE_64B;
    encode(fn, &maps.x, 2, x, {512, 2048, 1, 1}, {1024, 0, 0}, {64, 128, 1, 1}, S128);
    encode(fn, &maps.gu, 3, lo, {1792, 512, 2, 1}, {3584, diff, 0}, {64, 64, 2, 1}, S128);
    encode(fn, &maps.kv, 3, wqkv, {512, 512, 3, 1}, {3072, 1024, 0}, {64, 64, 2, 1}, S128);
    encode(fn, &maps.q64, 3, wqkv, {32, 512, 48, 1}, {3072, 64, 0}, {32, 64, 2, 1}, S64);
    encode(fn, &maps.gu64, 3, lo, {1792, 512, 2, 1}, {3584, diff, 0}, {32, 64, 2, 1}, S64);
    encode(fn, &maps.wdw, 3, wd, {64, 1792, 8, 1}, {1024, 128, 0}, {64, 64, 2, 1}, S128);
    encode(fn, &maps.wdh, 3, wd, {64, 1792, 8}, {1024, 128}, {64, 32, 2}, S128);
    encode(fn, &maps.wow, 3, wo, {64, 512, 8}, {1024, 128}, {64, 64, 2}, S128);
    encode(fn, &maps.wdp, 5, wd, {512, 2, 4, 4, 56}, {1024, 8192, 2048, 32768}, {64, 2, 4, 4, 2}, S128);
    encode(fn, &maps.wdph, 5, wd, {512, 2, 4, 4, 56}, {1024, 8192, 2048, 32768}, {64, 2, 4, 4, 1}, S128);
    encode(fn, &maps.wop, 5, wo, {512, 2, 4, 4, 16}, {1024, 8192, 2048, 32768}, {64, 2, 4, 4, 2}, S128);
    void* hx = nullptr;
    cudaGetSymbolAddress(&hx, g_hx);
    encode(fn, &maps.hx, 2, hx, {64, 16 * 8 * 5 * 128}, {128}, {64, 128}, S128);
    encode(fn, &maps.hxh, 2, hx, {64, 16 * 8 * 5 * 128}, {128}, {32, 128}, S128);
    cudaFuncSetAttribute(fused_kernel, cudaFuncAttributeMaxDynamicSharedMemorySize, SMEM_BYTES);
    cudaLaunchConfig_t cfg = {};
    cfg.gridDim = dim3(128);
    cfg.blockDim = dim3(384);
    cfg.dynamicSmemBytes = SMEM_BYTES;
    cfg.stream = cudaStreamPerThread;
    cudaLaunchAttribute at[1];
    at[0].id = cudaLaunchAttributeClusterDimension;
    at[0].val.clusterDim.x = 2; at[0].val.clusterDim.y = 1; at[0].val.clusterDim.z = 1;
    cfg.attrs = at;
    cfg.numAttrs = MC ? 1 : 0;
    cudaLaunchKernelEx(&cfg, fused_kernel, maps, (const __nv_bfloat16*)d_in[0], (const __nv_bfloat16*)d_in[7], wqkv, wg, wu, wd, wo, (__nv_bfloat16*)d_out);
}
```

```cpp
#include <cuda_runtime.h>
#include <cuda.h>
#include <cuda_bf16.h>
#include <stdint.h>

#define MC 0
#define PFMODE 2
#define PF_AFTER 0
#define PROF 0

namespace {

constexpr int kD = 512;
constexpr uint32_t OFF_X = 0, OFF_STG = 131072, OFF_RING = 147456, OFF_MISC = 229376;
constexpr uint32_t B_FULL = OFF_MISC, B_EMPTY = OFF_MISC + 40, B_XFULL = OFF_MISC + 80;
constexpr uint32_t B_GRDY = OFF_MISC + 152, B_KVDONE = OFF_MISC + 160, B_KVRDY = OFF_MISC + 168;
constexpr uint32_t B_HSENT = OFF_MISC + 176, B_XFREE = OFF_MISC + 216;
constexpr uint32_t OFF_EPOCH = OFF_MISC + 240, OFF_G = OFF_MISC + 256;
constexpr uint32_t OFF_KVF = OFF_MISC + 768, OFF_ZF = OFF_KVF + 2048;
constexpr uint32_t OFF_ONES = OFF_ZF + 128;
constexpr uint32_t SMEM_BYTES = OFF_ONES + 128;
constexpr uint32_t SPIN_GLOBAL = 1u << 14;

struct alignas(64) Maps { CUtensorMap x, gu, kv, q64, gu64, wdw, wow, wdp, wdph, wop, hx, hx2; };

}

__device__ uint4 g_part[16 * 2 * 4 * 4 * 1024];
__device__ uint4 g_hx[16 * 4 * 9 * 1024];
__device__ unsigned g_hflag[128 * 8];
__device__ uint4 g_gx[16 * 32];
__device__ float g_kvacc[2 * 8 * 4 * 272];
__device__ unsigned g_kvcnt[8 * 32];
__device__ unsigned g_epoch[128];
#define TS(role, idx)
#define TS2(idx)
#define TSG(role, idx)

namespace {

__device__ __forceinline__ void mbar_init(uint32_t bar, uint32_t cnt) { asm volatile("mbarrier.init.shared::cta.b64 [%0], %1;" :: "r"(bar), "r"(cnt) : "memory"); }
__device__ __forceinline__ void mbar_expect(uint32_t bar, uint32_t bytes) { asm volatile("mbarrier.arrive.expect_tx.shared::cta.b64 _, [%0], %1;" :: "r"(bar), "r"(bytes) : "memory"); }
__device__ __forceinline__ void mbar_arrive(uint32_t bar) { asm volatile("mbarrier.arrive.shared::cta.b64 _, [%0];" :: "r"(bar) : "memory"); }
__device__ __forceinline__ void mbar_arrive_cta(uint32_t bar, uint32_t cta) {
    asm volatile("{\n.reg .b32 ra;\nmapa.shared::cluster.u32 ra, %0, %1;\nmbarrier.arrive.shared::cluster.b64 _, [ra];\n}" :: "r"(bar), "r"(cta) : "memory");
}
__device__ __forceinline__ void mbar_wait(uint32_t bar, uint32_t parity) {
    asm volatile("{\n.reg .pred p;\n.reg .u32 c;\n"
                 "mbarrier.try_wait.parity.shared::cta.b64 p, [%0], %1;\n@p bra DONE;\n"
                 "mov.u32 c, 0;\nLAB_WAIT:\nmbarrier.try_wait.parity.shared::cta.b64 p, [%0], %1;\n@p bra DONE;\n"
                 "add.u32 c, c, 1;\nsetp.lt.u32 p, c, 65536;\n@p bra LAB_WAIT;\nDONE:\n}" :: "r"(bar), "r"(parity) : "memory");
}
__device__ __forceinline__ void tma2(uint32_t dst, const CUtensorMap* m, int c0, int c1, uint32_t bar) {
    asm volatile("cp.async.bulk.tensor.2d.shared::cluster.global.mbarrier::complete_tx::bytes [%0], [%1, {%3, %4}], [%2];"
        :: "r"(dst), "l"(m), "r"(bar), "r"(c0), "r"(c1) : "memory");
}
__device__ __forceinline__ void tmaw2(uint32_t dst, const CUtensorMap* m, int c0, int c1, uint32_t bar) {
    tma2(dst, m, c0, c1, bar);
}
__device__ __forceinline__ void tmaw3(uint32_t dst, const CUtensorMap* m, int c0, int c1, int c2, uint32_t bar) {
    asm volatile("cp.async.bulk.tensor.3d.shared::cluster.global.mbarrier::complete_tx::bytes [%0], [%1, {%3, %4, %5}], [%2];"
        :: "r"(dst), "l"(m), "r"(bar), "r"(c0), "r"(c1), "r"(c2) : "memory");
}
__device__ __forceinline__ void tmaw5(uint32_t dst, const CUtensorMap* m, int c0, int c4, uint32_t bar) {
    asm volatile("cp.async.bulk.tensor.5d.shared::cluster.global.mbarrier::complete_tx::bytes [%0], [%1, {%3, %5, %5, %5, %4}], [%2];"
        :: "r"(dst), "l"(m), "r"(bar), "r"(c0), "r"(c4), "r"(0) : "memory");
}
__device__ __forceinline__ void l2_prefetch(const void* p, uint32_t bytes) { asm volatile("cp.async.bulk.prefetch.L2.global [%0], %1;" :: "l"(p), "r"(bytes) : "memory"); }
__device__ __forceinline__ void wg_fence() { asm volatile("wgmma.fence.sync.aligned;" ::: "memory"); }
__device__ __forceinline__ void wg_commit() { asm volatile("wgmma.commit_group.sync.aligned;" ::: "memory"); }
template <int N> __device__ __forceinline__ void wg_wait() { asm volatile("wgmma.wait_group.sync.aligned %0;" :: "n"(N) : "memory"); }
template <int N> __device__ __forceinline__ void pin(float (&d)[N]) {
#pragma unroll
    for (int i = 0; i < N; i++) asm volatile("" : "+f"(d[i]) :: "memory");
}
__device__ __forceinline__ uint32_t pack2(float lo, float hi) { uint32_t r; asm("cvt.rn.bf16x2.f32 %0, %1, %2;" : "=r"(r) : "f"(hi), "f"(lo)); return r; }
__device__ __forceinline__ uint32_t hmul2(uint32_t a, uint32_t b) { uint32_t r; asm("mul.bf16x2 %0, %1, %2;" : "=r"(r) : "r"(a), "r"(b)); return r; }
__device__ __forceinline__ uint32_t phi2(float t0, float t1) {
    float e0, e1;
    asm("ex2.approx.ftz.f32 %0, %1;" : "=f"(e0) : "f"(t0 * 1.4426950408889634f));
    asm("ex2.approx.ftz.f32 %0, %1;" : "=f"(e1) : "f"(t1 * 1.4426950408889634f));
    uint32_t e = pack2(e0, e1), t = pack2(t0, t1), r;
    asm("min.bf16x2 %0, %0, %1;" : "+r"(e) : "r"(0x3f803f80u));
    asm("max.bf16x2 %0, %0, %1;" : "+r"(t) : "r"(0x35863586u));
    asm("add.bf16x2 %0, %1, %2;" : "=r"(r) : "r"(e), "r"(t));
    return r;
}
__device__ __forceinline__ void stsm4(uint32_t a, uint32_t r0, uint32_t r1, uint32_t r2, uint32_t r3) {
    asm volatile("stmatrix.sync.aligned.m8n8.x4.shared.b16 [%0], {%1,%2,%3,%4};" :: "r"(a), "r"(r0), "r"(r1), "r"(r2), "r"(r3) : "memory");
}
__device__ __forceinline__ void mma16816(float (&c)[4], uint32_t a0, uint32_t a1, uint32_t a2, uint32_t a3, uint32_t b0, uint32_t b1) {
    asm volatile("mma.sync.aligned.m16n8k16.row.col.f32.bf16.bf16.f32 {%0,%1,%2,%3}, {%4,%5,%6,%7}, {%8,%9}, {%10,%10,%10,%10};"
        : "=f"(c[0]), "=f"(c[1]), "=f"(c[2]), "=f"(c[3]) : "r"(a0), "r"(a1), "r"(a2), "r"(a3), "r"(b0), "r"(b1), "f"(0.f));
}
__device__ __forceinline__ float bf_lo(uint32_t w) { return __uint_as_float(w << 16); }
__device__ __forceinline__ float bf_hi(uint32_t w) { return __uint_as_float(w & 0xffff0000u); }
__device__ __forceinline__ void st_pkt(uint4* p, uint32_t w0, uint32_t w1, uint32_t w2, uint32_t w3) {
    asm volatile("{\n.reg .b64 lo, hi;\n.reg .b128 v;\nmov.b64 lo, {%1, %2};\nmov.b64 hi, {%3, %4};\nmov.b128 v, {lo, hi};\nst.relaxed.gpu.global.b128 [%0], v;\n}"
        :: "l"(p), "r"(w0), "r"(w1), "r"(w2), "r"(w3) : "memory");
}
__device__ __forceinline__ void ld_pkt(const uint4* p, uint32_t& w0, uint32_t& w1, uint32_t& w2, uint32_t& w3) {
    asm volatile("{\n.reg .b64 lo, hi;\n.reg .b128 v;\nld.relaxed.gpu.global.b128 v, [%4];\nmov.b128 {lo, hi}, v;\nmov.b64 {%0, %1}, lo;\nmov.b64 {%2, %3}, hi;\n}"
        : "=r"(w0), "=r"(w1), "=r"(w2), "=r"(w3) : "l"(p) : "memory");
}

__device__ __forceinline__ void wg_ss128(float (&d)[64], uint32_t alo, uint32_t ahi, uint32_t blo, uint32_t bhi) {
    asm volatile("{\n.reg .b64 da, db;\nmov.b64 da, {%64, %65};\nmov.b64 db, {%66, %67};\n"
        "wgmma.mma_async.sync.aligned.m64n128k16.f32.bf16.bf16 {%0,%1,%2,%3,%4,%5,%6,%7,%8,%9,%10,%11,%12,%13,%14,%15,%16,%17,%18,%19,%20,%21,%22,%23,%24,%25,%26,%27,%28,%29,%30,%31,%32,%33,%34,%35,%36,%37,%38,%39,%40,%41,%42,%43,%44,%45,%46,%47,%48,%49,%50,%51,%52,%53,%54,%55,%56,%57,%58,%59,%60,%61,%62,%63}, da, db, 1, 1, 1, 0, 1;\n}\n"
        : "+f"(d[0]),"+f"(d[1]),"+f"(d[2]),"+f"(d[3]),"+f"(d[4]),"+f"(d[5]),"+f"(d[6]),"+f"(d[7]),"+f"(d[8]),"+f"(d[9]),"+f"(d[10]),"+f"(d[11]),"+f"(d[12]),"+f"(d[13]),"+f"(d[14]),"+f"(d[15]),"+f"(d[16]),"+f"(d[17]),"+f"(d[18]),"+f"(d[19]),"+f"(d[20]),"+f"(d[21]),"+f"(d[22]),"+f"(d[23]),"+f"(d[24]),"+f"(d[25]),"+f"(d[26]),"+f"(d[27]),"+f"(d[28]),"+f"(d[29]),"+f"(d[30]),"+f"(d[31]),"+f"(d[32]),"+f"(d[33]),"+f"(d[34]),"+f"(d[35]),"+f"(d[36]),"+f"(d[37]),"+f"(d[38]),"+f"(d[39]),"+f"(d[40]),"+f"(d[41]),"+f"(d[42]),"+f"(d[43]),"+f"(d[44]),"+f"(d[45]),"+f"(d[46]),"+f"(d[47]),"+f"(d[48]),"+f"(d[49]),"+f"(d[50]),"+f"(d[51]),"+f"(d[52]),"+f"(d[53]),"+f"(d[54]),"+f"(d[55]),"+f"(d[56]),"+f"(d[57]),"+f"(d[58]),"+f"(d[59]),"+f"(d[60]),"+f"(d[61]),"+f"(d[62]),"+f"(d[63])
        : "r"(alo), "r"(ahi), "r"(blo), "r"(bhi));
}
__device__ __forceinline__ void wg_ss128_z(float (&d)[64], uint32_t alo, uint32_t ahi, uint32_t blo, uint32_t bhi) {
    asm volatile("{\n.reg .b64 da, db;\nmov.b64 da, {%64, %65};\nmov.b64 db, {%66, %67};\n"
        "wgmma.mma_async.sync.aligned.m64n128k16.f32.bf16.bf16 {%0,%1,%2,%3,%4,%5,%6,%7,%8,%9,%10,%11,%12,%13,%14,%15,%16,%17,%18,%19,%20,%21,%22,%23,%24,%25,%26,%27,%28,%29,%30,%31,%32,%33,%34,%35,%36,%37,%38,%39,%40,%41,%42,%43,%44,%45,%46,%47,%48,%49,%50,%51,%52,%53,%54,%55,%56,%57,%58,%59,%60,%61,%62,%63}, da, db, 0, 1, 1, 0, 1;\n}\n"
        : "=f"(d[0]),"=f"(d[1]),"=f"(d[2]),"=f"(d[3]),"=f"(d[4]),"=f"(d[5]),"=f"(d[6]),"=f"(d[7]),"=f"(d[8]),"=f"(d[9]),"=f"(d[10]),"=f"(d[11]),"=f"(d[12]),"=f"(d[13]),"=f"(d[14]),"=f"(d[15]),"=f"(d[16]),"=f"(d[17]),"=f"(d[18]),"=f"(d[19]),"=f"(d[20]),"=f"(d[21]),"=f"(d[22]),"=f"(d[23]),"=f"(d[24]),"=f"(d[25]),"=f"(d[26]),"=f"(d[27]),"=f"(d[28]),"=f"(d[29]),"=f"(d[30]),"=f"(d[31]),"=f"(d[32]),"=f"(d[33]),"=f"(d[34]),"=f"(d[35]),"=f"(d[36]),"=f"(d[37]),"=f"(d[38]),"=f"(d[39]),"=f"(d[40]),"=f"(d[41]),"=f"(d[42]),"=f"(d[43]),"=f"(d[44]),"=f"(d[45]),"=f"(d[46]),"=f"(d[47]),"=f"(d[48]),"=f"(d[49]),"=f"(d[50]),"=f"(d[51]),"=f"(d[52]),"=f"(d[53]),"=f"(d[54]),"=f"(d[55]),"=f"(d[56]),"=f"(d[57]),"=f"(d[58]),"=f"(d[59]),"=f"(d[60]),"=f"(d[61]),"=f"(d[62]),"=f"(d[63])
        : "r"(alo), "r"(ahi), "r"(blo), "r"(bhi));
}
__device__ __forceinline__ void wg_ss64(float (&d)[32], uint32_t alo, uint32_t ahi, uint32_t blo, uint32_t bhi) {
    asm volatile("{\n.reg .b64 da, db;\nmov.b64 da, {%32, %33};\nmov.b64 db, {%34, %35};\n"
        "wgmma.mma_async.sync.aligned.m64n64k16.f32.bf16.bf16 {%0,%1,%2,%3,%4,%5,%6,%7,%8,%9,%10,%11,%12,%13,%14,%15,%16,%17,%18,%19,%20,%21,%22,%23,%24,%25,%26,%27,%28,%29,%30,%31}, da, db, 1, 1, 1, 0, 1;\n}\n"
        : "+f"(d[0]),"+f"(d[1]),"+f"(d[2]),"+f"(d[3]),"+f"(d[4]),"+f"(d[5]),"+f"(d[6]),"+f"(d[7]),"+f"(d[8]),"+f"(d[9]),"+f"(d[10]),"+f"(d[11]),"+f"(d[12]),"+f"(d[13]),"+f"(d[14]),"+f"(d[15]),"+f"(d[16]),"+f"(d[17]),"+f"(d[18]),"+f"(d[19]),"+f"(d[20]),"+f"(d[21]),"+f"(d[22]),"+f"(d[23]),"+f"(d[24]),"+f"(d[25]),"+f"(d[26]),"+f"(d[27]),"+f"(d[28]),"+f"(d[29]),"+f"(d[30]),"+f"(d[31])
        : "r"(alo), "r"(ahi), "r"(blo), "r"(bhi));
}
__device__ __forceinline__ void wg_ss64_z(float (&d)[32], uint32_t alo, uint32_t ahi, uint32_t blo, uint32_t bhi) {
    asm volatile("{\n.reg .b64 da, db;\nmov.b64 da, {%32, %33};\nmov.b64 db, {%34, %35};\n"
        "wgmma.mma_async.sync.aligned.m64n64k16.f32.bf16.bf16 {%0,%1,%2,%3,%4,%5,%6,%7,%8,%9,%10,%11,%12,%13,%14,%15,%16,%17,%18,%19,%20,%21,%22,%23,%24,%25,%26,%27,%28,%29,%30,%31}, da, db, 0, 1, 1, 0, 1;\n}\n"
        : "=f"(d[0]),"=f"(d[1]),"=f"(d[2]),"=f"(d[3]),"=f"(d[4]),"=f"(d[5]),"=f"(d[6]),"=f"(d[7]),"=f"(d[8]),"=f"(d[9]),"=f"(d[10]),"=f"(d[11]),"=f"(d[12]),"=f"(d[13]),"=f"(d[14]),"=f"(d[15]),"=f"(d[16]),"=f"(d[17]),"=f"(d[18]),"=f"(d[19]),"=f"(d[20]),"=f"(d[21]),"=f"(d[22]),"=f"(d[23]),"=f"(d[24]),"=f"(d[25]),"=f"(d[26]),"=f"(d[27]),"=f"(d[28]),"=f"(d[29]),"=f"(d[30]),"=f"(d[31])
        : "r"(alo), "r"(ahi), "r"(blo), "r"(bhi));
}
__device__ __forceinline__ void wg_ss64t(float (&d)[32], uint32_t alo, uint32_t ahi, uint32_t blo, uint32_t bhi) {
    asm volatile("{\n.reg .b64 da, db;\nmov.b64 da, {%32, %33};\nmov.b64 db, {%34, %35};\n"
        "wgmma.mma_async.sync.aligned.m64n64k16.f32.bf16.bf16 {%0,%1,%2,%3,%4,%5,%6,%7,%8,%9,%10,%11,%12,%13,%14,%15,%16,%17,%18,%19,%20,%21,%22,%23,%24,%25,%26,%27,%28,%29,%30,%31}, da, db, 1, 1, 1, 1, 1;\n}\n"
        : "+f"(d[0]),"+f"(d[1]),"+f"(d[2]),"+f"(d[3]),"+f"(d[4]),"+f"(d[5]),"+f"(d[6]),"+f"(d[7]),"+f"(d[8]),"+f"(d[9]),"+f"(d[10]),"+f"(d[11]),"+f"(d[12]),"+f"(d[13]),"+f"(d[14]),"+f"(d[15]),"+f"(d[16]),"+f"(d[17]),"+f"(d[18]),"+f"(d[19]),"+f"(d[20]),"+f"(d[21]),"+f"(d[22]),"+f"(d[23]),"+f"(d[24]),"+f"(d[25]),"+f"(d[26]),"+f"(d[27]),"+f"(d[28]),"+f"(d[29]),"+f"(d[30]),"+f"(d[31])
        : "r"(alo), "r"(ahi), "r"(blo), "r"(bhi));
}
__device__ __forceinline__ void wg_ss64t_z(float (&d)[32], uint32_t alo, uint32_t ahi, uint32_t blo, uint32_t bhi) {
    asm volatile("{\n.reg .b64 da, db;\nmov.b64 da, {%32, %33};\nmov.b64 db, {%34, %35};\n"
        "wgmma.mma_async.sync.aligned.m64n64k16.f32.bf16.bf16 {%0,%1,%2,%3,%4,%5,%6,%7,%8,%9,%10,%11,%12,%13,%14,%15,%16,%17,%18,%19,%20,%21,%22,%23,%24,%25,%26,%27,%28,%29,%30,%31}, da, db, 0, 1, 1, 1, 1;\n}\n"
        : "=f"(d[0]),"=f"(d[1]),"=f"(d[2]),"=f"(d[3]),"=f"(d[4]),"=f"(d[5]),"=f"(d[6]),"=f"(d[7]),"=f"(d[8]),"=f"(d[9]),"=f"(d[10]),"=f"(d[11]),"=f"(d[12]),"=f"(d[13]),"=f"(d[14]),"=f"(d[15]),"=f"(d[16]),"=f"(d[17]),"=f"(d[18]),"=f"(d[19]),"=f"(d[20]),"=f"(d[21]),"=f"(d[22]),"=f"(d[23]),"=f"(d[24]),"=f"(d[25]),"=f"(d[26]),"=f"(d[27]),"=f"(d[28]),"=f"(d[29]),"=f"(d[30]),"=f"(d[31])
        : "r"(alo), "r"(ahi), "r"(blo), "r"(bhi));
}
__device__ __forceinline__ void wg_ss8t(float (&d)[4], uint32_t alo, uint32_t ahi, uint32_t blo, uint32_t bhi) {
    asm volatile("{\n.reg .b64 da, db;\nmov.b64 da, {%4, %5};\nmov.b64 db, {%6, %7};\n"
        "wgmma.mma_async.sync.aligned.m64n8k16.f32.bf16.bf16 {%0,%1,%2,%3}, da, db, 1, 1, 1, 1, 0;\n}\n"
        : "+f"(d[0]),"+f"(d[1]),"+f"(d[2]),"+f"(d[3])
        : "r"(alo), "r"(ahi), "r"(blo), "r"(bhi));
}
__device__ __forceinline__ void wg_ss8t_z(float (&d)[4], uint32_t alo, uint32_t ahi, uint32_t blo, uint32_t bhi) {
    asm volatile("{\n.reg .b64 da, db;\nmov.b64 da, {%4, %5};\nmov.b64 db, {%6, %7};\n"
        "wgmma.mma_async.sync.aligned.m64n8k16.f32.bf16.bf16 {%0,%1,%2,%3}, da, db, 0, 1, 1, 1, 0;\n}\n"
        : "=f"(d[0]),"=f"(d[1]),"=f"(d[2]),"=f"(d[3])
        : "r"(alo), "r"(ahi), "r"(blo), "r"(bhi));
}

constexpr uint32_t DH128 = 64u | 0x40000000u;
constexpr uint32_t DH64 = 32u | 0x80000000u;
constexpr uint32_t LBO4K = (4096u >> 4) << 16, LBO8K = (8192u >> 4) << 16, LBO1 = 1u << 16;

template <bool SW64, bool FIRST> __device__ __forceinline__ void g1_issue(float (&acc)[64], uint32_t alo, uint32_t blo) {
    wg_fence();
#pragma unroll
    for (int k = 0; k < 4; k++) {
        if (FIRST && k == 0) wg_ss128_z(acc, alo, DH128, blo, SW64 ? DH64 : DH128);
        else wg_ss128(acc, alo + 2 * k, DH128, blo + (SW64 ? 64 * k : 128 * k), SW64 ? DH64 : DH128);
    }
    wg_commit();
}

template <int N> __device__ __forceinline__ void stash(uint32_t base, uint32_t sw, const uint32_t (&f)[N]) {
#pragma unroll
    for (int t = 0; t < N / 4; t++) stsm4(base + ((sw ^ (2 * t)) << 4), f[4 * t], f[4 * t + 1], f[4 * t + 2], f[4 * t + 3]);
}

template <int V0, int V1, int N> __device__ __forceinline__ void send_frag(const uint32_t (&f)[N], uint4* p, uint32_t tag) {
#pragma unroll
    for (int v = V0; v < V1; v++) st_pkt(p + (v & 3) * 32, (f[4 * v] & ~1u) | tag, f[4 * v + 1], f[4 * v + 2], f[4 * v + 3]);
}
template <int H0, int H1, int N> __device__ __forceinline__ void send_h(const uint32_t (&f)[N], uint4* p) {
#pragma unroll
    for (int h = H0; h < H1; h++) {
        p[4 * h] = make_uint4(f[8 * h], f[8 * h + 2], f[8 * h + 4], f[8 * h + 6]);
        p[4 * h + 64] = make_uint4(f[8 * h + 1], f[8 * h + 3], f[8 * h + 5], f[8 * h + 7]);
    }
}
template <int O, int N, int M> __device__ __forceinline__ void pack_sub(uint32_t (&f)[N], const float (&acc)[M]) {
#pragma unroll
    for (int i = 0; i < N; i++) f[i] = pack2(acc[O + 2 * i], acc[O + 2 * i + 1]);
}
template <int N> __device__ __forceinline__ void recv_issue(uint32_t (&q)[N], const uint4* p) {
#pragma unroll
    for (int v = 0; v < N / 4; v++) ld_pkt(p + v * 32, q[4 * v], q[4 * v + 1], q[4 * v + 2], q[4 * v + 3]);
}
template <int N> __device__ __forceinline__ void recv_check(uint32_t (&q)[N], const uint4* p, uint32_t tag) {
    uint32_t it = 0;
    while (true) {
        uint32_t bad = 0;
#pragma unroll
        for (int v = 0; v < N / 4; v++) bad |= q[4 * v] ^ tag;
        if (__all_sync(0xffffffffu, (bad & 1u) == 0) || ++it > SPIN_GLOBAL) break;
        recv_issue(q, p);
    }
}
__device__ __forceinline__ void accum(const uint32_t (&q)[16], float (&sum)[32]) {
#pragma unroll
    for (int i = 0; i < 16; i++) { sum[2 * i] += bf_lo(q[i]); sum[2 * i + 1] += bf_hi(q[i]); }
}

}

__global__ void __launch_bounds__(384, 1)
fused_kernel(const __grid_constant__ Maps maps, const __nv_bfloat16* __restrict__ xg, const __nv_bfloat16* __restrict__ gate_w,
             const char* __restrict__ pf_qkv, const char* __restrict__ pf_g, const char* __restrict__ pf_u,
             const char* __restrict__ pf_d, const char* __restrict__ pf_o, __nv_bfloat16* __restrict__ out) {
    extern __shared__ __align__(1024) uint8_t smem_raw[];
    const uint32_t sb = (uint32_t)__cvta_generic_to_shared(smem_raw);
    const int tid = threadIdx.x, lane = tid & 31;
    const int warp = __shfl_sync(0xffffffffu, tid >> 5, 0);
    const int j = (blockIdx.x >> 1) & 7;
    const int r = ((blockIdx.x >> 4) << 1) | (blockIdx.x & 1);
    const uint32_t rank = blockIdx.x & 1;

    if (warp == 0) { TSG(0, 30); TS(0, 0); }
    if (tid == 256) {
        for (int i = 0; i < 5; i++) { mbar_init(sb + B_FULL + 8 * i, 1); mbar_init(sb + B_EMPTY + 8 * i, MC ? 4 : 2); }
        for (int i = 0; i < 9; i++) mbar_init(sb + B_XFULL + 8 * i, 1);
        asm volatile("fence.mbarrier_init.release.cluster;" ::: "memory");
        mbar_expect(sb + B_XFULL, 16384);
        tma2(sb + OFF_X, &maps.x, 0, r * 128, sb + B_XFULL);
        TS2(0);
        mbar_expect(sb + B_FULL, 16384);
        tmaw3(sb + OFF_RING, &maps.gu, 224 * j, 0, 0, sb + B_FULL);
        TS2(1);
        mbar_expect(sb + B_FULL + 8, 16384);
        tmaw3(sb + OFF_RING + 16384, &maps.kv, 64 * j, 0, 1, sb + B_FULL + 8);
    } else if (tid == 288) {
        for (int i = 0; i < 5; i++) mbar_init(sb + B_HSENT + 8 * i, 8);
        mbar_init(sb + B_XFREE, 2); mbar_init(sb + B_XFREE + 8, 2); mbar_init(sb + B_XFREE + 16, 2);
        mbar_init(sb + B_GRDY, 1); mbar_init(sb + B_KVDONE, 8); mbar_init(sb + B_KVRDY, 2);
        asm volatile("fence.mbarrier_init.release.cluster;" ::: "memory");
    } else if (warp == 10 && lane < 11) {
        asm volatile("prefetch.tensormap [%0];" :: "l"(&maps.gu + lane) : "memory");
    }
    __syncthreads();

    if (warp >= 8) {
        asm volatile("setmaxnreg.dec.sync.aligned.u32 72;");
        if (warp == 8) {
            if (lane == 0) {
                int slot = MC ? 0 : 2, ph = 1;
                uint32_t full, dst;
                if (!MC) { mbar_expect(sb + B_XFULL + 8, 16384); tma2(sb + OFF_X + 16384, &maps.x, 64, r * 128, sb + B_XFULL + 8); }
#define P_BEGIN(S, BYTES) full = sb + B_FULL + 8 * slot; dst = sb + OFF_RING + slot * 16384; \
                mbar_wait(sb + B_EMPTY + 8 * slot, ph); TS2(S); mbar_expect(full, BYTES); if (!MC || (((S) ^ rank) & 1) == 0)
#define P_END() if (++slot == 5) { slot = 0; ph ^= 1; }
                for (int s = MC ? 0 : 2; s < 16; s++) {
                    P_BEGIN(s, 16384) {
                        if (s & 1) tmaw3(dst, &maps.kv, 64 * j, 32 * (s - 1), 1, full);
                        else tmaw3(dst, &maps.gu, 224 * j, 32 * s, 0, full);
                    }
                    const int xb = (s == 4) ? 3 : !(s & 1) ? 0 : (s < 5) ? (s + 1) / 2 : (s <= 11) ? (s + 3) / 2 : 0;
                    if (xb) { mbar_expect(sb + B_XFULL + 8 * xb, 16384); tma2(sb + OFF_X + xb * 16384, &maps.x, 64 * xb, r * 128, sb + B_XFULL + 8 * xb); }
                    P_END()
                }
                for (int s = 0; s < 24; s++) {
                    P_BEGIN(16 + s, 16384) {
                        if ((s >> 3) == 1) {
                            tmaw3(dst, &maps.q64, 0, 64 * (s & 7), 2 * j, full);
                            tmaw3(dst + 8192, &maps.gu64, 224 * j + 192, 64 * (s & 7), 0, full);
                        } else {
                            tmaw3(dst, &maps.gu, 224 * j + 64 + 4 * (s & 16), 64 * (s & 7), 0, full);
                        }
                    }
                    P_END()
                }
                const int p = j >> 1;
#pragma unroll 1
                for (int t = 0; t < 18; t++) {
                    const int q = (t >= 7 && t != 9 && t != 10), u = t < 7 ? t : t < 9 ? t - 7 : t < 11 ? t - 2 : t - 9;
                    const int cw = (j & 1) * 4 + ((p & 2) ^ (q ? 0 : 2)), cc = 64 * cw;
                    P_BEGIN(40 + t, 16384) {
                        if (u == 4) {
                            tmaw5(dst, &maps.wdph, cc, 14 * p + 6, full); tmaw5(dst + 4096, &maps.wdph, cc, 14 * p + 13, full);
                            tmaw5(dst + 8192, &maps.wdph, cc + 64, 14 * p + 6, full); tmaw5(dst + 12288, &maps.wdph, cc + 64, 14 * p + 13, full);
                        } else if (u == 5 || u == 6) {
                            tmaw3(dst, u == 5 ? &maps.wow : &maps.wdw, 0, u == 5 ? 64 * j : 224 * j + 128, cw, full);
                        } else {
                            const CUtensorMap* m = u == 7 ? &maps.wop : &maps.wdp;
                            const int g = u == 7 ? 2 * (j ^ 1) : u == 8 ? 7 * (j ^ 1) + 4 : 14 * p + 7 * (u & 1) + (u & 2);
                            tmaw5(dst, m, cc, g, full); tmaw5(dst + 8192, m, cc + 64, g, full);
                        }
                    }
                    P_END()
                }
            }
        } else if (warp < 11) {
            const int hx = warp - 9;
            uint32_t epoch;
            asm volatile("ld.relaxed.gpu.global.u32 %0, [%1];" : "=r"(epoch) : "l"(g_epoch + blockIdx.x) : "memory");
            {
                const uint4* xr = (const uint4*)(xg + (size_t)(r * 128 + j * 16 + hx * 8) * kD) + lane;
                const uint4 wa = __ldg((const uint4*)gate_w + lane), wb = __ldg((const uint4*)gate_w + 32 + lane);
                const uint32_t tag = (epoch + 1) & 1;
                uint4* gp = g_gx + r * 32;
                if (lane < 2) st_pkt(gp + j * 4 + hx * 2 + lane, tag ^ 1, 0, 0, 0);
                float s[8];
#pragma unroll
                for (int i0 = 0; i0 < 8; i0 += 4) {
                    uint4 va[4], vb[4];
#pragma unroll
                    for (int i = 0; i < 4; i++) { va[i] = __ldg(xr + (i0 + i) * 64); vb[i] = __ldg(xr + (i0 + i) * 64 + 32); }
#pragma unroll
                    for (int i = 0; i < 4; i++) {
                        float t0 = bf_lo(va[i].x) * bf_lo(wa.x), t1 = bf_hi(va[i].x) * bf_hi(wa.x);
                        t0 = fmaf(bf_lo(va[i].y), bf_lo(wa.y), t0); t1 = fmaf(bf_hi(va[i].y), bf_hi(wa.y), t1);
                        t0 = fmaf(bf_lo(va[i].z), bf_lo(wa.z), t0); t1 = fmaf(bf_hi(va[i].z), bf_hi(wa.z), t1);
                        t0 = fmaf(bf_lo(va[i].w), bf_lo(wa.w), t0); t1 = fmaf(bf_hi(va[i].w), bf_hi(wa.w), t1);
                        t0 = fmaf(bf_lo(vb[i].x), bf_lo(wb.x), t0); t1 = fmaf(bf_hi(vb[i].x), bf_hi(wb.x), t1);
                        t0 = fmaf(bf_lo(vb[i].y), bf_lo(wb.y), t0); t1 = fmaf(bf_hi(vb[i].y), bf_hi(wb.y), t1);
                        t0 = fmaf(bf_lo(vb[i].z), bf_lo(wb.z), t0); t1 = fmaf(bf_hi(vb[i].z), bf_hi(wb.z), t1);
                        t0 = fmaf(bf_lo(vb[i].w), bf_lo(wb.w), t0); t1 = fmaf(bf_hi(vb[i].w), bf_hi(wb.w), t1);
                        s[i0 + i] = t0 + t1;
                    }
                }
#pragma unroll
                for (int i = 0; i < 8; i++) {
#pragma unroll
                    for (int o = 16; o; o >>= 1) s[i] += __shfl_xor_sync(0xffffffffu, s[i], o);
                    s[i] = 1.f / (1.f + __expf(-s[i]));
                }
                if (lane < 2) {
                    const float v0 = lane ? s[4] : s[0], v1 = lane ? s[5] : s[1], v2 = lane ? s[6] : s[2], v3 = lane ? s[7] : s[3];
                    st_pkt(gp + j * 4 + hx * 2 + lane, (__float_as_uint(v0) & ~1u) | tag, __float_as_uint(v1), __float_as_uint(v2), __float_as_uint(v3));
                }
                if (hx == 1) {
                    asm volatile("st.shared.u32 [%0], %1;" :: "r"(sb + OFF_ONES + lane * 4), "r"(0x3f803f80u) : "memory");
                    asm volatile("fence.proxy.async.shared::cta;" ::: "memory");
                }
                asm volatile("bar.sync 3, 96;" ::: "memory");
                if (hx == 0) {
                    uint32_t q[4];
                    recv_issue(q, gp + lane);
                    recv_check(q, gp + lane, tag);
                    asm volatile("st.shared.v4.u32 [%0], {%1,%2,%3,%4};" :: "r"(sb + OFF_G + lane * 16), "r"(q[0]), "r"(q[1]), "r"(q[2]), "r"(q[3]) : "memory");
                    if (lane == 0) {
                        asm volatile("st.shared.u32 [%0], %1;" :: "r"(sb + OFF_EPOCH), "r"(epoch) : "memory");
                        g_epoch[blockIdx.x] = epoch + 1;
                    }
                    __syncwarp();
                    if (lane == 0) mbar_arrive(sb + B_GRDY);
                } else {
                    if (r == 0) {
                        float4* zp = (float4*)(g_kvacc + (((epoch & 1) ^ 1) * 8 + j) * 4 * 272);
                        for (int i = lane; i < 272; i += 32) zp[i] = make_float4(0.f, 0.f, 0.f, 0.f);
                    }
                }
            }
            TS(2 + hx, 1);
#define PUBLISH_H(B) do { mbar_wait(sb + B_HSENT + 8 * (B), 0); if (lane == 0) { \
                asm volatile("st.release.gpu.global.u32 [%0], %1;" :: "l"(g_hflag + (r * 8 + j) * 8 + (B)), "r"(epoch + 1) : "memory"); } __syncwarp(); } while (0)
            if (hx == 1) {
#pragma unroll 1
                for (int b = 0; b < 4; b++) { PUBLISH_H(b); TS(3, 5 + b); }
            } else {
                const float* accp = g_kvacc + ((epoch & 1) * 8 + j) * 4 * 272;
                unsigned* cnt = g_kvcnt + j * 32;
                mbar_wait(sb + B_KVDONE, 0);
                TS(2, 5);
                if (lane == 0) asm volatile("red.release.gpu.global.add.u32 [%0], 1;" :: "l"(cnt) : "memory");
                __syncwarp();
                TS(2, 2);
                {
                    const unsigned target = 16u * (epoch + 1);
                    uint32_t it = 0, v;
                    do {
                        asm volatile("ld.acquire.gpu.global.u32 %0, [%1];" : "=r"(v) : "l"(cnt) : "memory");
                    } while ((int)(v - target) < 0 && ++it < SPIN_GLOBAL);
                }
                TS(2, 3);
#pragma unroll
                for (int h = 0; h < 4; h++) {
                    const float4 d0 = __ldcg((const float4*)(accp + h * 272) + lane);
                    const float4 d1 = __ldcg((const float4*)(accp + h * 272 + 128) + lane);
                    const float2 z0 = __ldcg((const float2*)(accp + h * 272 + 256) + (lane & 3));
                    const float2 z1 = __ldcg((const float2*)(accp + h * 272 + 264) + (lane & 3));
                    asm volatile("st.shared.v4.u32 [%0], {%1,%2,%3,%4};" :: "r"(sb + OFF_KVF + h * 512 + lane * 16),
                                 "r"(pack2(d0.x, d0.y)), "r"(pack2(d1.x, d1.y)), "r"(pack2(d0.z, d0.w)), "r"(pack2(d1.z, d1.w)) : "memory");
                    if (lane < 4) asm volatile("st.shared.v2.u32 [%0], {%1,%2};" :: "r"(sb + OFF_ZF + h * 32 + lane * 8), "r"(pack2(z0.x, z0.y)), "r"(pack2(z1.x, z1.y)) : "memory");
                }
                __syncwarp();
                if (lane == 0) mbar_arrive(sb + B_KVRDY);
                TS(2, 4);
                PUBLISH_H(4);
                TS(3, 9);
            }
        } else {
            uint32_t epoch;
            asm volatile("ld.relaxed.gpu.global.u32 %0, [%1];" : "=r"(epoch) : "l"(g_epoch + blockIdx.x) : "memory");
            asm volatile("bar.arrive 3, 96;" :: "r"(epoch) : "memory");
            const int b = blockIdx.x, p = j >> 1;
            mbar_wait(sb + B_XFULL + 8 * PF_AFTER, 0);
#pragma unroll
            for (int i = 0; i < 4; i++) {
                if (i < 3) asm volatile("prefetch.global.L2 [%0];" :: "l"(pf_qkv + b * 12288 + (i * 32 + lane) * 128));
                if (i < 3 || lane < 16) {
                    asm volatile("prefetch.global.L2 [%0];" :: "l"(pf_g + b * 14336 + (i * 32 + lane) * 128));
                    asm volatile("prefetch.global.L2 [%0];" :: "l"(pf_u + b * 14336 + (i * 32 + lane) * 128));
                }
            }
            {
                uint4* mb = g_part + (size_t)(r * 2 + (j & 1)) * 16384 + (((p ^ 1) * 4 + p) << 10) + lane;
#pragma unroll 8
                for (int i = 0; i < 32; i++) st_pkt(mb + i * 32, epoch & 1, 0, 0, 0);
                __syncwarp();
                if (lane == 0) mbar_arrive(sb + B_KVRDY);
            }
            mbar_wait(sb + B_XFULL + 8 * 7, 0);
#pragma unroll
            for (int i = 0; i < 4; i++)
                if (i < 3 || lane < 16) asm volatile("prefetch.global.L2 [%0];" :: "l"(pf_d + b * 14336 + (i * 32 + lane) * 128));
            asm volatile("prefetch.global.L2 [%0];" :: "l"(pf_o + b * 4096 + lane * 128));
            if (lane == 0) {
                const uint32_t want = epoch + 1;
                const int hrow = (r * 4 + p) * 9 * 128, po = (j & 1) ^ 1;
#pragma unroll 1
                for (int i = 0; i < 5; i++) {
#pragma unroll 1
                    for (int w = 0; w < (i < 3 ? 2 : 1); w++) {
                        const unsigned* fl = g_hflag + (r * 8 + (j ^ 1 ^ w)) * 8 + i;
                        uint32_t it = 0, v;
                        do {
                            asm volatile("ld.acquire.gpu.global.u32 %0, [%1];" : "=r"(v) : "l"(fl) : "memory");
                        } while (v != want && ++it < SPIN_GLOBAL);
                    }
                    asm volatile("fence.proxy.async.global;" ::: "memory");
                    if (i < 3) mbar_wait(sb + B_XFREE + 8 * i, 0);
                    const int piece = i < 3 ? 2 * i : i == 3 ? 5 : 8, tile = i < 3 ? 2 * i : 2 * i - 1 + po;
                    const uint32_t bar = sb + B_XFULL + 8 * (i == 0 ? 1 : piece);
                    TS2(140 + i);
                    mbar_expect(bar, i < 2 ? 32768 : 16384);
                    tma2(sb + OFF_X + piece * 16384, i < 2 ? &maps.hx2 : &maps.hx, 0, hrow + tile * 128, bar);
                }
            }
        }
    } else {
        asm volatile("setmaxnreg.inc.sync.aligned.u32 216;");
        const int wg = warp >> 2;
        const bool elect = (tid & 127) == 0;
        const uint32_t xlo = ((sb + OFF_X + wg * 8192) >> 4) | LBO1;
        const uint32_t ringlo = (sb + OFF_RING) >> 4;
        auto release = [&](int s) {
            if (elect) {
                mbar_arrive(sb + B_EMPTY + 8 * s);
            }
        };
#define S_WAIT(S) do { mbar_wait(sb + B_FULL + 8 * ((S) % 5), ((S) / 5) & 1); if (PROF && tid == 0) TS2(64 + (S)); } while (0)
#define S_B(S) (ringlo + ((S) % 5) * 1024)
#define G1(S, acc, SW, KB) do { S_WAIT(S); g1_issue<SW, (KB) == 0>(acc, xlo + (KB) * 1024, S_B(S) | (SW ? LBO4K : LBO8K)); } while (0)
#define RET(S) do { wg_wait<1>(); if ((S) - 1 < 53) release(((S) - 1) % 5); } while (0)
#define SCHED() mbar_wait(sb + B_XFULL + 8 * 7, 0)
#define A2_SYNC() do { asm volatile("fence.proxy.async.shared::cta;" ::: "memory"); asm volatile("bar.sync %0, 128;" :: "r"(wg + 1) : "memory"); } while (0)
#define H_EPI(acc, F, I0, I1, OG, OU) _Pragma("unroll") for (int i = (I0); i < (I1); i++) \
            F[i] = hmul2(pack2(acc[(OG) + 2 * i] * acc[(OU) + 2 * i], acc[(OG) + 2 * i + 1] * acc[(OU) + 2 * i + 1]), (i & 1) ? m_hi : m_lo)
#define PHI(acc, F, I0, I1) _Pragma("unroll") for (int i = (I0); i < (I1); i++) F[i] = phi2(acc[2 * i], acc[2 * i + 1])

        float a0[64], b0[64], a1[64], a2_[64], a3[64];
        mbar_wait(sb + B_XFULL, 0);
        G1(0, a0, false, 0);
        if ((warp & 3) == 0) TS(wg, 1);
        G1(1, b0, false, 0); RET(1);
#define C0(KB) mbar_wait(sb + B_XFULL + 8 * (KB), 0); if (PROF && tid == 0) TS2(128 + (KB)); \
        G1(2 * (KB), a0, false, KB); RET(2 * (KB)); G1(2 * (KB) + 1, b0, false, KB); RET(2 * (KB) + 1)
        C0(1); C0(2); C0(3); C0(4); C0(5); C0(6);
        mbar_wait(sb + B_XFULL + 8 * 7, 0);
        G1(14, a0, false, 7); RET(14);
        G1(15, b0, false, 7);
        mbar_wait(sb + B_GRDY, 0);
        float g_lo, g_hi;
        uint32_t tag;
        {
            const uint32_t ga = sb + OFF_G + (warp * 16 + (lane >> 2)) * 4;
            asm volatile("ld.shared.f32 %0, [%1];" : "=f"(g_lo) : "r"(ga) : "memory");
            asm volatile("ld.shared.f32 %0, [%1];" : "=f"(g_hi) : "r"(ga + 32) : "memory");
            asm volatile("ld.shared.u32 %0, [%1];" : "=r"(tag) : "r"(sb + OFF_EPOCH) : "memory");
        }
        float* const kvp = g_kvacc + (((tag & 1) * 8 + j) * 4 + (warp & 3)) * 272;
        tag = (tag + 1) & 1;
        const uint32_t m_lo = pack2(1.f - g_lo, 1.f - g_lo), m_hi = pack2(1.f - g_hi, 1.f - g_hi);
        const uint32_t lrow = ((lane & 7) + 8 * ((lane >> 3) & 1)) * 128;
        const uint32_t srow = (warp & 3) * 2048 + lrow;
        const uint32_t ssw = (lane >> 4) ^ (lane & 7);
        uint4* const hsend = g_hx + (size_t)((r * 4 + (j >> 1)) * 9 + (j & 1)) * 1024 + warp * 128 + (lane >> 2) * 8 + (lane & 3);
#define SENT_H(B) do { __syncwarp(); if (lane == 0) mbar_arrive(sb + B_HSENT + 8 * (B)); } while (0)
        RET(15);
        pin(a0);
        if ((warp & 3) == 0) TS(wg, 2);
        uint32_t fh0[16], fh1[16], fh2[16], fh3[8], fo[16];
        H_EPI(a0, fh0, 0, 16, 0, 32);

        float kv[32], zs[4];
        uint32_t pk[16], pv[16];
        const uint32_t stg = sb + OFF_STG + wg * 8192, stl = stg + (warp & 1) * 2048 + lrow;
        const uint32_t klo = (stg >> 4) | LBO1, vlo = klo + 256, olo = (sb + OFF_ONES) >> 4;
        G1(16, a1, false, 0); RET(16);
        pin(b0);
        G1(17, a1, false, 1); send_h<0, 1>(fh0, hsend); SCHED(); PHI(b0, pk, 0, 6); RET(17);
        G1(18, a1, false, 2); send_h<1, 2>(fh0, hsend); SENT_H(0); SCHED(); PHI(b0, pk, 6, 12); RET(18);
        G1(19, a1, false, 3); SCHED(); PHI(b0, pk, 12, 16); pack_sub<32>(pv, b0); RET(19);
        G1(20, a1, false, 4); if (!(warp & 2)) stash<16>(stl, ssw, pk); RET(20);
        G1(21, a1, false, 5); if (!(warp & 2)) stash<16>(stl + 4096, ssw, pv); RET(21);
        A2_SYNC();
        wg_fence();
        wg_ss64t_z(kv, vlo, DH128, klo, DH128); wg_ss64t(kv, vlo + 128, DH128, klo + 128, DH128);
        wg_ss8t_z(zs, klo, DH128, olo, 0); wg_ss8t(zs, klo + 128, DH128, olo, 0);
        wg_commit();
        G1(22, a1, false, 6); RET(22);
        G1(23, a1, false, 7); if (warp & 2) stash<16>(stl, ssw, pk); RET(23);
        if ((warp & 3) == 0) TS(wg, 3);

        G1(24, a2_, true, 0); if (warp & 2) stash<16>(stl + 4096, ssw, pv); RET(24);
        pin(a1);
        A2_SYNC();
        wg_fence();
        wg_ss64t(kv, vlo, DH128, klo, DH128); wg_ss64t(kv, vlo + 128, DH128, klo + 128, DH128);
        wg_ss8t(zs, klo, DH128, olo, 0); wg_ss8t(zs, klo + 128, DH128, olo, 0);
        wg_commit();
        G1(25, a2_, true, 1); RET(25);
        pin(kv); pin(zs);
        G1(26, a2_, true, 2);
#define KV_RED(W) do { asm volatile("red.global.add.v4.f32 [%0], {%1,%2,%3,%4};" :: "l"(kvp + lane * 4), "f"(kv[8 * W]), "f"(kv[8 * W + 1]), "f"(kv[8 * W + 2]), "f"(kv[8 * W + 3]) : "memory"); \
                       asm volatile("red.global.add.v4.f32 [%0], {%1,%2,%3,%4};" :: "l"(kvp + 128 + lane * 4), "f"(kv[8 * W + 4]), "f"(kv[8 * W + 5]), "f"(kv[8 * W + 6]), "f"(kv[8 * W + 7]) : "memory"); } while (0)
        if ((warp & 3) == 0) KV_RED(0); else if ((warp & 3) == 1) KV_RED(1); else if ((warp & 3) == 2) KV_RED(2); else KV_RED(3);
        if ((lane & 3) == 0) {
            asm volatile("red.global.add.f32 [%0], %1;" :: "l"(kvp + 256 + (lane >> 2)), "f"(zs[0]) : "memory");
            asm volatile("red.global.add.f32 [%0], %1;" :: "l"(kvp + 264 + (lane >> 2)), "f"(zs[2]) : "memory");
        }
        __syncwarp();
        if (lane == 0) mbar_arrive(sb + B_KVDONE);
        RET(26);
        G1(27, a2_, true, 3); SCHED(); H_EPI(a1, fh1, 0, 16, 0, 32); RET(27);
        G1(28, a2_, true, 4); RET(28);
        G1(29, a2_, true, 5); send_h<0, 1>(fh1, hsend + 2 * 1024); RET(29);
        G1(30, a2_, true, 6); send_h<1, 2>(fh1, hsend + 2 * 1024); SENT_H(1); RET(30);
        G1(31, a2_, true, 7); RET(31);
        if ((warp & 3) == 0) TS(wg, 4);

        const uint32_t a2 = sb + OFF_X + wg * 8192 + srow;
#define O_HEAD(h) do { uint32_t b0_, b1_, b2_, b3_, z0_, z1_; float n0[4], n1[4], dn[4]; \
            asm volatile("ld.shared.v4.u32 {%0,%1,%2,%3}, [%4];" : "=r"(b0_), "=r"(b1_), "=r"(b2_), "=r"(b3_) : "r"(sb + OFF_KVF + h * 512 + lane * 16) : "memory"); \
            asm volatile("ld.shared.v2.u32 {%0,%1}, [%2];" : "=r"(z0_), "=r"(z1_) : "r"(sb + OFF_ZF + h * 32 + (lane & 3) * 8) : "memory"); \
            mma16816(dn, fo[4 * h], fo[4 * h + 1], fo[4 * h + 2], fo[4 * h + 3], z0_, z1_); \
            mma16816(n0, fo[4 * h], fo[4 * h + 1], fo[4 * h + 2], fo[4 * h + 3], b0_, b1_); \
            mma16816(n1, fo[4 * h], fo[4 * h + 1], fo[4 * h + 2], fo[4 * h + 3], b2_, b3_); \
            const float s_lo = __fdividef(g_lo, dn[0] + 1e-6f), s_hi = __fdividef(g_hi, dn[2] + 1e-6f); \
            const uint32_t sl_ = pack2(s_lo, s_lo), sh_ = pack2(s_hi, s_hi); \
            fo[4 * h] = hmul2(pack2(n0[0], n0[1]), sl_); fo[4 * h + 1] = hmul2(pack2(n0[2], n0[3]), sh_); \
            fo[4 * h + 2] = hmul2(pack2(n1[0], n1[1]), sl_); fo[4 * h + 3] = hmul2(pack2(n1[2], n1[3]), sh_); } while (0)
        G1(32, a3, false, 0); RET(32);
        pin(a2_);
        G1(33, a3, false, 1); SCHED(); H_EPI(a2_, fh3, 0, 8, 32, 48);
        send_h<0, 1>(fh3, hsend + 4 * 1024 - (j & 1) * 1020); SENT_H(2); RET(33);
        G1(34, a3, false, 2); SCHED(); PHI(a2_, fo, 0, 5); RET(34);
        if (elect) mbar_arrive(sb + B_XFREE);
        G1(35, a3, false, 3); SCHED(); PHI(a2_, fo, 5, 11); RET(35);
        G1(36, a3, false, 4); SCHED(); PHI(a2_, fo, 11, 16); RET(36);
        if (elect) mbar_arrive(sb + B_XFREE + 8);
        G1(37, a3, false, 5);
        if ((warp & 3) == 0) TS(wg, 5);
        mbar_wait(sb + B_KVRDY, 0);
        if ((warp & 3) == 0) TS(wg, 6);
        O_HEAD(0); O_HEAD(1);
        RET(37);
        G1(38, a3, false, 6); send_h<0, 1>(fo, hsend + 5 * 1024); SCHED();
        O_HEAD(2); O_HEAD(3);
        RET(38);
        if (elect) mbar_arrive(sb + B_XFREE + 16);
        G1(39, a3, false, 7); send_h<1, 2>(fo, hsend + 5 * 1024); SENT_H(3); RET(39);
        if ((warp & 3) == 0) TS(wg, 7);

#define G2_PIECE(U) ((U) < 5 ? (U) : (U) == 5 ? 6 : (U) == 6 ? 7 : (U) == 7 ? 5 : 8)
#define G2(S, acc, U) do { S_WAIT(S); wg_fence(); _Pragma("unroll") for (int k = 0; k < 4; k++) { \
            if ((U) == 0 && k == 0) wg_ss128_z(acc, xlo, DH128, S_B(S) | LBO8K, DH128); \
            else wg_ss128(acc, xlo + G2_PIECE(U) * 1024 + 2 * k, DH128, (S_B(S) | LBO8K) + 128 * k, DH128); } wg_commit(); } while (0)
#define H_WAIT(P) do { mbar_wait(sb + B_XFULL + 8 * (P), (P) < 8); if (PROF && tid == 0) TS2(150 + (P)); } while (0)
        const int p = j >> 1;
        uint4* const pbase = g_part + (size_t)(r * 2 + (j & 1)) * 16384 + warp * 128 + lane;
        const int pw = (p & 2) ^ 2;
        auto other = [&](int d) { return d == 3 ? p ^ 1 : pw + d - 1; };
        auto sendp = [&](int d) { return pbase + ((other(d) * 4 + p) << 10); };
        auto recvp = [&](int d) { return pbase + ((p * 4 + other(d)) << 10); };

        float p1[64], p2[64];
        H_WAIT(1); G2(40, p1, 0); stash<16>(a2 + 6 * 16384, ssw, fo); RET(40);
        pin(a3);
        G2(41, p1, 1); SCHED(); H_EPI(a3, fh2, 0, 16, 0, 32); send_h<0, 2>(fh2, hsend + 7 * 1024); SENT_H(4); RET(41);
        H_WAIT(2); G2(42, p1, 2); RET(42);
        G2(43, p1, 3); stash<16>(a2 + 7 * 16384, ssw, fh2); RET(43);
        H_WAIT(4); G2(44, p1, 4); RET(44);
        A2_SYNC();
        G2(45, p1, 5); RET(45);
        G2(46, p1, 6); RET(46);
        G2(47, p2, 0); RET(47);
        G2(48, p2, 1); RET(48);
        H_WAIT(5); G2(49, p1, 7); RET(49);
        H_WAIT(8); G2(50, p1, 8); RET(50);
        if ((warp & 3) == 0) TS(wg, 8);
        uint32_t sa[16], sc[16], qa[16], qb[16];
        G2(51, p2, 2); RET(51);
        pin(p1);
        G2(52, p2, 3); SCHED(); pack_sub<0>(sa, p1); send_frag<0, 2>(sa, sendp(1), tag); RET(52);
        G2(53, p2, 4); SCHED(); pack_sub<32>(sc, p1); send_frag<2, 4>(sa, sendp(1), tag); RET(53);
        G2(54, p2, 5); send_frag<0, 2>(sc, sendp(2), tag); RET(54);
        G2(55, p2, 6); send_frag<2, 4>(sc, sendp(2), tag); RET(55);
        G2(56, p2, 7); RET(56);
        G2(57, p2, 8);
        recv_issue(qa, recvp(1)); recv_issue(qb, recvp(2));
        if ((warp & 3) == 0) TS(wg, 9);
        wg_wait<0>();
        pin(p2);
        if ((warp & 3) == 0) TS(wg, 11);
        float sum[32];
        if (p & 1) pack_sub<0>(sa, p2); else pack_sub<32>(sa, p2);
        send_frag<0, 4>(sa, sendp(3), tag);
        recv_issue(sc, recvp(3));
#pragma unroll
        for (int i = 0; i < 32; i++) sum[i] = (p & 1) ? p2[32 + i] : p2[i];
        recv_check(qa, recvp(1), tag); accum(qa, sum);
        recv_check(qb, recvp(2), tag); accum(qb, sum);
        if ((warp & 3) == 0) TS(wg, 12);
        recv_check(sc, recvp(3), tag); accum(sc, sum);
        if ((warp & 3) == 0) TS(wg, 13);
        {
            uint32_t f[16];
            pack_sub<0>(f, sum);
            const uint32_t slab = sb + OFF_X + wg * 8192;
            stash<16>(slab + srow, ssw, f);
            __syncwarp();
            __nv_bfloat16* op = out + (size_t)(r * 128 + warp * 16 + (lane >> 3)) * kD + (j & 1) * 256 + p * 64 + (lane & 7) * 8;
#pragma unroll
            for (int i = 0; i < 4; i++) {
                const int row = i * 4 + (lane >> 3);
                uint4 v;
                asm volatile("ld.shared.v4.u32 {%0,%1,%2,%3}, [%4];" : "=r"(v.x), "=r"(v.y), "=r"(v.z), "=r"(v.w)
                             : "r"(slab + ((warp & 3) * 16 + row) * 128 + (((lane & 7) ^ (row & 7)) << 4)) : "memory");
                *(uint4*)(op + i * 4 * kD) = v;
            }
        }
        if ((warp & 3) == 0) { TS(wg, 14); TSG(wg, 31); }
    }
}

typedef CUresult (*EncodeFn)(CUtensorMap*, CUtensorMapDataType, cuuint32_t, void*, const cuuint64_t*, const cuuint64_t*, const cuuint32_t*,
                             const cuuint32_t*, CUtensorMapInterleave, CUtensorMapSwizzle, CUtensorMapL2promotion, CUtensorMapFloatOOBfill);

static void encode(EncodeFn fn, CUtensorMap* m, int rank, const void* base, const cuuint64_t (&gd)[5], const cuuint64_t (&gs)[4],
                   const cuuint32_t (&bd)[5], CUtensorMapSwizzle sw) {
    cuuint32_t es[5] = {1, 1, 1, 1, 1};
    fn(m, CU_TENSOR_MAP_DATA_TYPE_BFLOAT16, rank, const_cast<void*>(base), gd, gs, bd, es, CU_TENSOR_MAP_INTERLEAVE_NONE, sw,
       CU_TENSOR_MAP_L2_PROMOTION_L2_128B, CU_TENSOR_MAP_FLOAT_OOB_FILL_NONE);
}

extern "C" void kernel_launch(void* const* d_in, const int* in_sizes, int n_in, void* d_out, int out_size) {
    const char* x = (const char*)d_in[0];
    const char* wqkv = (const char*)d_in[1];
    const char* wo = (const char*)d_in[2];
    const char* wg = (const char*)d_in[4];
    const char* wu = (const char*)d_in[5];
    const char* wd = (const char*)d_in[6];
    void* fnp = nullptr;
    cudaDriverEntryPointQueryResult qr;
    cudaGetDriverEntryPoint("cuTensorMapEncodeTiled", &fnp, cudaEnableDefault, &qr);
    EncodeFn fn = (EncodeFn)fnp;
    Maps maps;
    const char* lo = wg < wu ? wg : wu;
    const uint64_t diff = wg < wu ? (uint64_t)(wu - wg) : (uint64_t)(wg - wu);
    const CUtensorMapSwizzle S128 = CU_TENSOR_MAP_SWIZZLE_128B, S64 = CU_TENSOR_MAP_SWIZZLE_64B;
    encode(fn, &maps.x, 2, x, {512, 2048, 1, 1}, {1024, 0, 0}, {64, 128, 1, 1}, S128);
    encode(fn, &maps.gu, 3, lo, {1792, 512, 2, 1}, {3584, diff, 0}, {64, 64, 2, 1}, S128);
    encode(fn, &maps.kv, 3, wqkv, {512, 512, 3, 1}, {3072, 1024, 0}, {64, 64, 2, 1}, S128);
    encode(fn, &maps.q64, 3, wqkv, {32, 512, 48, 1}, {3072, 64, 0}, {32, 64, 2, 1}, S64);
    encode(fn, &maps.gu64, 3, lo, {1792, 512, 2, 1}, {3584, diff, 0}, {32, 64, 2, 1}, S64);
    encode(fn, &maps.wdw, 3, wd, {64, 1792, 8, 1}, {1024, 128, 0}, {64, 64, 2, 1}, S128);
    encode(fn, &maps.wow, 3, wo, {64, 512, 8}, {1024, 128}, {64, 64, 2}, S128);
    encode(fn, &maps.wdp, 5, wd, {512, 2, 4, 4, 56}, {1024, 8192, 2048, 32768}, {64, 2, 4, 4, 2}, S128);
    encode(fn, &maps.wdph, 5, wd, {512, 2, 4, 4, 56}, {1024, 8192, 2048, 32768}, {64, 2, 4, 4, 1}, S128);
    encode(fn, &maps.wop, 5, wo, {512, 2, 4, 4, 16}, {1024, 8192, 2048, 32768}, {64, 2, 4, 4, 2}, S128);
    void* hx = nullptr;
    cudaGetSymbolAddress(&hx, g_hx);
    encode(fn, &maps.hx, 2, hx, {64, 16 * 4 * 9 * 128}, {128}, {64, 128}, S128);
    encode(fn, &maps.hx2, 2, hx, {64, 16 * 4 * 9 * 128}, {128}, {64, 256}, S128);
    cudaFuncSetAttribute(fused_kernel, cudaFuncAttributeMaxDynamicSharedMemorySize, SMEM_BYTES);
    cudaLaunchConfig_t cfg = {};
    cfg.gridDim = dim3(128);
    cfg.blockDim = dim3(384);
    cfg.dynamicSmemBytes = SMEM_BYTES;
    cfg.stream = cudaStreamPerThread;
    cudaLaunchAttribute at[1];
    at[0].id = cudaLaunchAttributeClusterDimension;
    at[0].val.clusterDim.x = 2; at[0].val.clusterDim.y = 1; at[0].val.clusterDim.z = 1;
    cfg.attrs = at;
    cfg.numAttrs = MC ? 1 : 0;
    cudaLaunchKernelEx(&cfg, fused_kernel, maps, (const __nv_bfloat16*)d_in[0], (const __nv_bfloat16*)d_in[7], wqkv, wg, wu, wd, wo, (__nv_bfloat16*)d_out);
}
```

```cpp
#include <cuda_runtime.h>
#include <cuda.h>
#include <cuda_bf16.h>
#include <stdint.h>

#define MC 0
#define PFMODE 2
#define PROF 0

namespace {

constexpr int kD = 512;
constexpr uint32_t OFF_X = 0, OFF_STG = 131072, OFF_RING = 147456, OFF_MISC = 229376;
constexpr uint32_t B_FULL = OFF_MISC, B_EMPTY = OFF_MISC + 40, B_XFULL = OFF_MISC + 80;
constexpr uint32_t B_GRDY = OFF_MISC + 152, B_KVDONE = OFF_MISC + 160, B_KVRDY = OFF_MISC + 168;
constexpr uint32_t B_HSENT = OFF_MISC + 176, B_XFREE = OFF_MISC + 216;
constexpr uint32_t OFF_EPOCH = OFF_MISC + 240, OFF_G = OFF_MISC + 256;
constexpr uint32_t OFF_KVF = OFF_MISC + 768, OFF_ZF = OFF_KVF + 2048;
constexpr uint32_t OFF_ONES = OFF_ZF + 128;
constexpr uint32_t SMEM_BYTES = OFF_ONES + 128;
constexpr uint32_t SPIN_GLOBAL = 1u << 14;

struct alignas(64) Maps { CUtensorMap x, gu, kv, q64, gu64, wdw, wow, wdp, wdph, wop, hx, hx2; };

}

__device__ uint4 g_part[16 * 2 * 4 * 4 * 1024];
__device__ uint4 g_hx[16 * 4 * 9 * 1024];
__device__ unsigned g_hflag[128 * 8];
__device__ uint4 g_gx[16 * 32];
__device__ float g_kvacc[2 * 8 * 4 * 272];
__device__ unsigned g_kvcnt[8 * 32];
__device__ unsigned g_epoch[128];
#define TS(role, idx)
#define TS2(idx)
#define TSG(role, idx)

namespace {

__device__ __forceinline__ void mbar_init(uint32_t bar, uint32_t cnt) { asm volatile("mbarrier.init.shared::cta.b64 [%0], %1;" :: "r"(bar), "r"(cnt) : "memory"); }
__device__ __forceinline__ void mbar_expect(uint32_t bar, uint32_t bytes) { asm volatile("mbarrier.arrive.expect_tx.shared::cta.b64 _, [%0], %1;" :: "r"(bar), "r"(bytes) : "memory"); }
__device__ __forceinline__ void mbar_arrive(uint32_t bar) { asm volatile("mbarrier.arrive.shared::cta.b64 _, [%0];" :: "r"(bar) : "memory"); }
__device__ __forceinline__ void mbar_arrive_cta(uint32_t bar, uint32_t cta) {
    asm volatile("{\n.reg .b32 ra;\nmapa.shared::cluster.u32 ra, %0, %1;\nmbarrier.arrive.shared::cluster.b64 _, [ra];\n}" :: "r"(bar), "r"(cta) : "memory");
}
__device__ __forceinline__ void mbar_wait(uint32_t bar, uint32_t parity) {
    asm volatile("{\n.reg .pred p;\n.reg .u32 c;\n"
                 "mbarrier.try_wait.parity.shared::cta.b64 p, [%0], %1;\n@p bra DONE;\n"
                 "mov.u32 c, 0;\nLAB_WAIT:\nmbarrier.try_wait.parity.shared::cta.b64 p, [%0], %1;\n@p bra DONE;\n"
                 "add.u32 c, c, 1;\nsetp.lt.u32 p, c, 65536;\n@p bra LAB_WAIT;\nDONE:\n}" :: "r"(bar), "r"(parity) : "memory");
}
__device__ __forceinline__ void tma2(uint32_t dst, const CUtensorMap* m, int c0, int c1, uint32_t bar) {
    asm volatile("cp.async.bulk.tensor.2d.shared::cluster.global.mbarrier::complete_tx::bytes [%0], [%1, {%3, %4}], [%2];"
        :: "r"(dst), "l"(m), "r"(bar), "r"(c0), "r"(c1) : "memory");
}
__device__ __forceinline__ void tmaw2(uint32_t dst, const CUtensorMap* m, int c0, int c1, uint32_t bar) {
    tma2(dst, m, c0, c1, bar);
}
__device__ __forceinline__ void tmaw3(uint32_t dst, const CUtensorMap* m, int c0, int c1, int c2, uint32_t bar) {
    asm volatile("cp.async.bulk.tensor.3d.shared::cluster.global.mbarrier::complete_tx::bytes [%0], [%1, {%3, %4, %5}], [%2];"
        :: "r"(dst), "l"(m), "r"(bar), "r"(c0), "r"(c1), "r"(c2) : "memory");
}
__device__ __forceinline__ void tmaw5(uint32_t dst, const CUtensorMap* m, int c0, int c4, uint32_t bar) {
    asm volatile("cp.async.bulk.tensor.5d.shared::cluster.global.mbarrier::complete_tx::bytes [%0], [%1, {%3, %5, %5, %5, %4}], [%2];"
        :: "r"(dst), "l"(m), "r"(bar), "r"(c0), "r"(c4), "r"(0) : "memory");
}
__device__ __forceinline__ void l2_prefetch(const void* p, uint32_t bytes) { asm volatile("cp.async.bulk.prefetch.L2.global [%0], %1;" :: "l"(p), "r"(bytes) : "memory"); }
__device__ __forceinline__ void wg_fence() { asm volatile("wgmma.fence.sync.aligned;" ::: "memory"); }
__device__ __forceinline__ void wg_commit() { asm volatile("wgmma.commit_group.sync.aligned;" ::: "memory"); }
template <int N> __device__ __forceinline__ void wg_wait() { asm volatile("wgmma.wait_group.sync.aligned %0;" :: "n"(N) : "memory"); }
template <int N> __device__ __forceinline__ void pin(float (&d)[N]) {
#pragma unroll
    for (int i = 0; i < N; i++) asm volatile("" : "+f"(d[i]) :: "memory");
}
__device__ __forceinline__ uint32_t pack2(float lo, float hi) { uint32_t r; asm("cvt.rn.bf16x2.f32 %0, %1, %2;" : "=r"(r) : "f"(hi), "f"(lo)); return r; }
__device__ __forceinline__ uint32_t hmul2(uint32_t a, uint32_t b) { uint32_t r; asm("mul.bf16x2 %0, %1, %2;" : "=r"(r) : "r"(a), "r"(b)); return r; }
__device__ __forceinline__ uint32_t phi2(float t0, float t1) {
    float e0, e1;
    asm("ex2.approx.ftz.f32 %0, %1;" : "=f"(e0) : "f"(t0 * 1.4426950408889634f));
    asm("ex2.approx.ftz.f32 %0, %1;" : "=f"(e1) : "f"(t1 * 1.4426950408889634f));
    uint32_t e = pack2(e0, e1), t = pack2(t0, t1), r;
    asm("min.bf16x2 %0, %0, %1;" : "+r"(e) : "r"(0x3f803f80u));
    asm("max.bf16x2 %0, %0, %1;" : "+r"(t) : "r"(0x35863586u));
    asm("add.bf16x2 %0, %1, %2;" : "=r"(r) : "r"(e), "r"(t));
    return r;
}
__device__ __forceinline__ void stsm4(uint32_t a, uint32_t r0, uint32_t r1, uint32_t r2, uint32_t r3) {
    asm volatile("stmatrix.sync.aligned.m8n8.x4.shared.b16 [%0], {%1,%2,%3,%4};" :: "r"(a), "r"(r0), "r"(r1), "r"(r2), "r"(r3) : "memory");
}
__device__ __forceinline__ void mma16816(float (&c)[4], uint32_t a0, uint32_t a1, uint32_t a2, uint32_t a3, uint32_t b0, uint32_t b1) {
    asm volatile("mma.sync.aligned.m16n8k16.row.col.f32.bf16.bf16.f32 {%0,%1,%2,%3}, {%4,%5,%6,%7}, {%8,%9}, {%10,%10,%10,%10};"
        : "=f"(c[0]), "=f"(c[1]), "=f"(c[2]), "=f"(c[3]) : "r"(a0), "r"(a1), "r"(a2), "r"(a3), "r"(b0), "r"(b1), "f"(0.f));
}
__device__ __forceinline__ float bf_lo(uint32_t w) { return __uint_as_float(w << 16); }
__device__ __forceinline__ float bf_hi(uint32_t w) { return __uint_as_float(w & 0xffff0000u); }
__device__ __forceinline__ void st_pkt(uint4* p, uint32_t w0, uint32_t w1, uint32_t w2, uint32_t w3) {
    asm volatile("{\n.reg .b64 lo, hi;\n.reg .b128 v;\nmov.b64 lo, {%1, %2};\nmov.b64 hi, {%3, %4};\nmov.b128 v, {lo, hi};\nst.relaxed.gpu.global.b128 [%0], v;\n}"
        :: "l"(p), "r"(w0), "r"(w1), "r"(w2), "r"(w3) : "memory");
}
__device__ __forceinline__ void ld_pkt(const uint4* p, uint32_t& w0, uint32_t& w1, uint32_t& w2, uint32_t& w3) {
    asm volatile("{\n.reg .b64 lo, hi;\n.reg .b128 v;\nld.relaxed.gpu.global.b128 v, [%4];\nmov.b128 {lo, hi}, v;\nmov.b64 {%0, %1}, lo;\nmov.b64 {%2, %3}, hi;\n}"
        : "=r"(w0), "=r"(w1), "=r"(w2), "=r"(w3) : "l"(p) : "memory");
}

__device__ __forceinline__ void wg_ss128(float (&d)[64], uint32_t alo, uint32_t ahi, uint32_t blo, uint32_t bhi) {
    asm volatile("{\n.reg .b64 da, db;\nmov.b64 da, {%64, %65};\nmov.b64 db, {%66, %67};\n"
        "wgmma.mma_async.sync.aligned.m64n128k16.f32.bf16.bf16 {%0,%1,%2,%3,%4,%5,%6,%7,%8,%9,%10,%11,%12,%13,%14,%15,%16,%17,%18,%19,%20,%21,%22,%23,%24,%25,%26,%27,%28,%29,%30,%31,%32,%33,%34,%35,%36,%37,%38,%39,%40,%41,%42,%43,%44,%45,%46,%47,%48,%49,%50,%51,%52,%53,%54,%55,%56,%57,%58,%59,%60,%61,%62,%63}, da, db, 1, 1, 1, 0, 1;\n}\n"
        : "+f"(d[0]),"+f"(d[1]),"+f"(d[2]),"+f"(d[3]),"+f"(d[4]),"+f"(d[5]),"+f"(d[6]),"+f"(d[7]),"+f"(d[8]),"+f"(d[9]),"+f"(d[10]),"+f"(d[11]),"+f"(d[12]),"+f"(d[13]),"+f"(d[14]),"+f"(d[15]),"+f"(d[16]),"+f"(d[17]),"+f"(d[18]),"+f"(d[19]),"+f"(d[20]),"+f"(d[21]),"+f"(d[22]),"+f"(d[23]),"+f"(d[24]),"+f"(d[25]),"+f"(d[26]),"+f"(d[27]),"+f"(d[28]),"+f"(d[29]),"+f"(d[30]),"+f"(d[31]),"+f"(d[32]),"+f"(d[33]),"+f"(d[34]),"+f"(d[35]),"+f"(d[36]),"+f"(d[37]),"+f"(d[38]),"+f"(d[39]),"+f"(d[40]),"+f"(d[41]),"+f"(d[42]),"+f"(d[43]),"+f"(d[44]),"+f"(d[45]),"+f"(d[46]),"+f"(d[47]),"+f"(d[48]),"+f"(d[49]),"+f"(d[50]),"+f"(d[51]),"+f"(d[52]),"+f"(d[53]),"+f"(d[54]),"+f"(d[55]),"+f"(d[56]),"+f"(d[57]),"+f"(d[58]),"+f"(d[59]),"+f"(d[60]),"+f"(d[61]),"+f"(d[62]),"+f"(d[63])
        : "r"(alo), "r"(ahi), "r"(blo), "r"(bhi));
}
__device__ __forceinline__ void wg_ss128_z(float (&d)[64], uint32_t alo, uint32_t ahi, uint32_t blo, uint32_t bhi) {
    asm volatile("{\n.reg .b64 da, db;\nmov.b64 da, {%64, %65};\nmov.b64 db, {%66, %67};\n"
        "wgmma.mma_async.sync.aligned.m64n128k16.f32.bf16.bf16 {%0,%1,%2,%3,%4,%5,%6,%7,%8,%9,%10,%11,%12,%13,%14,%15,%16,%17,%18,%19,%20,%21,%22,%23,%24,%25,%26,%27,%28,%29,%30,%31,%32,%33,%34,%35,%36,%37,%38,%39,%40,%41,%42,%43,%44,%45,%46,%47,%48,%49,%50,%51,%52,%53,%54,%55,%56,%57,%58,%59,%60,%61,%62,%63}, da, db, 0, 1, 1, 0, 1;\n}\n"
        : "=f"(d[0]),"=f"(d[1]),"=f"(d[2]),"=f"(d[3]),"=f"(d[4]),"=f"(d[5]),"=f"(d[6]),"=f"(d[7]),"=f"(d[8]),"=f"(d[9]),"=f"(d[10]),"=f"(d[11]),"=f"(d[12]),"=f"(d[13]),"=f"(d[14]),"=f"(d[15]),"=f"(d[16]),"=f"(d[17]),"=f"(d[18]),"=f"(d[19]),"=f"(d[20]),"=f"(d[21]),"=f"(d[22]),"=f"(d[23]),"=f"(d[24]),"=f"(d[25]),"=f"(d[26]),"=f"(d[27]),"=f"(d[28]),"=f"(d[29]),"=f"(d[30]),"=f"(d[31]),"=f"(d[32]),"=f"(d[33]),"=f"(d[34]),"=f"(d[35]),"=f"(d[36]),"=f"(d[37]),"=f"(d[38]),"=f"(d[39]),"=f"(d[40]),"=f"(d[41]),"=f"(d[42]),"=f"(d[43]),"=f"(d[44]),"=f"(d[45]),"=f"(d[46]),"=f"(d[47]),"=f"(d[48]),"=f"(d[49]),"=f"(d[50]),"=f"(d[51]),"=f"(d[52]),"=f"(d[53]),"=f"(d[54]),"=f"(d[55]),"=f"(d[56]),"=f"(d[57]),"=f"(d[58]),"=f"(d[59]),"=f"(d[60]),"=f"(d[61]),"=f"(d[62]),"=f"(d[63])
        : "r"(alo), "r"(ahi), "r"(blo), "r"(bhi));
}
__device__ __forceinline__ void wg_ss64(float (&d)[32], uint32_t alo, uint32_t ahi, uint32_t blo, uint32_t bhi) {
    asm volatile("{\n.reg .b64 da, db;\nmov.b64 da, {%32, %33};\nmov.b64 db, {%34, %35};\n"
        "wgmma.mma_async.sync.aligned.m64n64k16.f32.bf16.bf16 {%0,%1,%2,%3,%4,%5,%6,%7,%8,%9,%10,%11,%12,%13,%14,%15,%16,%17,%18,%19,%20,%21,%22,%23,%24,%25,%26,%27,%28,%29,%30,%31}, da, db, 1, 1, 1, 0, 1;\n}\n"
        : "+f"(d[0]),"+f"(d[1]),"+f"(d[2]),"+f"(d[3]),"+f"(d[4]),"+f"(d[5]),"+f"(d[6]),"+f"(d[7]),"+f"(d[8]),"+f"(d[9]),"+f"(d[10]),"+f"(d[11]),"+f"(d[12]),"+f"(d[13]),"+f"(d[14]),"+f"(d[15]),"+f"(d[16]),"+f"(d[17]),"+f"(d[18]),"+f"(d[19]),"+f"(d[20]),"+f"(d[21]),"+f"(d[22]),"+f"(d[23]),"+f"(d[24]),"+f"(d[25]),"+f"(d[26]),"+f"(d[27]),"+f"(d[28]),"+f"(d[29]),"+f"(d[30]),"+f"(d[31])
        : "r"(alo), "r"(ahi), "r"(blo), "r"(bhi));
}
__device__ __forceinline__ void wg_ss64_z(float (&d)[32], uint32_t alo, uint32_t ahi, uint32_t blo, uint32_t bhi) {
    asm volatile("{\n.reg .b64 da, db;\nmov.b64 da, {%32, %33};\nmov.b64 db, {%34, %35};\n"
        "wgmma.mma_async.sync.aligned.m64n64k16.f32.bf16.bf16 {%0,%1,%2,%3,%4,%5,%6,%7,%8,%9,%10,%11,%12,%13,%14,%15,%16,%17,%18,%19,%20,%21,%22,%23,%24,%25,%26,%27,%28,%29,%30,%31}, da, db, 0, 1, 1, 0, 1;\n}\n"
        : "=f"(d[0]),"=f"(d[1]),"=f"(d[2]),"=f"(d[3]),"=f"(d[4]),"=f"(d[5]),"=f"(d[6]),"=f"(d[7]),"=f"(d[8]),"=f"(d[9]),"=f"(d[10]),"=f"(d[11]),"=f"(d[12]),"=f"(d[13]),"=f"(d[14]),"=f"(d[15]),"=f"(d[16]),"=f"(d[17]),"=f"(d[18]),"=f"(d[19]),"=f"(d[20]),"=f"(d[21]),"=f"(d[22]),"=f"(d[23]),"=f"(d[24]),"=f"(d[25]),"=f"(d[26]),"=f"(d[27]),"=f"(d[28]),"=f"(d[29]),"=f"(d[30]),"=f"(d[31])
        : "r"(alo), "r"(ahi), "r"(blo), "r"(bhi));
}
__device__ __forceinline__ void wg_ss64t(float (&d)[32], uint32_t alo, uint32_t ahi, uint32_t blo, uint32_t bhi) {
    asm volatile("{\n.reg .b64 da, db;\nmov.b64 da, {%32, %33};\nmov.b64 db, {%34, %35};\n"
        "wgmma.mma_async.sync.aligned.m64n64k16.f32.bf16.bf16 {%0,%1,%2,%3,%4,%5,%6,%7,%8,%9,%10,%11,%12,%13,%14,%15,%16,%17,%18,%19,%20,%21,%22,%23,%24,%25,%26,%27,%28,%29,%30,%31}, da, db, 1, 1, 1, 1, 1;\n}\n"
        : "+f"(d[0]),"+f"(d[1]),"+f"(d[2]),"+f"(d[3]),"+f"(d[4]),"+f"(d[5]),"+f"(d[6]),"+f"(d[7]),"+f"(d[8]),"+f"(d[9]),"+f"(d[10]),"+f"(d[11]),"+f"(d[12]),"+f"(d[13]),"+f"(d[14]),"+f"(d[15]),"+f"(d[16]),"+f"(d[17]),"+f"(d[18]),"+f"(d[19]),"+f"(d[20]),"+f"(d[21]),"+f"(d[22]),"+f"(d[23]),"+f"(d[24]),"+f"(d[25]),"+f"(d[26]),"+f"(d[27]),"+f"(d[28]),"+f"(d[29]),"+f"(d[30]),"+f"(d[31])
        : "r"(alo), "r"(ahi), "r"(blo), "r"(bhi));
}
__device__ __forceinline__ void wg_ss64t_z(float (&d)[32], uint32_t alo, uint32_t ahi, uint32_t blo, uint32_t bhi) {
    asm volatile("{\n.reg .b64 da, db;\nmov.b64 da, {%32, %33};\nmov.b64 db, {%34, %35};\n"
        "wgmma.mma_async.sync.aligned.m64n64k16.f32.bf16.bf16 {%0,%1,%2,%3,%4,%5,%6,%7,%8,%9,%10,%11,%12,%13,%14,%15,%16,%17,%18,%19,%20,%21,%22,%23,%24,%25,%26,%27,%28,%29,%30,%31}, da, db, 0, 1, 1, 1, 1;\n}\n"
        : "=f"(d[0]),"=f"(d[1]),"=f"(d[2]),"=f"(d[3]),"=f"(d[4]),"=f"(d[5]),"=f"(d[6]),"=f"(d[7]),"=f"(d[8]),"=f"(d[9]),"=f"(d[10]),"=f"(d[11]),"=f"(d[12]),"=f"(d[13]),"=f"(d[14]),"=f"(d[15]),"=f"(d[16]),"=f"(d[17]),"=f"(d[18]),"=f"(d[19]),"=f"(d[20]),"=f"(d[21]),"=f"(d[22]),"=f"(d[23]),"=f"(d[24]),"=f"(d[25]),"=f"(d[26]),"=f"(d[27]),"=f"(d[28]),"=f"(d[29]),"=f"(d[30]),"=f"(d[31])
        : "r"(alo), "r"(ahi), "r"(blo), "r"(bhi));
}
__device__ __forceinline__ void wg_ss8t(float (&d)[4], uint32_t alo, uint32_t ahi, uint32_t blo, uint32_t bhi) {
    asm volatile("{\n.reg .b64 da, db;\nmov.b64 da, {%4, %5};\nmov.b64 db, {%6, %7};\n"
        "wgmma.mma_async.sync.aligned.m64n8k16.f32.bf16.bf16 {%0,%1,%2,%3}, da, db, 1, 1, 1, 1, 0;\n}\n"
        : "+f"(d[0]),"+f"(d[1]),"+f"(d[2]),"+f"(d[3])
        : "r"(alo), "r"(ahi), "r"(blo), "r"(bhi));
}
__device__ __forceinline__ void wg_ss8t_z(float (&d)[4], uint32_t alo, uint32_t ahi, uint32_t blo, uint32_t bhi) {
    asm volatile("{\n.reg .b64 da, db;\nmov.b64 da, {%4, %5};\nmov.b64 db, {%6, %7};\n"
        "wgmma.mma_async.sync.aligned.m64n8k16.f32.bf16.bf16 {%0,%1,%2,%3}, da, db, 0, 1, 1, 1, 0;\n}\n"
        : "=f"(d[0]),"=f"(d[1]),"=f"(d[2]),"=f"(d[3])
        : "r"(alo), "r"(ahi), "r"(blo), "r"(bhi));
}

constexpr uint32_t DH128 = 64u | 0x40000000u;
constexpr uint32_t DH64 = 32u | 0x80000000u;
constexpr uint32_t LBO4K = (4096u >> 4) << 16, LBO8K = (8192u >> 4) << 16, LBO1 = 1u << 16;

template <bool SW64, bool FIRST> __device__ __forceinline__ void g1_issue(float (&acc)[64], uint32_t alo, uint32_t blo) {
    wg_fence();
#pragma unroll
    for (int k = 0; k < 4; k++) {
        if (FIRST && k == 0) wg_ss128_z(acc, alo, DH128, blo, SW64 ? DH64 : DH128);
        else wg_ss128(acc, alo + 2 * k, DH128, blo + (SW64 ? 64 * k : 128 * k), SW64 ? DH64 : DH128);
    }
    wg_commit();
}

template <int N> __device__ __forceinline__ void stash(uint32_t base, uint32_t sw, const uint32_t (&f)[N]) {
#pragma unroll
    for (int t = 0; t < N / 4; t++) stsm4(base + ((sw ^ (2 * t)) << 4), f[4 * t], f[4 * t + 1], f[4 * t + 2], f[4 * t + 3]);
}

template <int V0, int V1, int N> __device__ __forceinline__ void send_frag(const uint32_t (&f)[N], uint4* p, uint32_t tag) {
#pragma unroll
    for (int v = V0; v < V1; v++) st_pkt(p + (v & 3) * 32, (f[4 * v] & ~1u) | tag, f[4 * v + 1], f[4 * v + 2], f[4 * v + 3]);
}
template <int H0, int H1, int N> __device__ __forceinline__ void send_h(const uint32_t (&f)[N], uint4* p) {
#pragma unroll
    for (int h = H0; h < H1; h++) {
        p[4 * h] = make_uint4(f[8 * h], f[8 * h + 2], f[8 * h + 4], f[8 * h + 6]);
        p[4 * h + 64] = make_uint4(f[8 * h + 1], f[8 * h + 3], f[8 * h + 5], f[8 * h + 7]);
    }
}
template <int O, int N, int M> __device__ __forceinline__ void pack_sub(uint32_t (&f)[N], const float (&acc)[M]) {
#pragma unroll
    for (int i = 0; i < N; i++) f[i] = pack2(acc[O + 2 * i], acc[O + 2 * i + 1]);
}
template <int N> __device__ __forceinline__ void recv_issue(uint32_t (&q)[N], const uint4* p) {
#pragma unroll
    for (int v = 0; v < N / 4; v++) ld_pkt(p + v * 32, q[4 * v], q[4 * v + 1], q[4 * v + 2], q[4 * v + 3]);
}
template <int N> __device__ __forceinline__ void recv_check(uint32_t (&q)[N], const uint4* p, uint32_t tag) {
    uint32_t it = 0;
    while (true) {
        uint32_t bad = 0;
#pragma unroll
        for (int v = 0; v < N / 4; v++) bad |= q[4 * v] ^ tag;
        if (__all_sync(0xffffffffu, (bad & 1u) == 0) || ++it > SPIN_GLOBAL) break;
        recv_issue(q, p);
    }
}
__device__ __forceinline__ void accum(const uint32_t (&q)[16], float (&sum)[32]) {
#pragma unroll
    for (int i = 0; i < 16; i++) { sum[2 * i] += bf_lo(q[i]); sum[2 * i + 1] += bf_hi(q[i]); }
}

}

__global__ void __launch_bounds__(384, 1)
fused_kernel(const __grid_constant__ Maps maps, const __nv_bfloat16* __restrict__ xg, const __nv_bfloat16* __restrict__ gate_w,
             const char* __restrict__ pf_qkv, const char* __restrict__ pf_g, const char* __restrict__ pf_u,
             const char* __restrict__ pf_d, const char* __restrict__ pf_o, __nv_bfloat16* __restrict__ out) {
    extern __shared__ __align__(1024) uint8_t smem_raw[];
    const uint32_t sb = (uint32_t)__cvta_generic_to_shared(smem_raw);
    const int tid = threadIdx.x, lane = tid & 31;
    const int warp = __shfl_sync(0xffffffffu, tid >> 5, 0);
    const int j = (blockIdx.x >> 1) & 7;
    const int r = ((blockIdx.x >> 4) << 1) | (blockIdx.x & 1);
    const uint32_t rank = blockIdx.x & 1;

    if (warp == 0) { TSG(0, 30); TS(0, 0); }
    if (tid == 256) {
        for (int i = 0; i < 5; i++) { mbar_init(sb + B_FULL + 8 * i, 1); mbar_init(sb + B_EMPTY + 8 * i, MC ? 4 : 2); }
        for (int i = 0; i < 9; i++) mbar_init(sb + B_XFULL + 8 * i, 1);
        asm volatile("fence.mbarrier_init.release.cluster;" ::: "memory");
        mbar_expect(sb + B_XFULL, 16384);
        tma2(sb + OFF_X, &maps.x, 0, r * 128, sb + B_XFULL);
        TS2(0);
        mbar_expect(sb + B_FULL, 16384);
        tmaw3(sb + OFF_RING, &maps.gu, 224 * j, 0, 0, sb + B_FULL);
        TS2(1);
        mbar_expect(sb + B_FULL + 8, 16384);
        tmaw3(sb + OFF_RING + 16384, &maps.kv, 64 * j, 0, 1, sb + B_FULL + 8);
    } else if (tid == 288) {
        for (int i = 0; i < 5; i++) mbar_init(sb + B_HSENT + 8 * i, 8);
        mbar_init(sb + B_XFREE, 2); mbar_init(sb + B_XFREE + 8, 2); mbar_init(sb + B_XFREE + 16, 2);
        mbar_init(sb + B_GRDY, 1); mbar_init(sb + B_KVDONE, 8); mbar_init(sb + B_KVRDY, 2);
        asm volatile("fence.mbarrier_init.release.cluster;" ::: "memory");
    } else if (warp == 10 && lane < 11) {
        asm volatile("prefetch.tensormap [%0];" :: "l"(&maps.gu + lane) : "memory");
    }
    __syncthreads();

    if (warp >= 8) {
        asm volatile("setmaxnreg.dec.sync.aligned.u32 72;");
        if (warp == 8) {
            if (lane == 0) {
                int slot = MC ? 0 : 2, ph = 1;
                uint32_t full, dst;
                if (!MC) { mbar_expect(sb + B_XFULL + 8, 16384); tma2(sb + OFF_X + 16384, &maps.x, 64, r * 128, sb + B_XFULL + 8); }
#define P_BEGIN(S, BYTES) full = sb + B_FULL + 8 * slot; dst = sb + OFF_RING + slot * 16384; \
                mbar_wait(sb + B_EMPTY + 8 * slot, ph); TS2(S); mbar_expect(full, BYTES); if (!MC || (((S) ^ rank) & 1) == 0)
#define P_END() if (++slot == 5) { slot = 0; ph ^= 1; }
                for (int s = MC ? 0 : 2; s < 16; s++) {
                    P_BEGIN(s, 16384) {
                        const int sw = s == 13 ? 14 : s == 14 ? 13 : s;
                        if (sw & 1) tmaw3(dst, &maps.kv, 64 * j, 32 * (sw - 1), 1, full);
                        else tmaw3(dst, &maps.gu, 224 * j, 32 * sw, 0, full);
                    }
                    const int xb = (s == 4) ? 3 : (s == 10) ? 7 : !(s & 1) ? 0 : (s < 5) ? (s + 1) / 2 : (s <= 9) ? (s + 3) / 2 : 0;
                    if (xb) { mbar_expect(sb + B_XFULL + 8 * xb, 16384); tma2(sb + OFF_X + xb * 16384, &maps.x, 64 * xb, r * 128, sb + B_XFULL + 8 * xb); }
                    P_END()
                }
                for (int s = 0; s < 24; s++) {
                    P_BEGIN(16 + s, 16384) {
                        if ((s >> 3) == 1) {
                            tmaw3(dst, &maps.q64, 0, 64 * (s & 7), 2 * j, full);
                            tmaw3(dst + 8192, &maps.gu64, 224 * j + 192, 64 * (s & 7), 0, full);
                        } else {
                            tmaw3(dst, &maps.gu, 224 * j + 64 + 4 * (s & 16), 64 * (s & 7), 0, full);
                        }
                    }
                    P_END()
                }
                const int p = j >> 1;
#pragma unroll 1
                for (int i = 0; i < 18; i++) {
                    const int t = i < 14 ? i : i < 16 ? i + 2 : i - 2;
                    const int q = (t >= 7 && t != 9 && t != 10), u = t < 7 ? t : t < 9 ? t - 7 : t < 11 ? t - 2 : t - 9;
                    const int cw = (j & 1) * 4 + ((p & 2) ^ (q ? 0 : 2)), cc = 64 * cw;
                    if (t < 16) {
                        full = sb + B_FULL + 8 * slot; dst = sb + OFF_RING + slot * 16384;
                        mbar_wait(sb + B_EMPTY + 8 * slot, ph);
                        P_END()
                    } else {
                        full = sb + B_XFULL + (t - 16) * 24; dst = sb + OFF_X + (t - 16) * 16384;
                        mbar_wait(sb + B_XFREE + 8 * (t - 16), 1);
                    }
                    TS2(40 + t);
                    mbar_expect(full, 16384);
                    if (!MC || ((t ^ rank) & 1) == 0) {
                        if (u == 4) {
                            tmaw5(dst, &maps.wdph, cc, 14 * p + 6, full); tmaw5(dst + 4096, &maps.wdph, cc, 14 * p + 13, full);
                            tmaw5(dst + 8192, &maps.wdph, cc + 64, 14 * p + 6, full); tmaw5(dst + 12288, &maps.wdph, cc + 64, 14 * p + 13, full);
                        } else if (u == 5 || u == 6) {
                            tmaw3(dst, u == 5 ? &maps.wow : &maps.wdw, 0, u == 5 ? 64 * j : 224 * j + 128, cw, full);
                        } else {
                            const CUtensorMap* m = u == 7 ? &maps.wop : &maps.wdp;
                            const int g = u == 7 ? 2 * (j ^ 1) : u == 8 ? 7 * (j ^ 1) + 4 : 14 * p + 7 * (u & 1) + (u & 2);
                            tmaw5(dst, m, cc, g, full); tmaw5(dst + 8192, m, cc + 64, g, full);
                        }
                    }
                }
            }
        } else if (warp < 11) {
            const int hx = warp - 9;
            uint32_t epoch;
            asm volatile("ld.relaxed.gpu.global.u32 %0, [%1];" : "=r"(epoch) : "l"(g_epoch + blockIdx.x) : "memory");
            {
                const uint4* xr = (const uint4*)(xg + (size_t)(r * 128 + j * 16 + hx * 8) * kD) + lane;
                const uint4 wa = __ldg((const uint4*)gate_w + lane), wb = __ldg((const uint4*)gate_w + 32 + lane);
                const uint32_t tag = (epoch + 1) & 1;
                uint4* gp = g_gx + r * 32;
                if (lane < 2) st_pkt(gp + j * 4 + hx * 2 + lane, tag ^ 1, 0, 0, 0);
                float s[8];
#pragma unroll
                for (int i0 = 0; i0 < 8; i0 += 4) {
                    uint4 va[4], vb[4];
#pragma unroll
                    for (int i = 0; i < 4; i++) { va[i] = __ldg(xr + (i0 + i) * 64); vb[i] = __ldg(xr + (i0 + i) * 64 + 32); }
#pragma unroll
                    for (int i = 0; i < 4; i++) {
                        float t0 = bf_lo(va[i].x) * bf_lo(wa.x), t1 = bf_hi(va[i].x) * bf_hi(wa.x);
                        t0 = fmaf(bf_lo(va[i].y), bf_lo(wa.y), t0); t1 = fmaf(bf_hi(va[i].y), bf_hi(wa.y), t1);
                        t0 = fmaf(bf_lo(va[i].z), bf_lo(wa.z), t0); t1 = fmaf(bf_hi(va[i].z), bf_hi(wa.z), t1);
                        t0 = fmaf(bf_lo(va[i].w), bf_lo(wa.w), t0); t1 = fmaf(bf_hi(va[i].w), bf_hi(wa.w), t1);
                        t0 = fmaf(bf_lo(vb[i].x), bf_lo(wb.x), t0); t1 = fmaf(bf_hi(vb[i].x), bf_hi(wb.x), t1);
                        t0 = fmaf(bf_lo(vb[i].y), bf_lo(wb.y), t0); t1 = fmaf(bf_hi(vb[i].y), bf_hi(wb.y), t1);
                        t0 = fmaf(bf_lo(vb[i].z), bf_lo(wb.z), t0); t1 = fmaf(bf_hi(vb[i].z), bf_hi(wb.z), t1);
                        t0 = fmaf(bf_lo(vb[i].w), bf_lo(wb.w), t0); t1 = fmaf(bf_hi(vb[i].w), bf_hi(wb.w), t1);
                        s[i0 + i] = t0 + t1;
                    }
                }
#pragma unroll
                for (int i = 0; i < 8; i++) {
#pragma unroll
                    for (int o = 16; o; o >>= 1) s[i] += __shfl_xor_sync(0xffffffffu, s[i], o);
                    s[i] = 1.f / (1.f + __expf(-s[i]));
                }
                if (lane < 2) {
                    const float v0 = lane ? s[4] : s[0], v1 = lane ? s[5] : s[1], v2 = lane ? s[6] : s[2], v3 = lane ? s[7] : s[3];
                    st_pkt(gp + j * 4 + hx * 2 + lane, (__float_as_uint(v0) & ~1u) | tag, __float_as_uint(v1), __float_as_uint(v2), __float_as_uint(v3));
                }
                if (hx == 1) {
                    asm volatile("st.shared.u32 [%0], %1;" :: "r"(sb + OFF_ONES + lane * 4), "r"(0x3f803f80u) : "memory");
                    asm volatile("fence.proxy.async.shared::cta;" ::: "memory");
                }
                asm volatile("bar.sync 3, 96;" ::: "memory");
                if (hx == 0) {
                    uint32_t q[4];
                    recv_issue(q, gp + lane);
                    recv_check(q, gp + lane, tag);
                    asm volatile("st.shared.v4.u32 [%0], {%1,%2,%3,%4};" :: "r"(sb + OFF_G + lane * 16), "r"(q[0]), "r"(q[1]), "r"(q[2]), "r"(q[3]) : "memory");
                    if (lane == 0) {
                        asm volatile("st.shared.u32 [%0], %1;" :: "r"(sb + OFF_EPOCH), "r"(epoch) : "memory");
                        g_epoch[blockIdx.x] = epoch + 1;
                    }
                    __syncwarp();
                    if (lane == 0) mbar_arrive(sb + B_GRDY);
                } else {
                    if (r == 0) {
                        float4* zp = (float4*)(g_kvacc + (((epoch & 1) ^ 1) * 8 + j) * 4 * 272);
                        for (int i = lane; i < 272; i += 32) zp[i] = make_float4(0.f, 0.f, 0.f, 0.f);
                    }
                }
            }
            TS(2 + hx, 1);
#define PUBLISH_H(B) do { mbar_wait(sb + B_HSENT + 8 * (B), 0); if (lane == 0) { \
                asm volatile("st.release.gpu.global.u32 [%0], %1;" :: "l"(g_hflag + (r * 8 + j) * 8 + (B)), "r"(epoch + 1) : "memory"); } __syncwarp(); } while (0)
            if (hx == 1) {
#pragma unroll 1
                for (int b = 0; b < 4; b++) { PUBLISH_H(b); TS(3, 5 + b); }
            } else {
                const float* accp = g_kvacc + ((epoch & 1) * 8 + j) * 4 * 272;
                unsigned* cnt = g_kvcnt + j * 32;
                mbar_wait(sb + B_KVDONE, 0);
                TS(2, 5);
                if (lane == 0) asm volatile("red.release.gpu.global.add.u32 [%0], 1;" :: "l"(cnt) : "memory");
                __syncwarp();
                TS(2, 2);
                {
                    const unsigned target = 16u * (epoch + 1);
                    uint32_t it = 0, v;
                    do {
                        asm volatile("ld.acquire.gpu.global.u32 %0, [%1];" : "=r"(v) : "l"(cnt) : "memory");
                    } while ((int)(v - target) < 0 && ++it < SPIN_GLOBAL);
                }
                TS(2, 3);
#pragma unroll
                for (int h = 0; h < 4; h++) {
                    const float4 d0 = __ldcg((const float4*)(accp + h * 272) + lane);
                    const float4 d1 = __ldcg((const float4*)(accp + h * 272 + 128) + lane);
                    const float2 z0 = __ldcg((const float2*)(accp + h * 272 + 256) + (lane & 3));
                    const float2 z1 = __ldcg((const float2*)(accp + h * 272 + 264) + (lane & 3));
                    asm volatile("st.shared.v4.u32 [%0], {%1,%2,%3,%4};" :: "r"(sb + OFF_KVF + h * 512 + lane * 16),
                                 "r"(pack2(d0.x, d0.y)), "r"(pack2(d1.x, d1.y)), "r"(pack2(d0.z, d0.w)), "r"(pack2(d1.z, d1.w)) : "memory");
                    if (lane < 4) asm volatile("st.shared.v2.u32 [%0], {%1,%2};" :: "r"(sb + OFF_ZF + h * 32 + lane * 8), "r"(pack2(z0.x, z0.y)), "r"(pack2(z1.x, z1.y)) : "memory");
                }
                __syncwarp();
                if (lane == 0) mbar_arrive(sb + B_KVRDY);
                TS(2, 4);
                PUBLISH_H(4);
                TS(3, 9);
            }
        } else {
            uint32_t epoch;
            asm volatile("ld.relaxed.gpu.global.u32 %0, [%1];" : "=r"(epoch) : "l"(g_epoch + blockIdx.x) : "memory");
            asm volatile("bar.arrive 3, 96;" :: "r"(epoch) : "memory");
            const int b = blockIdx.x, p = j >> 1;
            mbar_wait(sb + B_XFULL, 0);
            {
                uint4* mb = g_part + (size_t)(r * 2 + (j & 1)) * 16384 + (((p ^ 1) * 4 + p) << 10) + lane;
#pragma unroll 8
                for (int i = 0; i < 32; i++) st_pkt(mb + i * 32, epoch & 1, 0, 0, 0);
                __syncwarp();
                if (lane == 0) mbar_arrive(sb + B_KVRDY);
            }
            mbar_wait(sb + B_XFULL + 8 * 7, 0);
#pragma unroll
            for (int i = 0; i < 4; i++)
                if (i < 3 || lane < 16) asm volatile("prefetch.global.L2 [%0];" :: "l"(pf_d + b * 14336 + (i * 32 + lane) * 128));
            asm volatile("prefetch.global.L2 [%0];" :: "l"(pf_o + b * 4096 + lane * 128));
            {
                const uint32_t want = epoch + 1;
                const int hrow = (r * 4 + p) * 9 * 128, po = (j & 1) ^ 1;
                const unsigned* fl = g_hflag + (r * 8 + (j & 6)) * 8 + (lane & 15);
                uint32_t it = 0;
                int i = 0;
                mbar_wait(sb + B_HSENT + 8, 0);
#pragma unroll 1
                while (i < 5 && ++it < SPIN_GLOBAL) {
                    uint32_t v;
                    asm volatile("ld.acquire.gpu.global.u32 %0, [%1];" : "=r"(v) : "l"(fl) : "memory");
                    const uint32_t rdy = __ballot_sync(0xffffffffu, v == want);
#pragma unroll 1
                    while (i < 5) {
                        const uint32_t need = i < 3 ? 0x101u << i : 1u << (8 * po + i);
                        if ((rdy & need) != need) break;
                        if (i < 3) mbar_wait(sb + B_XFREE + 8 * i, 0);
                        if (lane == 0) {
                            asm volatile("fence.proxy.async.global;" ::: "memory");
                            const int piece = i < 3 ? 2 * i : i == 3 ? 5 : 8, tile = i < 3 ? 2 * i : 2 * i - 1 + po;
                            const uint32_t bar = sb + B_XFULL + 8 * (i == 0 ? 1 : piece);
                            TS2(140 + i);
                            mbar_expect(bar, i < 2 ? 32768 : 16384);
                            tma2(sb + OFF_X + piece * 16384, i < 2 ? &maps.hx2 : &maps.hx, 0, hrow + tile * 128, bar);
                        }
                        i++;
                    }
                }
            }
        }
    } else {
        asm volatile("setmaxnreg.inc.sync.aligned.u32 216;");
        const int wg = warp >> 2;
        const bool elect = (tid & 127) == 0;
        const uint32_t xlo = ((sb + OFF_X + wg * 8192) >> 4) | LBO1;
        const uint32_t ringlo = (sb + OFF_RING) >> 4;
        auto release = [&](int s) {
            if (elect) {
                mbar_arrive(sb + B_EMPTY + 8 * s);
            }
        };
#define S_WAIT(S) do { if ((S) < 56) mbar_wait(sb + B_FULL + 8 * ((S) % 5), ((S) / 5) & 1); else mbar_wait(sb + B_XFULL + ((S) - 56) * 24, 1); \
            if (PROF && tid == 0) TS2(64 + (S)); } while (0)
#define S_B(S) ((S) < 56 ? ringlo + ((S) % 5) * 1024 : ((sb + OFF_X) >> 4) + ((S) - 56) * 1024)
#define G1(S, acc, SW, KB) do { S_WAIT(S); g1_issue<SW, (KB) == 0>(acc, xlo + (KB) * 1024, S_B(S) | (SW ? LBO4K : LBO8K)); } while (0)
#define RET(S) do { wg_wait<1>(); if ((S) - 1 < 51) release(((S) - 1) % 5); } while (0)
#define SCHED() mbar_wait(sb + B_XFULL + 8 * 7, 0)
#define A2_SYNC() do { asm volatile("fence.proxy.async.shared::cta;" ::: "memory"); asm volatile("bar.sync %0, 128;" :: "r"(wg + 1) : "memory"); } while (0)
#define H_EPI(acc, F, I0, I1, OG, OU) _Pragma("unroll") for (int i = (I0); i < (I1); i++) \
            F[i] = hmul2(pack2(acc[(OG) + 2 * i] * acc[(OU) + 2 * i], acc[(OG) + 2 * i + 1] * acc[(OU) + 2 * i + 1]), (i & 1) ? m_hi : m_lo)
#define PHI(acc, F, I0, I1) _Pragma("unroll") for (int i = (I0); i < (I1); i++) F[i] = phi2(acc[2 * i], acc[2 * i + 1])

        float a0[64], b0[64], a1[64], a2_[64], a3[64];
        mbar_wait(sb + B_XFULL, 0);
        G1(0, a0, false, 0);
        if ((warp & 3) == 0) TS(wg, 1);
        G1(1, b0, false, 0); RET(1);
#define C0(KB) mbar_wait(sb + B_XFULL + 8 * (KB), 0); if (PROF && tid == 0) TS2(128 + (KB)); \
        G1(2 * (KB), a0, false, KB); RET(2 * (KB)); G1(2 * (KB) + 1, b0, false, KB); RET(2 * (KB) + 1)
        C0(1); C0(2); C0(3); C0(4); C0(5);
        mbar_wait(sb + B_XFULL + 8 * 6, 0);
        G1(12, a0, false, 6); RET(12);
        mbar_wait(sb + B_XFULL + 8 * 7, 0);
        G1(13, a0, false, 7); RET(13);
        G1(14, b0, false, 6);
        mbar_wait(sb + B_GRDY, 0);
        float g_lo, g_hi;
        uint32_t tag;
        {
            const uint32_t ga = sb + OFF_G + (warp * 16 + (lane >> 2)) * 4;
            asm volatile("ld.shared.f32 %0, [%1];" : "=f"(g_lo) : "r"(ga) : "memory");
            asm volatile("ld.shared.f32 %0, [%1];" : "=f"(g_hi) : "r"(ga + 32) : "memory");
            asm volatile("ld.shared.u32 %0, [%1];" : "=r"(tag) : "r"(sb + OFF_EPOCH) : "memory");
        }
        float* const kvp = g_kvacc + (((tag & 1) * 8 + j) * 4 + (warp & 3)) * 272;
        tag = (tag + 1) & 1;
        const uint32_t m_lo = pack2(1.f - g_lo, 1.f - g_lo), m_hi = pack2(1.f - g_hi, 1.f - g_hi);
        const uint32_t lrow = ((lane & 7) + 8 * ((lane >> 3) & 1)) * 128;
        const uint32_t srow = (warp & 3) * 2048 + lrow;
        const uint32_t ssw = (lane >> 4) ^ (lane & 7);
        uint4* const hsend = g_hx + (size_t)((r * 4 + (j >> 1)) * 9 + (j & 1)) * 1024 + warp * 128 + (lane >> 2) * 8 + (lane & 3);
#define SENT_H(B) do { __syncwarp(); if (lane == 0) mbar_arrive(sb + B_HSENT + 8 * (B)); } while (0)
        RET(14);
        pin(a0);
        uint32_t fh0[16], fh1[16], fh2[16], fh3[8], fo[16];
        G1(15, b0, false, 7); SCHED(); H_EPI(a0, fh0, 0, 16, 0, 32); RET(15);
        if ((warp & 3) == 0) TS(wg, 2);

        float kv[32], zs[4];
        uint32_t pk[16], pv[16];
        const uint32_t stg = sb + OFF_STG + wg * 8192, stl = stg + (warp & 1) * 2048 + lrow;
        const uint32_t klo = (stg >> 4) | LBO1, vlo = klo + 256, olo = (sb + OFF_ONES) >> 4;
        G1(16, a1, false, 0); RET(16);
        pin(b0);
        G1(17, a1, false, 1); send_h<0, 1>(fh0, hsend); SCHED(); PHI(b0, pk, 0, 6); RET(17);
        G1(18, a1, false, 2); send_h<1, 2>(fh0, hsend); SENT_H(0); SCHED(); PHI(b0, pk, 6, 12); RET(18);
        G1(19, a1, false, 3); SCHED(); PHI(b0, pk, 12, 16); pack_sub<32>(pv, b0); RET(19);
        G1(20, a1, false, 4); if (!(warp & 2)) stash<16>(stl, ssw, pk); RET(20);
        G1(21, a1, false, 5); if (!(warp & 2)) stash<16>(stl + 4096, ssw, pv); RET(21);
        G1(22, a1, false, 6);
        A2_SYNC();
        wg_fence();
        wg_ss64t_z(kv, vlo, DH128, klo, DH128); wg_ss64t(kv, vlo + 128, DH128, klo + 128, DH128);
        wg_ss8t_z(zs, klo, DH128, olo, 0); wg_ss8t(zs, klo + 128, DH128, olo, 0);
        wg_commit();
        wg_wait<2>(); release(21 % 5);
        G1(23, a1, false, 7); RET(23);
        if ((warp & 3) == 0) TS(wg, 3);

        G1(24, a2_, true, 0); if (warp & 2) stash<16>(stl, ssw, pk); RET(24);
        pin(a1);
        G1(25, a2_, true, 1); if (warp & 2) stash<16>(stl + 4096, ssw, pv); RET(25);
        G1(26, a2_, true, 2);
        A2_SYNC();
        wg_fence();
        wg_ss64t(kv, vlo, DH128, klo, DH128); wg_ss64t(kv, vlo + 128, DH128, klo + 128, DH128);
        wg_ss8t(zs, klo, DH128, olo, 0); wg_ss8t(zs, klo + 128, DH128, olo, 0);
        wg_commit();
        wg_wait<2>(); release(25 % 5);
        G1(27, a2_, true, 3); SCHED(); H_EPI(a1, fh1, 0, 16, 0, 32); RET(27);
        pin(kv); pin(zs);
        G1(28, a2_, true, 4);
#define KV_RED(W) do { asm volatile("red.global.add.v4.f32 [%0], {%1,%2,%3,%4};" :: "l"(kvp + lane * 4), "f"(kv[8 * W]), "f"(kv[8 * W + 1]), "f"(kv[8 * W + 2]), "f"(kv[8 * W + 3]) : "memory"); \
                       asm volatile("red.global.add.v4.f32 [%0], {%1,%2,%3,%4};" :: "l"(kvp + 128 + lane * 4), "f"(kv[8 * W + 4]), "f"(kv[8 * W + 5]), "f"(kv[8 * W + 6]), "f"(kv[8 * W + 7]) : "memory"); } while (0)
        if ((warp & 3) == 0) KV_RED(0); else if ((warp & 3) == 1) KV_RED(1); else if ((warp & 3) == 2) KV_RED(2); else KV_RED(3);
        if ((lane & 3) == 0) {
            asm volatile("red.global.add.f32 [%0], %1;" :: "l"(kvp + 256 + (lane >> 2)), "f"(zs[0]) : "memory");
            asm volatile("red.global.add.f32 [%0], %1;" :: "l"(kvp + 264 + (lane >> 2)), "f"(zs[2]) : "memory");
        }
        __syncwarp();
        if (lane == 0) mbar_arrive(sb + B_KVDONE);
        RET(28);
        G1(29, a2_, true, 5); send_h<0, 1>(fh1, hsend + 2 * 1024); RET(29);
        G1(30, a2_, true, 6); send_h<1, 2>(fh1, hsend + 2 * 1024); SENT_H(1); RET(30);
        G1(31, a2_, true, 7); RET(31);
        if ((warp & 3) == 0) TS(wg, 4);

        const uint32_t a2 = sb + OFF_X + wg * 8192 + srow;
#define O_HEADS(h0) do { uint32_t kb_[2][6]; float n0[2][4], n1[2][4], dn[2][4]; \
            _Pragma("unroll") for (int i = 0; i < 2; i++) { \
                asm volatile("ld.shared.v4.u32 {%0,%1,%2,%3}, [%4];" : "=r"(kb_[i][0]), "=r"(kb_[i][1]), "=r"(kb_[i][2]), "=r"(kb_[i][3]) : "r"(sb + OFF_KVF + (h0 + i) * 512 + lane * 16) : "memory"); \
                asm volatile("ld.shared.v2.u32 {%0,%1}, [%2];" : "=r"(kb_[i][4]), "=r"(kb_[i][5]) : "r"(sb + OFF_ZF + (h0 + i) * 32 + (lane & 3) * 8) : "memory"); } \
            _Pragma("unroll") for (int i = 0; i < 2; i++) { const int f_ = 4 * (h0 + i); \
                mma16816(dn[i], fo[f_], fo[f_ + 1], fo[f_ + 2], fo[f_ + 3], kb_[i][4], kb_[i][5]); } \
            _Pragma("unroll") for (int i = 0; i < 2; i++) { const int f_ = 4 * (h0 + i); \
                mma16816(n0[i], fo[f_], fo[f_ + 1], fo[f_ + 2], fo[f_ + 3], kb_[i][0], kb_[i][1]); \
                mma16816(n1[i], fo[f_], fo[f_ + 1], fo[f_ + 2], fo[f_ + 3], kb_[i][2], kb_[i][3]); } \
            _Pragma("unroll") for (int i = 0; i < 2; i++) { const int f_ = 4 * (h0 + i); \
                const float s_lo = __fdividef(g_lo, dn[i][0] + 1e-6f), s_hi = __fdividef(g_hi, dn[i][2] + 1e-6f); \
                const uint32_t sl_ = pack2(s_lo, s_lo), sh_ = pack2(s_hi, s_hi); \
                fo[f_] = hmul2(pack2(n0[i][0], n0[i][1]), sl_); fo[f_ + 1] = hmul2(pack2(n0[i][2], n0[i][3]), sh_); \
                fo[f_ + 2] = hmul2(pack2(n1[i][0], n1[i][1]), sl_); fo[f_ + 3] = hmul2(pack2(n1[i][2], n1[i][3]), sh_); } } while (0)
        G1(32, a3, false, 0); RET(32);
        pin(a2_);
        G1(33, a3, false, 1); SCHED(); H_EPI(a2_, fh3, 0, 8, 32, 48);
        send_h<0, 1>(fh3, hsend + 4 * 1024 - (j & 1) * 1020); SENT_H(2); RET(33);
        G1(34, a3, false, 2); SCHED(); PHI(a2_, fo, 0, 4); RET(34);
        if (elect) mbar_arrive(sb + B_XFREE);
        G1(35, a3, false, 3); SCHED(); PHI(a2_, fo, 4, 8); RET(35);
        G1(36, a3, false, 4); SCHED(); PHI(a2_, fo, 8, 12); RET(36);
        if (elect) mbar_arrive(sb + B_XFREE + 8);
        G1(37, a3, false, 5); SCHED(); PHI(a2_, fo, 12, 16); RET(37);
        G1(38, a3, false, 6);
        if ((warp & 3) == 0) TS(wg, 5);
        mbar_wait(sb + B_KVRDY, 0);
        if ((warp & 3) == 0) TS(wg, 6);
        O_HEADS(0);
        if ((warp & 3) == 0) TS(wg, 15);
        RET(38);
        if (elect) mbar_arrive(sb + B_XFREE + 16);
        G1(39, a3, false, 7); send_h<0, 1>(fo, hsend + 5 * 1024); SCHED();
        O_HEADS(2);
        send_h<1, 2>(fo, hsend + 5 * 1024); SENT_H(3);
        RET(39);
        if ((warp & 3) == 0) TS(wg, 7);

#define G2_PIECE(U) ((U) < 5 ? (U) : (U) == 5 ? 6 : (U) == 6 ? 7 : (U) == 7 ? 5 : 8)
#define G2(S, acc, U) do { S_WAIT(S); wg_fence(); _Pragma("unroll") for (int k = 0; k < 4; k++) { \
            if ((U) == 0 && k == 0) wg_ss128_z(acc, xlo, DH128, S_B(S) | LBO8K, DH128); \
            else wg_ss128(acc, xlo + G2_PIECE(U) * 1024 + 2 * k, DH128, (S_B(S) | LBO8K) + 128 * k, DH128); } wg_commit(); } while (0)
#define H_WAIT(P) do { mbar_wait(sb + B_XFULL + 8 * (P), (P) < 8); if (PROF && tid == 0) TS2(150 + (P)); } while (0)
        const int p = j >> 1;
        uint4* const pbase = g_part + (size_t)(r * 2 + (j & 1)) * 16384 + warp * 128 + lane;
        const int pw = (p & 2) ^ 2;
        auto other = [&](int d) { return d == 3 ? p ^ 1 : pw + d - 1; };
        auto sendp = [&](int d) { return pbase + ((other(d) * 4 + p) << 10); };
        auto recvp = [&](int d) { return pbase + ((p * 4 + other(d)) << 10); };

        float p1[64], p2[64];
        H_WAIT(1); G2(40, p1, 0); stash<16>(a2 + 6 * 16384, ssw, fo); RET(40);
        pin(a3);
        G2(41, p1, 1); SCHED(); H_EPI(a3, fh2, 0, 16, 0, 32); send_h<0, 2>(fh2, hsend + 7 * 1024); SENT_H(4); RET(41);
        H_WAIT(2); G2(42, p1, 2); RET(42);
        G2(43, p1, 3); stash<16>(a2 + 7 * 16384, ssw, fh2); RET(43);
        H_WAIT(4); G2(44, p1, 4); A2_SYNC(); RET(44);
        G2(45, p1, 5); RET(45);
        G2(46, p1, 6); RET(46);
        G2(47, p2, 0); RET(47);
        G2(48, p2, 1); RET(48);
        if (elect) mbar_arrive(sb + B_XFREE);
        H_WAIT(5); G2(49, p1, 7); RET(49);
        if (elect) mbar_arrive(sb + B_XFREE + 8);
        H_WAIT(8); G2(50, p1, 8); RET(50);
        if ((warp & 3) == 0) TS(wg, 8);
        uint32_t sa[16], sc[16], qa[16], qb[16];
        G2(51, p2, 2); RET(51);
        pin(p1);
        G2(52, p2, 3); SCHED(); pack_sub<0>(sa, p1); send_frag<0, 2>(sa, sendp(1), tag); RET(52);
        G2(53, p2, 4); SCHED(); pack_sub<32>(sc, p1); send_frag<2, 4>(sa, sendp(1), tag); RET(53);
        G2(54, p2, 5); send_frag<0, 2>(sc, sendp(2), tag); RET(54);
        G2(55, p2, 6); send_frag<2, 4>(sc, sendp(2), tag); RET(55);
        G2(56, p2, 7); RET(56);
        G2(57, p2, 8);
        if ((warp & 3) == 0) TS(wg, 9);
        wg_wait<0>();
        pin(p2);
        if ((warp & 3) == 0) TS(wg, 11);
        float sum[32];
        if (p & 1) pack_sub<0>(sa, p2); else pack_sub<32>(sa, p2);
        send_frag<0, 4>(sa, sendp(3), tag);
        recv_issue(qa, recvp(1)); recv_issue(qb, recvp(2)); recv_issue(sc, recvp(3));
#pragma unroll
        for (int i = 0; i < 32; i++) sum[i] = (p & 1) ? p2[32 + i] : p2[i];
        recv_check(qa, recvp(1), tag); accum(qa, sum);
        recv_check(qb, recvp(2), tag); accum(qb, sum);
        if ((warp & 3) == 0) TS(wg, 12);
        recv_check(sc, recvp(3), tag); accum(sc, sum);
        if ((warp & 3) == 0) TS(wg, 13);
        {
            uint32_t f[16];
            pack_sub<0>(f, sum);
            const uint32_t slab = sb + OFF_X + 2 * 16384 + wg * 8192;
            stash<16>(slab + srow, ssw, f);
            __syncwarp();
            __nv_bfloat16* op = out + (size_t)(r * 128 + warp * 16 + (lane >> 3)) * kD + (j & 1) * 256 + p * 64 + (lane & 7) * 8;
#pragma unroll
            for (int i = 0; i < 4; i++) {
                const int row = i * 4 + (lane >> 3);
                uint4 v;
                asm volatile("ld.shared.v4.u32 {%0,%1,%2,%3}, [%4];" : "=r"(v.x), "=r"(v.y), "=r"(v.z), "=r"(v.w)
                             : "r"(slab + ((warp & 3) * 16 + row) * 128 + (((lane & 7) ^ (row & 7)) << 4)) : "memory");
                *(uint4*)(op + i * 4 * kD) = v;
            }
        }
        if ((warp & 3) == 0) { TS(wg, 14); TSG(wg, 31); }
    }
}

typedef CUresult (*EncodeFn)(CUtensorMap*, CUtensorMapDataType, cuuint32_t, void*, const cuuint64_t*, const cuuint64_t*, const cuuint32_t*,
                             const cuuint32_t*, CUtensorMapInterleave, CUtensorMapSwizzle, CUtensorMapL2promotion, CUtensorMapFloatOOBfill);

static void encode(EncodeFn fn, CUtensorMap* m, int rank, const void* base, const cuuint64_t (&gd)[5], const cuuint64_t (&gs)[4],
                   const cuuint32_t (&bd)[5], CUtensorMapSwizzle sw) {
    cuuint32_t es[5] = {1, 1, 1, 1, 1};
    fn(m, CU_TENSOR_MAP_DATA_TYPE_BFLOAT16, rank, const_cast<void*>(base), gd, gs, bd, es, CU_TENSOR_MAP_INTERLEAVE_NONE, sw,
       CU_TENSOR_MAP_L2_PROMOTION_L2_128B, CU_TENSOR_MAP_FLOAT_OOB_FILL_NONE);
}

extern "C" void kernel_launch(void* const* d_in, const int* in_sizes, int n_in, void* d_out, int out_size) {
    const char* x = (const char*)d_in[0];
    const char* wqkv = (const char*)d_in[1];
    const char* wo = (const char*)d_in[2];
    const char* wg = (const char*)d_in[4];
    const char* wu = (const char*)d_in[5];
    const char* wd = (const char*)d_in[6];
    void* fnp = nullptr;
    cudaDriverEntryPointQueryResult qr;
    cudaGetDriverEntryPoint("cuTensorMapEncodeTiled", &fnp, cudaEnableDefault, &qr);
    EncodeFn fn = (EncodeFn)fnp;
    Maps maps;
    const char* lo = wg < wu ? wg : wu;
    const uint64_t diff = wg < wu ? (uint64_t)(wu - wg) : (uint64_t)(wg - wu);
    const CUtensorMapSwizzle S128 = CU_TENSOR_MAP_SWIZZLE_128B, S64 = CU_TENSOR_MAP_SWIZZLE_64B;
    encode(fn, &maps.x, 2, x, {512, 2048, 1, 1}, {1024, 0, 0}, {64, 128, 1, 1}, S128);
    encode(fn, &maps.gu, 3, lo, {1792, 512, 2, 1}, {3584, diff, 0}, {64, 64, 2, 1}, S128);
    encode(fn, &maps.kv, 3, wqkv, {512, 512, 3, 1}, {3072, 1024, 0}, {64, 64, 2, 1}, S128);
    encode(fn, &maps.q64, 3, wqkv, {32, 512, 48, 1}, {3072, 64, 0}, {32, 64, 2, 1}, S64);
    encode(fn, &maps.gu64, 3, lo, {1792, 512, 2, 1}, {3584, diff, 0}, {32, 64, 2, 1}, S64);
    encode(fn, &maps.wdw, 3, wd, {64, 1792, 8, 1}, {1024, 128, 0}, {64, 64, 2, 1}, S128);
    encode(fn, &maps.wow, 3, wo, {64, 512, 8}, {1024, 128}, {64, 64, 2}, S128);
    encode(fn, &maps.wdp, 5, wd, {512, 2, 4, 4, 56}, {1024, 8192, 2048, 32768}, {64, 2, 4, 4, 2}, S128);
    encode(fn, &maps.wdph, 5, wd, {512, 2, 4, 4, 56}, {1024, 8192, 2048, 32768}, {64, 2, 4, 4, 1}, S128);
    encode(fn, &maps.wop, 5, wo, {512, 2, 4, 4, 16}, {1024, 8192, 2048, 32768}, {64, 2, 4, 4, 2}, S128);
    void* hx = nullptr;
    cudaGetSymbolAddress(&hx, g_hx);
    encode(fn, &maps.hx, 2, hx, {64, 16 * 4 * 9 * 128}, {128}, {64, 128}, S128);
    encode(fn, &maps.hx2, 2, hx, {64, 16 * 4 * 9 * 128}, {128}, {64, 256}, S128);
    cudaFuncSetAttribute(fused_kernel, cudaFuncAttributeMaxDynamicSharedMemorySize, SMEM_BYTES);
    cudaLaunchConfig_t cfg = {};
    cfg.gridDim = dim3(128);
    cfg.blockDim = dim3(384);
    cfg.dynamicSmemBytes = SMEM_BYTES;
    cfg.stream = cudaStreamPerThread;
    cudaLaunchAttribute at[1];
    at[0].id = cudaLaunchAttributeClusterDimension;
    at[0].val.clusterDim.x = 2; at[0].val.clusterDim.y = 1; at[0].val.clusterDim.z = 1;
    cfg.attrs = at;
    cfg.numAttrs = MC ? 1 : 0;
    cudaLaunchKernelEx(&cfg, fused_kernel, maps, (const __nv_bfloat16*)d_in[0], (const __nv_bfloat16*)d_in[7], wqkv, wg, wu, wd, wo, (__nv_bfloat16*)d_out);
}
```

```cpp
#include <cuda_runtime.h>
#include <cuda.h>
#include <cuda_bf16.h>
#include <stdint.h>

#define MC 0
#define PFMODE 1
#define PROF 0

namespace {

constexpr int kD = 512;
constexpr uint32_t OFF_X = 0, OFF_STG = 131072, OFF_RING = 147456, OFF_MISC = 229376;
constexpr uint32_t B_FULL = OFF_MISC, B_EMPTY = OFF_MISC + 40, B_XFULL = OFF_MISC + 80;
constexpr uint32_t B_GRDY = OFF_MISC + 152, B_KVDONE = OFF_MISC + 160, B_KVRDY = OFF_MISC + 168;
constexpr uint32_t B_HSENT = OFF_MISC + 176, B_XFREE = OFF_MISC + 216;
constexpr uint32_t OFF_EPOCH = OFF_MISC + 240, OFF_G = OFF_MISC + 256;
constexpr uint32_t OFF_KVF = OFF_MISC + 768, OFF_ZF = OFF_KVF + 2048;
constexpr uint32_t OFF_ONES = OFF_ZF + 128;
constexpr uint32_t SMEM_BYTES = OFF_ONES + 128;
constexpr uint32_t SPIN_GLOBAL = 1u << 14;

struct alignas(64) Maps { CUtensorMap x, gu, kv, q64, gu64, wdw, wow, wdp, wdph, wop, hx, hx2; };

}

__device__ uint4 g_part[16 * 2 * 4 * 4 * 1024];
__device__ uint4 g_hx[16 * 4 * 9 * 1024];
__device__ unsigned g_hflag[128 * 8];
__device__ uint4 g_gx[16 * 32];
__device__ float g_kvacc[2 * 8 * 4 * 272];
__device__ unsigned g_kvcnt[8 * 32];
__device__ unsigned g_epoch[128];
#define TS(role, idx)
#define TS2(idx)
#define TSG(role, idx)

namespace {

__device__ __forceinline__ void mbar_init(uint32_t bar, uint32_t cnt) { asm volatile("mbarrier.init.shared::cta.b64 [%0], %1;" :: "r"(bar), "r"(cnt) : "memory"); }
__device__ __forceinline__ void mbar_expect(uint32_t bar, uint32_t bytes) { asm volatile("mbarrier.arrive.expect_tx.shared::cta.b64 _, [%0], %1;" :: "r"(bar), "r"(bytes) : "memory"); }
__device__ __forceinline__ void mbar_arrive(uint32_t bar) { asm volatile("mbarrier.arrive.shared::cta.b64 _, [%0];" :: "r"(bar) : "memory"); }
__device__ __forceinline__ void mbar_arrive_cta(uint32_t bar, uint32_t cta) {
    asm volatile("{\n.reg .b32 ra;\nmapa.shared::cluster.u32 ra, %0, %1;\nmbarrier.arrive.shared::cluster.b64 _, [ra];\n}" :: "r"(bar), "r"(cta) : "memory");
}
__device__ __forceinline__ void mbar_wait(uint32_t bar, uint32_t parity) {
    asm volatile("{\n.reg .pred p;\n.reg .u32 c;\n"
                 "mbarrier.try_wait.parity.shared::cta.b64 p, [%0], %1;\n@p bra DONE;\n"
                 "mov.u32 c, 0;\nLAB_WAIT:\nmbarrier.try_wait.parity.shared::cta.b64 p, [%0], %1;\n@p bra DONE;\n"
                 "add.u32 c, c, 1;\nsetp.lt.u32 p, c, 65536;\n@p bra LAB_WAIT;\nDONE:\n}" :: "r"(bar), "r"(parity) : "memory");
}
__device__ __forceinline__ void tma2(uint32_t dst, const CUtensorMap* m, int c0, int c1, uint32_t bar) {
    asm volatile("cp.async.bulk.tensor.2d.shared::cluster.global.mbarrier::complete_tx::bytes [%0], [%1, {%3, %4}], [%2];"
        :: "r"(dst), "l"(m), "r"(bar), "r"(c0), "r"(c1) : "memory");
}
__device__ __forceinline__ void tmaw2(uint32_t dst, const CUtensorMap* m, int c0, int c1, uint32_t bar) {
    tma2(dst, m, c0, c1, bar);
}
__device__ __forceinline__ void tmaw3(uint32_t dst, const CUtensorMap* m, int c0, int c1, int c2, uint32_t bar) {
    asm volatile("cp.async.bulk.tensor.3d.shared::cluster.global.mbarrier::complete_tx::bytes [%0], [%1, {%3, %4, %5}], [%2];"
        :: "r"(dst), "l"(m), "r"(bar), "r"(c0), "r"(c1), "r"(c2) : "memory");
}
__device__ __forceinline__ void tmaw5(uint32_t dst, const CUtensorMap* m, int c0, int c4, uint32_t bar) {
    asm volatile("cp.async.bulk.tensor.5d.shared::cluster.global.mbarrier::complete_tx::bytes [%0], [%1, {%3, %5, %5, %5, %4}], [%2];"
        :: "r"(dst), "l"(m), "r"(bar), "r"(c0), "r"(c4), "r"(0) : "memory");
}
__device__ __forceinline__ void wg_fence() { asm volatile("wgmma.fence.sync.aligned;" ::: "memory"); }
__device__ __forceinline__ void wg_commit() { asm volatile("wgmma.commit_group.sync.aligned;" ::: "memory"); }
template <int N> __device__ __forceinline__ void wg_wait() { asm volatile("wgmma.wait_group.sync.aligned %0;" :: "n"(N) : "memory"); }
template <int N> __device__ __forceinline__ void pin(float (&d)[N]) {
#pragma unroll
    for (int i = 0; i < N; i++) asm volatile("" : "+f"(d[i]) :: "memory");
}
__device__ __forceinline__ uint32_t pack2(float lo, float hi) { uint32_t r; asm("cvt.rn.bf16x2.f32 %0, %1, %2;" : "=r"(r) : "f"(hi), "f"(lo)); return r; }
__device__ __forceinline__ uint32_t hmul2(uint32_t a, uint32_t b) { uint32_t r; asm("mul.bf16x2 %0, %1, %2;" : "=r"(r) : "r"(a), "r"(b)); return r; }
__device__ __forceinline__ uint32_t phi2(float t0, float t1) {
    float e0, e1;
    asm("ex2.approx.ftz.f32 %0, %1;" : "=f"(e0) : "f"(t0 * 1.4426950408889634f));
    asm("ex2.approx.ftz.f32 %0, %1;" : "=f"(e1) : "f"(t1 * 1.4426950408889634f));
    uint32_t e = pack2(e0, e1), t = pack2(t0, t1), r;
    asm("min.bf16x2 %0, %0, %1;" : "+r"(e) : "r"(0x3f803f80u));
    asm("max.bf16x2 %0, %0, %1;" : "+r"(t) : "r"(0x35863586u));
    asm("add.bf16x2 %0, %1, %2;" : "=r"(r) : "r"(e), "r"(t));
    return r;
}
__device__ __forceinline__ void stsm4(uint32_t a, uint32_t r0, uint32_t r1, uint32_t r2, uint32_t r3) {
    asm volatile("stmatrix.sync.aligned.m8n8.x4.shared.b16 [%0], {%1,%2,%3,%4};" :: "r"(a), "r"(r0), "r"(r1), "r"(r2), "r"(r3) : "memory");
}
__device__ __forceinline__ void mma16816(float (&c)[4], uint32_t a0, uint32_t a1, uint32_t a2, uint32_t a3, uint32_t b0, uint32_t b1) {
    asm volatile("mma.sync.aligned.m16n8k16.row.col.f32.bf16.bf16.f32 {%0,%1,%2,%3}, {%4,%5,%6,%7}, {%8,%9}, {%10,%10,%10,%10};"
        : "=f"(c[0]), "=f"(c[1]), "=f"(c[2]), "=f"(c[3]) : "r"(a0), "r"(a1), "r"(a2), "r"(a3), "r"(b0), "r"(b1), "f"(0.f));
}
__device__ __forceinline__ float bf_lo(uint32_t w) { return __uint_as_float(w << 16); }
__device__ __forceinline__ float bf_hi(uint32_t w) { return __uint_as_float(w & 0xffff0000u); }
__device__ __forceinline__ void st_pkt(uint4* p, uint32_t w0, uint32_t w1, uint32_t w2, uint32_t w3) {
    asm volatile("{\n.reg .b64 lo, hi;\n.reg .b128 v;\nmov.b64 lo, {%1, %2};\nmov.b64 hi, {%3, %4};\nmov.b128 v, {lo, hi};\nst.relaxed.gpu.global.b128 [%0], v;\n}"
        :: "l"(p), "r"(w0), "r"(w1), "r"(w2), "r"(w3) : "memory");
}
__device__ __forceinline__ void ld_pkt(const uint4* p, uint32_t& w0, uint32_t& w1, uint32_t& w2, uint32_t& w3) {
    asm volatile("{\n.reg .b64 lo, hi;\n.reg .b128 v;\nld.relaxed.gpu.global.b128 v, [%4];\nmov.b128 {lo, hi}, v;\nmov.b64 {%0, %1}, lo;\nmov.b64 {%2, %3}, hi;\n}"
        : "=r"(w0), "=r"(w1), "=r"(w2), "=r"(w3) : "l"(p) : "memory");
}

__device__ __forceinline__ void wg_ss128(float (&d)[64], uint32_t alo, uint32_t ahi, uint32_t blo, uint32_t bhi) {
    asm volatile("{\n.reg .b64 da, db;\nmov.b64 da, {%64, %65};\nmov.b64 db, {%66, %67};\n"
        "wgmma.mma_async.sync.aligned.m64n128k16.f32.bf16.bf16 {%0,%1,%2,%3,%4,%5,%6,%7,%8,%9,%10,%11,%12,%13,%14,%15,%16,%17,%18,%19,%20,%21,%22,%23,%24,%25,%26,%27,%28,%29,%30,%31,%32,%33,%34,%35,%36,%37,%38,%39,%40,%41,%42,%43,%44,%45,%46,%47,%48,%49,%50,%51,%52,%53,%54,%55,%56,%57,%58,%59,%60,%61,%62,%63}, da, db, 1, 1, 1, 0, 1;\n}\n"
        : "+f"(d[0]),"+f"(d[1]),"+f"(d[2]),"+f"(d[3]),"+f"(d[4]),"+f"(d[5]),"+f"(d[6]),"+f"(d[7]),"+f"(d[8]),"+f"(d[9]),"+f"(d[10]),"+f"(d[11]),"+f"(d[12]),"+f"(d[13]),"+f"(d[14]),"+f"(d[15]),"+f"(d[16]),"+f"(d[17]),"+f"(d[18]),"+f"(d[19]),"+f"(d[20]),"+f"(d[21]),"+f"(d[22]),"+f"(d[23]),"+f"(d[24]),"+f"(d[25]),"+f"(d[26]),"+f"(d[27]),"+f"(d[28]),"+f"(d[29]),"+f"(d[30]),"+f"(d[31]),"+f"(d[32]),"+f"(d[33]),"+f"(d[34]),"+f"(d[35]),"+f"(d[36]),"+f"(d[37]),"+f"(d[38]),"+f"(d[39]),"+f"(d[40]),"+f"(d[41]),"+f"(d[42]),"+f"(d[43]),"+f"(d[44]),"+f"(d[45]),"+f"(d[46]),"+f"(d[47]),"+f"(d[48]),"+f"(d[49]),"+f"(d[50]),"+f"(d[51]),"+f"(d[52]),"+f"(d[53]),"+f"(d[54]),"+f"(d[55]),"+f"(d[56]),"+f"(d[57]),"+f"(d[58]),"+f"(d[59]),"+f"(d[60]),"+f"(d[61]),"+f"(d[62]),"+f"(d[63])
        : "r"(alo), "r"(ahi), "r"(blo), "r"(bhi));
}
__device__ __forceinline__ void wg_ss128_z(float (&d)[64], uint32_t alo, uint32_t ahi, uint32_t blo, uint32_t bhi) {
    asm volatile("{\n.reg .b64 da, db;\nmov.b64 da, {%64, %65};\nmov.b64 db, {%66, %67};\n"
        "wgmma.mma_async.sync.aligned.m64n128k16.f32.bf16.bf16 {%0,%1,%2,%3,%4,%5,%6,%7,%8,%9,%10,%11,%12,%13,%14,%15,%16,%17,%18,%19,%20,%21,%22,%23,%24,%25,%26,%27,%28,%29,%30,%31,%32,%33,%34,%35,%36,%37,%38,%39,%40,%41,%42,%43,%44,%45,%46,%47,%48,%49,%50,%51,%52,%53,%54,%55,%56,%57,%58,%59,%60,%61,%62,%63}, da, db, 0, 1, 1, 0, 1;\n}\n"
        : "=f"(d[0]),"=f"(d[1]),"=f"(d[2]),"=f"(d[3]),"=f"(d[4]),"=f"(d[5]),"=f"(d[6]),"=f"(d[7]),"=f"(d[8]),"=f"(d[9]),"=f"(d[10]),"=f"(d[11]),"=f"(d[12]),"=f"(d[13]),"=f"(d[14]),"=f"(d[15]),"=f"(d[16]),"=f"(d[17]),"=f"(d[18]),"=f"(d[19]),"=f"(d[20]),"=f"(d[21]),"=f"(d[22]),"=f"(d[23]),"=f"(d[24]),"=f"(d[25]),"=f"(d[26]),"=f"(d[27]),"=f"(d[28]),"=f"(d[29]),"=f"(d[30]),"=f"(d[31]),"=f"(d[32]),"=f"(d[33]),"=f"(d[34]),"=f"(d[35]),"=f"(d[36]),"=f"(d[37]),"=f"(d[38]),"=f"(d[39]),"=f"(d[40]),"=f"(d[41]),"=f"(d[42]),"=f"(d[43]),"=f"(d[44]),"=f"(d[45]),"=f"(d[46]),"=f"(d[47]),"=f"(d[48]),"=f"(d[49]),"=f"(d[50]),"=f"(d[51]),"=f"(d[52]),"=f"(d[53]),"=f"(d[54]),"=f"(d[55]),"=f"(d[56]),"=f"(d[57]),"=f"(d[58]),"=f"(d[59]),"=f"(d[60]),"=f"(d[61]),"=f"(d[62]),"=f"(d[63])
        : "r"(alo), "r"(ahi), "r"(blo), "r"(bhi));
}
__device__ __forceinline__ void wg_ss64(float (&d)[32], uint32_t alo, uint32_t ahi, uint32_t blo, uint32_t bhi) {
    asm volatile("{\n.reg .b64 da, db;\nmov.b64 da, {%32, %33};\nmov.b64 db, {%34, %35};\n"
        "wgmma.mma_async.sync.aligned.m64n64k16.f32.bf16.bf16 {%0,%1,%2,%3,%4,%5,%6,%7,%8,%9,%10,%11,%12,%13,%14,%15,%16,%17,%18,%19,%20,%21,%22,%23,%24,%25,%26,%27,%28,%29,%30,%31}, da, db, 1, 1, 1, 0, 1;\n}\n"
        : "+f"(d[0]),"+f"(d[1]),"+f"(d[2]),"+f"(d[3]),"+f"(d[4]),"+f"(d[5]),"+f"(d[6]),"+f"(d[7]),"+f"(d[8]),"+f"(d[9]),"+f"(d[10]),"+f"(d[11]),"+f"(d[12]),"+f"(d[13]),"+f"(d[14]),"+f"(d[15]),"+f"(d[16]),"+f"(d[17]),"+f"(d[18]),"+f"(d[19]),"+f"(d[20]),"+f"(d[21]),"+f"(d[22]),"+f"(d[23]),"+f"(d[24]),"+f"(d[25]),"+f"(d[26]),"+f"(d[27]),"+f"(d[28]),"+f"(d[29]),"+f"(d[30]),"+f"(d[31])
        : "r"(alo), "r"(ahi), "r"(blo), "r"(bhi));
}
__device__ __forceinline__ void wg_ss64_z(float (&d)[32], uint32_t alo, uint32_t ahi, uint32_t blo, uint32_t bhi) {
    asm volatile("{\n.reg .b64 da, db;\nmov.b64 da, {%32, %33};\nmov.b64 db, {%34, %35};\n"
        "wgmma.mma_async.sync.aligned.m64n64k16.f32.bf16.bf16 {%0,%1,%2,%3,%4,%5,%6,%7,%8,%9,%10,%11,%12,%13,%14,%15,%16,%17,%18,%19,%20,%21,%22,%23,%24,%25,%26,%27,%28,%29,%30,%31}, da, db, 0, 1, 1, 0, 1;\n}\n"
        : "=f"(d[0]),"=f"(d[1]),"=f"(d[2]),"=f"(d[3]),"=f"(d[4]),"=f"(d[5]),"=f"(d[6]),"=f"(d[7]),"=f"(d[8]),"=f"(d[9]),"=f"(d[10]),"=f"(d[11]),"=f"(d[12]),"=f"(d[13]),"=f"(d[14]),"=f"(d[15]),"=f"(d[16]),"=f"(d[17]),"=f"(d[18]),"=f"(d[19]),"=f"(d[20]),"=f"(d[21]),"=f"(d[22]),"=f"(d[23]),"=f"(d[24]),"=f"(d[25]),"=f"(d[26]),"=f"(d[27]),"=f"(d[28]),"=f"(d[29]),"=f"(d[30]),"=f"(d[31])
        : "r"(alo), "r"(ahi), "r"(blo), "r"(bhi));
}
__device__ __forceinline__ void wg_ss64t(float (&d)[32], uint32_t alo, uint32_t ahi, uint32_t blo, uint32_t bhi) {
    asm volatile("{\n.reg .b64 da, db;\nmov.b64 da, {%32, %33};\nmov.b64 db, {%34, %35};\n"
        "wgmma.mma_async.sync.aligned.m64n64k16.f32.bf16.bf16 {%0,%1,%2,%3,%4,%5,%6,%7,%8,%9,%10,%11,%12,%13,%14,%15,%16,%17,%18,%19,%20,%21,%22,%23,%24,%25,%26,%27,%28,%29,%30,%31}, da, db, 1, 1, 1, 1, 1;\n}\n"
        : "+f"(d[0]),"+f"(d[1]),"+f"(d[2]),"+f"(d[3]),"+f"(d[4]),"+f"(d[5]),"+f"(d[6]),"+f"(d[7]),"+f"(d[8]),"+f"(d[9]),"+f"(d[10]),"+f"(d[11]),"+f"(d[12]),"+f"(d[13]),"+f"(d[14]),"+f"(d[15]),"+f"(d[16]),"+f"(d[17]),"+f"(d[18]),"+f"(d[19]),"+f"(d[20]),"+f"(d[21]),"+f"(d[22]),"+f"(d[23]),"+f"(d[24]),"+f"(d[25]),"+f"(d[26]),"+f"(d[27]),"+f"(d[28]),"+f"(d[29]),"+f"(d[30]),"+f"(d[31])
        : "r"(alo), "r"(ahi), "r"(blo), "r"(bhi));
}
__device__ __forceinline__ void wg_ss64t_z(float (&d)[32], uint32_t alo, uint32_t ahi, uint32_t blo, uint32_t bhi) {
    asm volatile("{\n.reg .b64 da, db;\nmov.b64 da, {%32, %33};\nmov.b64 db, {%34, %35};\n"
        "wgmma.mma_async.sync.aligned.m64n64k16.f32.bf16.bf16 {%0,%1,%2,%3,%4,%5,%6,%7,%8,%9,%10,%11,%12,%13,%14,%15,%16,%17,%18,%19,%20,%21,%22,%23,%24,%25,%26,%27,%28,%29,%30,%31}, da, db, 0, 1, 1, 1, 1;\n}\n"
        : "=f"(d[0]),"=f"(d[1]),"=f"(d[2]),"=f"(d[3]),"=f"(d[4]),"=f"(d[5]),"=f"(d[6]),"=f"(d[7]),"=f"(d[8]),"=f"(d[9]),"=f"(d[10]),"=f"(d[11]),"=f"(d[12]),"=f"(d[13]),"=f"(d[14]),"=f"(d[15]),"=f"(d[16]),"=f"(d[17]),"=f"(d[18]),"=f"(d[19]),"=f"(d[20]),"=f"(d[21]),"=f"(d[22]),"=f"(d[23]),"=f"(d[24]),"=f"(d[25]),"=f"(d[26]),"=f"(d[27]),"=f"(d[28]),"=f"(d[29]),"=f"(d[30]),"=f"(d[31])
        : "r"(alo), "r"(ahi), "r"(blo), "r"(bhi));
}
__device__ __forceinline__ void wg_ss8t(float (&d)[4], uint32_t alo, uint32_t ahi, uint32_t blo, uint32_t bhi) {
    asm volatile("{\n.reg .b64 da, db;\nmov.b64 da, {%4, %5};\nmov.b64 db, {%6, %7};\n"
        "wgmma.mma_async.sync.aligned.m64n8k16.f32.bf16.bf16 {%0,%1,%2,%3}, da, db, 1, 1, 1, 1, 0;\n}\n"
        : "+f"(d[0]),"+f"(d[1]),"+f"(d[2]),"+f"(d[3])
        : "r"(alo), "r"(ahi), "r"(blo), "r"(bhi));
}
__device__ __forceinline__ void wg_ss8t_z(float (&d)[4], uint32_t alo, uint32_t ahi, uint32_t blo, uint32_t bhi) {
    asm volatile("{\n.reg .b64 da, db;\nmov.b64 da, {%4, %5};\nmov.b64 db, {%6, %7};\n"
        "wgmma.mma_async.sync.aligned.m64n8k16.f32.bf16.bf16 {%0,%1,%2,%3}, da, db, 0, 1, 1, 1, 0;\n}\n"
        : "=f"(d[0]),"=f"(d[1]),"=f"(d[2]),"=f"(d[3])
        : "r"(alo), "r"(ahi), "r"(blo), "r"(bhi));
}

constexpr uint32_t DH128 = 64u | 0x40000000u;
constexpr uint32_t DH64 = 32u | 0x80000000u;
constexpr uint32_t LBO4K = (4096u >> 4) << 16, LBO8K = (8192u >> 4) << 16, LBO1 = 1u << 16;

template <bool SW64, bool FIRST> __device__ __forceinline__ void g1_issue(float (&acc)[64], uint32_t alo, uint32_t blo) {
    wg_fence();
#pragma unroll
    for (int k = 0; k < 4; k++) {
        if (FIRST && k == 0) wg_ss128_z(acc, alo, DH128, blo, SW64 ? DH64 : DH128);
        else wg_ss128(acc, alo + 2 * k, DH128, blo + (SW64 ? 64 * k : 128 * k), SW64 ? DH64 : DH128);
    }
    wg_commit();
}

template <int N> __device__ __forceinline__ void stash(uint32_t base, uint32_t sw, const uint32_t (&f)[N]) {
#pragma unroll
    for (int t = 0; t < N / 4; t++) stsm4(base + ((sw ^ (2 * t)) << 4), f[4 * t], f[4 * t + 1], f[4 * t + 2], f[4 * t + 3]);
}

template <int V0, int V1, int N> __device__ __forceinline__ void send_frag(const uint32_t (&f)[N], uint4* p, uint32_t tag) {
#pragma unroll
    for (int v = V0; v < V1; v++) st_pkt(p + (v & 3) * 32, (f[4 * v] & ~1u) | tag, f[4 * v + 1], f[4 * v + 2], f[4 * v + 3]);
}
template <int H0, int H1, int N> __device__ __forceinline__ void send_h(const uint32_t (&f)[N], uint4* p) {
#pragma unroll
    for (int h = H0; h < H1; h++) {
        p[4 * h] = make_uint4(f[8 * h], f[8 * h + 2], f[8 * h + 4], f[8 * h + 6]);
        p[4 * h + 64] = make_uint4(f[8 * h + 1], f[8 * h + 3], f[8 * h + 5], f[8 * h + 7]);
    }
}
template <int O, int N, int M> __device__ __forceinline__ void pack_sub(uint32_t (&f)[N], const float (&acc)[M]) {
#pragma unroll
    for (int i = 0; i < N; i++) f[i] = pack2(acc[O + 2 * i], acc[O + 2 * i + 1]);
}
template <int N> __device__ __forceinline__ void recv_issue(uint32_t (&q)[N], const uint4* p) {
#pragma unroll
    for (int v = 0; v < N / 4; v++) ld_pkt(p + v * 32, q[4 * v], q[4 * v + 1], q[4 * v + 2], q[4 * v + 3]);
}
template <int N> __device__ __forceinline__ void recv_check(uint32_t (&q)[N], const uint4* p, uint32_t tag) {
    uint32_t it = 0;
    while (true) {
        uint32_t bad = 0;
#pragma unroll
        for (int v = 0; v < N / 4; v++) bad |= q[4 * v] ^ tag;
        if (__all_sync(0xffffffffu, (bad & 1u) == 0) || ++it > SPIN_GLOBAL) break;
        recv_issue(q, p);
    }
}
__device__ __forceinline__ void accum(const uint32_t (&q)[16], float (&sum)[32]) {
#pragma unroll
    for (int i = 0; i < 16; i++) { sum[2 * i] += bf_lo(q[i]); sum[2 * i + 1] += bf_hi(q[i]); }
}

}

__global__ void __launch_bounds__(384, 1)
fused_kernel(const __grid_constant__ Maps maps, const __nv_bfloat16* __restrict__ xg, const __nv_bfloat16* __restrict__ gate_w,
             const char* __restrict__ pf_qkv, const char* __restrict__ pf_g, const char* __restrict__ pf_u,
             const char* __restrict__ pf_d, const char* __restrict__ pf_o, __nv_bfloat16* __restrict__ out) {
    extern __shared__ __align__(1024) uint8_t smem_raw[];
    const uint32_t sb = (uint32_t)__cvta_generic_to_shared(smem_raw);
    const int tid = threadIdx.x, lane = tid & 31;
    const int warp = __shfl_sync(0xffffffffu, tid >> 5, 0);
    const int j = (blockIdx.x >> 1) & 7;
    const int r = ((blockIdx.x >> 4) << 1) | (blockIdx.x & 1);
    const uint32_t rank = blockIdx.x & 1;

    if (warp == 0) { TSG(0, 30); TS(0, 0); }
    if (tid == 256) {
        for (int i = 0; i < 5; i++) { mbar_init(sb + B_FULL + 8 * i, 1); mbar_init(sb + B_EMPTY + 8 * i, MC ? 4 : 2); }
        for (int i = 0; i < 9; i++) mbar_init(sb + B_XFULL + 8 * i, 1);
        asm volatile("fence.mbarrier_init.release.cluster;" ::: "memory");
        mbar_expect(sb + B_XFULL, 16384);
        tma2(sb + OFF_X, &maps.x, 0, r * 128, sb + B_XFULL);
        TS2(0);
        mbar_expect(sb + B_FULL, 16384);
        tmaw3(sb + OFF_RING, &maps.gu, 224 * j, 0, 0, sb + B_FULL);
        TS2(1);
        mbar_expect(sb + B_FULL + 8, 16384);
        tmaw3(sb + OFF_RING + 16384, &maps.kv, 64 * j, 0, 1, sb + B_FULL + 8);
    } else if (tid == 288) {
        for (int i = 0; i < 5; i++) mbar_init(sb + B_HSENT + 8 * i, 8);
        mbar_init(sb + B_XFREE, 2); mbar_init(sb + B_XFREE + 8, 2); mbar_init(sb + B_XFREE + 16, 2);
        mbar_init(sb + B_GRDY, 1); mbar_init(sb + B_KVDONE, 8); mbar_init(sb + B_KVRDY, 2);
        asm volatile("fence.mbarrier_init.release.cluster;" ::: "memory");
    } else if (warp == 10 && lane < 11) {
        asm volatile("prefetch.tensormap [%0];" :: "l"(&maps.gu + lane) : "memory");
    }
    __syncthreads();

    if (warp >= 8) {
        asm volatile("setmaxnreg.dec.sync.aligned.u32 72;");
        if (warp == 8) {
            if (lane == 0) {
                int slot = MC ? 0 : 2, ph = 1;
                uint32_t full, dst;
                if (!MC) { mbar_expect(sb + B_XFULL + 8, 16384); tma2(sb + OFF_X + 16384, &maps.x, 64, r * 128, sb + B_XFULL + 8); }
#define P_BEGIN(S, BYTES) full = sb + B_FULL + 8 * slot; dst = sb + OFF_RING + slot * 16384; \
                mbar_wait(sb + B_EMPTY + 8 * slot, ph); TS2(S); mbar_expect(full, BYTES); if (!MC || (((S) ^ rank) & 1) == 0)
#define P_END() if (++slot == 5) { slot = 0; ph ^= 1; }
                for (int s = MC ? 0 : 2; s < 16; s++) {
                    P_BEGIN(s, 16384) {
                        const int sw = s == 13 ? 14 : s == 14 ? 13 : s;
                        if (sw & 1) tmaw3(dst, &maps.kv, 64 * j, 32 * (sw - 1), 1, full);
                        else tmaw3(dst, &maps.gu, 224 * j, 32 * sw, 0, full);
                    }
                    const int xb = (s == 4) ? 3 : (s == 10) ? 7 : !(s & 1) ? 0 : (s < 5) ? (s + 1) / 2 : (s <= 9) ? (s + 3) / 2 : 0;
                    if (xb) { mbar_expect(sb + B_XFULL + 8 * xb, 16384); tma2(sb + OFF_X + xb * 16384, &maps.x, 64 * xb, r * 128, sb + B_XFULL + 8 * xb); }
                    P_END()
                }
                for (int s = 0; s < 24; s++) {
                    P_BEGIN(16 + s, 16384) {
                        if ((s >> 3) == 1) {
                            tmaw3(dst, &maps.q64, 0, 64 * (s & 7), 2 * j, full);
                            tmaw3(dst + 8192, &maps.gu64, 224 * j + 192, 64 * (s & 7), 0, full);
                        } else {
                            tmaw3(dst, &maps.gu, 224 * j + 64 + 4 * (s & 16), 64 * (s & 7), 0, full);
                        }
                    }
                    P_END()
                }
                const int p = j >> 1;
#pragma unroll 1
                for (int i = 0; i < 18; i++) {
                    const int t = i < 14 ? i : i < 16 ? i + 2 : i - 2;
                    const int q = (t >= 7 && t != 9 && t != 10), u = t < 7 ? t : t < 9 ? t - 7 : t < 11 ? t - 2 : t - 9;
                    const int cw = (j & 1) * 4 + ((p & 2) ^ (q ? 0 : 2)), cc = 64 * cw;
                    if (t < 16) {
                        full = sb + B_FULL + 8 * slot; dst = sb + OFF_RING + slot * 16384;
                        mbar_wait(sb + B_EMPTY + 8 * slot, ph);
                        P_END()
                    } else {
                        full = sb + B_XFULL + (t - 16) * 24; dst = sb + OFF_X + (t - 16) * 16384;
                        mbar_wait(sb + B_XFREE + 8 * (t - 16), 1);
                    }
                    TS2(40 + t);
                    mbar_expect(full, 16384);
                    if (!MC || ((t ^ rank) & 1) == 0) {
                        if (u == 4) {
                            tmaw5(dst, &maps.wdph, cc, 14 * p + 6, full); tmaw5(dst + 4096, &maps.wdph, cc, 14 * p + 13, full);
                            tmaw5(dst + 8192, &maps.wdph, cc + 64, 14 * p + 6, full); tmaw5(dst + 12288, &maps.wdph, cc + 64, 14 * p + 13, full);
                        } else if (u == 5 || u == 6) {
                            tmaw3(dst, u == 5 ? &maps.wow : &maps.wdw, 0, u == 5 ? 64 * j : 224 * j + 128, cw, full);
                        } else {
                            const CUtensorMap* m = u == 7 ? &maps.wop : &maps.wdp;
                            const int g = u == 7 ? 2 * (j ^ 1) : u == 8 ? 7 * (j ^ 1) + 4 : 14 * p + 7 * (u & 1) + (u & 2);
                            tmaw5(dst, m, cc, g, full); tmaw5(dst + 8192, m, cc + 64, g, full);
                        }
                    }
                }
            }
        } else if (warp < 11) {
            const int hx = warp - 9;
            uint32_t epoch;
            asm volatile("ld.relaxed.gpu.global.u32 %0, [%1];" : "=r"(epoch) : "l"(g_epoch + blockIdx.x) : "memory");
            {
                const uint4* xr = (const uint4*)(xg + (size_t)(r * 128 + j * 16 + hx * 8) * kD) + lane;
                const uint4 wa = __ldg((const uint4*)gate_w + lane), wb = __ldg((const uint4*)gate_w + 32 + lane);
                const uint32_t tag = (epoch + 1) & 1;
                uint4* gp = g_gx + r * 32;
                if (lane < 2) st_pkt(gp + j * 4 + hx * 2 + lane, tag ^ 1, 0, 0, 0);
                float s[8];
#pragma unroll
                for (int i0 = 0; i0 < 8; i0 += 4) {
                    uint4 va[4], vb[4];
#pragma unroll
                    for (int i = 0; i < 4; i++) { va[i] = __ldg(xr + (i0 + i) * 64); vb[i] = __ldg(xr + (i0 + i) * 64 + 32); }
#pragma unroll
                    for (int i = 0; i < 4; i++) {
                        float t0 = bf_lo(va[i].x) * bf_lo(wa.x), t1 = bf_hi(va[i].x) * bf_hi(wa.x);
                        t0 = fmaf(bf_lo(va[i].y), bf_lo(wa.y), t0); t1 = fmaf(bf_hi(va[i].y), bf_hi(wa.y), t1);
                        t0 = fmaf(bf_lo(va[i].z), bf_lo(wa.z), t0); t1 = fmaf(bf_hi(va[i].z), bf_hi(wa.z), t1);
                        t0 = fmaf(bf_lo(va[i].w), bf_lo(wa.w), t0); t1 = fmaf(bf_hi(va[i].w), bf_hi(wa.w), t1);
                        t0 = fmaf(bf_lo(vb[i].x), bf_lo(wb.x), t0); t1 = fmaf(bf_hi(vb[i].x), bf_hi(wb.x), t1);
                        t0 = fmaf(bf_lo(vb[i].y), bf_lo(wb.y), t0); t1 = fmaf(bf_hi(vb[i].y), bf_hi(wb.y), t1);
                        t0 = fmaf(bf_lo(vb[i].z), bf_lo(wb.z), t0); t1 = fmaf(bf_hi(vb[i].z), bf_hi(wb.z), t1);
                        t0 = fmaf(bf_lo(vb[i].w), bf_lo(wb.w), t0); t1 = fmaf(bf_hi(vb[i].w), bf_hi(wb.w), t1);
                        s[i0 + i] = t0 + t1;
                    }
                }
#pragma unroll
                for (int i = 0; i < 8; i++) {
#pragma unroll
                    for (int o = 16; o; o >>= 1) s[i] += __shfl_xor_sync(0xffffffffu, s[i], o);
                    s[i] = 1.f / (1.f + __expf(-s[i]));
                }
                if (lane < 2) {
                    const float v0 = lane ? s[4] : s[0], v1 = lane ? s[5] : s[1], v2 = lane ? s[6] : s[2], v3 = lane ? s[7] : s[3];
                    st_pkt(gp + j * 4 + hx * 2 + lane, (__float_as_uint(v0) & ~1u) | tag, __float_as_uint(v1), __float_as_uint(v2), __float_as_uint(v3));
                }
                if (hx == 1) {
                    asm volatile("st.shared.u32 [%0], %1;" :: "r"(sb + OFF_ONES + lane * 4), "r"(0x3f803f80u) : "memory");
                    asm volatile("fence.proxy.async.shared::cta;" ::: "memory");
                }
                asm volatile("bar.sync 3, 96;" ::: "memory");
                if (hx == 0) {
                    uint32_t q[4];
                    recv_issue(q, gp + lane);
                    recv_check(q, gp + lane, tag);
                    asm volatile("st.shared.v4.u32 [%0], {%1,%2,%3,%4};" :: "r"(sb + OFF_G + lane * 16), "r"(q[0]), "r"(q[1]), "r"(q[2]), "r"(q[3]) : "memory");
                    if (lane == 0) {
                        asm volatile("st.shared.u32 [%0], %1;" :: "r"(sb + OFF_EPOCH), "r"(epoch) : "memory");
                        g_epoch[blockIdx.x] = epoch + 1;
                    }
                    __syncwarp();
                    if (lane == 0) mbar_arrive(sb + B_GRDY);
                } else {
                    if (r == 0) {
                        float4* zp = (float4*)(g_kvacc + (((epoch & 1) ^ 1) * 8 + j) * 4 * 272);
                        for (int i = lane; i < 272; i += 32) zp[i] = make_float4(0.f, 0.f, 0.f, 0.f);
                    }
                }
            }
            TS(2 + hx, 1);
#define PUBLISH_H(B) do { mbar_wait(sb + B_HSENT + 8 * (B), 0); if (lane == 0) { \
                asm volatile("st.release.gpu.global.u32 [%0], %1;" :: "l"(g_hflag + (r * 8 + j) * 8 + (B)), "r"(epoch + 1) : "memory"); } __syncwarp(); } while (0)
            if (hx == 1) {
#pragma unroll 1
                for (int b = 0; b < 4; b++) { PUBLISH_H(b); TS(3, 5 + b); }
            } else {
                const float* accp = g_kvacc + ((epoch & 1) * 8 + j) * 4 * 272;
                unsigned* cnt = g_kvcnt + j * 32;
                mbar_wait(sb + B_KVDONE, 0);
                TS(2, 5);
                if (lane == 0) asm volatile("red.release.gpu.global.add.u32 [%0], 1;" :: "l"(cnt) : "memory");
                __syncwarp();
                TS(2, 2);
                {
                    const unsigned target = 16u * (epoch + 1);
                    uint32_t it = 0, v;
                    do {
                        asm volatile("ld.acquire.gpu.global.u32 %0, [%1];" : "=r"(v) : "l"(cnt) : "memory");
                    } while ((int)(v - target) < 0 && ++it < SPIN_GLOBAL);
                }
                TS(2, 3);
#pragma unroll
                for (int h = 0; h < 4; h++) {
                    const float4 d0 = __ldcg((const float4*)(accp + h * 272) + lane);
                    const float4 d1 = __ldcg((const float4*)(accp + h * 272 + 128) + lane);
                    const float2 z0 = __ldcg((const float2*)(accp + h * 272 + 256) + (lane & 3));
                    const float2 z1 = __ldcg((const float2*)(accp + h * 272 + 264) + (lane & 3));
                    asm volatile("st.shared.v4.u32 [%0], {%1,%2,%3,%4};" :: "r"(sb + OFF_KVF + h * 512 + lane * 16),
                                 "r"(pack2(d0.x, d0.y)), "r"(pack2(d1.x, d1.y)), "r"(pack2(d0.z, d0.w)), "r"(pack2(d1.z, d1.w)) : "memory");
                    if (lane < 4) asm volatile("st.shared.v2.u32 [%0], {%1,%2};" :: "r"(sb + OFF_ZF + h * 32 + lane * 8), "r"(pack2(z0.x, z0.y)), "r"(pack2(z1.x, z1.y)) : "memory");
                }
                __syncwarp();
                if (lane == 0) mbar_arrive(sb + B_KVRDY);
                TS(2, 4);
                PUBLISH_H(4);
                TS(3, 9);
            }
        } else {
            uint32_t epoch;
            asm volatile("ld.relaxed.gpu.global.u32 %0, [%1];" : "=r"(epoch) : "l"(g_epoch + blockIdx.x) : "memory");
            asm volatile("bar.arrive 3, 96;" :: "r"(epoch) : "memory");
            const int b = blockIdx.x, p = j >> 1;
            mbar_wait(sb + B_XFULL, 0);
            {
                uint4* mb = g_part + (size_t)(r * 2 + (j & 1)) * 16384 + (((p ^ 1) * 4 + p) << 10) + lane;
#pragma unroll 8
                for (int i = 0; i < 32; i++) st_pkt(mb + i * 32, epoch & 1, 0, 0, 0);
                __syncwarp();
                if (lane == 0) mbar_arrive(sb + B_KVRDY);
            }
#pragma unroll 1
            for (int kb = 1; kb < 8; kb++) {
                mbar_wait(sb + B_XFULL + 8 * kb, 0);
                const char* base = kb < 3 ? pf_g : kb < 5 ? pf_u : kb == 5 ? pf_qkv : pf_d;
                const int off = kb == 5 ? b * 12288 : b * 14336 + ((kb < 5 ? kb - 1 : kb) & 1) * 7168;
                asm volatile("prefetch.global.L2 [%0];" :: "l"(base + off + lane * 128));
                if (kb == 5 || lane < 24) asm volatile("prefetch.global.L2 [%0];" :: "l"(base + off + 4096 + lane * 128));
                if (kb == 5) asm volatile("prefetch.global.L2 [%0];" :: "l"(base + off + 8192 + lane * 128));
                if (kb == 7) asm volatile("prefetch.global.L2 [%0];" :: "l"(pf_o + b * 4096 + lane * 128));
            }
            {
                const uint32_t want = epoch + 1;
                const int hrow = (r * 4 + p) * 9 * 128, po = (j & 1) ^ 1;
                const unsigned* fl = g_hflag + (r * 8 + (j & 6)) * 8 + (lane & 15);
                uint32_t it = 0;
                int i = 0;
                mbar_wait(sb + B_HSENT + 8, 0);
#pragma unroll 1
                while (i < 5 && ++it < SPIN_GLOBAL) {
                    uint32_t v;
                    asm volatile("ld.acquire.gpu.global.u32 %0, [%1];" : "=r"(v) : "l"(fl) : "memory");
                    const uint32_t rdy = __ballot_sync(0xffffffffu, v == want);
#pragma unroll 1
                    while (i < 5) {
                        const uint32_t need = i < 3 ? 0x101u << i : 1u << (8 * po + i);
                        if ((rdy & need) != need) break;
                        if (i < 3) mbar_wait(sb + B_XFREE + 8 * i, 0);
                        if (lane == 0) {
                            asm volatile("fence.proxy.async.global;" ::: "memory");
                            const int piece = i < 3 ? 2 * i : i == 3 ? 5 : 8, tile = i < 3 ? 2 * i : 2 * i - 1 + po;
                            const uint32_t bar = sb + B_XFULL + 8 * (i == 0 ? 1 : piece);
                            TS2(140 + i);
                            mbar_expect(bar, i < 2 ? 32768 : 16384);
                            tma2(sb + OFF_X + piece * 16384, i < 2 ? &maps.hx2 : &maps.hx, 0, hrow + tile * 128, bar);
                        }
                        i++;
                    }
                }
            }
        }
    } else {
        asm volatile("setmaxnreg.inc.sync.aligned.u32 216;");
        const int wg = warp >> 2;
        const bool elect = (tid & 127) == 0;
        const uint32_t xlo = ((sb + OFF_X + wg * 8192) >> 4) | LBO1;
        const uint32_t ringlo = (sb + OFF_RING) >> 4;
        auto release = [&](int s) {
            if (elect) {
                mbar_arrive(sb + B_EMPTY + 8 * s);
            }
        };
#define S_WAIT(S) do { if ((S) < 56) mbar_wait(sb + B_FULL + 8 * ((S) % 5), ((S) / 5) & 1); else mbar_wait(sb + B_XFULL + ((S) - 56) * 24, 1); \
            if (PROF && tid == 0) TS2(64 + (S)); } while (0)
#define S_B(S) ((S) < 56 ? ringlo + ((S) % 5) * 1024 : ((sb + OFF_X) >> 4) + ((S) - 56) * 1024)
#define G1(S, acc, SW, KB) do { S_WAIT(S); g1_issue<SW, (KB) == 0>(acc, xlo + (KB) * 1024, S_B(S) | (SW ? LBO4K : LBO8K)); } while (0)
#define RET(S) do { wg_wait<1>(); if ((S) - 1 < 51) release(((S) - 1) % 5); } while (0)
#define SCHED() mbar_wait(sb + B_XFULL + 8 * 7, 0)
#define A2_SYNC() do { asm volatile("fence.proxy.async.shared::cta;" ::: "memory"); asm volatile("bar.sync %0, 128;" :: "r"(wg + 1) : "memory"); } while (0)
#define H_EPI(acc, F, I0, I1, OG, OU) _Pragma("unroll") for (int i = (I0); i < (I1); i++) \
            F[i] = hmul2(pack2(acc[(OG) + 2 * i] * acc[(OU) + 2 * i], acc[(OG) + 2 * i + 1] * acc[(OU) + 2 * i + 1]), (i & 1) ? m_hi : m_lo)
#define PHI(acc, F, I0, I1) _Pragma("unroll") for (int i = (I0); i < (I1); i++) F[i] = phi2(acc[2 * i], acc[2 * i + 1])

        float a0[64], b0[64], a1[64], a2_[64], a3[64];
        mbar_wait(sb + B_XFULL, 0);
        G1(0, a0, false, 0);
        if ((warp & 3) == 0) TS(wg, 1);
        G1(1, b0, false, 0); RET(1);
#define C0(KB) mbar_wait(sb + B_XFULL + 8 * (KB), 0); if (PROF && tid == 0) TS2(128 + (KB)); \
        G1(2 * (KB), a0, false, KB); RET(2 * (KB)); G1(2 * (KB) + 1, b0, false, KB); RET(2 * (KB) + 1)
        C0(1); C0(2); C0(3); C0(4); C0(5);
        mbar_wait(sb + B_XFULL + 8 * 6, 0);
        G1(12, a0, false, 6); RET(12);
        mbar_wait(sb + B_XFULL + 8 * 7, 0);
        G1(13, a0, false, 7); RET(13);
        G1(14, b0, false, 6);
        mbar_wait(sb + B_GRDY, 0);
        float g_lo, g_hi;
        uint32_t tag;
        {
            const uint32_t ga = sb + OFF_G + (warp * 16 + (lane >> 2)) * 4;
            asm volatile("ld.shared.f32 %0, [%1];" : "=f"(g_lo) : "r"(ga) : "memory");
            asm volatile("ld.shared.f32 %0, [%1];" : "=f"(g_hi) : "r"(ga + 32) : "memory");
            asm volatile("ld.shared.u32 %0, [%1];" : "=r"(tag) : "r"(sb + OFF_EPOCH) : "memory");
        }
        float* const kvp = g_kvacc + (((tag & 1) * 8 + j) * 4 + (warp & 3)) * 272;
        tag = (tag + 1) & 1;
        const uint32_t m_lo = pack2(1.f - g_lo, 1.f - g_lo), m_hi = pack2(1.f - g_hi, 1.f - g_hi);
        const uint32_t lrow = ((lane & 7) + 8 * ((lane >> 3) & 1)) * 128;
        const uint32_t srow = (warp & 3) * 2048 + lrow;
        const uint32_t ssw = (lane >> 4) ^ (lane & 7);
        uint4* const hsend = g_hx + (size_t)((r * 4 + (j >> 1)) * 9 + (j & 1)) * 1024 + warp * 128 + (lane >> 2) * 8 + (lane & 3);
#define SENT_H(B) do { __syncwarp(); if (lane == 0) mbar_arrive(sb + B_HSENT + 8 * (B)); } while (0)
        RET(14);
        pin(a0);
        uint32_t fh0[16], fh1[16], fh2[16], fh3[8], fo[16];
        G1(15, b0, false, 7); SCHED(); H_EPI(a0, fh0, 0, 16, 0, 32); RET(15);
        if ((warp & 3) == 0) TS(wg, 2);

        float kv[32], zs[4];
        uint32_t pk[16], pv[16];
        const uint32_t stg = sb + OFF_STG + wg * 8192, stl = stg + (warp & 1) * 2048 + lrow;
        const uint32_t klo = (stg >> 4) | LBO1, vlo = klo + 256, olo = (sb + OFF_ONES) >> 4;
        G1(16, a1, false, 0); RET(16);
        pin(b0);
        G1(17, a1, false, 1); send_h<0, 1>(fh0, hsend); SCHED(); PHI(b0, pk, 0, 6); RET(17);
        G1(18, a1, false, 2); send_h<1, 2>(fh0, hsend); SENT_H(0); SCHED(); PHI(b0, pk, 6, 12); RET(18);
        G1(19, a1, false, 3); SCHED(); PHI(b0, pk, 12, 16); pack_sub<32>(pv, b0); RET(19);
#define KV_ROUND(Z) do { A2_SYNC(); wg_fence(); \
            wg_ss64t##Z(kv, vlo, DH128, klo, DH128); wg_ss64t(kv, vlo + 128, DH128, klo + 128, DH128); \
            wg_ss8t##Z(zs, klo, DH128, olo, 0); wg_ss8t(zs, klo + 128, DH128, olo, 0); wg_commit(); } while (0)
        G1(20, a1, false, 4); if (!(warp & 2)) { stash<16>(stl, ssw, pk); stash<16>(stl + 4096, ssw, pv); } RET(20);
        G1(21, a1, false, 5); KV_ROUND(_z); wg_wait<2>(); release(20 % 5);
        G1(22, a1, false, 6); RET(22);
        G1(23, a1, false, 7); if (warp & 2) { stash<16>(stl, ssw, pk); stash<16>(stl + 4096, ssw, pv); } RET(23);
        if ((warp & 3) == 0) TS(wg, 3);

        G1(24, a2_, true, 0); KV_ROUND(); wg_wait<2>(); release(23 % 5);
        pin(a1);
        G1(25, a2_, true, 1); RET(25);
        pin(kv); pin(zs);
        G1(26, a2_, true, 2);
#define KV_RED(W) do { asm volatile("red.global.add.v4.f32 [%0], {%1,%2,%3,%4};" :: "l"(kvp + lane * 4), "f"(kv[8 * W]), "f"(kv[8 * W + 1]), "f"(kv[8 * W + 2]), "f"(kv[8 * W + 3]) : "memory"); \
                       asm volatile("red.global.add.v4.f32 [%0], {%1,%2,%3,%4};" :: "l"(kvp + 128 + lane * 4), "f"(kv[8 * W + 4]), "f"(kv[8 * W + 5]), "f"(kv[8 * W + 6]), "f"(kv[8 * W + 7]) : "memory"); } while (0)
        if ((warp & 3) == 0) KV_RED(0); else if ((warp & 3) == 1) KV_RED(1); else if ((warp & 3) == 2) KV_RED(2); else KV_RED(3);
        if ((lane & 3) == 0) {
            asm volatile("red.global.add.f32 [%0], %1;" :: "l"(kvp + 256 + (lane >> 2)), "f"(zs[0]) : "memory");
            asm volatile("red.global.add.f32 [%0], %1;" :: "l"(kvp + 264 + (lane >> 2)), "f"(zs[2]) : "memory");
        }
        __syncwarp();
        if (lane == 0) mbar_arrive(sb + B_KVDONE);
        RET(26);
        G1(27, a2_, true, 3); SCHED(); H_EPI(a1, fh1, 0, 16, 0, 32); RET(27);
        G1(28, a2_, true, 4); RET(28);
        G1(29, a2_, true, 5); RET(29);
        G1(30, a2_, true, 6); send_h<0, 1>(fh1, hsend + 2 * 1024); RET(30);
        G1(31, a2_, true, 7); send_h<1, 2>(fh1, hsend + 2 * 1024); SENT_H(1); RET(31);
        if ((warp & 3) == 0) TS(wg, 4);

        const uint32_t a2 = sb + OFF_X + wg * 8192 + srow;
#define O_HEADS(h0) do { uint32_t kb_[2][6]; float n0[2][4], n1[2][4], dn[2][4]; \
            _Pragma("unroll") for (int i = 0; i < 2; i++) { \
                asm volatile("ld.shared.v4.u32 {%0,%1,%2,%3}, [%4];" : "=r"(kb_[i][0]), "=r"(kb_[i][1]), "=r"(kb_[i][2]), "=r"(kb_[i][3]) : "r"(sb + OFF_KVF + (h0 + i) * 512 + lane * 16) : "memory"); \
                asm volatile("ld.shared.v2.u32 {%0,%1}, [%2];" : "=r"(kb_[i][4]), "=r"(kb_[i][5]) : "r"(sb + OFF_ZF + (h0 + i) * 32 + (lane & 3) * 8) : "memory"); } \
            _Pragma("unroll") for (int i = 0; i < 2; i++) { const int f_ = 4 * (h0 + i); \
                mma16816(dn[i], fo[f_], fo[f_ + 1], fo[f_ + 2], fo[f_ + 3], kb_[i][4], kb_[i][5]); } \
            _Pragma("unroll") for (int i = 0; i < 2; i++) { const int f_ = 4 * (h0 + i); \
                mma16816(n0[i], fo[f_], fo[f_ + 1], fo[f_ + 2], fo[f_ + 3], kb_[i][0], kb_[i][1]); \
                mma16816(n1[i], fo[f_], fo[f_ + 1], fo[f_ + 2], fo[f_ + 3], kb_[i][2], kb_[i][3]); } \
            _Pragma("unroll") for (int i = 0; i < 2; i++) { const int f_ = 4 * (h0 + i); \
                const float s_lo = __fdividef(g_lo, dn[i][0] + 1e-6f), s_hi = __fdividef(g_hi, dn[i][2] + 1e-6f); \
                const uint32_t sl_ = pack2(s_lo, s_lo), sh_ = pack2(s_hi, s_hi); \
                fo[f_] = hmul2(pack2(n0[i][0], n0[i][1]), sl_); fo[f_ + 1] = hmul2(pack2(n0[i][2], n0[i][3]), sh_); \
                fo[f_ + 2] = hmul2(pack2(n1[i][0], n1[i][1]), sl_); fo[f_ + 3] = hmul2(pack2(n1[i][2], n1[i][3]), sh_); } } while (0)
        G1(32, a3, false, 0); RET(32);
        pin(a2_);
        G1(33, a3, false, 1); SCHED(); H_EPI(a2_, fh3, 0, 8, 32, 48);
        send_h<0, 1>(fh3, hsend + 4 * 1024 - (j & 1) * 1020); SENT_H(2); PHI(a2_, fo, 0, 2); RET(33);
        G1(34, a3, false, 2); SCHED(); PHI(a2_, fo, 2, 7); RET(34);
        if (elect) mbar_arrive(sb + B_XFREE);
        G1(35, a3, false, 3); SCHED(); PHI(a2_, fo, 7, 12); RET(35);
        G1(36, a3, false, 4); SCHED(); PHI(a2_, fo, 12, 16); RET(36);
        if (elect) mbar_arrive(sb + B_XFREE + 8);
        G1(37, a3, false, 5);
        if ((warp & 3) == 0) TS(wg, 5);
        mbar_wait(sb + B_KVRDY, 0);
        if ((warp & 3) == 0) TS(wg, 6);
        O_HEADS(0);
        if ((warp & 3) == 0) TS(wg, 15);
        RET(37);
        G1(38, a3, false, 6); send_h<0, 1>(fo, hsend + 5 * 1024); SCHED(); O_HEADS(2); RET(38);
        if (elect) mbar_arrive(sb + B_XFREE + 16);
        G1(39, a3, false, 7); send_h<1, 2>(fo, hsend + 5 * 1024); SENT_H(3); RET(39);
        if ((warp & 3) == 0) TS(wg, 7);

#define G2_PIECE(U) ((U) < 5 ? (U) : (U) == 5 ? 6 : (U) == 6 ? 7 : (U) == 7 ? 5 : 8)
#define G2(S, acc, U) do { S_WAIT(S); wg_fence(); _Pragma("unroll") for (int k = 0; k < 4; k++) { \
            if ((U) == 0 && k == 0) wg_ss128_z(acc, xlo, DH128, S_B(S) | LBO8K, DH128); \
            else wg_ss128(acc, xlo + G2_PIECE(U) * 1024 + 2 * k, DH128, (S_B(S) | LBO8K) + 128 * k, DH128); } wg_commit(); } while (0)
#define H_WAIT(P) do { mbar_wait(sb + B_XFULL + 8 * (P), (P) < 8); if (PROF && tid == 0) TS2(150 + (P)); } while (0)
        const int p = j >> 1;
        uint4* const pbase = g_part + (size_t)(r * 2 + (j & 1)) * 16384 + warp * 128 + lane;
        const int pw = (p & 2) ^ 2;
        auto other = [&](int d) { return d == 3 ? p ^ 1 : pw + d - 1; };
        auto sendp = [&](int d) { return pbase + ((other(d) * 4 + p) << 10); };
        auto recvp = [&](int d) { return pbase + ((p * 4 + other(d)) << 10); };

        float p1[64], p2[64];
        H_WAIT(1); G2(40, p1, 0); RET(40);
        pin(a3);
        G2(41, p1, 1); SCHED(); H_EPI(a3, fh2, 0, 16, 0, 32); send_h<0, 2>(fh2, hsend + 7 * 1024); SENT_H(4); RET(41);
        H_WAIT(2); G2(42, p1, 2); stash<16>(a2 + 6 * 16384, ssw, fo); RET(42);
        G2(43, p1, 3); stash<16>(a2 + 7 * 16384, ssw, fh2); RET(43);
        H_WAIT(4); G2(44, p1, 4); A2_SYNC(); RET(44);
        G2(45, p1, 5); RET(45);
        G2(46, p1, 6); RET(46);
        G2(47, p2, 0); RET(47);
        G2(48, p2, 1); RET(48);
        if (elect) mbar_arrive(sb + B_XFREE);
        H_WAIT(5); G2(49, p1, 7); RET(49);
        if (elect) mbar_arrive(sb + B_XFREE + 8);
        H_WAIT(8); G2(50, p1, 8); RET(50);
        if ((warp & 3) == 0) TS(wg, 8);
        uint32_t sa[16], sc[16], qa[16], qb[16];
        G2(51, p2, 2); RET(51);
        pin(p1);
        G2(52, p2, 3); SCHED(); pack_sub<0>(sa, p1); send_frag<0, 2>(sa, sendp(1), tag); RET(52);
        G2(53, p2, 4); SCHED(); pack_sub<32>(sc, p1); send_frag<2, 4>(sa, sendp(1), tag); RET(53);
        G2(54, p2, 5); send_frag<0, 2>(sc, sendp(2), tag); RET(54);
        G2(55, p2, 6); send_frag<2, 4>(sc, sendp(2), tag); RET(55);
        G2(56, p2, 7); RET(56);
        G2(57, p2, 8);
        if ((warp & 3) == 0) TS(wg, 9);
        wg_wait<0>();
        pin(p2);
        if ((warp & 3) == 0) TS(wg, 11);
        float sum[32];
        if (p & 1) pack_sub<0>(sa, p2); else pack_sub<32>(sa, p2);
        send_frag<0, 4>(sa, sendp(3), tag);
        recv_issue(qa, recvp(1)); recv_issue(qb, recvp(2)); recv_issue(sc, recvp(3));
#pragma unroll
        for (int i = 0; i < 32; i++) sum[i] = (p & 1) ? p2[32 + i] : p2[i];
        recv_check(qa, recvp(1), tag); accum(qa, sum);
        recv_check(qb, recvp(2), tag); accum(qb, sum);
        if ((warp & 3) == 0) TS(wg, 12);
        recv_check(sc, recvp(3), tag); accum(sc, sum);
        if ((warp & 3) == 0) TS(wg, 13);
        {
            uint32_t f[16];
            pack_sub<0>(f, sum);
            const uint32_t slab = sb + OFF_X + 2 * 16384 + wg * 8192;
            stash<16>(slab + srow, ssw, f);
            __syncwarp();
            __nv_bfloat16* op = out + (size_t)(r * 128 + warp * 16 + (lane >> 3)) * kD + (j & 1) * 256 + p * 64 + (lane & 7) * 8;
#pragma unroll
            for (int i = 0; i < 4; i++) {
                const int row = i * 4 + (lane >> 3);
                uint4 v;
                asm volatile("ld.shared.v4.u32 {%0,%1,%2,%3}, [%4];" : "=r"(v.x), "=r"(v.y), "=r"(v.z), "=r"(v.w)
                             : "r"(slab + ((warp & 3) * 16 + row) * 128 + (((lane & 7) ^ (row & 7)) << 4)) : "memory");
                *(uint4*)(op + i * 4 * kD) = v;
            }
        }
        if ((warp & 3) == 0) { TS(wg, 14); TSG(wg, 31); }
    }
}

typedef CUresult (*EncodeFn)(CUtensorMap*, CUtensorMapDataType, cuuint32_t, void*, const cuuint64_t*, const cuuint64_t*, const cuuint32_t*,
                             const cuuint32_t*, CUtensorMapInterleave, CUtensorMapSwizzle, CUtensorMapL2promotion, CUtensorMapFloatOOBfill);

static void encode(EncodeFn fn, CUtensorMap* m, int rank, const void* base, const cuuint64_t (&gd)[5], const cuuint64_t (&gs)[4],
                   const cuuint32_t (&bd)[5], CUtensorMapSwizzle sw) {
    cuuint32_t es[5] = {1, 1, 1, 1, 1};
    fn(m, CU_TENSOR_MAP_DATA_TYPE_BFLOAT16, rank, const_cast<void*>(base), gd, gs, bd, es, CU_TENSOR_MAP_INTERLEAVE_NONE, sw,
       CU_TENSOR_MAP_L2_PROMOTION_L2_128B, CU_TENSOR_MAP_FLOAT_OOB_FILL_NONE);
}

extern "C" void kernel_launch(void* const* d_in, const int* in_sizes, int n_in, void* d_out, int out_size) {
    const char* x = (const char*)d_in[0];
    const char* wqkv = (const char*)d_in[1];
    const char* wo = (const char*)d_in[2];
    const char* wg = (const char*)d_in[4];
    const char* wu = (const char*)d_in[5];
    const char* wd = (const char*)d_in[6];
    void* fnp = nullptr;
    cudaDriverEntryPointQueryResult qr;
    cudaGetDriverEntryPoint("cuTensorMapEncodeTiled", &fnp, cudaEnableDefault, &qr);
    EncodeFn fn = (EncodeFn)fnp;
    Maps maps;
    const char* lo = wg < wu ? wg : wu;
    const uint64_t diff = wg < wu ? (uint64_t)(wu - wg) : (uint64_t)(wg - wu);
    const CUtensorMapSwizzle S128 = CU_TENSOR_MAP_SWIZZLE_128B, S64 = CU_TENSOR_MAP_SWIZZLE_64B;
    encode(fn, &maps.x, 2, x, {512, 2048, 1, 1}, {1024, 0, 0}, {64, 128, 1, 1}, S128);
    encode(fn, &maps.gu, 3, lo, {1792, 512, 2, 1}, {3584, diff, 0}, {64, 64, 2, 1}, S128);
    encode(fn, &maps.kv, 3, wqkv, {512, 512, 3, 1}, {3072, 1024, 0}, {64, 64, 2, 1}, S128);
    encode(fn, &maps.q64, 3, wqkv, {32, 512, 48, 1}, {3072, 64, 0}, {32, 64, 2, 1}, S64);
    encode(fn, &maps.gu64, 3, lo, {1792, 512, 2, 1}, {3584, diff, 0}, {32, 64, 2, 1}, S64);
    encode(fn, &maps.wdw, 3, wd, {64, 1792, 8, 1}, {1024, 128, 0}, {64, 64, 2, 1}, S128);
    encode(fn, &maps.wow, 3, wo, {64, 512, 8}, {1024, 128}, {64, 64, 2}, S128);
    encode(fn, &maps.wdp, 5, wd, {512, 2, 4, 4, 56}, {1024, 8192, 2048, 32768}, {64, 2, 4, 4, 2}, S128);
    encode(fn, &maps.wdph, 5, wd, {512, 2, 4, 4, 56}, {1024, 8192, 2048, 32768}, {64, 2, 4, 4, 1}, S128);
    encode(fn, &maps.wop, 5, wo, {512, 2, 4, 4, 16}, {1024, 8192, 2048, 32768}, {64, 2, 4, 4, 2}, S128);
    void* hx = nullptr;
    cudaGetSymbolAddress(&hx, g_hx);
    encode(fn, &maps.hx, 2, hx, {64, 16 * 4 * 9 * 128}, {128}, {64, 128}, S128);
    encode(fn, &maps.hx2, 2, hx, {64, 16 * 4 * 9 * 128}, {128}, {64, 256}, S128);
    cudaFuncSetAttribute(fused_kernel, cudaFuncAttributeMaxDynamicSharedMemorySize, SMEM_BYTES);
    cudaLaunchConfig_t cfg = {};
    cfg.gridDim = dim3(128);
    cfg.blockDim = dim3(384);
    cfg.dynamicSmemBytes = SMEM_BYTES;
    cfg.stream = cudaStreamPerThread;
    cudaLaunchAttribute at[1];
    at[0].id = cudaLaunchAttributeClusterDimension;
    at[0].val.clusterDim.x = 2; at[0].val.clusterDim.y = 1; at[0].val.clusterDim.z = 1;
    cfg.attrs = at;
    cfg.numAttrs = MC ? 1 : 0;
    cudaLaunchKernelEx(&cfg, fused_kernel, maps, (const __nv_bfloat16*)d_in[0], (const __nv_bfloat16*)d_in[7], wqkv, wg, wu, wd, wo, (__nv_bfloat16*)d_out);
}
```

```cpp
#include <cuda_runtime.h>
#include <cuda.h>
#include <cuda_bf16.h>
#include <stdint.h>

#define MC 0
#define PFMODE 1
#define PROF 0

namespace {

constexpr int kD = 512;
constexpr uint32_t OFF_X = 0, OFF_STG = 131072, OFF_RING = 147456, OFF_MISC = 229376;
constexpr uint32_t B_FULL = OFF_MISC, B_EMPTY = OFF_MISC + 40, B_XFULL = OFF_MISC + 80;
constexpr uint32_t B_GRDY = OFF_MISC + 152, B_KVDONE = OFF_MISC + 160, B_KVRDY = OFF_MISC + 168;
constexpr uint32_t B_HSENT = OFF_MISC + 176, B_XFREE = OFF_MISC + 216;
constexpr uint32_t OFF_EPOCH = OFF_MISC + 240, OFF_G = OFF_MISC + 256;
constexpr uint32_t B_AHEAD = OFF_MISC + 248;
constexpr uint32_t OFF_ONES = OFF_MISC + 768;
constexpr uint32_t SMEM_BYTES = OFF_ONES + 128;
constexpr uint32_t SPIN_GLOBAL = 1u << 14;

struct alignas(64) Maps { CUtensorMap x, gu, kv, q64, gu64, wdw, wow, wdp, wdph, wop, hx, hx2; };

}

__device__ uint4 g_part[16 * 2 * 4 * 4 * 1024];
__device__ uint4 g_hx[16 * 4 * 9 * 1024];
__device__ unsigned g_hflag[128 * 8];
__device__ uint4 g_gx[16 * 32];
__device__ float g_kvacc[2 * 8 * 4 * 272];
__device__ unsigned g_kvcnt[8 * 32];
__device__ unsigned g_epoch[128];
#define TS(role, idx)
#define TS2(idx)
#define TSG(role, idx)

namespace {

__device__ __forceinline__ void mbar_init(uint32_t bar, uint32_t cnt) { asm volatile("mbarrier.init.shared::cta.b64 [%0], %1;" :: "r"(bar), "r"(cnt) : "memory"); }
__device__ __forceinline__ void mbar_expect(uint32_t bar, uint32_t bytes) { asm volatile("mbarrier.arrive.expect_tx.shared::cta.b64 _, [%0], %1;" :: "r"(bar), "r"(bytes) : "memory"); }
__device__ __forceinline__ void mbar_arrive(uint32_t bar) { asm volatile("mbarrier.arrive.shared::cta.b64 _, [%0];" :: "r"(bar) : "memory"); }
__device__ __forceinline__ void mbar_arrive_cta(uint32_t bar, uint32_t cta) {
    asm volatile("{\n.reg .b32 ra;\nmapa.shared::cluster.u32 ra, %0, %1;\nmbarrier.arrive.shared::cluster.b64 _, [ra];\n}" :: "r"(bar), "r"(cta) : "memory");
}
__device__ __forceinline__ void mbar_wait(uint32_t bar, uint32_t parity) {
    asm volatile("{\n.reg .pred p;\n.reg .u32 c;\n"
                 "mbarrier.try_wait.parity.shared::cta.b64 p, [%0], %1;\n@p bra DONE;\n"
                 "mov.u32 c, 0;\nLAB_WAIT:\nmbarrier.try_wait.parity.shared::cta.b64 p, [%0], %1;\n@p bra DONE;\n"
                 "add.u32 c, c, 1;\nsetp.lt.u32 p, c, 65536;\n@p bra LAB_WAIT;\nDONE:\n}" :: "r"(bar), "r"(parity) : "memory");
}
__device__ __forceinline__ void tma2(uint32_t dst, const CUtensorMap* m, int c0, int c1, uint32_t bar) {
    asm volatile("cp.async.bulk.tensor.2d.shared::cluster.global.mbarrier::complete_tx::bytes [%0], [%1, {%3, %4}], [%2];"
        :: "r"(dst), "l"(m), "r"(bar), "r"(c0), "r"(c1) : "memory");
}
__device__ __forceinline__ void tmaw2(uint32_t dst, const CUtensorMap* m, int c0, int c1, uint32_t bar) {
    tma2(dst, m, c0, c1, bar);
}
__device__ __forceinline__ void tmaw3(uint32_t dst, const CUtensorMap* m, int c0, int c1, int c2, uint32_t bar) {
    asm volatile("cp.async.bulk.tensor.3d.shared::cluster.global.mbarrier::complete_tx::bytes [%0], [%1, {%3, %4, %5}], [%2];"
        :: "r"(dst), "l"(m), "r"(bar), "r"(c0), "r"(c1), "r"(c2) : "memory");
}
__device__ __forceinline__ void tmaw5(uint32_t dst, const CUtensorMap* m, int c0, int c4, uint32_t bar) {
    asm volatile("cp.async.bulk.tensor.5d.shared::cluster.global.mbarrier::complete_tx::bytes [%0], [%1, {%3, %5, %5, %5, %4}], [%2];"
        :: "r"(dst), "l"(m), "r"(bar), "r"(c0), "r"(c4), "r"(0) : "memory");
}
__device__ __forceinline__ void wg_fence() { asm volatile("wgmma.fence.sync.aligned;" ::: "memory"); }
__device__ __forceinline__ void wg_commit() { asm volatile("wgmma.commit_group.sync.aligned;" ::: "memory"); }
template <int N> __device__ __forceinline__ void wg_wait() { asm volatile("wgmma.wait_group.sync.aligned %0;" :: "n"(N) : "memory"); }
template <int N> __device__ __forceinline__ void pin(float (&d)[N]) {
#pragma unroll
    for (int i = 0; i < N; i++) asm volatile("" : "+f"(d[i]) :: "memory");
}
__device__ __forceinline__ uint32_t pack2(float lo, float hi) { uint32_t r; asm("cvt.rn.bf16x2.f32 %0, %1, %2;" : "=r"(r) : "f"(hi), "f"(lo)); return r; }
__device__ __forceinline__ uint32_t hmul2(uint32_t a, uint32_t b) { uint32_t r; asm("mul.bf16x2 %0, %1, %2;" : "=r"(r) : "r"(a), "r"(b)); return r; }
__device__ __forceinline__ uint32_t phi2(float t0, float t1) {
    float e0, e1;
    asm("ex2.approx.ftz.f32 %0, %1;" : "=f"(e0) : "f"(t0 * 1.4426950408889634f));
    asm("ex2.approx.ftz.f32 %0, %1;" : "=f"(e1) : "f"(t1 * 1.4426950408889634f));
    uint32_t e = pack2(e0, e1), t = pack2(t0, t1), r;
    asm("min.bf16x2 %0, %0, %1;" : "+r"(e) : "r"(0x3f803f80u));
    asm("max.bf16x2 %0, %0, %1;" : "+r"(t) : "r"(0x35863586u));
    asm("add.bf16x2 %0, %1, %2;" : "=r"(r) : "r"(e), "r"(t));
    return r;
}
__device__ __forceinline__ void stsm4(uint32_t a, uint32_t r0, uint32_t r1, uint32_t r2, uint32_t r3) {
    asm volatile("stmatrix.sync.aligned.m8n8.x4.shared.b16 [%0], {%1,%2,%3,%4};" :: "r"(a), "r"(r0), "r"(r1), "r"(r2), "r"(r3) : "memory");
}
__device__ __forceinline__ float bf_lo(uint32_t w) { return __uint_as_float(w << 16); }
__device__ __forceinline__ float bf_hi(uint32_t w) { return __uint_as_float(w & 0xffff0000u); }
__device__ __forceinline__ void st_pkt(uint4* p, uint32_t w0, uint32_t w1, uint32_t w2, uint32_t w3) {
    asm volatile("{\n.reg .b64 lo, hi;\n.reg .b128 v;\nmov.b64 lo, {%1, %2};\nmov.b64 hi, {%3, %4};\nmov.b128 v, {lo, hi};\nst.relaxed.gpu.global.b128 [%0], v;\n}"
        :: "l"(p), "r"(w0), "r"(w1), "r"(w2), "r"(w3) : "memory");
}
__device__ __forceinline__ void ld_pkt(const uint4* p, uint32_t& w0, uint32_t& w1, uint32_t& w2, uint32_t& w3) {
    asm volatile("{\n.reg .b64 lo, hi;\n.reg .b128 v;\nld.relaxed.gpu.global.b128 v, [%4];\nmov.b128 {lo, hi}, v;\nmov.b64 {%0, %1}, lo;\nmov.b64 {%2, %3}, hi;\n}"
        : "=r"(w0), "=r"(w1), "=r"(w2), "=r"(w3) : "l"(p) : "memory");
}

__device__ __forceinline__ void wg_ss128(float (&d)[64], uint32_t alo, uint32_t ahi, uint32_t blo, uint32_t bhi) {
    asm volatile("{\n.reg .b64 da, db;\nmov.b64 da, {%64, %65};\nmov.b64 db, {%66, %67};\n"
        "wgmma.mma_async.sync.aligned.m64n128k16.f32.bf16.bf16 {%0,%1,%2,%3,%4,%5,%6,%7,%8,%9,%10,%11,%12,%13,%14,%15,%16,%17,%18,%19,%20,%21,%22,%23,%24,%25,%26,%27,%28,%29,%30,%31,%32,%33,%34,%35,%36,%37,%38,%39,%40,%41,%42,%43,%44,%45,%46,%47,%48,%49,%50,%51,%52,%53,%54,%55,%56,%57,%58,%59,%60,%61,%62,%63}, da, db, 1, 1, 1, 0, 1;\n}\n"
        : "+f"(d[0]),"+f"(d[1]),"+f"(d[2]),"+f"(d[3]),"+f"(d[4]),"+f"(d[5]),"+f"(d[6]),"+f"(d[7]),"+f"(d[8]),"+f"(d[9]),"+f"(d[10]),"+f"(d[11]),"+f"(d[12]),"+f"(d[13]),"+f"(d[14]),"+f"(d[15]),"+f"(d[16]),"+f"(d[17]),"+f"(d[18]),"+f"(d[19]),"+f"(d[20]),"+f"(d[21]),"+f"(d[22]),"+f"(d[23]),"+f"(d[24]),"+f"(d[25]),"+f"(d[26]),"+f"(d[27]),"+f"(d[28]),"+f"(d[29]),"+f"(d[30]),"+f"(d[31]),"+f"(d[32]),"+f"(d[33]),"+f"(d[34]),"+f"(d[35]),"+f"(d[36]),"+f"(d[37]),"+f"(d[38]),"+f"(d[39]),"+f"(d[40]),"+f"(d[41]),"+f"(d[42]),"+f"(d[43]),"+f"(d[44]),"+f"(d[45]),"+f"(d[46]),"+f"(d[47]),"+f"(d[48]),"+f"(d[49]),"+f"(d[50]),"+f"(d[51]),"+f"(d[52]),"+f"(d[53]),"+f"(d[54]),"+f"(d[55]),"+f"(d[56]),"+f"(d[57]),"+f"(d[58]),"+f"(d[59]),"+f"(d[60]),"+f"(d[61]),"+f"(d[62]),"+f"(d[63])
        : "r"(alo), "r"(ahi), "r"(blo), "r"(bhi));
}
__device__ __forceinline__ void wg_ss128_z(float (&d)[64], uint32_t alo, uint32_t ahi, uint32_t blo, uint32_t bhi) {
    asm volatile("{\n.reg .b64 da, db;\nmov.b64 da, {%64, %65};\nmov.b64 db, {%66, %67};\n"
        "wgmma.mma_async.sync.aligned.m64n128k16.f32.bf16.bf16 {%0,%1,%2,%3,%4,%5,%6,%7,%8,%9,%10,%11,%12,%13,%14,%15,%16,%17,%18,%19,%20,%21,%22,%23,%24,%25,%26,%27,%28,%29,%30,%31,%32,%33,%34,%35,%36,%37,%38,%39,%40,%41,%42,%43,%44,%45,%46,%47,%48,%49,%50,%51,%52,%53,%54,%55,%56,%57,%58,%59,%60,%61,%62,%63}, da, db, 0, 1, 1, 0, 1;\n}\n"
        : "=f"(d[0]),"=f"(d[1]),"=f"(d[2]),"=f"(d[3]),"=f"(d[4]),"=f"(d[5]),"=f"(d[6]),"=f"(d[7]),"=f"(d[8]),"=f"(d[9]),"=f"(d[10]),"=f"(d[11]),"=f"(d[12]),"=f"(d[13]),"=f"(d[14]),"=f"(d[15]),"=f"(d[16]),"=f"(d[17]),"=f"(d[18]),"=f"(d[19]),"=f"(d[20]),"=f"(d[21]),"=f"(d[22]),"=f"(d[23]),"=f"(d[24]),"=f"(d[25]),"=f"(d[26]),"=f"(d[27]),"=f"(d[28]),"=f"(d[29]),"=f"(d[30]),"=f"(d[31]),"=f"(d[32]),"=f"(d[33]),"=f"(d[34]),"=f"(d[35]),"=f"(d[36]),"=f"(d[37]),"=f"(d[38]),"=f"(d[39]),"=f"(d[40]),"=f"(d[41]),"=f"(d[42]),"=f"(d[43]),"=f"(d[44]),"=f"(d[45]),"=f"(d[46]),"=f"(d[47]),"=f"(d[48]),"=f"(d[49]),"=f"(d[50]),"=f"(d[51]),"=f"(d[52]),"=f"(d[53]),"=f"(d[54]),"=f"(d[55]),"=f"(d[56]),"=f"(d[57]),"=f"(d[58]),"=f"(d[59]),"=f"(d[60]),"=f"(d[61]),"=f"(d[62]),"=f"(d[63])
        : "r"(alo), "r"(ahi), "r"(blo), "r"(bhi));
}
__device__ __forceinline__ void wg_ss64(float (&d)[32], uint32_t alo, uint32_t ahi, uint32_t blo, uint32_t bhi) {
    asm volatile("{\n.reg .b64 da, db;\nmov.b64 da, {%32, %33};\nmov.b64 db, {%34, %35};\n"
        "wgmma.mma_async.sync.aligned.m64n64k16.f32.bf16.bf16 {%0,%1,%2,%3,%4,%5,%6,%7,%8,%9,%10,%11,%12,%13,%14,%15,%16,%17,%18,%19,%20,%21,%22,%23,%24,%25,%26,%27,%28,%29,%30,%31}, da, db, 1, 1, 1, 0, 1;\n}\n"
        : "+f"(d[0]),"+f"(d[1]),"+f"(d[2]),"+f"(d[3]),"+f"(d[4]),"+f"(d[5]),"+f"(d[6]),"+f"(d[7]),"+f"(d[8]),"+f"(d[9]),"+f"(d[10]),"+f"(d[11]),"+f"(d[12]),"+f"(d[13]),"+f"(d[14]),"+f"(d[15]),"+f"(d[16]),"+f"(d[17]),"+f"(d[18]),"+f"(d[19]),"+f"(d[20]),"+f"(d[21]),"+f"(d[22]),"+f"(d[23]),"+f"(d[24]),"+f"(d[25]),"+f"(d[26]),"+f"(d[27]),"+f"(d[28]),"+f"(d[29]),"+f"(d[30]),"+f"(d[31])
        : "r"(alo), "r"(ahi), "r"(blo), "r"(bhi));
}
__device__ __forceinline__ void wg_ss64_z(float (&d)[32], uint32_t alo, uint32_t ahi, uint32_t blo, uint32_t bhi) {
    asm volatile("{\n.reg .b64 da, db;\nmov.b64 da, {%32, %33};\nmov.b64 db, {%34, %35};\n"
        "wgmma.mma_async.sync.aligned.m64n64k16.f32.bf16.bf16 {%0,%1,%2,%3,%4,%5,%6,%7,%8,%9,%10,%11,%12,%13,%14,%15,%16,%17,%18,%19,%20,%21,%22,%23,%24,%25,%26,%27,%28,%29,%30,%31}, da, db, 0, 1, 1, 0, 1;\n}\n"
        : "=f"(d[0]),"=f"(d[1]),"=f"(d[2]),"=f"(d[3]),"=f"(d[4]),"=f"(d[5]),"=f"(d[6]),"=f"(d[7]),"=f"(d[8]),"=f"(d[9]),"=f"(d[10]),"=f"(d[11]),"=f"(d[12]),"=f"(d[13]),"=f"(d[14]),"=f"(d[15]),"=f"(d[16]),"=f"(d[17]),"=f"(d[18]),"=f"(d[19]),"=f"(d[20]),"=f"(d[21]),"=f"(d[22]),"=f"(d[23]),"=f"(d[24]),"=f"(d[25]),"=f"(d[26]),"=f"(d[27]),"=f"(d[28]),"=f"(d[29]),"=f"(d[30]),"=f"(d[31])
        : "r"(alo), "r"(ahi), "r"(blo), "r"(bhi));
}
__device__ __forceinline__ void wg_ss64t(float (&d)[32], uint32_t alo, uint32_t ahi, uint32_t blo, uint32_t bhi) {
    asm volatile("{\n.reg .b64 da, db;\nmov.b64 da, {%32, %33};\nmov.b64 db, {%34, %35};\n"
        "wgmma.mma_async.sync.aligned.m64n64k16.f32.bf16.bf16 {%0,%1,%2,%3,%4,%5,%6,%7,%8,%9,%10,%11,%12,%13,%14,%15,%16,%17,%18,%19,%20,%21,%22,%23,%24,%25,%26,%27,%28,%29,%30,%31}, da, db, 1, 1, 1, 1, 1;\n}\n"
        : "+f"(d[0]),"+f"(d[1]),"+f"(d[2]),"+f"(d[3]),"+f"(d[4]),"+f"(d[5]),"+f"(d[6]),"+f"(d[7]),"+f"(d[8]),"+f"(d[9]),"+f"(d[10]),"+f"(d[11]),"+f"(d[12]),"+f"(d[13]),"+f"(d[14]),"+f"(d[15]),"+f"(d[16]),"+f"(d[17]),"+f"(d[18]),"+f"(d[19]),"+f"(d[20]),"+f"(d[21]),"+f"(d[22]),"+f"(d[23]),"+f"(d[24]),"+f"(d[25]),"+f"(d[26]),"+f"(d[27]),"+f"(d[28]),"+f"(d[29]),"+f"(d[30]),"+f"(d[31])
        : "r"(alo), "r"(ahi), "r"(blo), "r"(bhi));
}
__device__ __forceinline__ void wg_ss64t_z(float (&d)[32], uint32_t alo, uint32_t ahi, uint32_t blo, uint32_t bhi) {
    asm volatile("{\n.reg .b64 da, db;\nmov.b64 da, {%32, %33};\nmov.b64 db, {%34, %35};\n"
        "wgmma.mma_async.sync.aligned.m64n64k16.f32.bf16.bf16 {%0,%1,%2,%3,%4,%5,%6,%7,%8,%9,%10,%11,%12,%13,%14,%15,%16,%17,%18,%19,%20,%21,%22,%23,%24,%25,%26,%27,%28,%29,%30,%31}, da, db, 0, 1, 1, 1, 1;\n}\n"
        : "=f"(d[0]),"=f"(d[1]),"=f"(d[2]),"=f"(d[3]),"=f"(d[4]),"=f"(d[5]),"=f"(d[6]),"=f"(d[7]),"=f"(d[8]),"=f"(d[9]),"=f"(d[10]),"=f"(d[11]),"=f"(d[12]),"=f"(d[13]),"=f"(d[14]),"=f"(d[15]),"=f"(d[16]),"=f"(d[17]),"=f"(d[18]),"=f"(d[19]),"=f"(d[20]),"=f"(d[21]),"=f"(d[22]),"=f"(d[23]),"=f"(d[24]),"=f"(d[25]),"=f"(d[26]),"=f"(d[27]),"=f"(d[28]),"=f"(d[29]),"=f"(d[30]),"=f"(d[31])
        : "r"(alo), "r"(ahi), "r"(blo), "r"(bhi));
}
__device__ __forceinline__ void wg_ss8t(float (&d)[4], uint32_t alo, uint32_t ahi, uint32_t blo, uint32_t bhi) {
    asm volatile("{\n.reg .b64 da, db;\nmov.b64 da, {%4, %5};\nmov.b64 db, {%6, %7};\n"
        "wgmma.mma_async.sync.aligned.m64n8k16.f32.bf16.bf16 {%0,%1,%2,%3}, da, db, 1, 1, 1, 1, 0;\n}\n"
        : "+f"(d[0]),"+f"(d[1]),"+f"(d[2]),"+f"(d[3])
        : "r"(alo), "r"(ahi), "r"(blo), "r"(bhi));
}
__device__ __forceinline__ void wg_ss8t_z(float (&d)[4], uint32_t alo, uint32_t ahi, uint32_t blo, uint32_t bhi) {
    asm volatile("{\n.reg .b64 da, db;\nmov.b64 da, {%4, %5};\nmov.b64 db, {%6, %7};\n"
        "wgmma.mma_async.sync.aligned.m64n8k16.f32.bf16.bf16 {%0,%1,%2,%3}, da, db, 0, 1, 1, 1, 0;\n}\n"
        : "=f"(d[0]),"=f"(d[1]),"=f"(d[2]),"=f"(d[3])
        : "r"(alo), "r"(ahi), "r"(blo), "r"(bhi));
}
__device__ __forceinline__ void wg_rs24_z(float (&d)[12], uint32_t a0, uint32_t a1, uint32_t a2, uint32_t a3, uint32_t blo, uint32_t bhi) {
    asm volatile("{\n.reg .b64 db;\nmov.b64 db, {%16, %17};\n"
        "wgmma.mma_async.sync.aligned.m64n24k16.f32.bf16.bf16 {%0,%1,%2,%3,%4,%5,%6,%7,%8,%9,%10,%11}, {%12,%13,%14,%15}, db, 0, 1, 1, 0;\n}\n"
        : "=f"(d[0]),"=f"(d[1]),"=f"(d[2]),"=f"(d[3]),"=f"(d[4]),"=f"(d[5]),"=f"(d[6]),"=f"(d[7]),"=f"(d[8]),"=f"(d[9]),"=f"(d[10]),"=f"(d[11])
        : "r"(a0), "r"(a1), "r"(a2), "r"(a3), "r"(blo), "r"(bhi));
}

constexpr uint32_t DH128 = 64u | 0x40000000u;
constexpr uint32_t DH64 = 32u | 0x80000000u;
constexpr uint32_t LBO4K = (4096u >> 4) << 16, LBO8K = (8192u >> 4) << 16, LBO1 = 1u << 16;

template <bool SW64, bool FIRST> __device__ __forceinline__ void g1_issue(float (&acc)[64], uint32_t alo, uint32_t blo) {
    wg_fence();
#pragma unroll
    for (int k = 0; k < 4; k++) {
        if (FIRST && k == 0) wg_ss128_z(acc, alo, DH128, blo, SW64 ? DH64 : DH128);
        else wg_ss128(acc, alo + 2 * k, DH128, blo + (SW64 ? 64 * k : 128 * k), SW64 ? DH64 : DH128);
    }
    wg_commit();
}

template <int N> __device__ __forceinline__ void stash(uint32_t base, uint32_t sw, const uint32_t (&f)[N]) {
#pragma unroll
    for (int t = 0; t < N / 4; t++) stsm4(base + ((sw ^ (2 * t)) << 4), f[4 * t], f[4 * t + 1], f[4 * t + 2], f[4 * t + 3]);
}

template <int V0, int V1, int N> __device__ __forceinline__ void send_frag(const uint32_t (&f)[N], uint4* p, uint32_t tag) {
#pragma unroll
    for (int v = V0; v < V1; v++) st_pkt(p + v * 32, (f[4 * v] & ~1u) | tag, f[4 * v + 1], f[4 * v + 2], f[4 * v + 3]);
}
template <int H0, int H1, int N> __device__ __forceinline__ void send_h(const uint32_t (&f)[N], uint4* p) {
#pragma unroll
    for (int h = H0; h < H1; h++) {
        p[4 * h] = make_uint4(f[8 * h], f[8 * h + 2], f[8 * h + 4], f[8 * h + 6]);
        p[4 * h + 64] = make_uint4(f[8 * h + 1], f[8 * h + 3], f[8 * h + 5], f[8 * h + 7]);
    }
}
template <int O, int N, int M> __device__ __forceinline__ void pack_sub(uint32_t (&f)[N], const float (&acc)[M]) {
#pragma unroll
    for (int i = 0; i < N; i++) f[i] = pack2(acc[O + 2 * i], acc[O + 2 * i + 1]);
}
template <int N> __device__ __forceinline__ void recv_issue(uint32_t (&q)[N], const uint4* p) {
#pragma unroll
    for (int v = 0; v < N / 4; v++) ld_pkt(p + v * 32, q[4 * v], q[4 * v + 1], q[4 * v + 2], q[4 * v + 3]);
}
template <int N> __device__ __forceinline__ void recv_check(uint32_t (&q)[N], const uint4* p, uint32_t tag) {
    uint32_t it = 0;
    while (true) {
        uint32_t bad = 0;
#pragma unroll
        for (int v = 0; v < N / 4; v++) bad |= q[4 * v] ^ tag;
        if (__all_sync(0xffffffffu, (bad & 1u) == 0) || ++it > SPIN_GLOBAL) break;
        recv_issue(q, p);
    }
}
__device__ __forceinline__ void accum(const uint32_t (&q)[32], float (&sum)[64]) {
#pragma unroll
    for (int i = 0; i < 32; i++) { sum[2 * i] += bf_lo(q[i]); sum[2 * i + 1] += bf_hi(q[i]); }
}

}

__global__ void __launch_bounds__(384, 1)
fused_kernel(const __grid_constant__ Maps maps, const __nv_bfloat16* __restrict__ xg, const __nv_bfloat16* __restrict__ gate_w,
             const char* __restrict__ pf_qkv, const char* __restrict__ pf_g, const char* __restrict__ pf_u,
             const char* __restrict__ pf_d, const char* __restrict__ pf_o, __nv_bfloat16* __restrict__ out) {
    extern __shared__ __align__(1024) uint8_t smem_raw[];
    const uint32_t sb = (uint32_t)__cvta_generic_to_shared(smem_raw);
    const int tid = threadIdx.x, lane = tid & 31;
    const int warp = __shfl_sync(0xffffffffu, tid >> 5, 0);
    const int j = (blockIdx.x >> 1) & 7;
    const int r = ((blockIdx.x >> 4) << 1) | (blockIdx.x & 1);
    const uint32_t rank = blockIdx.x & 1;

    if (warp == 0) { TSG(0, 30); TS(0, 0); }
    if (tid == 256) {
        for (int i = 0; i < 5; i++) { mbar_init(sb + B_FULL + 8 * i, 1); mbar_init(sb + B_EMPTY + 8 * i, MC ? 4 : 2); }
        for (int i = 0; i < 9; i++) mbar_init(sb + B_XFULL + 8 * i, 1);
        asm volatile("fence.mbarrier_init.release.cluster;" ::: "memory");
        mbar_expect(sb + B_XFULL, 16384);
        tma2(sb + OFF_X, &maps.x, 0, r * 128, sb + B_XFULL);
        TS2(0);
        mbar_expect(sb + B_FULL, 16384);
        tmaw3(sb + OFF_RING, &maps.gu, 224 * j, 0, 0, sb + B_FULL);
        TS2(1);
        mbar_expect(sb + B_FULL + 8, 16384);
        tmaw3(sb + OFF_RING + 16384, &maps.kv, 64 * j, 0, 1, sb + B_FULL + 8);
    } else if (tid == 288) {
        for (int i = 0; i < 5; i++) mbar_init(sb + B_HSENT + 8 * i, 8);
        mbar_init(sb + B_XFREE, 2); mbar_init(sb + B_XFREE + 8, 2); mbar_init(sb + B_XFREE + 16, 2);
        mbar_init(sb + B_AHEAD, 1); mbar_init(sb + B_GRDY, 1); mbar_init(sb + B_KVDONE, 8); mbar_init(sb + B_KVRDY, 2);
        asm volatile("fence.mbarrier_init.release.cluster;" ::: "memory");
    } else if (warp == 10 && lane < 11) {
        asm volatile("prefetch.tensormap [%0];" :: "l"(&maps.gu + lane) : "memory");
    }
    __syncthreads();

    if (warp >= 8) {
        asm volatile("setmaxnreg.dec.sync.aligned.u32 72;");
        if (warp == 8) {
            if (lane == 0) {
                int slot = MC ? 0 : 2, ph = 1;
                uint32_t full, dst;
                if (!MC) { mbar_expect(sb + B_XFULL + 8, 16384); tma2(sb + OFF_X + 16384, &maps.x, 64, r * 128, sb + B_XFULL + 8); }
#define P_BEGIN(S, BYTES) full = sb + B_FULL + 8 * slot; dst = sb + OFF_RING + slot * 16384; \
                mbar_wait(sb + B_EMPTY + 8 * slot, ph); TS2(S); mbar_expect(full, BYTES); if (!MC || (((S) ^ rank) & 1) == 0)
#define P_END() if (++slot == 5) { slot = 0; ph ^= 1; }
                for (int s = MC ? 0 : 2; s < 16; s++) {
                    P_BEGIN(s, 16384) {
                        const int sw = s == 13 ? 14 : s == 14 ? 13 : s;
                        if (sw & 1) tmaw3(dst, &maps.kv, 64 * j, 32 * (sw - 1), 1, full);
                        else tmaw3(dst, &maps.gu, 224 * j, 32 * sw, 0, full);
                    }
                    const int xb = (s == 4) ? 3 : (s == 10) ? 7 : !(s & 1) ? 0 : (s < 5) ? (s + 1) / 2 : (s <= 9) ? (s + 3) / 2 : 0;
                    if (xb) { mbar_expect(sb + B_XFULL + 8 * xb, 16384); tma2(sb + OFF_X + xb * 16384, &maps.x, 64 * xb, r * 128, sb + B_XFULL + 8 * xb); }
                    P_END()
                }
                for (int s = 0; s < 24; s++) {
                    P_BEGIN(16 + s, 16384) {
                        if ((s >> 3) == 1) {
                            tmaw3(dst, &maps.q64, 0, 64 * (s & 7), 2 * j, full);
                            tmaw3(dst + 8192, &maps.gu64, 224 * j + 192, 64 * (s & 7), 0, full);
                        } else {
                            tmaw3(dst, &maps.gu, 224 * j + 64 + 4 * (s & 16), 64 * (s & 7), 0, full);
                        }
                    }
                    P_END()
                }
                const int p = j >> 1;
#pragma unroll 1
                for (int i = 0; i < 18; i++) {
                    const int t = i < 14 ? i : i < 16 ? i + 2 : i - 2;
                    const int q = (t >= 7 && t != 9 && t != 10), u = t < 7 ? t : t < 9 ? t - 7 : t < 11 ? t - 2 : t - 9;
                    const int cw = (j & 1) * 4 + ((p & 2) ^ (q ? 0 : 2)), cc = 64 * cw;
                    if (t < 16) {
                        full = sb + B_FULL + 8 * slot; dst = sb + OFF_RING + slot * 16384;
                        mbar_wait(sb + B_EMPTY + 8 * slot, ph);
                        P_END()
                    } else {
                        full = sb + B_XFULL + (t - 16) * 24; dst = sb + OFF_X + (t - 16) * 16384;
                        mbar_wait(sb + B_XFREE + 8 * (t - 16), 1);
                    }
                    TS2(40 + t);
                    mbar_expect(full, 16384);
                    if (!MC || ((t ^ rank) & 1) == 0) {
                        if (u == 4) {
                            tmaw5(dst, &maps.wdph, cc, 14 * p + 6, full); tmaw5(dst + 4096, &maps.wdph, cc, 14 * p + 13, full);
                            tmaw5(dst + 8192, &maps.wdph, cc + 64, 14 * p + 6, full); tmaw5(dst + 12288, &maps.wdph, cc + 64, 14 * p + 13, full);
                        } else if (u == 5 || u == 6) {
                            tmaw3(dst, u == 5 ? &maps.wow : &maps.wdw, 0, u == 5 ? 64 * j : 224 * j + 128, cw, full);
                        } else {
                            const CUtensorMap* m = u == 7 ? &maps.wop : &maps.wdp;
                            const int g = u == 7 ? 2 * (j ^ 1) : u == 8 ? 7 * (j ^ 1) + 4 : 14 * p + 7 * (u & 1) + (u & 2);
                            tmaw5(dst, m, cc, g, full); tmaw5(dst + 8192, m, cc + 64, g, full);
                        }
                    }
                }
            }
        } else if (warp < 11) {
            const int hx = warp - 9;
            uint32_t epoch;
            asm volatile("ld.relaxed.gpu.global.u32 %0, [%1];" : "=r"(epoch) : "l"(g_epoch + blockIdx.x) : "memory");
            {
                const uint4* xr = (const uint4*)(xg + (size_t)(r * 128 + j * 16 + hx * 8) * kD) + lane;
                const uint4 wa = __ldg((const uint4*)gate_w + lane), wb = __ldg((const uint4*)gate_w + 32 + lane);
                const uint32_t tag = (epoch + 1) & 1;
                uint4* gp = g_gx + r * 32;
                if (lane < 2) st_pkt(gp + j * 4 + hx * 2 + lane, tag ^ 1, 0, 0, 0);
                float s[8];
#pragma unroll
                for (int i0 = 0; i0 < 8; i0 += 4) {
                    uint4 va[4], vb[4];
#pragma unroll
                    for (int i = 0; i < 4; i++) { va[i] = __ldg(xr + (i0 + i) * 64); vb[i] = __ldg(xr + (i0 + i) * 64 + 32); }
#pragma unroll
                    for (int i = 0; i < 4; i++) {
                        float t0 = bf_lo(va[i].x) * bf_lo(wa.x), t1 = bf_hi(va[i].x) * bf_hi(wa.x);
                        t0 = fmaf(bf_lo(va[i].y), bf_lo(wa.y), t0); t1 = fmaf(bf_hi(va[i].y), bf_hi(wa.y), t1);
                        t0 = fmaf(bf_lo(va[i].z), bf_lo(wa.z), t0); t1 = fmaf(bf_hi(va[i].z), bf_hi(wa.z), t1);
                        t0 = fmaf(bf_lo(va[i].w), bf_lo(wa.w), t0); t1 = fmaf(bf_hi(va[i].w), bf_hi(wa.w), t1);
                        t0 = fmaf(bf_lo(vb[i].x), bf_lo(wb.x), t0); t1 = fmaf(bf_hi(vb[i].x), bf_hi(wb.x), t1);
                        t0 = fmaf(bf_lo(vb[i].y), bf_lo(wb.y), t0); t1 = fmaf(bf_hi(vb[i].y), bf_hi(wb.y), t1);
                        t0 = fmaf(bf_lo(vb[i].z), bf_lo(wb.z), t0); t1 = fmaf(bf_hi(vb[i].z), bf_hi(wb.z), t1);
                        t0 = fmaf(bf_lo(vb[i].w), bf_lo(wb.w), t0); t1 = fmaf(bf_hi(vb[i].w), bf_hi(wb.w), t1);
                        s[i0 + i] = t0 + t1;
                    }
                }
#pragma unroll
                for (int i = 0; i < 8; i++) {
#pragma unroll
                    for (int o = 16; o; o >>= 1) s[i] += __shfl_xor_sync(0xffffffffu, s[i], o);
                    s[i] = 1.f / (1.f + __expf(-s[i]));
                }
                if (lane < 2) {
                    const float v0 = lane ? s[4] : s[0], v1 = lane ? s[5] : s[1], v2 = lane ? s[6] : s[2], v3 = lane ? s[7] : s[3];
                    st_pkt(gp + j * 4 + hx * 2 + lane, (__float_as_uint(v0) & ~1u) | tag, __float_as_uint(v1), __float_as_uint(v2), __float_as_uint(v3));
                }
                if (hx == 1) {
                    asm volatile("st.shared.u32 [%0], %1;" :: "r"(sb + OFF_ONES + lane * 4), "r"(0x3f803f80u) : "memory");
                    asm volatile("fence.proxy.async.shared::cta;" ::: "memory");
                }
                asm volatile("bar.sync 3, 96;" ::: "memory");
                if (hx == 0) {
                    uint32_t q[4];
                    recv_issue(q, gp + lane);
                    recv_check(q, gp + lane, tag);
                    asm volatile("st.shared.v4.u32 [%0], {%1,%2,%3,%4};" :: "r"(sb + OFF_G + lane * 16), "r"(q[0]), "r"(q[1]), "r"(q[2]), "r"(q[3]) : "memory");
                    if (lane == 0) {
                        asm volatile("st.shared.u32 [%0], %1;" :: "r"(sb + OFF_EPOCH), "r"(epoch) : "memory");
                        g_epoch[blockIdx.x] = epoch + 1;
                    }
                    __syncwarp();
                    if (lane == 0) mbar_arrive(sb + B_GRDY);
                } else {
                    if (r == 0) {
                        float4* zp = (float4*)(g_kvacc + (((epoch & 1) ^ 1) * 8 + j) * 4 * 272);
                        for (int i = lane; i < 272; i += 32) zp[i] = make_float4(0.f, 0.f, 0.f, 0.f);
                    }
                }
            }
            TS(2 + hx, 1);
#define PUBLISH_H(B) do { mbar_wait(sb + B_HSENT + 8 * (B), 0); if (lane == 0) { \
                asm volatile("st.release.gpu.global.u32 [%0], %1;" :: "l"(g_hflag + (r * 8 + j) * 8 + (B)), "r"(epoch + 1) : "memory"); } __syncwarp(); } while (0)
            if (hx == 1) {
#pragma unroll 1
                for (int b = 0; b < 4; b++) { PUBLISH_H(b); TS(3, 5 + b); }
            } else {
                const float* accp = g_kvacc + ((epoch & 1) * 8 + j) * 4 * 272;
                unsigned* cnt = g_kvcnt + j * 32;
                mbar_wait(sb + B_KVDONE, 0);
                TS(2, 5);
                if (lane == 0) asm volatile("red.release.gpu.global.add.u32 [%0], 1;" :: "l"(cnt) : "memory");
                __syncwarp();
                TS(2, 2);
                {
                    const unsigned target = 16u * (epoch + 1);
                    uint32_t it = 0, v;
                    do {
                        asm volatile("ld.acquire.gpu.global.u32 %0, [%1];" : "=r"(v) : "l"(cnt) : "memory");
                    } while ((int)(v - target) < 0 && ++it < SPIN_GLOBAL);
                }
                TS(2, 3);
#pragma unroll
                for (int h = 0; h < 4; h++) {
                    const float4 d0 = __ldcg((const float4*)(accp + h * 272) + lane);
                    const float4 d1 = __ldcg((const float4*)(accp + h * 272 + 128) + lane);
                    const float2 z0 = __ldcg((const float2*)(accp + h * 272 + 256) + (lane & 3));
                    const float2 z1 = __ldcg((const float2*)(accp + h * 272 + 264) + (lane & 3));
                    const uint32_t ba = sb + OFF_STG + h * 768 + lane * 4;
                    asm volatile("st.shared.u32 [%0], %1;" :: "r"(ba), "r"(pack2(d0.x, d0.y)) : "memory");
                    asm volatile("st.shared.u32 [%0], %1;" :: "r"(ba + 128), "r"(pack2(d1.x, d1.y)) : "memory");
                    asm volatile("st.shared.u32 [%0], %1;" :: "r"(ba + 256), "r"(pack2(d0.z, d0.w)) : "memory");
                    asm volatile("st.shared.u32 [%0], %1;" :: "r"(ba + 384), "r"(pack2(d1.z, d1.w)) : "memory");
                    asm volatile("st.shared.u32 [%0], %1;" :: "r"(ba + 512), "r"(pack2(z0.x, z0.y)) : "memory");
                    asm volatile("st.shared.u32 [%0], %1;" :: "r"(ba + 640), "r"(pack2(z1.x, z1.y)) : "memory");
                }
                asm volatile("fence.proxy.async.shared::cta;" ::: "memory");
                __syncwarp();
                if (lane == 0) mbar_arrive(sb + B_KVRDY);
                TS(2, 4);
                PUBLISH_H(4);
                TS(3, 9);
            }
        } else {
            uint32_t epoch;
            asm volatile("ld.relaxed.gpu.global.u32 %0, [%1];" : "=r"(epoch) : "l"(g_epoch + blockIdx.x) : "memory");
            asm volatile("bar.arrive 3, 96;" :: "r"(epoch) : "memory");
            const int b = blockIdx.x, p = j >> 1;
            mbar_wait(sb + B_XFULL, 0);
            {
                uint4* mb = g_part + (size_t)(r * 2 + (j & 1)) * 16384 + (p << 10) + lane;
#pragma unroll 8
                for (int i = 0; i < 64; i++) st_pkt(mb + (((i & 32) ? p ^ 1 : p ^ 3) << 12) + (i & 31) * 32, epoch & 1, 0, 0, 0);
                __syncwarp();
                if (lane == 0) mbar_arrive(sb + B_KVRDY);
            }
#pragma unroll 1
            for (int kb = 1; kb < 8; kb++) {
                mbar_wait(sb + B_XFULL + 8 * kb, 0);
                const char* base = kb < 3 ? pf_g : kb < 5 ? pf_u : kb == 5 ? pf_qkv : pf_d;
                const int off = kb == 5 ? b * 12288 : b * 14336 + ((kb < 5 ? kb - 1 : kb) & 1) * 7168;
                asm volatile("prefetch.global.L2 [%0];" :: "l"(base + off + lane * 128));
                if (kb == 5 || lane < 24) asm volatile("prefetch.global.L2 [%0];" :: "l"(base + off + 4096 + lane * 128));
                if (kb == 5) asm volatile("prefetch.global.L2 [%0];" :: "l"(base + off + 8192 + lane * 128));
                if (kb == 7) asm volatile("prefetch.global.L2 [%0];" :: "l"(pf_o + b * 4096 + lane * 128));
            }
            {
                const uint32_t want = epoch + 1;
                const int hrow = (r * 4 + p) * 9 * 128, po = (j & 1) ^ 1;
                const unsigned* fl = g_hflag + (r * 8 + (j & 6)) * 8 + (lane & 15);
                uint32_t it = 0;
                int i = 0;
                mbar_wait(sb + B_HSENT + 8, 0);
#pragma unroll 1
                while (i < 5 && ++it < SPIN_GLOBAL) {
                    uint32_t v;
                    asm volatile("ld.acquire.gpu.global.u32 %0, [%1];" : "=r"(v) : "l"(fl) : "memory");
                    const uint32_t rdy = __ballot_sync(0xffffffffu, v == want);
#pragma unroll 1
                    while (i < 5) {
                        const uint32_t need = i < 3 ? 0x101u << i : 1u << (8 * po + i);
                        if ((rdy & need) != need) break;
                        if (i < 3) mbar_wait(sb + B_XFREE + 8 * i, 0);
                        if (lane == 0) {
                            asm volatile("fence.proxy.async.global;" ::: "memory");
                            const int piece = i < 3 ? 2 * i : i == 3 ? 5 : 8, tile = i < 3 ? 2 * i : 2 * i - 1 + po;
                            const uint32_t bar = sb + B_XFULL + 8 * (i == 0 ? 1 : piece);
                            TS2(140 + i);
                            mbar_expect(bar, i < 2 ? 32768 : 16384);
                            tma2(sb + OFF_X + piece * 16384, i < 2 ? &maps.hx2 : &maps.hx, 0, hrow + tile * 128, bar);
                        }
                        i++;
                    }
                }
            }
        }
    } else {
        asm volatile("setmaxnreg.inc.sync.aligned.u32 216;");
        const int wg = warp >> 2;
        const bool elect = (tid & 127) == 0;
        const uint32_t xlo = ((sb + OFF_X + wg * 8192) >> 4) | LBO1;
        const uint32_t ringlo = (sb + OFF_RING) >> 4;
        auto release = [&](int s) {
            if (elect) {
                mbar_arrive(sb + B_EMPTY + 8 * s);
            }
        };
#define S_WAIT(S) do { if ((S) < 56) mbar_wait(sb + B_FULL + 8 * ((S) % 5), ((S) / 5) & 1); else mbar_wait(sb + B_XFULL + ((S) - 56) * 24, 1); \
            if (PROF && tid == 0) TS2(64 + (S)); } while (0)
#define S_B(S) ((S) < 56 ? ringlo + ((S) % 5) * 1024 : ((sb + OFF_X) >> 4) + ((S) - 56) * 1024)
#define G1(S, acc, SW, KB) do { S_WAIT(S); g1_issue<SW, (KB) == 0>(acc, xlo + (KB) * 1024, S_B(S) | (SW ? LBO4K : LBO8K)); } while (0)
#define RET(S) do { wg_wait<1>(); if ((S) - 1 < 51) release(((S) - 1) % 5); } while (0)
#define SCHED() mbar_wait(sb + B_XFULL + 8 * 7, 0)
#define A2_SYNC() do { asm volatile("fence.proxy.async.shared::cta;" ::: "memory"); asm volatile("bar.sync %0, 128;" :: "r"(wg + 1) : "memory"); } while (0)
#define H_EPI(acc, F, I0, I1, OG, OU) _Pragma("unroll") for (int i = (I0); i < (I1); i++) \
            F[i] = hmul2(pack2(acc[(OG) + 2 * i] * acc[(OU) + 2 * i], acc[(OG) + 2 * i + 1] * acc[(OU) + 2 * i + 1]), (i & 1) ? m_hi : m_lo)
#define PHI(acc, F, I0, I1) _Pragma("unroll") for (int i = (I0); i < (I1); i++) F[i] = phi2(acc[2 * i], acc[2 * i + 1])

        float a0[64], b0[64], a1[64], a2_[64], a3[64];
        mbar_wait(sb + B_XFULL, 0);
        G1(0, a0, false, 0);
        if ((warp & 3) == 0) TS(wg, 1);
        G1(1, b0, false, 0); RET(1);
#define C0(KB) mbar_wait(sb + B_XFULL + 8 * (KB), 0); if (PROF && tid == 0) TS2(128 + (KB)); \
        G1(2 * (KB), a0, false, KB); RET(2 * (KB)); G1(2 * (KB) + 1, b0, false, KB); RET(2 * (KB) + 1)
        C0(1); C0(2); C0(3); C0(4); C0(5);
        mbar_wait(sb + B_XFULL + 8 * 6, 0);
        G1(12, a0, false, 6); RET(12);
        mbar_wait(sb + B_XFULL + 8 * 7, 0);
        G1(13, a0, false, 7); RET(13);
        G1(14, b0, false, 6);
        mbar_wait(sb + B_GRDY, 0);
        float g_lo, g_hi;
        uint32_t tag;
        {
            const uint32_t ga = sb + OFF_G + (warp * 16 + (lane >> 2)) * 4;
            asm volatile("ld.shared.f32 %0, [%1];" : "=f"(g_lo) : "r"(ga) : "memory");
            asm volatile("ld.shared.f32 %0, [%1];" : "=f"(g_hi) : "r"(ga + 32) : "memory");
            asm volatile("ld.shared.u32 %0, [%1];" : "=r"(tag) : "r"(sb + OFF_EPOCH) : "memory");
        }
        float* const kvp = g_kvacc + (((tag & 1) * 8 + j) * 4 + (warp & 3)) * 272;
        tag = (tag + 1) & 1;
        const uint32_t m_lo = pack2(1.f - g_lo, 1.f - g_lo), m_hi = pack2(1.f - g_hi, 1.f - g_hi);
        const uint32_t lrow = ((lane & 7) + 8 * ((lane >> 3) & 1)) * 128;
        const uint32_t srow = (warp & 3) * 2048 + lrow;
        const uint32_t ssw = (lane >> 4) ^ (lane & 7);
        uint4* const hsend = g_hx + (size_t)((r * 4 + (j >> 1)) * 9 + (j & 1)) * 1024 + warp * 128 + (lane >> 2) * 8 + (lane & 3);
#define SENT_H(B) do { __syncwarp(); if (lane == 0) mbar_arrive(sb + B_HSENT + 8 * (B)); } while (0)
        RET(14);
        pin(a0);
        uint32_t fh0[16], fh1[16], fh2[16], fh3[8], fo[16];
        G1(15, b0, false, 7); SCHED(); H_EPI(a0, fh0, 0, 16, 0, 32); RET(15);
        if ((warp & 3) == 0) TS(wg, 2);

        float kv[32], zs[4];
        uint32_t pk[16], pv[16];
        const uint32_t stg = sb + OFF_STG + wg * 8192, stl = stg + (warp & 1) * 2048 + lrow;
        const uint32_t klo = (stg >> 4) | LBO1, vlo = klo + 256, olo = (sb + OFF_ONES) >> 4;
        G1(16, a1, false, 0); RET(16);
        pin(b0);
        G1(17, a1, false, 1); send_h<0, 1>(fh0, hsend); SCHED(); PHI(b0, pk, 0, 6); RET(17);
        G1(18, a1, false, 2); send_h<1, 2>(fh0, hsend); SENT_H(0); SCHED(); PHI(b0, pk, 6, 12); RET(18);
        G1(19, a1, false, 3); SCHED(); PHI(b0, pk, 12, 16); pack_sub<32>(pv, b0); RET(19);
#define KV_ROUND(Z) do { A2_SYNC(); wg_fence(); \
            wg_ss64t##Z(kv, vlo, DH128, klo, DH128); wg_ss64t(kv, vlo + 128, DH128, klo + 128, DH128); \
            wg_ss8t##Z(zs, klo, DH128, olo, 0); wg_ss8t(zs, klo + 128, DH128, olo, 0); wg_commit(); } while (0)
        G1(20, a1, false, 4); if (!(warp & 2)) { stash<16>(stl, ssw, pk); stash<16>(stl + 4096, ssw, pv); } RET(20);
        G1(21, a1, false, 5); KV_ROUND(_z); wg_wait<2>(); release(20 % 5);
        G1(22, a1, false, 6); RET(22);
        G1(23, a1, false, 7); if (warp & 2) { stash<16>(stl, ssw, pk); stash<16>(stl + 4096, ssw, pv); } RET(23);
        if ((warp & 3) == 0) TS(wg, 3);

        G1(24, a2_, true, 0); KV_ROUND(); wg_wait<2>(); release(23 % 5);
        pin(a1);
        G1(25, a2_, true, 1); RET(25);
        pin(kv); pin(zs);
        G1(26, a2_, true, 2);
#define KV_RED(W) do { asm volatile("red.global.add.v4.f32 [%0], {%1,%2,%3,%4};" :: "l"(kvp + lane * 4), "f"(kv[8 * W]), "f"(kv[8 * W + 1]), "f"(kv[8 * W + 2]), "f"(kv[8 * W + 3]) : "memory"); \
                       asm volatile("red.global.add.v4.f32 [%0], {%1,%2,%3,%4};" :: "l"(kvp + 128 + lane * 4), "f"(kv[8 * W + 4]), "f"(kv[8 * W + 5]), "f"(kv[8 * W + 6]), "f"(kv[8 * W + 7]) : "memory"); } while (0)
        if ((warp & 3) == 0) KV_RED(0); else if ((warp & 3) == 1) KV_RED(1); else if ((warp & 3) == 2) KV_RED(2); else KV_RED(3);
        if ((lane & 3) == 0) {
            asm volatile("red.global.add.f32 [%0], %1;" :: "l"(kvp + 256 + (lane >> 2)), "f"(zs[0]) : "memory");
            asm volatile("red.global.add.f32 [%0], %1;" :: "l"(kvp + 264 + (lane >> 2)), "f"(zs[2]) : "memory");
        }
        __syncwarp();
        if (lane == 0) mbar_arrive(sb + B_KVDONE);
        RET(26);
        G1(27, a2_, true, 3); SCHED(); H_EPI(a1, fh1, 0, 16, 0, 32); RET(27);
        G1(28, a2_, true, 4); RET(28);
        G1(29, a2_, true, 5); RET(29);
        G1(30, a2_, true, 6); send_h<0, 1>(fh1, hsend + 2 * 1024); RET(30);
        G1(31, a2_, true, 7); send_h<1, 2>(fh1, hsend + 2 * 1024); SENT_H(1); RET(31);
        if ((warp & 3) == 0) TS(wg, 4);

        const uint32_t a2 = sb + OFF_X + wg * 8192 + srow;
        float on[4][12];
#define O_SCALE(h) do { const float s_lo = __fdividef(g_lo, on[h][8] + 1e-6f), s_hi = __fdividef(g_hi, on[h][10] + 1e-6f); \
            const uint32_t sl_ = pack2(s_lo, s_lo), sh_ = pack2(s_hi, s_hi); \
            fo[4 * h] = hmul2(pack2(on[h][0], on[h][1]), sl_); fo[4 * h + 1] = hmul2(pack2(on[h][2], on[h][3]), sh_); \
            fo[4 * h + 2] = hmul2(pack2(on[h][4], on[h][5]), sl_); fo[4 * h + 3] = hmul2(pack2(on[h][6], on[h][7]), sh_); } while (0)
        G1(32, a3, false, 0); RET(32);
        pin(a2_);
        G1(33, a3, false, 1); SCHED(); H_EPI(a2_, fh3, 0, 8, 32, 48);
        send_h<0, 1>(fh3, hsend + 4 * 1024 - (j & 1) * 1020); SENT_H(2); PHI(a2_, fo, 0, 2); RET(33);
        G1(34, a3, false, 2); SCHED(); PHI(a2_, fo, 2, 7); RET(34);
        if (elect) mbar_arrive(sb + B_XFREE);
        G1(35, a3, false, 3); SCHED(); PHI(a2_, fo, 7, 12); RET(35);
        G1(36, a3, false, 4); SCHED(); PHI(a2_, fo, 12, 16); RET(36);
        if (elect) mbar_arrive(sb + B_XFREE + 8);
        G1(37, a3, false, 5);
        if ((warp & 3) == 0) TS(wg, 5);
        mbar_wait(sb + B_KVRDY, 0);
        if ((warp & 3) == 0) TS(wg, 6);
        wg_fence();
#pragma unroll
        for (int h = 0; h < 4; h++)
            wg_rs24_z(on[h], fo[4 * h], fo[4 * h + 1], fo[4 * h + 2], fo[4 * h + 3], (((sb + OFF_STG) >> 4) + h * 48) | (8u << 16), 16u);
        wg_commit();
        wg_wait<2>(); release(36 % 5);
        G1(38, a3, false, 6); RET(38);
        if (elect) mbar_arrive(sb + B_XFREE + 16);
        pin(on[0]); pin(on[1]); pin(on[2]); pin(on[3]);
        G1(39, a3, false, 7); SCHED();
        O_SCALE(0); O_SCALE(1); send_h<0, 1>(fo, hsend + 5 * 1024);
        O_SCALE(2); O_SCALE(3);
        RET(39);
        if ((warp & 3) == 0) TS(wg, 7);

#define G2_PIECE(U) ((U) < 5 ? (U) : (U) == 5 ? 6 : (U) == 6 ? 7 : (U) == 7 ? 5 : 8)
#define G2(S, acc, U) do { S_WAIT(S); wg_fence(); _Pragma("unroll") for (int k = 0; k < 4; k++) { \
            if ((U) == 0 && k == 0) wg_ss128_z(acc, xlo, DH128, S_B(S) | LBO8K, DH128); \
            else wg_ss128(acc, xlo + G2_PIECE(U) * 1024 + 2 * k, DH128, (S_B(S) | LBO8K) + 128 * k, DH128); } wg_commit(); } while (0)
#define H_WAIT(P) do { mbar_wait(sb + B_XFULL + 8 * (P), (P) < 8); if (PROF && tid == 0) TS2(150 + (P)); } while (0)
        const int p = j >> 1, pw = (p & 2) ^ 2;
        const bool own = wg == (p & 1);
        uint4* const pbase = g_part + (size_t)(r * 2 + (j & 1)) * 16384 + (warp & 3) * 256 + lane;

        float p1[64], p2[64];
        H_WAIT(1); G2(40, p1, 0); send_h<1, 2>(fo, hsend + 5 * 1024); SENT_H(3); RET(40);
        pin(a3);
        G2(41, p1, 1); SCHED(); H_EPI(a3, fh2, 0, 16, 0, 32); send_h<0, 2>(fh2, hsend + 7 * 1024); SENT_H(4); RET(41);
        H_WAIT(2); G2(42, p1, 2); stash<16>(a2 + 6 * 16384, ssw, fo); RET(42);
        G2(43, p1, 3); stash<16>(a2 + 7 * 16384, ssw, fh2); RET(43);
        H_WAIT(4); G2(44, p1, 4); A2_SYNC(); RET(44);
        G2(45, p1, 5); RET(45);
        G2(46, p1, 6); RET(46);
        G2(47, p2, 0); RET(47);
        G2(48, p2, 1); RET(48);
        if (elect) mbar_arrive(sb + B_XFREE);
        H_WAIT(5); G2(49, p1, 7); RET(49);
        if (elect) mbar_arrive(sb + B_XFREE + 8);
        H_WAIT(8); G2(50, p1, 8); RET(50);
        if ((warp & 3) == 0) TS(wg, 8);
        uint32_t sp[32];
        uint4* const s1 = pbase + (((pw + wg) * 4 + p) << 10);
        G2(51, p2, 2); RET(51);
        pin(p1);
        if (own) {
            pack_sub<0>(sp, p1); send_frag<0, 8>(sp, s1, tag);
            mbar_wait(sb + B_AHEAD, 0);
        }
        G2(52, p2, 3); RET(52);
        G2(53, p2, 4); RET(53);
        G2(54, p2, 5);
        if (!own && elect) mbar_arrive(sb + B_AHEAD);
        RET(54);
        uint32_t qa[32], qb[32];
        G2(55, p2, 6); SCHED();
        if (!own) { pack_sub<0>(sp, p1); send_frag<0, 2>(sp, s1, tag); }
        RET(55);
        G2(56, p2, 7);
        if (!own) send_frag<2, 5>(sp, s1, tag); else recv_issue(qa, pbase + ((p * 4 + pw + wg) << 10));
        RET(56);
        G2(57, p2, 8);
        if (!own) send_frag<5, 8>(sp, s1, tag);
        if ((warp & 3) == 0) TS(wg, 9);
        wg_wait<0>();
        pin(p2);
        if ((warp & 3) == 0) TS(wg, 11);
        if (!own) {
            pack_sub<0>(sp, p2); send_frag<0, 8>(sp, pbase + (((p ^ 1) * 4 + p) << 10), tag);
        } else {
            const uint4* rb = pbase + ((p * 4 + pw + (wg ^ 1)) << 10);
            const uint4* rc = pbase + ((p * 4 + (p ^ 1)) << 10);
            recv_issue(qb, rb); recv_issue(sp, rc);
            recv_check(qa, pbase + ((p * 4 + pw + wg) << 10), tag); accum(qa, p2);
            recv_check(qb, rb, tag); accum(qb, p2);
            if ((warp & 3) == 0) TS(wg, 12);
            recv_check(sp, rc, tag); accum(sp, p2);
            if ((warp & 3) == 0) TS(wg, 13);
            uint32_t f0[16], f1[16];
            pack_sub<0>(f0, p2); pack_sub<32>(f1, p2);
            const uint32_t slab = sb + OFF_X + 2 * 16384 + wg * 8192;
            stash<16>(slab + srow, ssw, f0); stash<16>(slab + 16384 + srow, ssw, f1);
            __syncwarp();
            __nv_bfloat16* op = out + (size_t)(r * 128 + warp * 16 + (lane >> 4)) * kD + (j & 1) * 256 + (p & 2) * 64 + (lane & 15) * 8;
#pragma unroll
            for (int i = 0; i < 8; i++) {
                const int row = i * 2 + (lane >> 4);
                uint4 v;
                asm volatile("ld.shared.v4.u32 {%0,%1,%2,%3}, [%4];" : "=r"(v.x), "=r"(v.y), "=r"(v.z), "=r"(v.w)
                             : "r"(slab + (lane & 8) * 2048 + ((warp & 3) * 16 + row) * 128 + (((lane & 7) ^ (row & 7)) << 4)) : "memory");
                *(uint4*)(op + i * 2 * kD) = v;
            }
        }
        if ((warp & 3) == 0) { TS(wg, 14); TSG(wg, 31); }
    }
}

typedef CUresult (*EncodeFn)(CUtensorMap*, CUtensorMapDataType, cuuint32_t, void*, const cuuint64_t*, const cuuint64_t*, const cuuint32_t*,
                             const cuuint32_t*, CUtensorMapInterleave, CUtensorMapSwizzle, CUtensorMapL2promotion, CUtensorMapFloatOOBfill);

static void encode(EncodeFn fn, CUtensorMap* m, int rank, const void* base, const cuuint64_t (&gd)[5], const cuuint64_t (&gs)[4],
                   const cuuint32_t (&bd)[5], CUtensorMapSwizzle sw) {
    cuuint32_t es[5] = {1, 1, 1, 1, 1};
    fn(m, CU_TENSOR_MAP_DATA_TYPE_BFLOAT16, rank, const_cast<void*>(base), gd, gs, bd, es, CU_TENSOR_MAP_INTERLEAVE_NONE, sw,
       CU_TENSOR_MAP_L2_PROMOTION_L2_128B, CU_TENSOR_MAP_FLOAT_OOB_FILL_NONE);
}

extern "C" void kernel_launch(void* const* d_in, const int* in_sizes, int n_in, void* d_out, int out_size) {
    const char* x = (const char*)d_in[0];
    const char* wqkv = (const char*)d_in[1];
    const char* wo = (const char*)d_in[2];
    const char* wg = (const char*)d_in[4];
    const char* wu = (const char*)d_in[5];
    const char* wd = (const char*)d_in[6];
    void* fnp = nullptr;
    cudaDriverEntryPointQueryResult qr;
    cudaGetDriverEntryPoint("cuTensorMapEncodeTiled", &fnp, cudaEnableDefault, &qr);
    EncodeFn fn = (EncodeFn)fnp;
    Maps maps;
    const char* lo = wg < wu ? wg : wu;
    const uint64_t diff = wg < wu ? (uint64_t)(wu - wg) : (uint64_t)(wg - wu);
    const CUtensorMapSwizzle S128 = CU_TENSOR_MAP_SWIZZLE_128B, S64 = CU_TENSOR_MAP_SWIZZLE_64B;
    encode(fn, &maps.x, 2, x, {512, 2048, 1, 1}, {1024, 0, 0}, {64, 128, 1, 1}, S128);
    encode(fn, &maps.gu, 3, lo, {1792, 512, 2, 1}, {3584, diff, 0}, {64, 64, 2, 1}, S128);
    encode(fn, &maps.kv, 3, wqkv, {512, 512, 3, 1}, {3072, 1024, 0}, {64, 64, 2, 1}, S128);
    encode(fn, &maps.q64, 3, wqkv, {32, 512, 48, 1}, {3072, 64, 0}, {32, 64, 2, 1}, S64);
    encode(fn, &maps.gu64, 3, lo, {1792, 512, 2, 1}, {3584, diff, 0}, {32, 64, 2, 1}, S64);
    encode(fn, &maps.wdw, 3, wd, {64, 1792, 8, 1}, {1024, 128, 0}, {64, 64, 2, 1}, S128);
    encode(fn, &maps.wow, 3, wo, {64, 512, 8}, {1024, 128}, {64, 64, 2}, S128);
    encode(fn, &maps.wdp, 5, wd, {512, 2, 4, 4, 56}, {1024, 8192, 2048, 32768}, {64, 2, 4, 4, 2}, S128);
    encode(fn, &maps.wdph, 5, wd, {512, 2, 4, 4, 56}, {1024, 8192, 2048, 32768}, {64, 2, 4, 4, 1}, S128);
    encode(fn, &maps.wop, 5, wo, {512, 2, 4, 4, 16}, {1024, 8192, 2048, 32768}, {64, 2, 4, 4, 2}, S128);
    void* hx = nullptr;
    cudaGetSymbolAddress(&hx, g_hx);
    encode(fn, &maps.hx, 2, hx, {64, 16 * 4 * 9 * 128}, {128}, {64, 128}, S128);
    encode(fn, &maps.hx2, 2, hx, {64, 16 * 4 * 9 * 128}, {128}, {64, 256}, S128);
    cudaFuncSetAttribute(fused_kernel, cudaFuncAttributeMaxDynamicSharedMemorySize, SMEM_BYTES);
    cudaLaunchConfig_t cfg = {};
    cfg.gridDim = dim3(128);
    cfg.blockDim = dim3(384);
    cfg.dynamicSmemBytes = SMEM_BYTES;
    cfg.stream = cudaStreamPerThread;
    cudaLaunchAttribute at[1];
    at[0].id = cudaLaunchAttributeClusterDimension;
    at[0].val.clusterDim.x = 2; at[0].val.clusterDim.y = 1; at[0].val.clusterDim.z = 1;
    cfg.attrs = at;
    cfg.numAttrs = MC ? 1 : 0;
    cudaLaunchKernelEx(&cfg, fused_kernel, maps, (const __nv_bfloat16*)d_in[0], (const __nv_bfloat16*)d_in[7], wqkv, wg, wu, wd, wo, (__nv_bfloat16*)d_out);
}
```

```cpp
#include <cuda_runtime.h>
#include <cuda.h>
#include <cuda_bf16.h>
#include <stdint.h>

#define MC 0
#define PFMODE 1
#define PROF 0

namespace {

constexpr int kD = 512;
constexpr uint32_t OFF_X = 0, OFF_STG = 131072, OFF_RING = 147456, OFF_MISC = 229376;
constexpr uint32_t B_FULL = OFF_MISC, B_EMPTY = OFF_MISC + 40, B_XFULL = OFF_MISC + 80;
constexpr uint32_t B_GRDY = OFF_MISC + 152, B_KVDONE = OFF_MISC + 160, B_KVRDY = OFF_MISC + 168;
constexpr uint32_t B_HSENT = OFF_MISC + 176, B_XFREE = OFF_MISC + 200;
constexpr uint32_t OFF_EPOCH = OFF_MISC + 240, OFF_G = OFF_MISC + 256;
constexpr uint32_t B_AHEAD = OFF_MISC + 248;
constexpr uint32_t OFF_ONES = OFF_MISC + 768;
constexpr uint32_t B_EFULL = OFF_MISC + 896, B_EEMPTY = OFF_MISC + 928;
constexpr uint32_t SMEM_BYTES = OFF_MISC + 960;
constexpr uint32_t SPIN_GLOBAL = 1u << 14;

struct alignas(64) Maps { CUtensorMap x, gu, kv, q64, gu64, wdw, wow, wdp, wdph, hx, hx2; };

}

__device__ uint4 g_part[16 * 2 * 4 * 4 * 1024];
__device__ uint4 g_hx[16 * 4 * 5 * 1024];
__device__ uint4 g_lx[16 * 8 * 2 * 1024];
__device__ unsigned g_hflag[128 * 8];
__device__ uint4 g_gx[16 * 32];
__device__ float g_kvacc[2 * 8 * 4 * 272];
__device__ unsigned g_kvcnt[8 * 32];
__device__ unsigned g_epoch[128];
#define TS(role, idx)
#define TS2(idx)
#define TSG(role, idx)

namespace {

__device__ __forceinline__ void mbar_init(uint32_t bar, uint32_t cnt) { asm volatile("mbarrier.init.shared::cta.b64 [%0], %1;" :: "r"(bar), "r"(cnt) : "memory"); }
__device__ __forceinline__ void mbar_expect(uint32_t bar, uint32_t bytes) { asm volatile("mbarrier.arrive.expect_tx.shared::cta.b64 _, [%0], %1;" :: "r"(bar), "r"(bytes) : "memory"); }
__device__ __forceinline__ void mbar_arrive(uint32_t bar) { asm volatile("mbarrier.arrive.shared::cta.b64 _, [%0];" :: "r"(bar) : "memory"); }
__device__ __forceinline__ void mbar_arrive_cta(uint32_t bar, uint32_t cta) {
    asm volatile("{\n.reg .b32 ra;\nmapa.shared::cluster.u32 ra, %0, %1;\nmbarrier.arrive.shared::cluster.b64 _, [ra];\n}" :: "r"(bar), "r"(cta) : "memory");
}
__device__ __forceinline__ void mbar_wait(uint32_t bar, uint32_t parity) {
    asm volatile("{\n.reg .pred p;\n.reg .u32 c;\n"
                 "mbarrier.try_wait.parity.shared::cta.b64 p, [%0], %1;\n@p bra DONE;\n"
                 "mov.u32 c, 0;\nLAB_WAIT:\nmbarrier.try_wait.parity.shared::cta.b64 p, [%0], %1;\n@p bra DONE;\n"
                 "add.u32 c, c, 1;\nsetp.lt.u32 p, c, 65536;\n@p bra LAB_WAIT;\nDONE:\n}" :: "r"(bar), "r"(parity) : "memory");
}
__device__ __forceinline__ void tma2(uint32_t dst, const CUtensorMap* m, int c0, int c1, uint32_t bar) {
    asm volatile("cp.async.bulk.tensor.2d.shared::cluster.global.mbarrier::complete_tx::bytes [%0], [%1, {%3, %4}], [%2];"
        :: "r"(dst), "l"(m), "r"(bar), "r"(c0), "r"(c1) : "memory");
}
__device__ __forceinline__ void tmaw2(uint32_t dst, const CUtensorMap* m, int c0, int c1, uint32_t bar) {
    tma2(dst, m, c0, c1, bar);
}
__device__ __forceinline__ void tmaw3(uint32_t dst, const CUtensorMap* m, int c0, int c1, int c2, uint32_t bar) {
    asm volatile("cp.async.bulk.tensor.3d.shared::cluster.global.mbarrier::complete_tx::bytes [%0], [%1, {%3, %4, %5}], [%2];"
        :: "r"(dst), "l"(m), "r"(bar), "r"(c0), "r"(c1), "r"(c2) : "memory");
}
__device__ __forceinline__ void tmaw5(uint32_t dst, const CUtensorMap* m, int c0, int c4, uint32_t bar) {
    asm volatile("cp.async.bulk.tensor.5d.shared::cluster.global.mbarrier::complete_tx::bytes [%0], [%1, {%3, %5, %5, %5, %4}], [%2];"
        :: "r"(dst), "l"(m), "r"(bar), "r"(c0), "r"(c4), "r"(0) : "memory");
}
__device__ __forceinline__ void wg_fence() { asm volatile("wgmma.fence.sync.aligned;" ::: "memory"); }
__device__ __forceinline__ void wg_commit() { asm volatile("wgmma.commit_group.sync.aligned;" ::: "memory"); }
template <int N> __device__ __forceinline__ void wg_wait() { asm volatile("wgmma.wait_group.sync.aligned %0;" :: "n"(N) : "memory"); }
template <int N> __device__ __forceinline__ void pin(float (&d)[N]) {
#pragma unroll
    for (int i = 0; i < N; i++) asm volatile("" : "+f"(d[i]) :: "memory");
}
__device__ __forceinline__ uint32_t pack2(float lo, float hi) { uint32_t r; asm("cvt.rn.bf16x2.f32 %0, %1, %2;" : "=r"(r) : "f"(hi), "f"(lo)); return r; }
__device__ __forceinline__ uint32_t keep(uint32_t v) { asm volatile("" : "+r"(v)); return v; }
__device__ __forceinline__ uint32_t hmul2(uint32_t a, uint32_t b) { uint32_t r; asm("mul.bf16x2 %0, %1, %2;" : "=r"(r) : "r"(a), "r"(b)); return r; }
__device__ __forceinline__ uint32_t phi2(float t0, float t1) {
    float e0, e1;
    asm("ex2.approx.ftz.f32 %0, %1;" : "=f"(e0) : "f"(t0 * 1.4426950408889634f));
    asm("ex2.approx.ftz.f32 %0, %1;" : "=f"(e1) : "f"(t1 * 1.4426950408889634f));
    uint32_t e = pack2(e0, e1), t = pack2(t0, t1), r;
    asm("min.bf16x2 %0, %0, %1;" : "+r"(e) : "r"(0x3f803f80u));
    asm("max.bf16x2 %0, %0, %1;" : "+r"(t) : "r"(0x35863586u));
    asm("add.bf16x2 %0, %1, %2;" : "=r"(r) : "r"(e), "r"(t));
    return r;
}
__device__ __forceinline__ void stsm4(uint32_t a, uint32_t r0, uint32_t r1, uint32_t r2, uint32_t r3) {
    asm volatile("stmatrix.sync.aligned.m8n8.x4.shared.b16 [%0], {%1,%2,%3,%4};" :: "r"(a), "r"(r0), "r"(r1), "r"(r2), "r"(r3) : "memory");
}
__device__ __forceinline__ float bf_lo(uint32_t w) { return __uint_as_float(w << 16); }
__device__ __forceinline__ float bf_hi(uint32_t w) { return __uint_as_float(w & 0xffff0000u); }
__device__ __forceinline__ void st_pkt(uint4* p, uint32_t w0, uint32_t w1, uint32_t w2, uint32_t w3) {
    asm volatile("{\n.reg .b64 lo, hi;\n.reg .b128 v;\nmov.b64 lo, {%1, %2};\nmov.b64 hi, {%3, %4};\nmov.b128 v, {lo, hi};\nst.relaxed.gpu.global.b128 [%0], v;\n}"
        :: "l"(p), "r"(w0), "r"(w1), "r"(w2), "r"(w3) : "memory");
}
__device__ __forceinline__ void ld_pkt(const uint4* p, uint32_t& w0, uint32_t& w1, uint32_t& w2, uint32_t& w3) {
    asm volatile("{\n.reg .b64 lo, hi;\n.reg .b128 v;\nld.relaxed.gpu.global.b128 v, [%4];\nmov.b128 {lo, hi}, v;\nmov.b64 {%0, %1}, lo;\nmov.b64 {%2, %3}, hi;\n}"
        : "=r"(w0), "=r"(w1), "=r"(w2), "=r"(w3) : "l"(p) : "memory");
}

__device__ __forceinline__ void wg_rs128(float (&d)[64], uint32_t a0, uint32_t a1, uint32_t a2, uint32_t a3, uint32_t blo, uint32_t bhi) {
    asm volatile("{\n.reg .b64 db;\nmov.b64 db, {%68, %69};\n"
        "wgmma.mma_async.sync.aligned.m64n128k16.f32.bf16.bf16 {%0,%1,%2,%3,%4,%5,%6,%7,%8,%9,%10,%11,%12,%13,%14,%15,%16,%17,%18,%19,%20,%21,%22,%23,%24,%25,%26,%27,%28,%29,%30,%31,%32,%33,%34,%35,%36,%37,%38,%39,%40,%41,%42,%43,%44,%45,%46,%47,%48,%49,%50,%51,%52,%53,%54,%55,%56,%57,%58,%59,%60,%61,%62,%63}, {%64,%65,%66,%67}, db, 1, 1, 1, 1;\n}\n"
        : "+f"(d[0]),"+f"(d[1]),"+f"(d[2]),"+f"(d[3]),"+f"(d[4]),"+f"(d[5]),"+f"(d[6]),"+f"(d[7]),"+f"(d[8]),"+f"(d[9]),"+f"(d[10]),"+f"(d[11]),"+f"(d[12]),"+f"(d[13]),"+f"(d[14]),"+f"(d[15]),"+f"(d[16]),"+f"(d[17]),"+f"(d[18]),"+f"(d[19]),"+f"(d[20]),"+f"(d[21]),"+f"(d[22]),"+f"(d[23]),"+f"(d[24]),"+f"(d[25]),"+f"(d[26]),"+f"(d[27]),"+f"(d[28]),"+f"(d[29]),"+f"(d[30]),"+f"(d[31]),"+f"(d[32]),"+f"(d[33]),"+f"(d[34]),"+f"(d[35]),"+f"(d[36]),"+f"(d[37]),"+f"(d[38]),"+f"(d[39]),"+f"(d[40]),"+f"(d[41]),"+f"(d[42]),"+f"(d[43]),"+f"(d[44]),"+f"(d[45]),"+f"(d[46]),"+f"(d[47]),"+f"(d[48]),"+f"(d[49]),"+f"(d[50]),"+f"(d[51]),"+f"(d[52]),"+f"(d[53]),"+f"(d[54]),"+f"(d[55]),"+f"(d[56]),"+f"(d[57]),"+f"(d[58]),"+f"(d[59]),"+f"(d[60]),"+f"(d[61]),"+f"(d[62]),"+f"(d[63])
        : "r"(a0), "r"(a1), "r"(a2), "r"(a3), "r"(blo), "r"(bhi));
}
__device__ __forceinline__ void wg_rs128_z(float (&d)[64], uint32_t a0, uint32_t a1, uint32_t a2, uint32_t a3, uint32_t blo, uint32_t bhi) {
    asm volatile("{\n.reg .b64 db;\nmov.b64 db, {%68, %69};\n"
        "wgmma.mma_async.sync.aligned.m64n128k16.f32.bf16.bf16 {%0,%1,%2,%3,%4,%5,%6,%7,%8,%9,%10,%11,%12,%13,%14,%15,%16,%17,%18,%19,%20,%21,%22,%23,%24,%25,%26,%27,%28,%29,%30,%31,%32,%33,%34,%35,%36,%37,%38,%39,%40,%41,%42,%43,%44,%45,%46,%47,%48,%49,%50,%51,%52,%53,%54,%55,%56,%57,%58,%59,%60,%61,%62,%63}, {%64,%65,%66,%67}, db, 0, 1, 1, 1;\n}\n"
        : "=f"(d[0]),"=f"(d[1]),"=f"(d[2]),"=f"(d[3]),"=f"(d[4]),"=f"(d[5]),"=f"(d[6]),"=f"(d[7]),"=f"(d[8]),"=f"(d[9]),"=f"(d[10]),"=f"(d[11]),"=f"(d[12]),"=f"(d[13]),"=f"(d[14]),"=f"(d[15]),"=f"(d[16]),"=f"(d[17]),"=f"(d[18]),"=f"(d[19]),"=f"(d[20]),"=f"(d[21]),"=f"(d[22]),"=f"(d[23]),"=f"(d[24]),"=f"(d[25]),"=f"(d[26]),"=f"(d[27]),"=f"(d[28]),"=f"(d[29]),"=f"(d[30]),"=f"(d[31]),"=f"(d[32]),"=f"(d[33]),"=f"(d[34]),"=f"(d[35]),"=f"(d[36]),"=f"(d[37]),"=f"(d[38]),"=f"(d[39]),"=f"(d[40]),"=f"(d[41]),"=f"(d[42]),"=f"(d[43]),"=f"(d[44]),"=f"(d[45]),"=f"(d[46]),"=f"(d[47]),"=f"(d[48]),"=f"(d[49]),"=f"(d[50]),"=f"(d[51]),"=f"(d[52]),"=f"(d[53]),"=f"(d[54]),"=f"(d[55]),"=f"(d[56]),"=f"(d[57]),"=f"(d[58]),"=f"(d[59]),"=f"(d[60]),"=f"(d[61]),"=f"(d[62]),"=f"(d[63])
        : "r"(a0), "r"(a1), "r"(a2), "r"(a3), "r"(blo), "r"(bhi));
}
__device__ __forceinline__ void wg_ss128(float (&d)[64], uint32_t alo, uint32_t ahi, uint32_t blo, uint32_t bhi) {
    asm volatile("{\n.reg .b64 da, db;\nmov.b64 da, {%64, %65};\nmov.b64 db, {%66, %67};\n"
        "wgmma.mma_async.sync.aligned.m64n128k16.f32.bf16.bf16 {%0,%1,%2,%3,%4,%5,%6,%7,%8,%9,%10,%11,%12,%13,%14,%15,%16,%17,%18,%19,%20,%21,%22,%23,%24,%25,%26,%27,%28,%29,%30,%31,%32,%33,%34,%35,%36,%37,%38,%39,%40,%41,%42,%43,%44,%45,%46,%47,%48,%49,%50,%51,%52,%53,%54,%55,%56,%57,%58,%59,%60,%61,%62,%63}, da, db, 1, 1, 1, 0, 1;\n}\n"
        : "+f"(d[0]),"+f"(d[1]),"+f"(d[2]),"+f"(d[3]),"+f"(d[4]),"+f"(d[5]),"+f"(d[6]),"+f"(d[7]),"+f"(d[8]),"+f"(d[9]),"+f"(d[10]),"+f"(d[11]),"+f"(d[12]),"+f"(d[13]),"+f"(d[14]),"+f"(d[15]),"+f"(d[16]),"+f"(d[17]),"+f"(d[18]),"+f"(d[19]),"+f"(d[20]),"+f"(d[21]),"+f"(d[22]),"+f"(d[23]),"+f"(d[24]),"+f"(d[25]),"+f"(d[26]),"+f"(d[27]),"+f"(d[28]),"+f"(d[29]),"+f"(d[30]),"+f"(d[31]),"+f"(d[32]),"+f"(d[33]),"+f"(d[34]),"+f"(d[35]),"+f"(d[36]),"+f"(d[37]),"+f"(d[38]),"+f"(d[39]),"+f"(d[40]),"+f"(d[41]),"+f"(d[42]),"+f"(d[43]),"+f"(d[44]),"+f"(d[45]),"+f"(d[46]),"+f"(d[47]),"+f"(d[48]),"+f"(d[49]),"+f"(d[50]),"+f"(d[51]),"+f"(d[52]),"+f"(d[53]),"+f"(d[54]),"+f"(d[55]),"+f"(d[56]),"+f"(d[57]),"+f"(d[58]),"+f"(d[59]),"+f"(d[60]),"+f"(d[61]),"+f"(d[62]),"+f"(d[63])
        : "r"(alo), "r"(ahi), "r"(blo), "r"(bhi));
}
__device__ __forceinline__ void wg_ss128_z(float (&d)[64], uint32_t alo, uint32_t ahi, uint32_t blo, uint32_t bhi) {
    asm volatile("{\n.reg .b64 da, db;\nmov.b64 da, {%64, %65};\nmov.b64 db, {%66, %67};\n"
        "wgmma.mma_async.sync.aligned.m64n128k16.f32.bf16.bf16 {%0,%1,%2,%3,%4,%5,%6,%7,%8,%9,%10,%11,%12,%13,%14,%15,%16,%17,%18,%19,%20,%21,%22,%23,%24,%25,%26,%27,%28,%29,%30,%31,%32,%33,%34,%35,%36,%37,%38,%39,%40,%41,%42,%43,%44,%45,%46,%47,%48,%49,%50,%51,%52,%53,%54,%55,%56,%57,%58,%59,%60,%61,%62,%63}, da, db, 0, 1, 1, 0, 1;\n}\n"
        : "=f"(d[0]),"=f"(d[1]),"=f"(d[2]),"=f"(d[3]),"=f"(d[4]),"=f"(d[5]),"=f"(d[6]),"=f"(d[7]),"=f"(d[8]),"=f"(d[9]),"=f"(d[10]),"=f"(d[11]),"=f"(d[12]),"=f"(d[13]),"=f"(d[14]),"=f"(d[15]),"=f"(d[16]),"=f"(d[17]),"=f"(d[18]),"=f"(d[19]),"=f"(d[20]),"=f"(d[21]),"=f"(d[22]),"=f"(d[23]),"=f"(d[24]),"=f"(d[25]),"=f"(d[26]),"=f"(d[27]),"=f"(d[28]),"=f"(d[29]),"=f"(d[30]),"=f"(d[31]),"=f"(d[32]),"=f"(d[33]),"=f"(d[34]),"=f"(d[35]),"=f"(d[36]),"=f"(d[37]),"=f"(d[38]),"=f"(d[39]),"=f"(d[40]),"=f"(d[41]),"=f"(d[42]),"=f"(d[43]),"=f"(d[44]),"=f"(d[45]),"=f"(d[46]),"=f"(d[47]),"=f"(d[48]),"=f"(d[49]),"=f"(d[50]),"=f"(d[51]),"=f"(d[52]),"=f"(d[53]),"=f"(d[54]),"=f"(d[55]),"=f"(d[56]),"=f"(d[57]),"=f"(d[58]),"=f"(d[59]),"=f"(d[60]),"=f"(d[61]),"=f"(d[62]),"=f"(d[63])
        : "r"(alo), "r"(ahi), "r"(blo), "r"(bhi));
}
__device__ __forceinline__ void wg_ss64(float (&d)[32], uint32_t alo, uint32_t ahi, uint32_t blo, uint32_t bhi) {
    asm volatile("{\n.reg .b64 da, db;\nmov.b64 da, {%32, %33};\nmov.b64 db, {%34, %35};\n"
        "wgmma.mma_async.sync.aligned.m64n64k16.f32.bf16.bf16 {%0,%1,%2,%3,%4,%5,%6,%7,%8,%9,%10,%11,%12,%13,%14,%15,%16,%17,%18,%19,%20,%21,%22,%23,%24,%25,%26,%27,%28,%29,%30,%31}, da, db, 1, 1, 1, 0, 1;\n}\n"
        : "+f"(d[0]),"+f"(d[1]),"+f"(d[2]),"+f"(d[3]),"+f"(d[4]),"+f"(d[5]),"+f"(d[6]),"+f"(d[7]),"+f"(d[8]),"+f"(d[9]),"+f"(d[10]),"+f"(d[11]),"+f"(d[12]),"+f"(d[13]),"+f"(d[14]),"+f"(d[15]),"+f"(d[16]),"+f"(d[17]),"+f"(d[18]),"+f"(d[19]),"+f"(d[20]),"+f"(d[21]),"+f"(d[22]),"+f"(d[23]),"+f"(d[24]),"+f"(d[25]),"+f"(d[26]),"+f"(d[27]),"+f"(d[28]),"+f"(d[29]),"+f"(d[30]),"+f"(d[31])
        : "r"(alo), "r"(ahi), "r"(blo), "r"(bhi));
}
__device__ __forceinline__ void wg_ss64_z(float (&d)[32], uint32_t alo, uint32_t ahi, uint32_t blo, uint32_t bhi) {
    asm volatile("{\n.reg .b64 da, db;\nmov.b64 da, {%32, %33};\nmov.b64 db, {%34, %35};\n"
        "wgmma.mma_async.sync.aligned.m64n64k16.f32.bf16.bf16 {%0,%1,%2,%3,%4,%5,%6,%7,%8,%9,%10,%11,%12,%13,%14,%15,%16,%17,%18,%19,%20,%21,%22,%23,%24,%25,%26,%27,%28,%29,%30,%31}, da, db, 0, 1, 1, 0, 1;\n}\n"
        : "=f"(d[0]),"=f"(d[1]),"=f"(d[2]),"=f"(d[3]),"=f"(d[4]),"=f"(d[5]),"=f"(d[6]),"=f"(d[7]),"=f"(d[8]),"=f"(d[9]),"=f"(d[10]),"=f"(d[11]),"=f"(d[12]),"=f"(d[13]),"=f"(d[14]),"=f"(d[15]),"=f"(d[16]),"=f"(d[17]),"=f"(d[18]),"=f"(d[19]),"=f"(d[20]),"=f"(d[21]),"=f"(d[22]),"=f"(d[23]),"=f"(d[24]),"=f"(d[25]),"=f"(d[26]),"=f"(d[27]),"=f"(d[28]),"=f"(d[29]),"=f"(d[30]),"=f"(d[31])
        : "r"(alo), "r"(ahi), "r"(blo), "r"(bhi));
}
__device__ __forceinline__ void wg_ss64t(float (&d)[32], uint32_t alo, uint32_t ahi, uint32_t blo, uint32_t bhi) {
    asm volatile("{\n.reg .b64 da, db;\nmov.b64 da, {%32, %33};\nmov.b64 db, {%34, %35};\n"
        "wgmma.mma_async.sync.aligned.m64n64k16.f32.bf16.bf16 {%0,%1,%2,%3,%4,%5,%6,%7,%8,%9,%10,%11,%12,%13,%14,%15,%16,%17,%18,%19,%20,%21,%22,%23,%24,%25,%26,%27,%28,%29,%30,%31}, da, db, 1, 1, 1, 1, 1;\n}\n"
        : "+f"(d[0]),"+f"(d[1]),"+f"(d[2]),"+f"(d[3]),"+f"(d[4]),"+f"(d[5]),"+f"(d[6]),"+f"(d[7]),"+f"(d[8]),"+f"(d[9]),"+f"(d[10]),"+f"(d[11]),"+f"(d[12]),"+f"(d[13]),"+f"(d[14]),"+f"(d[15]),"+f"(d[16]),"+f"(d[17]),"+f"(d[18]),"+f"(d[19]),"+f"(d[20]),"+f"(d[21]),"+f"(d[22]),"+f"(d[23]),"+f"(d[24]),"+f"(d[25]),"+f"(d[26]),"+f"(d[27]),"+f"(d[28]),"+f"(d[29]),"+f"(d[30]),"+f"(d[31])
        : "r"(alo), "r"(ahi), "r"(blo), "r"(bhi));
}
__device__ __forceinline__ void wg_ss64t_z(float (&d)[32], uint32_t alo, uint32_t ahi, uint32_t blo, uint32_t bhi) {
    asm volatile("{\n.reg .b64 da, db;\nmov.b64 da, {%32, %33};\nmov.b64 db, {%34, %35};\n"
        "wgmma.mma_async.sync.aligned.m64n64k16.f32.bf16.bf16 {%0,%1,%2,%3,%4,%5,%6,%7,%8,%9,%10,%11,%12,%13,%14,%15,%16,%17,%18,%19,%20,%21,%22,%23,%24,%25,%26,%27,%28,%29,%30,%31}, da, db, 0, 1, 1, 1, 1;\n}\n"
        : "=f"(d[0]),"=f"(d[1]),"=f"(d[2]),"=f"(d[3]),"=f"(d[4]),"=f"(d[5]),"=f"(d[6]),"=f"(d[7]),"=f"(d[8]),"=f"(d[9]),"=f"(d[10]),"=f"(d[11]),"=f"(d[12]),"=f"(d[13]),"=f"(d[14]),"=f"(d[15]),"=f"(d[16]),"=f"(d[17]),"=f"(d[18]),"=f"(d[19]),"=f"(d[20]),"=f"(d[21]),"=f"(d[22]),"=f"(d[23]),"=f"(d[24]),"=f"(d[25]),"=f"(d[26]),"=f"(d[27]),"=f"(d[28]),"=f"(d[29]),"=f"(d[30]),"=f"(d[31])
        : "r"(alo), "r"(ahi), "r"(blo), "r"(bhi));
}
__device__ __forceinline__ void wg_ss8t(float (&d)[4], uint32_t alo, uint32_t ahi, uint32_t blo, uint32_t bhi) {
    asm volatile("{\n.reg .b64 da, db;\nmov.b64 da, {%4, %5};\nmov.b64 db, {%6, %7};\n"
        "wgmma.mma_async.sync.aligned.m64n8k16.f32.bf16.bf16 {%0,%1,%2,%3}, da, db, 1, 1, 1, 1, 0;\n}\n"
        : "+f"(d[0]),"+f"(d[1]),"+f"(d[2]),"+f"(d[3])
        : "r"(alo), "r"(ahi), "r"(blo), "r"(bhi));
}
__device__ __forceinline__ void wg_ss8t_z(float (&d)[4], uint32_t alo, uint32_t ahi, uint32_t blo, uint32_t bhi) {
    asm volatile("{\n.reg .b64 da, db;\nmov.b64 da, {%4, %5};\nmov.b64 db, {%6, %7};\n"
        "wgmma.mma_async.sync.aligned.m64n8k16.f32.bf16.bf16 {%0,%1,%2,%3}, da, db, 0, 1, 1, 1, 0;\n}\n"
        : "=f"(d[0]),"=f"(d[1]),"=f"(d[2]),"=f"(d[3])
        : "r"(alo), "r"(ahi), "r"(blo), "r"(bhi));
}
__device__ __forceinline__ void wg_rs24_z(float (&d)[12], uint32_t a0, uint32_t a1, uint32_t a2, uint32_t a3, uint32_t blo, uint32_t bhi) {
    asm volatile("{\n.reg .b64 db;\nmov.b64 db, {%16, %17};\n"
        "wgmma.mma_async.sync.aligned.m64n24k16.f32.bf16.bf16 {%0,%1,%2,%3,%4,%5,%6,%7,%8,%9,%10,%11}, {%12,%13,%14,%15}, db, 0, 1, 1, 0;\n}\n"
        : "=f"(d[0]),"=f"(d[1]),"=f"(d[2]),"=f"(d[3]),"=f"(d[4]),"=f"(d[5]),"=f"(d[6]),"=f"(d[7]),"=f"(d[8]),"=f"(d[9]),"=f"(d[10]),"=f"(d[11])
        : "r"(a0), "r"(a1), "r"(a2), "r"(a3), "r"(blo), "r"(bhi));
}

constexpr uint32_t DH128 = 64u | 0x40000000u;
constexpr uint32_t DH64 = 32u | 0x80000000u;
constexpr uint32_t LBO4K = (4096u >> 4) << 16, LBO8K = (8192u >> 4) << 16, LBO1 = 1u << 16;

template <bool SW64, bool FIRST> __device__ __forceinline__ void g1_issue(float (&acc)[64], uint32_t alo, uint32_t blo) {
    wg_fence();
#pragma unroll
    for (int k = 0; k < 4; k++) {
        if (FIRST && k == 0) wg_ss128_z(acc, alo, DH128, blo, SW64 ? DH64 : DH128);
        else wg_ss128(acc, alo + 2 * k, DH128, blo + (SW64 ? 64 * k : 128 * k), SW64 ? DH64 : DH128);
    }
    wg_commit();
}

template <int N> __device__ __forceinline__ void stash(uint32_t base, uint32_t sw, const uint32_t (&f)[N]) {
#pragma unroll
    for (int t = 0; t < N / 4; t++) stsm4(base + ((sw ^ (2 * t)) << 4), f[4 * t], f[4 * t + 1], f[4 * t + 2], f[4 * t + 3]);
}

template <int V0, int V1, int N> __device__ __forceinline__ void send_frag(const uint32_t (&f)[N], uint4* p, uint32_t tag) {
#pragma unroll
    for (int v = V0; v < V1; v++) st_pkt(p + v * 32, (f[4 * v] & ~1u) | tag, f[4 * v + 1], f[4 * v + 2], f[4 * v + 3]);
}
template <int H0, int H1, int N> __device__ __forceinline__ void send_h(const uint32_t (&f)[N], uint4* p) {
#pragma unroll
    for (int h = H0; h < H1; h++) {
        p[4 * h] = make_uint4(f[8 * h], f[8 * h + 2], f[8 * h + 4], f[8 * h + 6]);
        p[4 * h + 64] = make_uint4(f[8 * h + 1], f[8 * h + 3], f[8 * h + 5], f[8 * h + 7]);
    }
}
template <int O, int N, int M> __device__ __forceinline__ void pack_sub(uint32_t (&f)[N], const float (&acc)[M]) {
#pragma unroll
    for (int i = 0; i < N; i++) f[i] = keep(pack2(acc[O + 2 * i], acc[O + 2 * i + 1]));
}
template <int N> __device__ __forceinline__ void recv_issue(uint32_t (&q)[N], const uint4* p) {
#pragma unroll
    for (int v = 0; v < N / 4; v++) ld_pkt(p + v * 32, q[4 * v], q[4 * v + 1], q[4 * v + 2], q[4 * v + 3]);
}
template <int N> __device__ __forceinline__ void recv_check(uint32_t (&q)[N], const uint4* p, uint32_t tag) {
    uint32_t it = 0;
    while (true) {
        uint32_t bad = 0;
#pragma unroll
        for (int v = 0; v < N / 4; v++) bad |= q[4 * v] ^ tag;
        if (__all_sync(0xffffffffu, (bad & 1u) == 0) || ++it > SPIN_GLOBAL) break;
        recv_issue(q, p);
    }
}
__device__ __forceinline__ void accum(const uint32_t (&q)[32], float (&sum)[64]) {
#pragma unroll
    for (int i = 0; i < 32; i++) { sum[2 * i] += bf_lo(q[i]); sum[2 * i + 1] += bf_hi(q[i]); }
}

}

__global__ void __launch_bounds__(384, 1)
fused_kernel(const __grid_constant__ Maps maps, const __nv_bfloat16* __restrict__ xg, const __nv_bfloat16* __restrict__ gate_w,
             const char* __restrict__ pf_qkv, const char* __restrict__ pf_g, const char* __restrict__ pf_u,
             const char* __restrict__ pf_d, const char* __restrict__ pf_o, __nv_bfloat16* __restrict__ out) {
    extern __shared__ __align__(1024) uint8_t smem_raw[];
    const uint32_t sb = (uint32_t)__cvta_generic_to_shared(smem_raw);
    const int tid = threadIdx.x, lane = tid & 31;
    const int warp = __shfl_sync(0xffffffffu, tid >> 5, 0);
    const int j = (blockIdx.x >> 1) & 7;
    const int r = ((blockIdx.x >> 4) << 1) | (blockIdx.x & 1);
    const uint32_t rank = blockIdx.x & 1;

    if (warp == 0) { TSG(0, 30); TS(0, 0); }
    if (tid == 256) {
        for (int i = 0; i < 5; i++) { mbar_init(sb + B_FULL + 8 * i, 1); mbar_init(sb + B_EMPTY + 8 * i, MC ? 4 : 2); }
        for (int i = 0; i < 9; i++) mbar_init(sb + B_XFULL + 8 * i, 1);
        asm volatile("fence.mbarrier_init.release.cluster;" ::: "memory");
        mbar_expect(sb + B_XFULL, 16384);
        tma2(sb + OFF_X, &maps.x, 0, r * 128, sb + B_XFULL);
        TS2(0);
        mbar_expect(sb + B_FULL, 16384);
        tmaw3(sb + OFF_RING, &maps.gu, 224 * j, 0, 0, sb + B_FULL);
        TS2(1);
        mbar_expect(sb + B_FULL + 8, 16384);
        tmaw3(sb + OFF_RING + 16384, &maps.kv, 64 * j, 0, 1, sb + B_FULL + 8);
    } else if (tid == 288) {
        for (int i = 0; i < 3; i++) mbar_init(sb + B_HSENT + 8 * i, 8);
        for (int i = 0; i < 4; i++) { mbar_init(sb + B_EFULL + 8 * i, 1); mbar_init(sb + B_EEMPTY + 8 * i, MC ? 4 : 2); }
        mbar_init(sb + B_XFREE, 2); mbar_init(sb + B_XFREE + 8, 2); mbar_init(sb + B_XFREE + 16, 2);
        mbar_init(sb + B_AHEAD, 1); mbar_init(sb + B_GRDY, 1); mbar_init(sb + B_KVDONE, 8); mbar_init(sb + B_KVRDY, 2);
        asm volatile("fence.mbarrier_init.release.cluster;" ::: "memory");
    } else if (warp == 10 && lane < 10) {
        asm volatile("prefetch.tensormap [%0];" :: "l"(&maps.gu + lane) : "memory");
    }
    __syncthreads();

    if (warp >= 8) {
        asm volatile("setmaxnreg.dec.sync.aligned.u32 56;");
        if (warp == 8) {
            if (lane == 0) {
                int slot = MC ? 0 : 2, ph = 1;
                uint32_t full, dst;
                if (!MC) { mbar_expect(sb + B_XFULL + 8, 16384); tma2(sb + OFF_X + 16384, &maps.x, 64, r * 128, sb + B_XFULL + 8); }
#define P_BEGIN(S, BYTES) full = sb + B_FULL + 8 * slot; dst = sb + OFF_RING + slot * 16384; \
                mbar_wait(sb + B_EMPTY + 8 * slot, ph); TS2(S); mbar_expect(full, BYTES); if (!MC || (((S) ^ rank) & 1) == 0)
#define P_END() if (++slot == 5) { slot = 0; ph ^= 1; }
                for (int s = MC ? 0 : 2; s < 16; s++) {
                    P_BEGIN(s, 16384) {
                        const int sw = s == 13 ? 14 : s == 14 ? 13 : s;
                        if (sw & 1) tmaw3(dst, &maps.kv, 64 * j, 32 * (sw - 1), 1, full);
                        else tmaw3(dst, &maps.gu, 224 * j, 32 * sw, 0, full);
                    }
                    const int xb = (s == 4) ? 3 : (s == 10) ? 7 : !(s & 1) ? 0 : (s < 5) ? (s + 1) / 2 : (s <= 9) ? (s + 3) / 2 : 0;
                    if (xb) { mbar_expect(sb + B_XFULL + 8 * xb, 16384); tma2(sb + OFF_X + xb * 16384, &maps.x, 64 * xb, r * 128, sb + B_XFULL + 8 * xb); }
                    P_END()
                }
                for (int s = 0; s < 24; s++) {
                    P_BEGIN(16 + s, 16384) {
                        if ((s >> 3) == 1) {
                            tmaw3(dst, &maps.q64, 0, 64 * (s & 7), 2 * j, full);
                            tmaw3(dst + 8192, &maps.gu64, 224 * j + 192, 64 * (s & 7), 0, full);
                        } else {
                            tmaw3(dst, &maps.gu, 224 * j + 64 + 4 * (s & 16), 64 * (s & 7), 0, full);
                        }
                    }
                    P_END()
                }
                const int p = j >> 1;
#pragma unroll 1
                for (int t = 0; t < 18; t++) {
                    const int q = t >= 9, sl = t - 9 * q, u = !q ? t : sl < 4 ? sl + 5 : sl - 4;
                    const int cw = (j & 1) * 4 + ((p & 2) ^ (q ? 0 : 2)), cc = 64 * cw;
                    if (sl < 5) {
                        full = sb + B_FULL + 8 * sl; dst = sb + OFF_RING + sl * 16384;
                        mbar_wait(sb + B_EMPTY + 8 * sl, q ^ 1);
                    } else {
                        full = sb + B_EFULL + 8 * (sl - 5); dst = sb + OFF_X + (sl == 7 ? 8 : sl == 8 ? 7 : sl) * 16384;
                        mbar_wait(sb + B_EEMPTY + 8 * (sl - 5), q);
                    }
                    TS2(40 + t);
                    mbar_expect(full, 16384);
                    if (!MC || ((t ^ rank) & 1) == 0) {
                        if (u == 4) {
                            tmaw5(dst, &maps.wdph, cc, 14 * p + 6, full); tmaw5(dst + 4096, &maps.wdph, cc, 14 * p + 13, full);
                            tmaw5(dst + 8192, &maps.wdph, cc + 64, 14 * p + 6, full); tmaw5(dst + 12288, &maps.wdph, cc + 64, 14 * p + 13, full);
                        } else if (u > 4) {
                            const int js = u > 6 ? j ^ 1 : j;
                            tmaw3(dst, (u & 1) ? &maps.wow : &maps.wdw, 0, (u & 1) ? 64 * js : 224 * js + 128, cw, full);
                        } else {
                            const int g = 14 * p + 7 * (u & 1) + (u & 2);
                            tmaw5(dst, &maps.wdp, cc, g, full); tmaw5(dst + 8192, &maps.wdp, cc + 64, g, full);
                        }
                    }
                }
            }
        } else if (warp < 11) {
            const int hx = warp - 9;
            uint32_t epoch;
            asm volatile("ld.relaxed.gpu.global.u32 %0, [%1];" : "=r"(epoch) : "l"(g_epoch + blockIdx.x) : "memory");
            {
                const uint4* xr = (const uint4*)(xg + (size_t)(r * 128 + j * 16 + hx * 8) * kD) + lane;
                const uint4 wa = __ldg((const uint4*)gate_w + lane), wb = __ldg((const uint4*)gate_w + 32 + lane);
                const uint32_t tag = (epoch + 1) & 1;
                uint4* gp = g_gx + r * 32;
                if (lane < 2) st_pkt(gp + j * 4 + hx * 2 + lane, tag ^ 1, 0, 0, 0);
                float s[8];
#pragma unroll
                for (int i0 = 0; i0 < 8; i0 += 4) {
                    uint4 va[4], vb[4];
#pragma unroll
                    for (int i = 0; i < 4; i++) { va[i] = __ldg(xr + (i0 + i) * 64); vb[i] = __ldg(xr + (i0 + i) * 64 + 32); }
#pragma unroll
                    for (int i = 0; i < 4; i++) {
                        float t0 = bf_lo(va[i].x) * bf_lo(wa.x), t1 = bf_hi(va[i].x) * bf_hi(wa.x);
                        t0 = fmaf(bf_lo(va[i].y), bf_lo(wa.y), t0); t1 = fmaf(bf_hi(va[i].y), bf_hi(wa.y), t1);
                        t0 = fmaf(bf_lo(va[i].z), bf_lo(wa.z), t0); t1 = fmaf(bf_hi(va[i].z), bf_hi(wa.z), t1);
                        t0 = fmaf(bf_lo(va[i].w), bf_lo(wa.w), t0); t1 = fmaf(bf_hi(va[i].w), bf_hi(wa.w), t1);
                        t0 = fmaf(bf_lo(vb[i].x), bf_lo(wb.x), t0); t1 = fmaf(bf_hi(vb[i].x), bf_hi(wb.x), t1);
                        t0 = fmaf(bf_lo(vb[i].y), bf_lo(wb.y), t0); t1 = fmaf(bf_hi(vb[i].y), bf_hi(wb.y), t1);
                        t0 = fmaf(bf_lo(vb[i].z), bf_lo(wb.z), t0); t1 = fmaf(bf_hi(vb[i].z), bf_hi(wb.z), t1);
                        t0 = fmaf(bf_lo(vb[i].w), bf_lo(wb.w), t0); t1 = fmaf(bf_hi(vb[i].w), bf_hi(wb.w), t1);
                        s[i0 + i] = t0 + t1;
                    }
                }
#pragma unroll
                for (int i = 0; i < 8; i++) {
#pragma unroll
                    for (int o = 16; o; o >>= 1) s[i] += __shfl_xor_sync(0xffffffffu, s[i], o);
                    s[i] = 1.f / (1.f + __expf(-s[i]));
                }
                if (lane < 2) {
                    const float v0 = lane ? s[4] : s[0], v1 = lane ? s[5] : s[1], v2 = lane ? s[6] : s[2], v3 = lane ? s[7] : s[3];
                    st_pkt(gp + j * 4 + hx * 2 + lane, (__float_as_uint(v0) & ~1u) | tag, __float_as_uint(v1), __float_as_uint(v2), __float_as_uint(v3));
                }
                if (hx == 1) {
                    asm volatile("st.shared.u32 [%0], %1;" :: "r"(sb + OFF_ONES + lane * 4), "r"(0x3f803f80u) : "memory");
                    asm volatile("fence.proxy.async.shared::cta;" ::: "memory");
                }
                asm volatile("bar.sync 3, 96;" ::: "memory");
                if (hx == 0) {
                    uint32_t q[4];
                    recv_issue(q, gp + lane);
                    recv_check(q, gp + lane, tag);
                    asm volatile("st.shared.v4.u32 [%0], {%1,%2,%3,%4};" :: "r"(sb + OFF_G + lane * 16), "r"(q[0]), "r"(q[1]), "r"(q[2]), "r"(q[3]) : "memory");
                    if (lane == 0) {
                        asm volatile("st.shared.u32 [%0], %1;" :: "r"(sb + OFF_EPOCH), "r"(epoch) : "memory");
                        g_epoch[blockIdx.x] = epoch + 1;
                    }
                    __syncwarp();
                    if (lane == 0) mbar_arrive(sb + B_GRDY);
                } else {
                    if (r == 0) {
                        float4* zp = (float4*)(g_kvacc + (((epoch & 1) ^ 1) * 8 + j) * 4 * 272);
                        for (int i = lane; i < 272; i += 32) zp[i] = make_float4(0.f, 0.f, 0.f, 0.f);
                    }
                }
            }
            TS(2 + hx, 1);
#define PUBLISH_H(B) do { mbar_wait(sb + B_HSENT + 8 * (B), 0); if (lane == 0) { \
                asm volatile("st.release.gpu.global.u32 [%0], %1;" :: "l"(g_hflag + (r * 8 + j) * 8 + (B)), "r"(epoch + 1) : "memory"); } __syncwarp(); } while (0)
            if (hx == 1) {
#pragma unroll 1
                for (int b = 0; b < 3; b++) { PUBLISH_H(b); TS(3, 5 + b); }
            } else {
                const float* accp = g_kvacc + ((epoch & 1) * 8 + j) * 4 * 272;
                unsigned* cnt = g_kvcnt + j * 32;
                mbar_wait(sb + B_KVDONE, 0);
                TS(2, 5);
                if (lane == 0) asm volatile("red.release.gpu.global.add.u32 [%0], 1;" :: "l"(cnt) : "memory");
                __syncwarp();
                TS(2, 2);
                {
                    const unsigned target = 16u * (epoch + 1);
                    uint32_t it = 0, v;
                    do {
                        asm volatile("ld.acquire.gpu.global.u32 %0, [%1];" : "=r"(v) : "l"(cnt) : "memory");
                    } while ((int)(v - target) < 0 && ++it < SPIN_GLOBAL);
                }
                TS(2, 3);
#pragma unroll
                for (int h = 0; h < 4; h++) {
                    const float4 d0 = __ldcg((const float4*)(accp + h * 272) + lane);
                    const float4 d1 = __ldcg((const float4*)(accp + h * 272 + 128) + lane);
                    const float2 z0 = __ldcg((const float2*)(accp + h * 272 + 256) + (lane & 3));
                    const float2 z1 = __ldcg((const float2*)(accp + h * 272 + 264) + (lane & 3));
                    const uint32_t ba = sb + OFF_STG + h * 768 + lane * 4;
                    asm volatile("st.shared.u32 [%0], %1;" :: "r"(ba), "r"(pack2(d0.x, d0.y)) : "memory");
                    asm volatile("st.shared.u32 [%0], %1;" :: "r"(ba + 128), "r"(pack2(d1.x, d1.y)) : "memory");
                    asm volatile("st.shared.u32 [%0], %1;" :: "r"(ba + 256), "r"(pack2(d0.z, d0.w)) : "memory");
                    asm volatile("st.shared.u32 [%0], %1;" :: "r"(ba + 384), "r"(pack2(d1.z, d1.w)) : "memory");
                    asm volatile("st.shared.u32 [%0], %1;" :: "r"(ba + 512), "r"(pack2(z0.x, z0.y)) : "memory");
                    asm volatile("st.shared.u32 [%0], %1;" :: "r"(ba + 640), "r"(pack2(z1.x, z1.y)) : "memory");
                }
                asm volatile("fence.proxy.async.shared::cta;" ::: "memory");
                __syncwarp();
                if (lane == 0) mbar_arrive(sb + B_KVRDY);
                TS(2, 4);
            }
        } else {
            uint32_t epoch;
            asm volatile("ld.relaxed.gpu.global.u32 %0, [%1];" : "=r"(epoch) : "l"(g_epoch + blockIdx.x) : "memory");
            asm volatile("bar.arrive 3, 96;" :: "r"(epoch) : "memory");
            const int b = blockIdx.x, p = j >> 1;
            mbar_wait(sb + B_XFULL, 0);
            {
                uint4* mb = g_part + (size_t)(r * 2 + (j & 1)) * 16384 + (((p ^ 1) * 4 + p) << 10) + lane;
                uint4* ml = g_lx + (size_t)(r * 8 + j) * 2048 + lane;
#pragma unroll 8
                for (int i = 0; i < 32; i++) st_pkt(mb + i * 32, epoch & 1, 0, 0, 0);
#pragma unroll 8
                for (int i = 0; i < 64; i++) st_pkt(ml + i * 32, epoch & 1, 0, 0, 0);
                __syncwarp();
                if (lane == 0) mbar_arrive(sb + B_KVRDY);
            }
#pragma unroll 1
            for (int kb = 1; kb < 8; kb++) {
                mbar_wait(sb + B_XFULL + 8 * kb, 0);
                const char* base = kb < 3 ? pf_g : kb < 5 ? pf_u : kb == 5 ? pf_qkv : pf_d;
                const int off = kb == 5 ? b * 12288 : b * 14336 + ((kb < 5 ? kb - 1 : kb) & 1) * 7168;
                asm volatile("prefetch.global.L2 [%0];" :: "l"(base + off + lane * 128));
                if (kb == 5 || lane < 24) asm volatile("prefetch.global.L2 [%0];" :: "l"(base + off + 4096 + lane * 128));
                if (kb == 5) asm volatile("prefetch.global.L2 [%0];" :: "l"(base + off + 8192 + lane * 128));
                if (kb == 7) asm volatile("prefetch.global.L2 [%0];" :: "l"(pf_o + b * 4096 + lane * 128));
            }
            {
                const uint32_t want = epoch + 1;
                const int hrow = (r * 4 + p) * 5 * 128;
                const unsigned* fl = g_hflag + (r * 8 + (j & 6)) * 8 + (lane & 15);
                uint32_t it = 0;
                int i = 0;
                mbar_wait(sb + B_HSENT + 8, 0);
#pragma unroll 1
                while (i < 3 && ++it < SPIN_GLOBAL) {
                    uint32_t v;
                    asm volatile("ld.acquire.gpu.global.u32 %0, [%1];" : "=r"(v) : "l"(fl) : "memory");
                    const uint32_t rdy = __ballot_sync(0xffffffffu, v == want);
#pragma unroll 1
                    while (i < 3 && ((rdy >> i) & 0x101u) == 0x101u) {
                        mbar_wait(sb + B_XFREE + 8 * i, 0);
                        if (lane == 0) {
                            asm volatile("fence.proxy.async.global;" ::: "memory");
                            TS2(140 + i);
                            mbar_expect(sb + B_XFULL + 16 * i, i < 2 ? 32768 : 16384);
                            tma2(sb + OFF_X + i * 32768, i < 2 ? &maps.hx2 : &maps.hx, 0, hrow + i * 256, sb + B_XFULL + 16 * i);
                        }
                        i++;
                    }
                }
            }
        }
    } else {
        asm volatile("setmaxnreg.inc.sync.aligned.u32 224;");
        const int wg = warp >> 2;
        const bool elect = (tid & 127) == 0;
        const uint32_t xlo = ((sb + OFF_X + wg * 8192) >> 4) | LBO1;
        const uint32_t ringlo = (sb + OFF_RING) >> 4;
        auto release = [&](uint32_t bar) {
            if (elect) {
                mbar_arrive(sb + bar);
            }
        };
#define S_SL(S) ((S) < 40 ? (S) % 5 : ((S) - 40) % 9)
#define S_WAIT(S) do { mbar_wait(sb + (S_SL(S) < 5 ? B_FULL + 8 * S_SL(S) : B_EFULL + 8 * (S_SL(S) - 5)), (S) < 40 ? ((S) / 5) & 1 : (S) >= 49); \
            if (PROF && tid == 0) TS2(64 + (S)); } while (0)
#define S_B(S) (S_SL(S) < 5 ? ringlo + S_SL(S) * 1024 : ((sb + OFF_X) >> 4) + (S_SL(S) == 7 ? 8 : S_SL(S) == 8 ? 7 : S_SL(S)) * 1024)
#define S_REL(S) do { if ((S) < 49) release(S_SL(S) < 5 ? B_EMPTY + 8 * S_SL(S) : B_EEMPTY + 8 * (S_SL(S) - 5)); } while (0)
#define G1(S, acc, SW, KB) g1_issue<SW, (KB) == 0>(acc, xlo + (KB) * 1024, S_B(S) | (SW ? LBO4K : LBO8K))
#define RET(S) do { S_WAIT((S) + 1); wg_wait<1>(); S_REL((S) - 1); } while (0)
#define RET2(S) do { S_WAIT((S) + 1); wg_wait<2>(); S_REL((S) - 1); } while (0)
#define SCHED() mbar_wait(sb + B_GRDY, 0)
#define A2_SYNC() do { asm volatile("fence.proxy.async.shared::cta;" ::: "memory"); asm volatile("bar.sync %0, 128;" :: "r"(wg + 1) : "memory"); } while (0)
#define H_EPI(acc, F, I0, I1, OG, OU) _Pragma("unroll") for (int i = (I0); i < (I1); i++) \
            F[i] = keep(hmul2(pack2(acc[(OG) + 2 * i] * acc[(OU) + 2 * i], acc[(OG) + 2 * i + 1] * acc[(OU) + 2 * i + 1]), (i & 1) ? m_hi : m_lo))
#define PHI(acc, F, I0, I1) _Pragma("unroll") for (int i = (I0); i < (I1); i++) F[i] = keep(phi2(acc[2 * i], acc[2 * i + 1]))

        float a0[64], b0[64], a1[64], a2_[64], a3[64];
        mbar_wait(sb + B_XFULL, 0);
        S_WAIT(0); G1(0, a0, false, 0);
        if ((warp & 3) == 0) TS(wg, 1);
        S_WAIT(1); G1(1, b0, false, 0); RET(1);
#define C0(KB) mbar_wait(sb + B_XFULL + 8 * (KB), 0); if (PROF && tid == 0) TS2(128 + (KB)); \
        G1(2 * (KB), a0, false, KB); RET(2 * (KB)); G1(2 * (KB) + 1, b0, false, KB); RET(2 * (KB) + 1)
        C0(1); C0(2); C0(3); C0(4); C0(5);
        mbar_wait(sb + B_XFULL + 8 * 6, 0);
        G1(12, a0, false, 6); RET(12);
        mbar_wait(sb + B_XFULL + 8 * 7, 0);
        G1(13, a0, false, 7); RET(13);
        G1(14, b0, false, 6);
        mbar_wait(sb + B_GRDY, 0);
        float g_lo, g_hi;
        uint32_t tag;
        {
            const uint32_t ga = sb + OFF_G + (warp * 16 + (lane >> 2)) * 4;
            asm volatile("ld.shared.f32 %0, [%1];" : "=f"(g_lo) : "r"(ga) : "memory");
            asm volatile("ld.shared.f32 %0, [%1];" : "=f"(g_hi) : "r"(ga + 32) : "memory");
            asm volatile("ld.shared.u32 %0, [%1];" : "=r"(tag) : "r"(sb + OFF_EPOCH) : "memory");
        }
        float* const kvp = g_kvacc + (((tag & 1) * 8 + j) * 4 + (warp & 3)) * 272;
        tag = (tag + 1) & 1;
        const uint32_t m_lo = pack2(1.f - g_lo, 1.f - g_lo), m_hi = pack2(1.f - g_hi, 1.f - g_hi);
        const uint32_t lrow = ((lane & 7) + 8 * ((lane >> 3) & 1)) * 128;
        const uint32_t srow = (warp & 3) * 2048 + lrow;
        const uint32_t ssw = (lane >> 4) ^ (lane & 7);
        uint4* const hsend = g_hx + (size_t)((r * 4 + (j >> 1)) * 5 + (j & 1)) * 1024 + warp * 128 + (lane >> 2) * 8 + (lane & 3);
#define SENT_H(B) do { __syncwarp(); if (lane == 0) mbar_arrive(sb + B_HSENT + 8 * (B)); } while (0)
        RET(14);
        pin(a0);
        uint32_t fh0[16], fh1[16], fh2[16], fh3[8], fo[16];
        G1(15, b0, false, 7); SCHED(); H_EPI(a0, fh0, 0, 16, 0, 32); RET(15);
        if ((warp & 3) == 0) TS(wg, 2);

        float kv[32], zs[4];
        uint32_t pk[16], pv[16];
        const uint32_t stg = sb + OFF_STG + wg * 8192, stl = stg + (warp & 1) * 2048 + lrow;
        const uint32_t klo = (stg >> 4) | LBO1, vlo = klo + 256, olo = (sb + OFF_ONES) >> 4;
        G1(16, a1, false, 0); RET(16);
        pin(b0);
        G1(17, a1, false, 1); send_h<0, 1>(fh0, hsend); SCHED(); PHI(b0, pk, 0, 6); RET(17);
        G1(18, a1, false, 2); send_h<1, 2>(fh0, hsend); SENT_H(0); SCHED(); PHI(b0, pk, 6, 12); RET(18);
        G1(19, a1, false, 3); SCHED(); PHI(b0, pk, 12, 16); pack_sub<32>(pv, b0); RET(19);
#define KV_ROUND(Z) do { A2_SYNC(); wg_fence(); \
            wg_ss64t##Z(kv, vlo, DH128, klo, DH128); wg_ss64t(kv, vlo + 128, DH128, klo + 128, DH128); \
            wg_ss8t##Z(zs, klo, DH128, olo, 0); wg_ss8t(zs, klo + 128, DH128, olo, 0); wg_commit(); } while (0)
        G1(20, a1, false, 4); if (!(warp & 2)) { stash<16>(stl, ssw, pk); stash<16>(stl + 4096, ssw, pv); } RET(20);
        G1(21, a1, false, 5); KV_ROUND(_z); RET2(21);
        G1(22, a1, false, 6); RET(22);
        G1(23, a1, false, 7); if (warp & 2) { stash<16>(stl, ssw, pk); stash<16>(stl + 4096, ssw, pv); } RET(23);
        if ((warp & 3) == 0) TS(wg, 3);

        G1(24, a2_, true, 0); KV_ROUND(); RET2(24);
        pin(a1);
        G1(25, a2_, true, 1); RET(25);
        pin(kv); pin(zs);
        G1(26, a2_, true, 2);
#define KV_RED(W) do { asm volatile("red.global.add.v4.f32 [%0], {%1,%2,%3,%4};" :: "l"(kvp + lane * 4), "f"(kv[8 * W]), "f"(kv[8 * W + 1]), "f"(kv[8 * W + 2]), "f"(kv[8 * W + 3]) : "memory"); \
                       asm volatile("red.global.add.v4.f32 [%0], {%1,%2,%3,%4};" :: "l"(kvp + 128 + lane * 4), "f"(kv[8 * W + 4]), "f"(kv[8 * W + 5]), "f"(kv[8 * W + 6]), "f"(kv[8 * W + 7]) : "memory"); } while (0)
        if ((warp & 3) == 0) KV_RED(0); else if ((warp & 3) == 1) KV_RED(1); else if ((warp & 3) == 2) KV_RED(2); else KV_RED(3);
        if ((lane & 3) == 0) {
            asm volatile("red.global.add.f32 [%0], %1;" :: "l"(kvp + 256 + (lane >> 2)), "f"(zs[0]) : "memory");
            asm volatile("red.global.add.f32 [%0], %1;" :: "l"(kvp + 264 + (lane >> 2)), "f"(zs[2]) : "memory");
        }
        __syncwarp();
        if (lane == 0) mbar_arrive(sb + B_KVDONE);
        RET(26);
        G1(27, a2_, true, 3); SCHED(); H_EPI(a1, fh1, 0, 16, 0, 32); RET(27);
        G1(28, a2_, true, 4); RET(28);
        G1(29, a2_, true, 5); RET(29);
        G1(30, a2_, true, 6); send_h<0, 1>(fh1, hsend + 2 * 1024); RET(30);
        G1(31, a2_, true, 7); send_h<1, 2>(fh1, hsend + 2 * 1024); SENT_H(1); RET(31);
        if ((warp & 3) == 0) TS(wg, 4);

        float on[4][12];
#define O_SCALE(h) do { const float s_lo = __fdividef(g_lo, on[h][8] + 1e-6f), s_hi = __fdividef(g_hi, on[h][10] + 1e-6f); \
            const uint32_t sl_ = pack2(s_lo, s_lo), sh_ = pack2(s_hi, s_hi); \
            fo[4 * h] = hmul2(pack2(on[h][0], on[h][1]), sl_); fo[4 * h + 1] = hmul2(pack2(on[h][2], on[h][3]), sh_); \
            fo[4 * h + 2] = hmul2(pack2(on[h][4], on[h][5]), sl_); fo[4 * h + 3] = hmul2(pack2(on[h][6], on[h][7]), sh_); } while (0)
        G1(32, a3, false, 0); RET(32);
        pin(a2_);
        G1(33, a3, false, 1); SCHED(); H_EPI(a2_, fh3, 0, 8, 32, 48);
        send_h<0, 1>(fh3, hsend + 4 * 1024 - (j & 1) * 1020); SENT_H(2); PHI(a2_, fo, 0, 2); RET(33);
        G1(34, a3, false, 2); SCHED(); PHI(a2_, fo, 2, 7); RET(34);
        if (elect) mbar_arrive(sb + B_XFREE);
        G1(35, a3, false, 3); SCHED(); PHI(a2_, fo, 7, 12); RET(35);
        G1(36, a3, false, 4); SCHED(); PHI(a2_, fo, 12, 16); RET(36);
        if (elect) mbar_arrive(sb + B_XFREE + 8);
        G1(37, a3, false, 5);
        if ((warp & 3) == 0) TS(wg, 5);
        mbar_wait(sb + B_KVRDY, 0);
        if ((warp & 3) == 0) TS(wg, 6);
        wg_fence();
#pragma unroll
        for (int h = 0; h < 4; h++)
            wg_rs24_z(on[h], fo[4 * h], fo[4 * h + 1], fo[4 * h + 2], fo[4 * h + 3], (((sb + OFF_STG) >> 4) + h * 48) | (8u << 16), 16u);
        wg_commit();
        RET2(37);
        G1(38, a3, false, 6); RET(38);
        if (elect) mbar_arrive(sb + B_XFREE + 16);
        release(B_EEMPTY); release(B_EEMPTY + 16);
        pin(on[0]); pin(on[1]); pin(on[2]); pin(on[3]);
        uint4* const lsend = g_lx + (size_t)(r * 8 + j) * 2048 + warp * 128 + lane;
        const uint4* const lrecv = g_lx + (size_t)(r * 8 + (j ^ 1)) * 2048 + warp * 128 + lane;
        G1(39, a3, false, 7); SCHED();
        O_SCALE(0); O_SCALE(1); send_frag<0, 2>(fo, lsend, tag);
        O_SCALE(2); O_SCALE(3);
        RET(39);
        release(B_EEMPTY + 8);
        if ((warp & 3) == 0) TS(wg, 7);

#define G2S(S, acc, U) do { wg_fence(); _Pragma("unroll") for (int k = 0; k < 4; k++) { \
            if ((S) == 40 && k == 0) wg_ss128_z(acc, xlo, DH128, S_B(S) | LBO8K, DH128); \
            else wg_ss128(acc, xlo + (U) * 1024 + 2 * k, DH128, (S_B(S) | LBO8K) + 128 * k, DH128); } wg_commit(); } while (0)
#define G2R(S, acc, F) do { wg_fence(); _Pragma("unroll") for (int k = 0; k < 4; k++) { \
            if ((S) == 49 && k == 0) wg_rs128_z(acc, F[0], F[1], F[2], F[3], S_B(S) | LBO8K, DH128); \
            else wg_rs128(acc, F[4 * k], F[4 * k + 1], F[4 * k + 2], F[4 * k + 3], (S_B(S) | LBO8K) + 128 * k, DH128); } wg_commit(); } while (0)
#define H_WAIT(P) do { mbar_wait(sb + B_XFULL + 8 * (P), 1); if (PROF && tid == 0) TS2(150 + (P)); } while (0)
        const int p = j >> 1, pw = (p & 2) ^ 2;
        const bool own = wg == (p & 1);
        uint4* const pbase = g_part + (size_t)(r * 2 + (j & 1)) * 16384 + (warp & 3) * 256 + lane;

        float p1[64], p2[64];
        uint32_t po[16], ph2[16];
        H_WAIT(0); G2S(40, p1, 0); send_frag<2, 4>(fo, lsend, tag); RET(40);
        release(B_EEMPTY + 24);
        pin(a3);
        G2S(41, p1, 1); SCHED(); H_EPI(a3, fh2, 0, 16, 0, 32); send_frag<0, 2>(fh2, lsend + 1024, tag); RET(41);
        H_WAIT(2); G2S(42, p1, 2); send_frag<2, 4>(fh2, lsend + 1024, tag); RET(42);
        G2S(43, p1, 3); recv_issue(po, lrecv); RET(43);
        H_WAIT(4); G2S(44, p1, 4); RET(44);
        G2R(45, p1, fo); recv_issue(ph2, lrecv + 1024); RET(45);
        G2R(46, p1, fh2); SCHED(); recv_check(po, lrecv, tag); RET(46);
        G2R(47, p1, po); SCHED(); recv_check(ph2, lrecv + 1024, tag); RET(47);
        G2R(48, p1, ph2); RET(48);
        if ((warp & 3) == 0) TS(wg, 8);
        uint32_t sp[32], qa[32], qb[32];
        uint4* const s1 = pbase + (((pw + wg) * 4 + p) << 10);
        G2R(49, p2, fo); RET(49);
        pin(p1);
        G2R(50, p2, fh2); SCHED(); pack_sub<0>(sp, p1); send_frag<0, 2>(sp, s1, tag); RET(50);
        G2R(51, p2, po); send_frag<2, 5>(sp, s1, tag); RET(51);
        G2R(52, p2, ph2); send_frag<5, 8>(sp, s1, tag); RET(52);
        if (own) mbar_wait(sb + B_AHEAD, 0);
        G2S(53, p2, 0); RET(53);
        G2S(54, p2, 1); RET(54);
        G2S(55, p2, 2);
        if (!own && elect) mbar_arrive(sb + B_AHEAD);
        const uint4* ra = pbase + ((p * 4 + pw) << 10);
        if (own) recv_issue(qa, ra);
        RET(55);
        G2S(56, p2, 3);
        if (own) recv_issue(qb, ra + 1024);
        RET(56);
        G2S(57, p2, 4);
        if ((warp & 3) == 0) TS(wg, 9);
        wg_wait<0>();
        pin(p2);
        if ((warp & 3) == 0) TS(wg, 11);
        if (!own) {
            pack_sub<0>(sp, p2); send_frag<0, 8>(sp, pbase + (((p ^ 1) * 4 + p) << 10), tag);
        } else {
            const uint4* rc = pbase + ((p * 4 + (p ^ 1)) << 10);
            recv_issue(sp, rc);
            recv_check(qa, ra, tag); accum(qa, p2);
            recv_check(qb, ra + 1024, tag); accum(qb, p2);
            if ((warp & 3) == 0) TS(wg, 12);
            recv_check(sp, rc, tag); accum(sp, p2);
            if ((warp & 3) == 0) TS(wg, 13);
            uint32_t f0[16], f1[16];
            pack_sub<0>(f0, p2); pack_sub<32>(f1, p2);
            const uint32_t slab = sb + OFF_X + 2 * 16384 + wg * 8192;
            stash<16>(slab + srow, ssw, f0); stash<16>(slab + 16384 + srow, ssw, f1);
            __syncwarp();
            __nv_bfloat16* op = out + (size_t)(r * 128 + warp * 16 + (lane >> 4)) * kD + (j & 1) * 256 + (p & 2) * 64 + (lane & 15) * 8;
#pragma unroll
            for (int i = 0; i < 8; i++) {
                const int row = i * 2 + (lane >> 4);
                uint4 v;
                asm volatile("ld.shared.v4.u32 {%0,%1,%2,%3}, [%4];" : "=r"(v.x), "=r"(v.y), "=r"(v.z), "=r"(v.w)
                             : "r"(slab + (lane & 8) * 2048 + ((warp & 3) * 16 + row) * 128 + (((lane & 7) ^ (row & 7)) << 4)) : "memory");
                *(uint4*)(op + i * 2 * kD) = v;
            }
        }
        if ((warp & 3) == 0) { TS(wg, 14); TSG(wg, 31); }
    }
}

typedef CUresult (*EncodeFn)(CUtensorMap*, CUtensorMapDataType, cuuint32_t, void*, const cuuint64_t*, const cuuint64_t*, const cuuint32_t*,
                             const cuuint32_t*, CUtensorMapInterleave, CUtensorMapSwizzle, CUtensorMapL2promotion, CUtensorMapFloatOOBfill);

static void encode(EncodeFn fn, CUtensorMap* m, int rank, const void* base, const cuuint64_t (&gd)[5], const cuuint64_t (&gs)[4],
                   const cuuint32_t (&bd)[5], CUtensorMapSwizzle sw) {
    cuuint32_t es[5] = {1, 1, 1, 1, 1};
    fn(m, CU_TENSOR_MAP_DATA_TYPE_BFLOAT16, rank, const_cast<void*>(base), gd, gs, bd, es, CU_TENSOR_MAP_INTERLEAVE_NONE, sw,
       CU_TENSOR_MAP_L2_PROMOTION_L2_128B, CU_TENSOR_MAP_FLOAT_OOB_FILL_NONE);
}

extern "C" void kernel_launch(void* const* d_in, const int* in_sizes, int n_in, void* d_out, int out_size) {
    const char* x = (const char*)d_in[0];
    const char* wqkv = (const char*)d_in[1];
    const char* wo = (const char*)d_in[2];
    const char* wg = (const char*)d_in[4];
    const char* wu = (const char*)d_in[5];
    const char* wd = (const char*)d_in[6];
    void* fnp = nullptr;
    cudaDriverEntryPointQueryResult qr;
    cudaGetDriverEntryPoint("cuTensorMapEncodeTiled", &fnp, cudaEnableDefault, &qr);
    EncodeFn fn = (EncodeFn)fnp;
    Maps maps;
    const char* lo = wg < wu ? wg : wu;
    const uint64_t diff = wg < wu ? (uint64_t)(wu - wg) : (uint64_t)(wg - wu);
    const CUtensorMapSwizzle S128 = CU_TENSOR_MAP_SWIZZLE_128B, S64 = CU_TENSOR_MAP_SWIZZLE_64B;
    encode(fn, &maps.x, 2, x, {512, 2048, 1, 1}, {1024, 0, 0}, {64, 128, 1, 1}, S128);
    encode(fn, &maps.gu, 3, lo, {1792, 512, 2, 1}, {3584, diff, 0}, {64, 64, 2, 1}, S128);
    encode(fn, &maps.kv, 3, wqkv, {512, 512, 3, 1}, {3072, 1024, 0}, {64, 64, 2, 1}, S128);
    encode(fn, &maps.q64, 3, wqkv, {32, 512, 48, 1}, {3072, 64, 0}, {32, 64, 2, 1}, S64);
    encode(fn, &maps.gu64, 3, lo, {1792, 512, 2, 1}, {3584, diff, 0}, {32, 64, 2, 1}, S64);
    encode(fn, &maps.wdw, 3, wd, {64, 1792, 8, 1}, {1024, 128, 0}, {64, 64, 2, 1}, S128);
    encode(fn, &maps.wow, 3, wo, {64, 512, 8}, {1024, 128}, {64, 64, 2}, S128);
    encode(fn, &maps.wdp, 5, wd, {512, 2, 4, 4, 56}, {1024, 8192, 2048, 32768}, {64, 2, 4, 4, 2}, S128);
    encode(fn, &maps.wdph, 5, wd, {512, 2, 4, 4, 56}, {1024, 8192, 2048, 32768}, {64, 2, 4, 4, 1}, S128);
    void* hx = nullptr;
    cudaGetSymbolAddress(&hx, g_hx);
    encode(fn, &maps.hx, 2, hx, {64, 16 * 4 * 5 * 128}, {128}, {64, 128}, S128);
    encode(fn, &maps.hx2, 2, hx, {64, 16 * 4 * 5 * 128}, {128}, {64, 256}, S128);
    cudaFuncSetAttribute(fused_kernel, cudaFuncAttributeMaxDynamicSharedMemorySize, SMEM_BYTES);
    cudaLaunchConfig_t cfg = {};
    cfg.gridDim = dim3(128);
    cfg.blockDim = dim3(384);
    cfg.dynamicSmemBytes = SMEM_BYTES;
    cfg.stream = cudaStreamPerThread;
    cudaLaunchAttribute at[1];
    at[0].id = cudaLaunchAttributeClusterDimension;
    at[0].val.clusterDim.x = 2; at[0].val.clusterDim.y = 1; at[0].val.clusterDim.z = 1;
    cfg.attrs = at;
    cfg.numAttrs = MC ? 1 : 0;
    cudaLaunchKernelEx(&cfg, fused_kernel, maps, (const __nv_bfloat16*)d_in[0], (const __nv_bfloat16*)d_in[7], wqkv, wg, wu, wd, wo, (__nv_bfloat16*)d_out);
}
```

```cpp
#include <cuda_runtime.h>
#include <cuda.h>
#include <cuda_bf16.h>
#include <stdint.h>

#define MC 0
#define PFMODE 1
#define PROF 0

namespace {

constexpr int kD = 512;
constexpr uint32_t OFF_X = 0, OFF_STG = 131072, OFF_RING = 147456, OFF_MISC = 229376;
constexpr uint32_t B_FULL = OFF_MISC, B_EMPTY = OFF_MISC + 40, B_XFULL = OFF_MISC + 80;
constexpr uint32_t B_GRDY = OFF_MISC + 152, B_KVDONE = OFF_MISC + 160, B_KVRDY = OFF_MISC + 168;
constexpr uint32_t B_HSENT = OFF_MISC + 176, B_XFREE = OFF_MISC + 200;
constexpr uint32_t OFF_EPOCH = OFF_MISC + 240, OFF_G = OFF_MISC + 256;
constexpr uint32_t B_AHEAD = OFF_MISC + 248;
constexpr uint32_t OFF_ONES = OFF_MISC + 768;
constexpr uint32_t B_EFULL = OFF_MISC + 896, B_EEMPTY = OFF_MISC + 928;
constexpr uint32_t SMEM_BYTES = OFF_MISC + 960;
constexpr uint32_t SPIN_GLOBAL = 1u << 14;

struct alignas(64) Maps { CUtensorMap x, gu, kv, q64, gu64, wdw, wow, wdp, wdph, hx, hx2; };

}

__device__ uint4 g_part[16 * 2 * 4 * 4 * 1024];
__device__ uint4 g_hx[16 * 4 * 5 * 1024];
__device__ uint4 g_lx[16 * 8 * 2 * 1024];
__device__ unsigned g_hflag[128 * 8];
__device__ uint4 g_gx[16 * 32];
__device__ float g_kvacc[2 * 8 * 4 * 272];
__device__ unsigned g_kvcnt[8 * 32];
__device__ unsigned g_epoch[128];
#define TS(role, idx)
#define TS2(idx)
#define TSG(role, idx)

namespace {

__device__ __forceinline__ void mbar_init(uint32_t bar, uint32_t cnt) { asm volatile("mbarrier.init.shared::cta.b64 [%0], %1;" :: "r"(bar), "r"(cnt) : "memory"); }
__device__ __forceinline__ void mbar_expect(uint32_t bar, uint32_t bytes) { asm volatile("mbarrier.arrive.expect_tx.shared::cta.b64 _, [%0], %1;" :: "r"(bar), "r"(bytes) : "memory"); }
__device__ __forceinline__ void mbar_arrive(uint32_t bar) { asm volatile("mbarrier.arrive.shared::cta.b64 _, [%0];" :: "r"(bar) : "memory"); }
__device__ __forceinline__ void mbar_arrive_cta(uint32_t bar, uint32_t cta) {
    asm volatile("{\n.reg .b32 ra;\nmapa.shared::cluster.u32 ra, %0, %1;\nmbarrier.arrive.shared::cluster.b64 _, [ra];\n}" :: "r"(bar), "r"(cta) : "memory");
}
__device__ __forceinline__ void mbar_wait(uint32_t bar, uint32_t parity) {
    asm volatile("{\n.reg .pred p;\n.reg .u32 c;\n"
                 "mbarrier.try_wait.parity.shared::cta.b64 p, [%0], %1;\n@p bra DONE;\n"
                 "mov.u32 c, 0;\nLAB_WAIT:\nmbarrier.try_wait.parity.shared::cta.b64 p, [%0], %1;\n@p bra DONE;\n"
                 "add.u32 c, c, 1;\nsetp.lt.u32 p, c, 65536;\n@p bra LAB_WAIT;\nDONE:\n}" :: "r"(bar), "r"(parity) : "memory");
}
__device__ __forceinline__ void tma2(uint32_t dst, const CUtensorMap* m, int c0, int c1, uint32_t bar) {
    asm volatile("cp.async.bulk.tensor.2d.shared::cluster.global.mbarrier::complete_tx::bytes [%0], [%1, {%3, %4}], [%2];"
        :: "r"(dst), "l"(m), "r"(bar), "r"(c0), "r"(c1) : "memory");
}
__device__ __forceinline__ void tmaw2(uint32_t dst, const CUtensorMap* m, int c0, int c1, uint32_t bar) {
    tma2(dst, m, c0, c1, bar);
}
__device__ __forceinline__ void tmaw3(uint32_t dst, const CUtensorMap* m, int c0, int c1, int c2, uint32_t bar) {
    asm volatile("cp.async.bulk.tensor.3d.shared::cluster.global.mbarrier::complete_tx::bytes [%0], [%1, {%3, %4, %5}], [%2];"
        :: "r"(dst), "l"(m), "r"(bar), "r"(c0), "r"(c1), "r"(c2) : "memory");
}
__device__ __forceinline__ void tmaw5(uint32_t dst, const CUtensorMap* m, int c0, int c4, uint32_t bar) {
    asm volatile("cp.async.bulk.tensor.5d.shared::cluster.global.mbarrier::complete_tx::bytes [%0], [%1, {%3, %5, %5, %5, %4}], [%2];"
        :: "r"(dst), "l"(m), "r"(bar), "r"(c0), "r"(c4), "r"(0) : "memory");
}
__device__ __forceinline__ void wg_fence() { asm volatile("wgmma.fence.sync.aligned;" ::: "memory"); }
__device__ __forceinline__ void wg_commit() { asm volatile("wgmma.commit_group.sync.aligned;" ::: "memory"); }
template <int N> __device__ __forceinline__ void wg_wait() { asm volatile("wgmma.wait_group.sync.aligned %0;" :: "n"(N) : "memory"); }
template <int N> __device__ __forceinline__ void pin(float (&d)[N]) {
#pragma unroll
    for (int i = 0; i < N; i++) asm volatile("" : "+f"(d[i]) :: "memory");
}
__device__ __forceinline__ uint32_t pack2(float lo, float hi) { uint32_t r; asm("cvt.rn.bf16x2.f32 %0, %1, %2;" : "=r"(r) : "f"(hi), "f"(lo)); return r; }
__device__ __forceinline__ uint32_t keep(uint32_t v) { asm volatile("" : "+r"(v)); return v; }
__device__ __forceinline__ uint32_t hmul2(uint32_t a, uint32_t b) { uint32_t r; asm("mul.bf16x2 %0, %1, %2;" : "=r"(r) : "r"(a), "r"(b)); return r; }
__device__ __forceinline__ uint32_t phi2(float t0, float t1) {
    float e0, e1;
    asm("ex2.approx.ftz.f32 %0, %1;" : "=f"(e0) : "f"(t0 * 1.4426950408889634f));
    asm("ex2.approx.ftz.f32 %0, %1;" : "=f"(e1) : "f"(t1 * 1.4426950408889634f));
    uint32_t e = pack2(e0, e1), t = pack2(t0, t1), r;
    asm("min.bf16x2 %0, %0, %1;" : "+r"(e) : "r"(0x3f803f80u));
    asm("max.bf16x2 %0, %0, %1;" : "+r"(t) : "r"(0x35863586u));
    asm("add.bf16x2 %0, %1, %2;" : "=r"(r) : "r"(e), "r"(t));
    return r;
}
__device__ __forceinline__ void stsm4(uint32_t a, uint32_t r0, uint32_t r1, uint32_t r2, uint32_t r3) {
    asm volatile("stmatrix.sync.aligned.m8n8.x4.shared.b16 [%0], {%1,%2,%3,%4};" :: "r"(a), "r"(r0), "r"(r1), "r"(r2), "r"(r3) : "memory");
}
__device__ __forceinline__ float bf_lo(uint32_t w) { return __uint_as_float(w << 16); }
__device__ __forceinline__ float bf_hi(uint32_t w) { return __uint_as_float(w & 0xffff0000u); }
__device__ __forceinline__ void st_pkt(uint4* p, uint32_t w0, uint32_t w1, uint32_t w2, uint32_t w3) {
    asm volatile("{\n.reg .b64 lo, hi;\n.reg .b128 v;\nmov.b64 lo, {%1, %2};\nmov.b64 hi, {%3, %4};\nmov.b128 v, {lo, hi};\nst.relaxed.gpu.global.b128 [%0], v;\n}"
        :: "l"(p), "r"(w0), "r"(w1), "r"(w2), "r"(w3) : "memory");
}
__device__ __forceinline__ void ld_pkt(const uint4* p, uint32_t& w0, uint32_t& w1, uint32_t& w2, uint32_t& w3) {
    asm volatile("{\n.reg .b64 lo, hi;\n.reg .b128 v;\nld.relaxed.gpu.global.b128 v, [%4];\nmov.b128 {lo, hi}, v;\nmov.b64 {%0, %1}, lo;\nmov.b64 {%2, %3}, hi;\n}"
        : "=r"(w0), "=r"(w1), "=r"(w2), "=r"(w3) : "l"(p) : "memory");
}

__device__ __forceinline__ void wg_rs128(float (&d)[64], uint32_t a0, uint32_t a1, uint32_t a2, uint32_t a3, uint32_t blo, uint32_t bhi) {
    asm volatile("{\n.reg .b64 db;\nmov.b64 db, {%68, %69};\n"
        "wgmma.mma_async.sync.aligned.m64n128k16.f32.bf16.bf16 {%0,%1,%2,%3,%4,%5,%6,%7,%8,%9,%10,%11,%12,%13,%14,%15,%16,%17,%18,%19,%20,%21,%22,%23,%24,%25,%26,%27,%28,%29,%30,%31,%32,%33,%34,%35,%36,%37,%38,%39,%40,%41,%42,%43,%44,%45,%46,%47,%48,%49,%50,%51,%52,%53,%54,%55,%56,%57,%58,%59,%60,%61,%62,%63}, {%64,%65,%66,%67}, db, 1, 1, 1, 1;\n}\n"
        : "+f"(d[0]),"+f"(d[1]),"+f"(d[2]),"+f"(d[3]),"+f"(d[4]),"+f"(d[5]),"+f"(d[6]),"+f"(d[7]),"+f"(d[8]),"+f"(d[9]),"+f"(d[10]),"+f"(d[11]),"+f"(d[12]),"+f"(d[13]),"+f"(d[14]),"+f"(d[15]),"+f"(d[16]),"+f"(d[17]),"+f"(d[18]),"+f"(d[19]),"+f"(d[20]),"+f"(d[21]),"+f"(d[22]),"+f"(d[23]),"+f"(d[24]),"+f"(d[25]),"+f"(d[26]),"+f"(d[27]),"+f"(d[28]),"+f"(d[29]),"+f"(d[30]),"+f"(d[31]),"+f"(d[32]),"+f"(d[33]),"+f"(d[34]),"+f"(d[35]),"+f"(d[36]),"+f"(d[37]),"+f"(d[38]),"+f"(d[39]),"+f"(d[40]),"+f"(d[41]),"+f"(d[42]),"+f"(d[43]),"+f"(d[44]),"+f"(d[45]),"+f"(d[46]),"+f"(d[47]),"+f"(d[48]),"+f"(d[49]),"+f"(d[50]),"+f"(d[51]),"+f"(d[52]),"+f"(d[53]),"+f"(d[54]),"+f"(d[55]),"+f"(d[56]),"+f"(d[57]),"+f"(d[58]),"+f"(d[59]),"+f"(d[60]),"+f"(d[61]),"+f"(d[62]),"+f"(d[63])
        : "r"(a0), "r"(a1), "r"(a2), "r"(a3), "r"(blo), "r"(bhi));
}
__device__ __forceinline__ void wg_ss128(float (&d)[64], uint32_t alo, uint32_t ahi, uint32_t blo, uint32_t bhi) {
    asm volatile("{\n.reg .b64 da, db;\nmov.b64 da, {%64, %65};\nmov.b64 db, {%66, %67};\n"
        "wgmma.mma_async.sync.aligned.m64n128k16.f32.bf16.bf16 {%0,%1,%2,%3,%4,%5,%6,%7,%8,%9,%10,%11,%12,%13,%14,%15,%16,%17,%18,%19,%20,%21,%22,%23,%24,%25,%26,%27,%28,%29,%30,%31,%32,%33,%34,%35,%36,%37,%38,%39,%40,%41,%42,%43,%44,%45,%46,%47,%48,%49,%50,%51,%52,%53,%54,%55,%56,%57,%58,%59,%60,%61,%62,%63}, da, db, 1, 1, 1, 0, 1;\n}\n"
        : "+f"(d[0]),"+f"(d[1]),"+f"(d[2]),"+f"(d[3]),"+f"(d[4]),"+f"(d[5]),"+f"(d[6]),"+f"(d[7]),"+f"(d[8]),"+f"(d[9]),"+f"(d[10]),"+f"(d[11]),"+f"(d[12]),"+f"(d[13]),"+f"(d[14]),"+f"(d[15]),"+f"(d[16]),"+f"(d[17]),"+f"(d[18]),"+f"(d[19]),"+f"(d[20]),"+f"(d[21]),"+f"(d[22]),"+f"(d[23]),"+f"(d[24]),"+f"(d[25]),"+f"(d[26]),"+f"(d[27]),"+f"(d[28]),"+f"(d[29]),"+f"(d[30]),"+f"(d[31]),"+f"(d[32]),"+f"(d[33]),"+f"(d[34]),"+f"(d[35]),"+f"(d[36]),"+f"(d[37]),"+f"(d[38]),"+f"(d[39]),"+f"(d[40]),"+f"(d[41]),"+f"(d[42]),"+f"(d[43]),"+f"(d[44]),"+f"(d[45]),"+f"(d[46]),"+f"(d[47]),"+f"(d[48]),"+f"(d[49]),"+f"(d[50]),"+f"(d[51]),"+f"(d[52]),"+f"(d[53]),"+f"(d[54]),"+f"(d[55]),"+f"(d[56]),"+f"(d[57]),"+f"(d[58]),"+f"(d[59]),"+f"(d[60]),"+f"(d[61]),"+f"(d[62]),"+f"(d[63])
        : "r"(alo), "r"(ahi), "r"(blo), "r"(bhi));
}
__device__ __forceinline__ void wg_ss128_z(float (&d)[64], uint32_t alo, uint32_t ahi, uint32_t blo, uint32_t bhi) {
    asm volatile("{\n.reg .b64 da, db;\nmov.b64 da, {%64, %65};\nmov.b64 db, {%66, %67};\n"
        "wgmma.mma_async.sync.aligned.m64n128k16.f32.bf16.bf16 {%0,%1,%2,%3,%4,%5,%6,%7,%8,%9,%10,%11,%12,%13,%14,%15,%16,%17,%18,%19,%20,%21,%22,%23,%24,%25,%26,%27,%28,%29,%30,%31,%32,%33,%34,%35,%36,%37,%38,%39,%40,%41,%42,%43,%44,%45,%46,%47,%48,%49,%50,%51,%52,%53,%54,%55,%56,%57,%58,%59,%60,%61,%62,%63}, da, db, 0, 1, 1, 0, 1;\n}\n"
        : "=f"(d[0]),"=f"(d[1]),"=f"(d[2]),"=f"(d[3]),"=f"(d[4]),"=f"(d[5]),"=f"(d[6]),"=f"(d[7]),"=f"(d[8]),"=f"(d[9]),"=f"(d[10]),"=f"(d[11]),"=f"(d[12]),"=f"(d[13]),"=f"(d[14]),"=f"(d[15]),"=f"(d[16]),"=f"(d[17]),"=f"(d[18]),"=f"(d[19]),"=f"(d[20]),"=f"(d[21]),"=f"(d[22]),"=f"(d[23]),"=f"(d[24]),"=f"(d[25]),"=f"(d[26]),"=f"(d[27]),"=f"(d[28]),"=f"(d[29]),"=f"(d[30]),"=f"(d[31]),"=f"(d[32]),"=f"(d[33]),"=f"(d[34]),"=f"(d[35]),"=f"(d[36]),"=f"(d[37]),"=f"(d[38]),"=f"(d[39]),"=f"(d[40]),"=f"(d[41]),"=f"(d[42]),"=f"(d[43]),"=f"(d[44]),"=f"(d[45]),"=f"(d[46]),"=f"(d[47]),"=f"(d[48]),"=f"(d[49]),"=f"(d[50]),"=f"(d[51]),"=f"(d[52]),"=f"(d[53]),"=f"(d[54]),"=f"(d[55]),"=f"(d[56]),"=f"(d[57]),"=f"(d[58]),"=f"(d[59]),"=f"(d[60]),"=f"(d[61]),"=f"(d[62]),"=f"(d[63])
        : "r"(alo), "r"(ahi), "r"(blo), "r"(bhi));
}
__device__ __forceinline__ void wg_ss64(float (&d)[32], uint32_t alo, uint32_t ahi, uint32_t blo, uint32_t bhi) {
    asm volatile("{\n.reg .b64 da, db;\nmov.b64 da, {%32, %33};\nmov.b64 db, {%34, %35};\n"
        "wgmma.mma_async.sync.aligned.m64n64k16.f32.bf16.bf16 {%0,%1,%2,%3,%4,%5,%6,%7,%8,%9,%10,%11,%12,%13,%14,%15,%16,%17,%18,%19,%20,%21,%22,%23,%24,%25,%26,%27,%28,%29,%30,%31}, da, db, 1, 1, 1, 0, 1;\n}\n"
        : "+f"(d[0]),"+f"(d[1]),"+f"(d[2]),"+f"(d[3]),"+f"(d[4]),"+f"(d[5]),"+f"(d[6]),"+f"(d[7]),"+f"(d[8]),"+f"(d[9]),"+f"(d[10]),"+f"(d[11]),"+f"(d[12]),"+f"(d[13]),"+f"(d[14]),"+f"(d[15]),"+f"(d[16]),"+f"(d[17]),"+f"(d[18]),"+f"(d[19]),"+f"(d[20]),"+f"(d[21]),"+f"(d[22]),"+f"(d[23]),"+f"(d[24]),"+f"(d[25]),"+f"(d[26]),"+f"(d[27]),"+f"(d[28]),"+f"(d[29]),"+f"(d[30]),"+f"(d[31])
        : "r"(alo), "r"(ahi), "r"(blo), "r"(bhi));
}
__device__ __forceinline__ void wg_ss64_z(float (&d)[32], uint32_t alo, uint32_t ahi, uint32_t blo, uint32_t bhi) {
    asm volatile("{\n.reg .b64 da, db;\nmov.b64 da, {%32, %33};\nmov.b64 db, {%34, %35};\n"
        "wgmma.mma_async.sync.aligned.m64n64k16.f32.bf16.bf16 {%0,%1,%2,%3,%4,%5,%6,%7,%8,%9,%10,%11,%12,%13,%14,%15,%16,%17,%18,%19,%20,%21,%22,%23,%24,%25,%26,%27,%28,%29,%30,%31}, da, db, 0, 1, 1, 0, 1;\n}\n"
        : "=f"(d[0]),"=f"(d[1]),"=f"(d[2]),"=f"(d[3]),"=f"(d[4]),"=f"(d[5]),"=f"(d[6]),"=f"(d[7]),"=f"(d[8]),"=f"(d[9]),"=f"(d[10]),"=f"(d[11]),"=f"(d[12]),"=f"(d[13]),"=f"(d[14]),"=f"(d[15]),"=f"(d[16]),"=f"(d[17]),"=f"(d[18]),"=f"(d[19]),"=f"(d[20]),"=f"(d[21]),"=f"(d[22]),"=f"(d[23]),"=f"(d[24]),"=f"(d[25]),"=f"(d[26]),"=f"(d[27]),"=f"(d[28]),"=f"(d[29]),"=f"(d[30]),"=f"(d[31])
        : "r"(alo), "r"(ahi), "r"(blo), "r"(bhi));
}
__device__ __forceinline__ void wg_ss64t(float (&d)[32], uint32_t alo, uint32_t ahi, uint32_t blo, uint32_t bhi) {
    asm volatile("{\n.reg .b64 da, db;\nmov.b64 da, {%32, %33};\nmov.b64 db, {%34, %35};\n"
        "wgmma.mma_async.sync.aligned.m64n64k16.f32.bf16.bf16 {%0,%1,%2,%3,%4,%5,%6,%7,%8,%9,%10,%11,%12,%13,%14,%15,%16,%17,%18,%19,%20,%21,%22,%23,%24,%25,%26,%27,%28,%29,%30,%31}, da, db, 1, 1, 1, 1, 1;\n}\n"
        : "+f"(d[0]),"+f"(d[1]),"+f"(d[2]),"+f"(d[3]),"+f"(d[4]),"+f"(d[5]),"+f"(d[6]),"+f"(d[7]),"+f"(d[8]),"+f"(d[9]),"+f"(d[10]),"+f"(d[11]),"+f"(d[12]),"+f"(d[13]),"+f"(d[14]),"+f"(d[15]),"+f"(d[16]),"+f"(d[17]),"+f"(d[18]),"+f"(d[19]),"+f"(d[20]),"+f"(d[21]),"+f"(d[22]),"+f"(d[23]),"+f"(d[24]),"+f"(d[25]),"+f"(d[26]),"+f"(d[27]),"+f"(d[28]),"+f"(d[29]),"+f"(d[30]),"+f"(d[31])
        : "r"(alo), "r"(ahi), "r"(blo), "r"(bhi));
}
__device__ __forceinline__ void wg_ss64t_z(float (&d)[32], uint32_t alo, uint32_t ahi, uint32_t blo, uint32_t bhi) {
    asm volatile("{\n.reg .b64 da, db;\nmov.b64 da, {%32, %33};\nmov.b64 db, {%34, %35};\n"
        "wgmma.mma_async.sync.aligned.m64n64k16.f32.bf16.bf16 {%0,%1,%2,%3,%4,%5,%6,%7,%8,%9,%10,%11,%12,%13,%14,%15,%16,%17,%18,%19,%20,%21,%22,%23,%24,%25,%26,%27,%28,%29,%30,%31}, da, db, 0, 1, 1, 1, 1;\n}\n"
        : "=f"(d[0]),"=f"(d[1]),"=f"(d[2]),"=f"(d[3]),"=f"(d[4]),"=f"(d[5]),"=f"(d[6]),"=f"(d[7]),"=f"(d[8]),"=f"(d[9]),"=f"(d[10]),"=f"(d[11]),"=f"(d[12]),"=f"(d[13]),"=f"(d[14]),"=f"(d[15]),"=f"(d[16]),"=f"(d[17]),"=f"(d[18]),"=f"(d[19]),"=f"(d[20]),"=f"(d[21]),"=f"(d[22]),"=f"(d[23]),"=f"(d[24]),"=f"(d[25]),"=f"(d[26]),"=f"(d[27]),"=f"(d[28]),"=f"(d[29]),"=f"(d[30]),"=f"(d[31])
        : "r"(alo), "r"(ahi), "r"(blo), "r"(bhi));
}
__device__ __forceinline__ void wg_ss8t(float (&d)[4], uint32_t alo, uint32_t ahi, uint32_t blo, uint32_t bhi) {
    asm volatile("{\n.reg .b64 da, db;\nmov.b64 da, {%4, %5};\nmov.b64 db, {%6, %7};\n"
        "wgmma.mma_async.sync.aligned.m64n8k16.f32.bf16.bf16 {%0,%1,%2,%3}, da, db, 1, 1, 1, 1, 0;\n}\n"
        : "+f"(d[0]),"+f"(d[1]),"+f"(d[2]),"+f"(d[3])
        : "r"(alo), "r"(ahi), "r"(blo), "r"(bhi));
}
__device__ __forceinline__ void wg_ss8t_z(float (&d)[4], uint32_t alo, uint32_t ahi, uint32_t blo, uint32_t bhi) {
    asm volatile("{\n.reg .b64 da, db;\nmov.b64 da, {%4, %5};\nmov.b64 db, {%6, %7};\n"
        "wgmma.mma_async.sync.aligned.m64n8k16.f32.bf16.bf16 {%0,%1,%2,%3}, da, db, 0, 1, 1, 1, 0;\n}\n"
        : "=f"(d[0]),"=f"(d[1]),"=f"(d[2]),"=f"(d[3])
        : "r"(alo), "r"(ahi), "r"(blo), "r"(bhi));
}
__device__ __forceinline__ void wg_rs24_z(float (&d)[12], uint32_t a0, uint32_t a1, uint32_t a2, uint32_t a3, uint32_t blo, uint32_t bhi) {
    asm volatile("{\n.reg .b64 db;\nmov.b64 db, {%16, %17};\n"
        "wgmma.mma_async.sync.aligned.m64n24k16.f32.bf16.bf16 {%0,%1,%2,%3,%4,%5,%6,%7,%8,%9,%10,%11}, {%12,%13,%14,%15}, db, 0, 1, 1, 0;\n}\n"
        : "=f"(d[0]),"=f"(d[1]),"=f"(d[2]),"=f"(d[3]),"=f"(d[4]),"=f"(d[5]),"=f"(d[6]),"=f"(d[7]),"=f"(d[8]),"=f"(d[9]),"=f"(d[10]),"=f"(d[11])
        : "r"(a0), "r"(a1), "r"(a2), "r"(a3), "r"(blo), "r"(bhi));
}

constexpr uint32_t DH128 = 64u | 0x40000000u;
constexpr uint32_t DH64 = 32u | 0x80000000u;
constexpr uint32_t LBO4K = (4096u >> 4) << 16, LBO8K = (8192u >> 4) << 16, LBO1 = 1u << 16;

template <bool SW64, bool FIRST> __device__ __forceinline__ void g1_issue(float (&acc)[64], uint32_t alo, uint32_t blo) {
    wg_fence();
#pragma unroll
    for (int k = 0; k < 4; k++) {
        if (FIRST && k == 0) wg_ss128_z(acc, alo, DH128, blo, SW64 ? DH64 : DH128);
        else wg_ss128(acc, alo + 2 * k, DH128, blo + (SW64 ? 64 * k : 128 * k), SW64 ? DH64 : DH128);
    }
    wg_commit();
}

template <int N> __device__ __forceinline__ void stash(uint32_t base, uint32_t sw, const uint32_t (&f)[N]) {
#pragma unroll
    for (int t = 0; t < N / 4; t++) stsm4(base + ((sw ^ (2 * t)) << 4), f[4 * t], f[4 * t + 1], f[4 * t + 2], f[4 * t + 3]);
}

template <int V0, int V1, int N> __device__ __forceinline__ void send_frag(const uint32_t (&f)[N], uint4* p, uint32_t tag) {
#pragma unroll
    for (int v = V0; v < V1; v++) st_pkt(p + v * 32, (f[4 * v] & ~1u) | tag, f[4 * v + 1], f[4 * v + 2], f[4 * v + 3]);
}
template <int H0, int H1, int N> __device__ __forceinline__ void send_h(const uint32_t (&f)[N], uint4* p) {
#pragma unroll
    for (int h = H0; h < H1; h++) {
        p[4 * h] = make_uint4(f[8 * h], f[8 * h + 2], f[8 * h + 4], f[8 * h + 6]);
        p[4 * h + 64] = make_uint4(f[8 * h + 1], f[8 * h + 3], f[8 * h + 5], f[8 * h + 7]);
    }
}
template <int O, int N, int M> __device__ __forceinline__ void pack_sub(uint32_t (&f)[N], const float (&acc)[M]) {
#pragma unroll
    for (int i = 0; i < N; i++) f[i] = keep(pack2(acc[O + 2 * i], acc[O + 2 * i + 1]));
}
template <int N> __device__ __forceinline__ void recv_issue(uint32_t (&q)[N], const uint4* p) {
#pragma unroll
    for (int v = 0; v < N / 4; v++) ld_pkt(p + v * 32, q[4 * v], q[4 * v + 1], q[4 * v + 2], q[4 * v + 3]);
}
template <int N> __device__ __forceinline__ void recv_check(uint32_t (&q)[N], const uint4* p, uint32_t tag) {
    uint32_t it = 0;
    while (true) {
        uint32_t bad = 0;
#pragma unroll
        for (int v = 0; v < N / 4; v++) bad |= q[4 * v] ^ tag;
        if (__all_sync(0xffffffffu, (bad & 1u) == 0) || ++it > SPIN_GLOBAL) break;
        recv_issue(q, p);
    }
}
__device__ __forceinline__ void accum(const uint32_t (&q)[32], float (&sum)[64]) {
#pragma unroll
    for (int i = 0; i < 32; i++) { sum[2 * i] += bf_lo(q[i]); sum[2 * i + 1] += bf_hi(q[i]); }
}

}

__global__ void __launch_bounds__(384, 1)
fused_kernel(const __grid_constant__ Maps maps, const __nv_bfloat16* __restrict__ xg, const __nv_bfloat16* __restrict__ gate_w,
             const char* __restrict__ pf_qkv, const char* __restrict__ pf_g, const char* __restrict__ pf_u,
             const char* __restrict__ pf_d, const char* __restrict__ pf_o, __nv_bfloat16* __restrict__ out) {
    extern __shared__ __align__(1024) uint8_t smem_raw[];
    const uint32_t sb = (uint32_t)__cvta_generic_to_shared(smem_raw);
    const int tid = threadIdx.x, lane = tid & 31;
    const int warp = __shfl_sync(0xffffffffu, tid >> 5, 0);
    const int j = (blockIdx.x >> 1) & 7;
    const int r = ((blockIdx.x >> 4) << 1) | (blockIdx.x & 1);
    const uint32_t rank = blockIdx.x & 1;

    if (warp == 0) { TSG(0, 30); TS(0, 0); }
    if (tid == 256) {
        for (int i = 0; i < 5; i++) { mbar_init(sb + B_FULL + 8 * i, 1); mbar_init(sb + B_EMPTY + 8 * i, MC ? 4 : 2); }
        for (int i = 0; i < 9; i++) mbar_init(sb + B_XFULL + 8 * i, 1);
        asm volatile("fence.mbarrier_init.release.cluster;" ::: "memory");
        mbar_expect(sb + B_XFULL, 16384);
        tma2(sb + OFF_X, &maps.x, 0, r * 128, sb + B_XFULL);
        TS2(0);
        mbar_expect(sb + B_FULL, 16384);
        tmaw3(sb + OFF_RING, &maps.gu, 224 * j, 0, 0, sb + B_FULL);
        TS2(1);
        mbar_expect(sb + B_FULL + 8, 16384);
        tmaw3(sb + OFF_RING + 16384, &maps.kv, 64 * j, 0, 1, sb + B_FULL + 8);
    } else if (tid == 288) {
        for (int i = 0; i < 3; i++) mbar_init(sb + B_HSENT + 8 * i, 8);
        for (int i = 0; i < 4; i++) { mbar_init(sb + B_EFULL + 8 * i, 1); mbar_init(sb + B_EEMPTY + 8 * i, MC ? 4 : 2); }
        mbar_init(sb + B_XFREE, 2); mbar_init(sb + B_XFREE + 8, 2); mbar_init(sb + B_XFREE + 16, 2);
        mbar_init(sb + B_AHEAD, 1); mbar_init(sb + B_GRDY, 1); mbar_init(sb + B_KVDONE, 8); mbar_init(sb + B_KVRDY, 2);
        asm volatile("fence.mbarrier_init.release.cluster;" ::: "memory");
    } else if (warp == 10 && lane < 10) {
        asm volatile("prefetch.tensormap [%0];" :: "l"(&maps.gu + lane) : "memory");
    }
    __syncthreads();

    if (warp >= 8) {
        asm volatile("setmaxnreg.dec.sync.aligned.u32 56;");
        if (warp == 8) {
            if (lane == 0) {
                int slot = MC ? 0 : 2, ph = 1;
                uint32_t full, dst;
                if (!MC) { mbar_expect(sb + B_XFULL + 8, 16384); tma2(sb + OFF_X + 16384, &maps.x, 64, r * 128, sb + B_XFULL + 8); }
#define P_BEGIN(S, BYTES) full = sb + B_FULL + 8 * slot; dst = sb + OFF_RING + slot * 16384; \
                mbar_wait(sb + B_EMPTY + 8 * slot, ph); TS2(S); mbar_expect(full, BYTES); if (!MC || (((S) ^ rank) & 1) == 0)
#define P_END() if (++slot == 5) { slot = 0; ph ^= 1; }
                for (int s = MC ? 0 : 2; s < 16; s++) {
                    P_BEGIN(s, 16384) {
                        const int sw = s == 13 ? 14 : s == 14 ? 13 : s;
                        if (sw & 1) tmaw3(dst, &maps.kv, 64 * j, 32 * (sw - 1), 1, full);
                        else tmaw3(dst, &maps.gu, 224 * j, 32 * sw, 0, full);
                    }
                    const int xb = (s == 4) ? 3 : (s == 10) ? 7 : !(s & 1) ? 0 : (s < 5) ? (s + 1) / 2 : (s <= 9) ? (s + 3) / 2 : 0;
                    if (xb) { mbar_expect(sb + B_XFULL + 8 * xb, 16384); tma2(sb + OFF_X + xb * 16384, &maps.x, 64 * xb, r * 128, sb + B_XFULL + 8 * xb); }
                    P_END()
                }
                for (int s = 0; s < 24; s++) {
                    P_BEGIN(16 + s, 16384) {
                        if ((s >> 3) == 1) {
                            tmaw3(dst, &maps.q64, 0, 64 * (s & 7), 2 * j, full);
                            tmaw3(dst + 8192, &maps.gu64, 224 * j + 192, 64 * (s & 7), 0, full);
                        } else {
                            tmaw3(dst, &maps.gu, 224 * j + 64 + 4 * (s & 16), 64 * (s & 7), 0, full);
                        }
                    }
                    P_END()
                }
                const int p = j >> 1;
#pragma unroll 1
                for (int t = 0; t < 18; t++) {
                    const int u = (int)((t < 16 ? 0x2187658704653210ull >> (4 * t) : 0x43ull >> (4 * (t - 16))) & 15);
                    const int q = t >= 9, sl = t - 9 * q;
                    const int cw = (j & 1) * 4 + ((p & 2) ^ ((t == 7 || t > 9) ? 0 : 2)), cc = 64 * cw;
                    if (sl < 5) {
                        full = sb + B_FULL + 8 * sl; dst = sb + OFF_RING + sl * 16384;
                        mbar_wait(sb + B_EMPTY + 8 * sl, q ^ 1);
                    } else {
                        full = sb + B_EFULL + 8 * (sl - 5); dst = sb + OFF_X + (sl == 7 ? 8 : sl == 8 ? 7 : sl) * 16384;
                        mbar_wait(sb + B_EEMPTY + 8 * (sl - 5), q);
                    }
                    TS2(40 + t);
                    mbar_expect(full, 16384);
                    if (!MC || ((t ^ rank) & 1) == 0) {
                        if (u == 4) {
                            tmaw5(dst, &maps.wdph, cc, 14 * p + 6, full); tmaw5(dst + 4096, &maps.wdph, cc, 14 * p + 13, full);
                            tmaw5(dst + 8192, &maps.wdph, cc + 64, 14 * p + 6, full); tmaw5(dst + 12288, &maps.wdph, cc + 64, 14 * p + 13, full);
                        } else if (u > 4) {
                            const int js = u > 6 ? j ^ 1 : j;
                            tmaw3(dst, (u & 1) ? &maps.wow : &maps.wdw, 0, (u & 1) ? 64 * js : 224 * js + 128, cw, full);
                        } else {
                            const int g = 14 * p + 7 * (u & 1) + (u & 2);
                            tmaw5(dst, &maps.wdp, cc, g, full); tmaw5(dst + 8192, &maps.wdp, cc + 64, g, full);
                        }
                    }
                }
            }
        } else if (warp < 11) {
            const int hx = warp - 9;
            uint32_t epoch;
            asm volatile("ld.relaxed.gpu.global.u32 %0, [%1];" : "=r"(epoch) : "l"(g_epoch + blockIdx.x) : "memory");
            {
                const uint4* xr = (const uint4*)(xg + (size_t)(r * 128 + j * 16 + hx * 8) * kD) + lane;
                const uint4 wa = __ldg((const uint4*)gate_w + lane), wb = __ldg((const uint4*)gate_w + 32 + lane);
                const uint32_t tag = (epoch + 1) & 1;
                uint4* gp = g_gx + r * 32;
                if (lane < 2) st_pkt(gp + j * 4 + hx * 2 + lane, tag ^ 1, 0, 0, 0);
                float s[8];
#pragma unroll
                for (int i0 = 0; i0 < 8; i0 += 4) {
                    uint4 va[4], vb[4];
#pragma unroll
                    for (int i = 0; i < 4; i++) { va[i] = __ldg(xr + (i0 + i) * 64); vb[i] = __ldg(xr + (i0 + i) * 64 + 32); }
#pragma unroll
                    for (int i = 0; i < 4; i++) {
                        float t0 = bf_lo(va[i].x) * bf_lo(wa.x), t1 = bf_hi(va[i].x) * bf_hi(wa.x);
                        t0 = fmaf(bf_lo(va[i].y), bf_lo(wa.y), t0); t1 = fmaf(bf_hi(va[i].y), bf_hi(wa.y), t1);
                        t0 = fmaf(bf_lo(va[i].z), bf_lo(wa.z), t0); t1 = fmaf(bf_hi(va[i].z), bf_hi(wa.z), t1);
                        t0 = fmaf(bf_lo(va[i].w), bf_lo(wa.w), t0); t1 = fmaf(bf_hi(va[i].w), bf_hi(wa.w), t1);
                        t0 = fmaf(bf_lo(vb[i].x), bf_lo(wb.x), t0); t1 = fmaf(bf_hi(vb[i].x), bf_hi(wb.x), t1);
                        t0 = fmaf(bf_lo(vb[i].y), bf_lo(wb.y), t0); t1 = fmaf(bf_hi(vb[i].y), bf_hi(wb.y), t1);
                        t0 = fmaf(bf_lo(vb[i].z), bf_lo(wb.z), t0); t1 = fmaf(bf_hi(vb[i].z), bf_hi(wb.z), t1);
                        t0 = fmaf(bf_lo(vb[i].w), bf_lo(wb.w), t0); t1 = fmaf(bf_hi(vb[i].w), bf_hi(wb.w), t1);
                        s[i0 + i] = t0 + t1;
                    }
                }
#pragma unroll
                for (int i = 0; i < 8; i++) {
#pragma unroll
                    for (int o = 16; o; o >>= 1) s[i] += __shfl_xor_sync(0xffffffffu, s[i], o);
                    s[i] = 1.f / (1.f + __expf(-s[i]));
                }
                if (lane < 2) {
                    const float v0 = lane ? s[4] : s[0], v1 = lane ? s[5] : s[1], v2 = lane ? s[6] : s[2], v3 = lane ? s[7] : s[3];
                    st_pkt(gp + j * 4 + hx * 2 + lane, (__float_as_uint(v0) & ~1u) | tag, __float_as_uint(v1), __float_as_uint(v2), __float_as_uint(v3));
                }
                if (hx == 1) {
                    asm volatile("st.shared.u32 [%0], %1;" :: "r"(sb + OFF_ONES + lane * 4), "r"(0x3f803f80u) : "memory");
                    asm volatile("fence.proxy.async.shared::cta;" ::: "memory");
                }
                asm volatile("bar.sync 3, 96;" ::: "memory");
                if (hx == 0) {
                    uint32_t q[4];
                    recv_issue(q, gp + lane);
                    recv_check(q, gp + lane, tag);
                    asm volatile("st.shared.v4.u32 [%0], {%1,%2,%3,%4};" :: "r"(sb + OFF_G + lane * 16), "r"(q[0]), "r"(q[1]), "r"(q[2]), "r"(q[3]) : "memory");
                    if (lane == 0) {
                        asm volatile("st.shared.u32 [%0], %1;" :: "r"(sb + OFF_EPOCH), "r"(epoch) : "memory");
                        g_epoch[blockIdx.x] = epoch + 1;
                    }
                    __syncwarp();
                    if (lane == 0) mbar_arrive(sb + B_GRDY);
                } else {
                    if (r == 0) {
                        float4* zp = (float4*)(g_kvacc + (((epoch & 1) ^ 1) * 8 + j) * 4 * 272);
                        for (int i = lane; i < 272; i += 32) zp[i] = make_float4(0.f, 0.f, 0.f, 0.f);
                    }
                }
            }
            TS(2 + hx, 1);
#define PUBLISH_H(B) do { mbar_wait(sb + B_HSENT + 8 * (B), 0); if (lane == 0) { \
                asm volatile("st.release.gpu.global.u32 [%0], %1;" :: "l"(g_hflag + (r * 8 + j) * 8 + (B)), "r"(epoch + 1) : "memory"); } __syncwarp(); } while (0)
            if (hx == 1) {
#pragma unroll 1
                for (int b = 0; b < 3; b++) { PUBLISH_H(b); TS(3, 5 + b); }
            } else {
                const float* accp = g_kvacc + ((epoch & 1) * 8 + j) * 4 * 272;
                unsigned* cnt = g_kvcnt + j * 32;
                mbar_wait(sb + B_KVDONE, 0);
                TS(2, 5);
                if (lane == 0) asm volatile("red.release.gpu.global.add.u32 [%0], 1;" :: "l"(cnt) : "memory");
                __syncwarp();
                TS(2, 2);
                {
                    const unsigned target = 16u * (epoch + 1);
                    uint32_t it = 0, v;
                    do {
                        asm volatile("ld.acquire.gpu.global.u32 %0, [%1];" : "=r"(v) : "l"(cnt) : "memory");
                    } while ((int)(v - target) < 0 && ++it < SPIN_GLOBAL);
                }
                TS(2, 3);
#pragma unroll
                for (int h = 0; h < 4; h++) {
                    const float4 d0 = __ldcg((const float4*)(accp + h * 272) + lane);
                    const float4 d1 = __ldcg((const float4*)(accp + h * 272 + 128) + lane);
                    const float2 z0 = __ldcg((const float2*)(accp + h * 272 + 256) + (lane & 3));
                    const float2 z1 = __ldcg((const float2*)(accp + h * 272 + 264) + (lane & 3));
                    const uint32_t ba = sb + OFF_STG + h * 768 + lane * 4;
                    asm volatile("st.shared.u32 [%0], %1;" :: "r"(ba), "r"(pack2(d0.x, d0.y)) : "memory");
                    asm volatile("st.shared.u32 [%0], %1;" :: "r"(ba + 128), "r"(pack2(d1.x, d1.y)) : "memory");
                    asm volatile("st.shared.u32 [%0], %1;" :: "r"(ba + 256), "r"(pack2(d0.z, d0.w)) : "memory");
                    asm volatile("st.shared.u32 [%0], %1;" :: "r"(ba + 384), "r"(pack2(d1.z, d1.w)) : "memory");
                    asm volatile("st.shared.u32 [%0], %1;" :: "r"(ba + 512), "r"(pack2(z0.x, z0.y)) : "memory");
                    asm volatile("st.shared.u32 [%0], %1;" :: "r"(ba + 640), "r"(pack2(z1.x, z1.y)) : "memory");
                }
                asm volatile("fence.proxy.async.shared::cta;" ::: "memory");
                __syncwarp();
                if (lane == 0) mbar_arrive(sb + B_KVRDY);
                TS(2, 4);
            }
        } else {
            uint32_t epoch;
            asm volatile("ld.relaxed.gpu.global.u32 %0, [%1];" : "=r"(epoch) : "l"(g_epoch + blockIdx.x) : "memory");
            asm volatile("bar.arrive 3, 96;" :: "r"(epoch) : "memory");
            const int b = blockIdx.x, p = j >> 1;
            mbar_wait(sb + B_XFULL, 0);
#pragma unroll 1
            for (int kb = 1; kb < 8; kb++) {
                mbar_wait(sb + B_XFULL + 8 * kb, 0);
                const char* base = kb < 3 ? pf_g : kb < 5 ? pf_u : kb == 5 ? pf_qkv : pf_d;
                const int off = kb == 5 ? b * 12288 : b * 14336 + ((kb < 5 ? kb - 1 : kb) & 1) * 7168;
                asm volatile("prefetch.global.L2 [%0];" :: "l"(base + off + lane * 128));
                if (kb == 5 || lane < 24) asm volatile("prefetch.global.L2 [%0];" :: "l"(base + off + 4096 + lane * 128));
                if (kb == 5) asm volatile("prefetch.global.L2 [%0];" :: "l"(base + off + 8192 + lane * 128));
                if (kb == 7) asm volatile("prefetch.global.L2 [%0];" :: "l"(pf_o + b * 4096 + lane * 128));
            }
            {
                uint4* mb = g_part + (size_t)(r * 2 + (j & 1)) * 16384 + (((p ^ 1) * 4 + p) << 10) + lane;
#pragma unroll 1
                for (int i = 0; i < 32; i++) { st_pkt(mb + i * 32, epoch & 1, 0, 0, 0); __nanosleep(40); }
                __syncwarp();
                if (lane == 0) mbar_arrive(sb + B_KVRDY);
            }
            {
                const uint32_t want = epoch + 1;
                const int hrow = (r * 4 + p) * 5 * 128;
                const unsigned* fl = g_hflag + (r * 8 + (j & 6)) * 8 + (lane & 15);
                uint32_t it = 0;
                int i = 0;
                mbar_wait(sb + B_HSENT + 8, 0);
#pragma unroll 1
                while (i < 3 && ++it < SPIN_GLOBAL) {
                    uint32_t v;
                    asm volatile("ld.acquire.gpu.global.u32 %0, [%1];" : "=r"(v) : "l"(fl) : "memory");
                    const uint32_t rdy = __ballot_sync(0xffffffffu, v == want);
#pragma unroll 1
                    while (i < 3 && ((rdy >> i) & 0x101u) == 0x101u) {
                        mbar_wait(sb + B_XFREE + 8 * i, 0);
                        if (lane == 0) {
                            asm volatile("fence.proxy.async.global;" ::: "memory");
                            TS2(140 + i);
                            mbar_expect(sb + B_XFULL + 16 * i, i < 2 ? 32768 : 16384);
                            tma2(sb + OFF_X + i * 32768, i < 2 ? &maps.hx2 : &maps.hx, 0, hrow + i * 256, sb + B_XFULL + 16 * i);
                        }
                        i++;
                    }
                }
            }
        }
    } else {
        asm volatile("setmaxnreg.inc.sync.aligned.u32 224;");
        const int wg = warp >> 2;
        const bool elect = (tid & 127) == 0;
        const uint32_t xlo = ((sb + OFF_X + wg * 8192) >> 4) | LBO1;
        const uint32_t ringlo = (sb + OFF_RING) >> 4;
        auto release = [&](uint32_t bar) {
            if (elect) {
                mbar_arrive(sb + bar);
            }
        };
#define S_SL(S) ((S) < 40 ? (S) % 5 : ((S) - 40) % 9)
#define S_WAIT(S) do { mbar_wait(sb + (S_SL(S) < 5 ? B_FULL + 8 * S_SL(S) : B_EFULL + 8 * (S_SL(S) - 5)), (S) < 40 ? ((S) / 5) & 1 : (S) >= 49); \
            if (PROF && tid == 0) TS2(64 + (S)); } while (0)
#define S_B(S) (S_SL(S) < 5 ? ringlo + S_SL(S) * 1024 : ((sb + OFF_X) >> 4) + (S_SL(S) == 7 ? 8 : S_SL(S) == 8 ? 7 : S_SL(S)) * 1024)
#define S_REL(S) do { if ((S) < 49) release(S_SL(S) < 5 ? B_EMPTY + 8 * S_SL(S) : B_EEMPTY + 8 * (S_SL(S) - 5)); } while (0)
#define G1(S, acc, SW, KB) g1_issue<SW, (KB) == 0>(acc, xlo + (KB) * 1024, S_B(S) | (SW ? LBO4K : LBO8K))
#define RET(S) do { S_WAIT((S) + 1); wg_wait<1>(); S_REL((S) - 1); } while (0)
#define RET2(S) do { S_WAIT((S) + 1); wg_wait<2>(); S_REL((S) - 1); } while (0)
#define SCHED() mbar_wait(sb + B_GRDY, 0)
#define A2_SYNC() do { asm volatile("fence.proxy.async.shared::cta;" ::: "memory"); asm volatile("bar.sync %0, 128;" :: "r"(wg + 1) : "memory"); } while (0)
#define H_EPI(acc, F, I0, I1, OG, OU) _Pragma("unroll") for (int i = (I0); i < (I1); i++) \
            F[i] = keep(hmul2(pack2(acc[(OG) + 2 * i] * acc[(OU) + 2 * i], acc[(OG) + 2 * i + 1] * acc[(OU) + 2 * i + 1]), (i & 1) ? m_hi : m_lo))
#define PHI(acc, F, I0, I1) _Pragma("unroll") for (int i = (I0); i < (I1); i++) F[i] = keep(phi2(acc[2 * i], acc[2 * i + 1]))

        float a0[64], b0[64], a1[64], a2_[64], a3[64];
        mbar_wait(sb + B_XFULL, 0);
        S_WAIT(0); G1(0, a0, false, 0);
        if ((warp & 3) == 0) TS(wg, 1);
        S_WAIT(1); G1(1, b0, false, 0); RET(1);
#define C0(KB) mbar_wait(sb + B_XFULL + 8 * (KB), 0); if (PROF && tid == 0) TS2(128 + (KB)); \
        G1(2 * (KB), a0, false, KB); RET(2 * (KB)); G1(2 * (KB) + 1, b0, false, KB); RET(2 * (KB) + 1)
        C0(1); C0(2); C0(3); C0(4); C0(5);
        mbar_wait(sb + B_XFULL + 8 * 6, 0);
        G1(12, a0, false, 6); RET(12);
        mbar_wait(sb + B_XFULL + 8 * 7, 0);
        G1(13, a0, false, 7); RET(13);
        G1(14, b0, false, 6);
        mbar_wait(sb + B_GRDY, 0);
        float g_lo, g_hi;
        uint32_t tag;
        {
            const uint32_t ga = sb + OFF_G + (warp * 16 + (lane >> 2)) * 4;
            asm volatile("ld.shared.f32 %0, [%1];" : "=f"(g_lo) : "r"(ga) : "memory");
            asm volatile("ld.shared.f32 %0, [%1];" : "=f"(g_hi) : "r"(ga + 32) : "memory");
            asm volatile("ld.shared.u32 %0, [%1];" : "=r"(tag) : "r"(sb + OFF_EPOCH) : "memory");
        }
        float* const kvp = g_kvacc + (((tag & 1) * 8 + j) * 4 + (warp & 3)) * 272;
        tag = (tag + 1) & 1;
        const uint32_t m_lo = pack2(1.f - g_lo, 1.f - g_lo), m_hi = pack2(1.f - g_hi, 1.f - g_hi);
        const uint32_t lrow = ((lane & 7) + 8 * ((lane >> 3) & 1)) * 128;
        const uint32_t srow = (warp & 3) * 2048 + lrow;
        const uint32_t ssw = (lane >> 4) ^ (lane & 7);
        uint4* const hsend = g_hx + (size_t)((r * 4 + (j >> 1)) * 5 + (j & 1)) * 1024 + warp * 128 + (lane >> 2) * 8 + (lane & 3);
#define SENT_H(B) do { __syncwarp(); if (lane == 0) mbar_arrive(sb + B_HSENT + 8 * (B)); } while (0)
        RET(14);
        pin(a0);
        uint32_t fh0[16], fh1[16], fh2[16], fh3[8], fo[16];
        G1(15, b0, false, 7); SCHED(); H_EPI(a0, fh0, 0, 16, 0, 32); RET(15);
        if ((warp & 3) == 0) TS(wg, 2);

        float kv[32], zs[4];
        uint32_t pk[16], pv[16];
        const uint32_t stg = sb + OFF_STG + wg * 8192, stl = stg + (warp & 1) * 2048 + lrow;
        const uint32_t klo = (stg >> 4) | LBO1, vlo = klo + 256, olo = (sb + OFF_ONES) >> 4;
        G1(16, a1, false, 0); RET(16);
        pin(b0);
        G1(17, a1, false, 1); send_h<0, 1>(fh0, hsend); SCHED(); PHI(b0, pk, 0, 6); RET(17);
        G1(18, a1, false, 2); send_h<1, 2>(fh0, hsend); SENT_H(0); SCHED(); PHI(b0, pk, 6, 12); RET(18);
        G1(19, a1, false, 3); SCHED(); PHI(b0, pk, 12, 16); pack_sub<32>(pv, b0); RET(19);
#define KV_ROUND(Z) do { A2_SYNC(); wg_fence(); \
            wg_ss64t##Z(kv, vlo, DH128, klo, DH128); wg_ss64t(kv, vlo + 128, DH128, klo + 128, DH128); \
            wg_ss8t##Z(zs, klo, DH128, olo, 0); wg_ss8t(zs, klo + 128, DH128, olo, 0); wg_commit(); } while (0)
        G1(20, a1, false, 4); if (!(warp & 2)) { stash<16>(stl, ssw, pk); stash<16>(stl + 4096, ssw, pv); } RET(20);
        G1(21, a1, false, 5); KV_ROUND(_z); RET2(21);
        G1(22, a1, false, 6); RET(22);
        G1(23, a1, false, 7); if (warp & 2) { stash<16>(stl, ssw, pk); stash<16>(stl + 4096, ssw, pv); } RET(23);
        if ((warp & 3) == 0) TS(wg, 3);

        G1(24, a2_, true, 0); KV_ROUND(); RET2(24);
        pin(a1);
        G1(25, a2_, true, 1); RET(25);
        pin(kv); pin(zs);
        G1(26, a2_, true, 2);
#define KV_RED(W) do { asm volatile("red.global.add.v4.f32 [%0], {%1,%2,%3,%4};" :: "l"(kvp + lane * 4), "f"(kv[8 * W]), "f"(kv[8 * W + 1]), "f"(kv[8 * W + 2]), "f"(kv[8 * W + 3]) : "memory"); \
                       asm volatile("red.global.add.v4.f32 [%0], {%1,%2,%3,%4};" :: "l"(kvp + 128 + lane * 4), "f"(kv[8 * W + 4]), "f"(kv[8 * W + 5]), "f"(kv[8 * W + 6]), "f"(kv[8 * W + 7]) : "memory"); } while (0)
        if ((warp & 3) == 0) KV_RED(0); else if ((warp & 3) == 1) KV_RED(1); else if ((warp & 3) == 2) KV_RED(2); else KV_RED(3);
        if ((lane & 3) == 0) {
            asm volatile("red.global.add.f32 [%0], %1;" :: "l"(kvp + 256 + (lane >> 2)), "f"(zs[0]) : "memory");
            asm volatile("red.global.add.f32 [%0], %1;" :: "l"(kvp + 264 + (lane >> 2)), "f"(zs[2]) : "memory");
        }
        __syncwarp();
        if (lane == 0) mbar_arrive(sb + B_KVDONE);
        RET(26);
        G1(27, a2_, true, 3); SCHED(); H_EPI(a1, fh1, 0, 16, 0, 32); RET(27);
        G1(28, a2_, true, 4); RET(28);
        G1(29, a2_, true, 5); RET(29);
        G1(30, a2_, true, 6); send_h<0, 1>(fh1, hsend + 2 * 1024); RET(30);
        G1(31, a2_, true, 7); send_h<1, 2>(fh1, hsend + 2 * 1024); SENT_H(1); RET(31);
        if ((warp & 3) == 0) TS(wg, 4);

        float on[4][12];
#define O_SCALE(h) do { const float s_lo = __fdividef(g_lo, on[h][8] + 1e-6f), s_hi = __fdividef(g_hi, on[h][10] + 1e-6f); \
            const uint32_t sl_ = pack2(s_lo, s_lo), sh_ = pack2(s_hi, s_hi); \
            fo[4 * h] = hmul2(pack2(on[h][0], on[h][1]), sl_); fo[4 * h + 1] = hmul2(pack2(on[h][2], on[h][3]), sh_); \
            fo[4 * h + 2] = hmul2(pack2(on[h][4], on[h][5]), sl_); fo[4 * h + 3] = hmul2(pack2(on[h][6], on[h][7]), sh_); } while (0)
        G1(32, a3, false, 0); RET(32);
        pin(a2_);
        G1(33, a3, false, 1); SCHED(); H_EPI(a2_, fh3, 0, 8, 32, 48);
        send_h<0, 1>(fh3, hsend + 4 * 1024 - (j & 1) * 1020); SENT_H(2); PHI(a2_, fo, 0, 2); RET(33);
        G1(34, a3, false, 2); SCHED(); PHI(a2_, fo, 2, 7); RET(34);
        if (elect) mbar_arrive(sb + B_XFREE);
        G1(35, a3, false, 3); SCHED(); PHI(a2_, fo, 7, 12); RET(35);
        G1(36, a3, false, 4); SCHED(); PHI(a2_, fo, 12, 16); RET(36);
        if (elect) mbar_arrive(sb + B_XFREE + 8);
        G1(37, a3, false, 5);
        if ((warp & 3) == 0) TS(wg, 5);
        mbar_wait(sb + B_KVRDY, 0);
        if ((warp & 3) == 0) TS(wg, 6);
        wg_fence();
#pragma unroll
        for (int h = 0; h < 4; h++)
            wg_rs24_z(on[h], fo[4 * h], fo[4 * h + 1], fo[4 * h + 2], fo[4 * h + 3], (((sb + OFF_STG) >> 4) + h * 48) | (8u << 16), 16u);
        wg_commit();
        RET2(37);
        if (elect) mbar_arrive(sb + B_XFREE + 16);
        G1(38, a3, false, 6); RET(38);
        release(B_EEMPTY); release(B_EEMPTY + 16);
        pin(on[0]); pin(on[1]); pin(on[2]); pin(on[3]);
        uint4* const lsend = g_lx + (size_t)(r * 8 + j) * 2048 + warp * 128 + lane;
        const uint4* const lrecv = g_lx + (size_t)(r * 8 + (j ^ 1)) * 2048 + warp * 128 + lane;
        G1(39, a3, false, 7); SCHED();
        O_SCALE(0); O_SCALE(1); send_frag<0, 2>(fo, lsend, tag);
        O_SCALE(2); O_SCALE(3);
        RET(39);
        release(B_EEMPTY + 8);
        if ((warp & 3) == 0) TS(wg, 7);

#define G2S(S, acc, U) do { wg_fence(); _Pragma("unroll") for (int k = 0; k < 4; k++) { \
            if (((S) == 40 || (S) == 47) && k == 0) wg_ss128_z(acc, xlo, DH128, S_B(S) | LBO8K, DH128); \
            else wg_ss128(acc, xlo + (U) * 1024 + 2 * k, DH128, (S_B(S) | LBO8K) + 128 * k, DH128); } wg_commit(); } while (0)
#define G2R(S, acc, F) do { wg_fence(); _Pragma("unroll") for (int k = 0; k < 4; k++) { \
            wg_rs128(acc, F[4 * k], F[4 * k + 1], F[4 * k + 2], F[4 * k + 3], (S_B(S) | LBO8K) + 128 * k, DH128); } wg_commit(); } while (0)
#define H_WAIT(P) do { mbar_wait(sb + B_XFULL + 8 * (P), 1); if (PROF && tid == 0) TS2(150 + (P)); } while (0)
        const int p = j >> 1, pw = (p & 2) ^ 2;
        const bool own = wg == (p & 1);
        uint4* const pbase = g_part + (size_t)(r * 2 + (j & 1)) * 16384 + (warp & 3) * 256 + lane;

        float p1[64], p2[64];
        uint32_t po[16], ph2[16];
        H_WAIT(0); G2S(40, p1, 0); send_frag<2, 4>(fo, lsend, tag); RET(40);
        release(B_EEMPTY + 24);
        pin(a3);
        G2S(41, p1, 1); SCHED(); H_EPI(a3, fh2, 0, 16, 0, 32); send_frag<0, 2>(fh2, lsend + 1024, tag); RET(41);
        H_WAIT(2); G2S(42, p1, 2); send_frag<2, 4>(fh2, lsend + 1024, tag); RET(42);
        G2S(43, p1, 3); RET(43);
        G2R(44, p1, fo); RET(44);
        G2R(45, p1, fh2); recv_issue(po, lrecv); RET(45);
        H_WAIT(4); G2S(46, p1, 4); recv_issue(ph2, lrecv + 1024); RET(46);
        G2S(47, p2, 0); SCHED(); recv_check(po, lrecv, tag); RET(47);
        G2R(48, p1, po); SCHED(); recv_check(ph2, lrecv + 1024, tag); RET(48);
        G2R(49, p1, ph2); RET(49);
        if ((warp & 3) == 0) TS(wg, 8);
        uint32_t sp[32], qa[32], qb[32];
        uint4* const s1 = pbase + (((pw + wg) * 4 + p) << 10);
        G2R(50, p2, fo); RET(50);
        pin(p1);
        G2R(51, p2, fh2); SCHED(); pack_sub<0>(sp, p1); send_frag<0, 2>(sp, s1, tag); RET(51);
        G2R(52, p2, po); send_frag<2, 5>(sp, s1, tag); RET(52);
        G2R(53, p2, ph2); send_frag<5, 8>(sp, s1, tag); RET(53);
        const uint4* ra = pbase + ((p * 4 + pw) << 10);
        const uint4* rc = pbase + ((p * 4 + (p ^ 1)) << 10);
        if (own) { mbar_wait(sb + B_AHEAD, 0); recv_issue(qa, ra); recv_issue(qb, ra + 1024); }
        G2S(54, p2, 1); RET(54);
        G2S(55, p2, 2); RET(55);
        G2S(56, p2, 3); RET(56);
        G2S(57, p2, 4);
        if ((warp & 3) == 0) TS(wg, 9);
        if (!own) {
            if (elect) mbar_arrive(sb + B_AHEAD);
        } else {
            recv_check(qa, ra, tag); recv_check(qb, ra + 1024, tag);
            recv_issue(sp, rc);
        }
        wg_wait<0>();
        pin(p2);
        if ((warp & 3) == 0) TS(wg, 11);
        if (!own) {
            pack_sub<0>(sp, p2); send_frag<0, 8>(sp, pbase + (((p ^ 1) * 4 + p) << 10), tag);
        } else {
            accum(qa, p2); accum(qb, p2);
            if ((warp & 3) == 0) TS(wg, 12);
            recv_check(sp, rc, tag); accum(sp, p2);
            if ((warp & 3) == 0) TS(wg, 13);
            uint32_t f0[16], f1[16];
            pack_sub<0>(f0, p2); pack_sub<32>(f1, p2);
            const uint32_t slab = sb + OFF_X + 2 * 16384 + wg * 8192;
            stash<16>(slab + srow, ssw, f0); stash<16>(slab + 16384 + srow, ssw, f1);
            __syncwarp();
            __nv_bfloat16* op = out + (size_t)(r * 128 + warp * 16 + (lane >> 4)) * kD + (j & 1) * 256 + (p & 2) * 64 + (lane & 15) * 8;
#pragma unroll
            for (int i = 0; i < 8; i++) {
                const int row = i * 2 + (lane >> 4);
                uint4 v;
                asm volatile("ld.shared.v4.u32 {%0,%1,%2,%3}, [%4];" : "=r"(v.x), "=r"(v.y), "=r"(v.z), "=r"(v.w)
                             : "r"(slab + (lane & 8) * 2048 + ((warp & 3) * 16 + row) * 128 + (((lane & 7) ^ (row & 7)) << 4)) : "memory");
                *(uint4*)(op + i * 2 * kD) = v;
            }
        }
        if ((warp & 3) == 0) { TS(wg, 14); TSG(wg, 31); }
    }
}

typedef CUresult (*EncodeFn)(CUtensorMap*, CUtensorMapDataType, cuuint32_t, void*, const cuuint64_t*, const cuuint64_t*, const cuuint32_t*,
                             const cuuint32_t*, CUtensorMapInterleave, CUtensorMapSwizzle, CUtensorMapL2promotion, CUtensorMapFloatOOBfill);

static void encode(EncodeFn fn, CUtensorMap* m, int rank, const void* base, const cuuint64_t (&gd)[5], const cuuint64_t (&gs)[4],
                   const cuuint32_t (&bd)[5], CUtensorMapSwizzle sw) {
    cuuint32_t es[5] = {1, 1, 1, 1, 1};
    fn(m, CU_TENSOR_MAP_DATA_TYPE_BFLOAT16, rank, const_cast<void*>(base), gd, gs, bd, es, CU_TENSOR_MAP_INTERLEAVE_NONE, sw,
       CU_TENSOR_MAP_L2_PROMOTION_L2_128B, CU_TENSOR_MAP_FLOAT_OOB_FILL_NONE);
}

extern "C" void kernel_launch(void* const* d_in, const int* in_sizes, int n_in, void* d_out, int out_size) {
    const char* x = (const char*)d_in[0];
    const char* wqkv = (const char*)d_in[1];
    const char* wo = (const char*)d_in[2];
    const char* wg = (const char*)d_in[4];
    const char* wu = (const char*)d_in[5];
    const char* wd = (const char*)d_in[6];
    void* fnp = nullptr;
    cudaDriverEntryPointQueryResult qr;
    cudaGetDriverEntryPoint("cuTensorMapEncodeTiled", &fnp, cudaEnableDefault, &qr);
    EncodeFn fn = (EncodeFn)fnp;
    Maps maps;
    const char* lo = wg < wu ? wg : wu;
    const uint64_t diff = wg < wu ? (uint64_t)(wu - wg) : (uint64_t)(wg - wu);
    const CUtensorMapSwizzle S128 = CU_TENSOR_MAP_SWIZZLE_128B, S64 = CU_TENSOR_MAP_SWIZZLE_64B;
    encode(fn, &maps.x, 2, x, {512, 2048, 1, 1}, {1024, 0, 0}, {64, 128, 1, 1}, S128);
    encode(fn, &maps.gu, 3, lo, {1792, 512, 2, 1}, {3584, diff, 0}, {64, 64, 2, 1}, S128);
    encode(fn, &maps.kv, 3, wqkv, {512, 512, 3, 1}, {3072, 1024, 0}, {64, 64, 2, 1}, S128);
    encode(fn, &maps.q64, 3, wqkv, {32, 512, 48, 1}, {3072, 64, 0}, {32, 64, 2, 1}, S64);
    encode(fn, &maps.gu64, 3, lo, {1792, 512, 2, 1}, {3584, diff, 0}, {32, 64, 2, 1}, S64);
    encode(fn, &maps.wdw, 3, wd, {64, 1792, 8, 1}, {1024, 128, 0}, {64, 64, 2, 1}, S128);
    encode(fn, &maps.wow, 3, wo, {64, 512, 8}, {1024, 128}, {64, 64, 2}, S128);
    encode(fn, &maps.wdp, 5, wd, {512, 2, 4, 4, 56}, {1024, 8192, 2048, 32768}, {64, 2, 4, 4, 2}, S128);
    encode(fn, &maps.wdph, 5, wd, {512, 2, 4, 4, 56}, {1024, 8192, 2048, 32768}, {64, 2, 4, 4, 1}, S128);
    void* hx = nullptr;
    cudaGetSymbolAddress(&hx, g_hx);
    encode(fn, &maps.hx, 2, hx, {64, 16 * 4 * 5 * 128}, {128}, {64, 128}, S128);
    encode(fn, &maps.hx2, 2, hx, {64, 16 * 4 * 5 * 128}, {128}, {64, 256}, S128);
    cudaFuncSetAttribute(fused_kernel, cudaFuncAttributeMaxDynamicSharedMemorySize, SMEM_BYTES);
    cudaLaunchConfig_t cfg = {};
    cfg.gridDim = dim3(128);
    cfg.blockDim = dim3(384);
    cfg.dynamicSmemBytes = SMEM_BYTES;
    cfg.stream = cudaStreamPerThread;
    cudaLaunchAttribute at[1];
    at[0].id = cudaLaunchAttributeClusterDimension;
    at[0].val.clusterDim.x = 2; at[0].val.clusterDim.y = 1; at[0].val.clusterDim.z = 1;
    cfg.attrs = at;
    cfg.numAttrs = MC ? 1 : 0;
    cudaLaunchKernelEx(&cfg, fused_kernel, maps, (const __nv_bfloat16*)d_in[0], (const __nv_bfloat16*)d_in[7], wqkv, wg, wu, wd, wo, (__nv_bfloat16*)d_out);
}
```

```cpp
#include <cuda_runtime.h>
#include <cuda.h>
#include <cuda_bf16.h>
#include <stdint.h>

#define MC 0
#define PFMODE 1
#define PAUSE_NS 200
#define PROF 0

namespace {

constexpr int kD = 512;
constexpr uint32_t OFF_X = 0, OFF_STG = 131072, OFF_RING = 147456, OFF_MISC = 229376;
constexpr uint32_t B_FULL = OFF_MISC, B_EMPTY = OFF_MISC + 40, B_XFULL = OFF_MISC + 80;
constexpr uint32_t B_GRDY = OFF_MISC + 152, B_KVDONE = OFF_MISC + 160, B_KVRDY = OFF_MISC + 168;
constexpr uint32_t B_HSENT = OFF_MISC + 176, B_XFREE = OFF_MISC + 200;
constexpr uint32_t OFF_EPOCH = OFF_MISC + 240, OFF_G = OFF_MISC + 256;
constexpr uint32_t B_AHEAD = OFF_MISC + 248;
constexpr uint32_t OFF_ONES = OFF_MISC + 768;
constexpr uint32_t B_EFULL = OFF_MISC + 896, B_EEMPTY = OFF_MISC + 928;
constexpr uint32_t SMEM_BYTES = OFF_MISC + 960;
constexpr uint32_t SPIN_GLOBAL = 1u << 14;

struct alignas(64) Maps { CUtensorMap x, gu, kv, q64, gu64, wdw, wow, wdp, wdph, hx, hx2; };

}

__device__ uint4 g_part[16 * 2 * 4 * 4 * 1024];
__device__ uint4 g_hx[16 * 4 * 5 * 1024];
__device__ uint4 g_lx[16 * 8 * 2 * 1024];
__device__ unsigned g_hflag[128 * 8];
__device__ uint4 g_gx[16 * 32];
__device__ float g_kvacc[2 * 8 * 4 * 272];
__device__ unsigned g_kvcnt[8 * 32];
__device__ unsigned g_epoch[128];
#define TS(role, idx)
#define TS2(idx)
#define TSG(role, idx)

namespace {

__device__ __forceinline__ void mbar_init(uint32_t bar, uint32_t cnt) { asm volatile("mbarrier.init.shared::cta.b64 [%0], %1;" :: "r"(bar), "r"(cnt) : "memory"); }
__device__ __forceinline__ void mbar_expect(uint32_t bar, uint32_t bytes) { asm volatile("mbarrier.arrive.expect_tx.shared::cta.b64 _, [%0], %1;" :: "r"(bar), "r"(bytes) : "memory"); }
__device__ __forceinline__ void mbar_arrive(uint32_t bar) { asm volatile("mbarrier.arrive.shared::cta.b64 _, [%0];" :: "r"(bar) : "memory"); }
__device__ __forceinline__ void mbar_arrive_cta(uint32_t bar, uint32_t cta) {
    asm volatile("{\n.reg .b32 ra;\nmapa.shared::cluster.u32 ra, %0, %1;\nmbarrier.arrive.shared::cluster.b64 _, [ra];\n}" :: "r"(bar), "r"(cta) : "memory");
}
__device__ __forceinline__ void mbar_wait(uint32_t bar, uint32_t parity) {
    asm volatile("{\n.reg .pred p;\n.reg .u32 c;\n"
                 "mbarrier.try_wait.parity.shared::cta.b64 p, [%0], %1;\n@p bra DONE;\n"
                 "mov.u32 c, 0;\nLAB_WAIT:\nmbarrier.try_wait.parity.shared::cta.b64 p, [%0], %1;\n@p bra DONE;\n"
                 "add.u32 c, c, 1;\nsetp.lt.u32 p, c, 65536;\n@p bra LAB_WAIT;\nDONE:\n}" :: "r"(bar), "r"(parity) : "memory");
}
__device__ __forceinline__ void tma2(uint32_t dst, const CUtensorMap* m, int c0, int c1, uint32_t bar) {
    asm volatile("cp.async.bulk.tensor.2d.shared::cluster.global.mbarrier::complete_tx::bytes [%0], [%1, {%3, %4}], [%2];"
        :: "r"(dst), "l"(m), "r"(bar), "r"(c0), "r"(c1) : "memory");
}
__device__ __forceinline__ void tmaw2(uint32_t dst, const CUtensorMap* m, int c0, int c1, uint32_t bar) {
    tma2(dst, m, c0, c1, bar);
}
__device__ __forceinline__ void tmaw3(uint32_t dst, const CUtensorMap* m, int c0, int c1, int c2, uint32_t bar) {
    asm volatile("cp.async.bulk.tensor.3d.shared::cluster.global.mbarrier::complete_tx::bytes [%0], [%1, {%3, %4, %5}], [%2];"
        :: "r"(dst), "l"(m), "r"(bar), "r"(c0), "r"(c1), "r"(c2) : "memory");
}
__device__ __forceinline__ void tmaw5(uint32_t dst, const CUtensorMap* m, int c0, int c4, uint32_t bar) {
    asm volatile("cp.async.bulk.tensor.5d.shared::cluster.global.mbarrier::complete_tx::bytes [%0], [%1, {%3, %5, %5, %5, %4}], [%2];"
        :: "r"(dst), "l"(m), "r"(bar), "r"(c0), "r"(c4), "r"(0) : "memory");
}
__device__ __forceinline__ void wg_fence() { asm volatile("wgmma.fence.sync.aligned;" ::: "memory"); }
__device__ __forceinline__ void wg_commit() { asm volatile("wgmma.commit_group.sync.aligned;" ::: "memory"); }
template <int N> __device__ __forceinline__ void wg_wait() { asm volatile("wgmma.wait_group.sync.aligned %0;" :: "n"(N) : "memory"); }
template <int N> __device__ __forceinline__ void pin(float (&d)[N]) {
#pragma unroll
    for (int i = 0; i < N; i++) asm volatile("" : "+f"(d[i]) :: "memory");
}
__device__ __forceinline__ uint32_t pack2(float lo, float hi) { uint32_t r; asm("cvt.rn.bf16x2.f32 %0, %1, %2;" : "=r"(r) : "f"(hi), "f"(lo)); return r; }
__device__ __forceinline__ uint32_t keep(uint32_t v) { asm volatile("" : "+r"(v)); return v; }
__device__ __forceinline__ uint32_t hmul2(uint32_t a, uint32_t b) { uint32_t r; asm("mul.bf16x2 %0, %1, %2;" : "=r"(r) : "r"(a), "r"(b)); return r; }
__device__ __forceinline__ uint32_t phi2(float t0, float t1) {
    float e0, e1;
    asm("ex2.approx.ftz.f32 %0, %1;" : "=f"(e0) : "f"(t0 * 1.4426950408889634f));
    asm("ex2.approx.ftz.f32 %0, %1;" : "=f"(e1) : "f"(t1 * 1.4426950408889634f));
    uint32_t e = pack2(e0, e1), t = pack2(t0, t1), r;
    asm("min.bf16x2 %0, %0, %1;" : "+r"(e) : "r"(0x3f803f80u));
    asm("max.bf16x2 %0, %0, %1;" : "+r"(t) : "r"(0x35863586u));
    asm("add.bf16x2 %0, %1, %2;" : "=r"(r) : "r"(e), "r"(t));
    return r;
}
__device__ __forceinline__ void stsm4(uint32_t a, uint32_t r0, uint32_t r1, uint32_t r2, uint32_t r3) {
    asm volatile("stmatrix.sync.aligned.m8n8.x4.shared.b16 [%0], {%1,%2,%3,%4};" :: "r"(a), "r"(r0), "r"(r1), "r"(r2), "r"(r3) : "memory");
}
__device__ __forceinline__ float bf_lo(uint32_t w) { return __uint_as_float(w << 16); }
__device__ __forceinline__ float bf_hi(uint32_t w) { return __uint_as_float(w & 0xffff0000u); }
__device__ __forceinline__ void st_pkt(uint4* p, uint32_t w0, uint32_t w1, uint32_t w2, uint32_t w3) {
    asm volatile("{\n.reg .b64 lo, hi;\n.reg .b128 v;\nmov.b64 lo, {%1, %2};\nmov.b64 hi, {%3, %4};\nmov.b128 v, {lo, hi};\nst.relaxed.gpu.global.b128 [%0], v;\n}"
        :: "l"(p), "r"(w0), "r"(w1), "r"(w2), "r"(w3) : "memory");
}
__device__ __forceinline__ void ld_pkt(const uint4* p, uint32_t& w0, uint32_t& w1, uint32_t& w2, uint32_t& w3) {
    asm volatile("{\n.reg .b64 lo, hi;\n.reg .b128 v;\nld.relaxed.gpu.global.b128 v, [%4];\nmov.b128 {lo, hi}, v;\nmov.b64 {%0, %1}, lo;\nmov.b64 {%2, %3}, hi;\n}"
        : "=r"(w0), "=r"(w1), "=r"(w2), "=r"(w3) : "l"(p) : "memory");
}

__device__ __forceinline__ void wg_rs128(float (&d)[64], uint32_t a0, uint32_t a1, uint32_t a2, uint32_t a3, uint32_t blo, uint32_t bhi) {
    asm volatile("{\n.reg .b64 db;\nmov.b64 db, {%68, %69};\n"
        "wgmma.mma_async.sync.aligned.m64n128k16.f32.bf16.bf16 {%0,%1,%2,%3,%4,%5,%6,%7,%8,%9,%10,%11,%12,%13,%14,%15,%16,%17,%18,%19,%20,%21,%22,%23,%24,%25,%26,%27,%28,%29,%30,%31,%32,%33,%34,%35,%36,%37,%38,%39,%40,%41,%42,%43,%44,%45,%46,%47,%48,%49,%50,%51,%52,%53,%54,%55,%56,%57,%58,%59,%60,%61,%62,%63}, {%64,%65,%66,%67}, db, 1, 1, 1, 1;\n}\n"
        : "+f"(d[0]),"+f"(d[1]),"+f"(d[2]),"+f"(d[3]),"+f"(d[4]),"+f"(d[5]),"+f"(d[6]),"+f"(d[7]),"+f"(d[8]),"+f"(d[9]),"+f"(d[10]),"+f"(d[11]),"+f"(d[12]),"+f"(d[13]),"+f"(d[14]),"+f"(d[15]),"+f"(d[16]),"+f"(d[17]),"+f"(d[18]),"+f"(d[19]),"+f"(d[20]),"+f"(d[21]),"+f"(d[22]),"+f"(d[23]),"+f"(d[24]),"+f"(d[25]),"+f"(d[26]),"+f"(d[27]),"+f"(d[28]),"+f"(d[29]),"+f"(d[30]),"+f"(d[31]),"+f"(d[32]),"+f"(d[33]),"+f"(d[34]),"+f"(d[35]),"+f"(d[36]),"+f"(d[37]),"+f"(d[38]),"+f"(d[39]),"+f"(d[40]),"+f"(d[41]),"+f"(d[42]),"+f"(d[43]),"+f"(d[44]),"+f"(d[45]),"+f"(d[46]),"+f"(d[47]),"+f"(d[48]),"+f"(d[49]),"+f"(d[50]),"+f"(d[51]),"+f"(d[52]),"+f"(d[53]),"+f"(d[54]),"+f"(d[55]),"+f"(d[56]),"+f"(d[57]),"+f"(d[58]),"+f"(d[59]),"+f"(d[60]),"+f"(d[61]),"+f"(d[62]),"+f"(d[63])
        : "r"(a0), "r"(a1), "r"(a2), "r"(a3), "r"(blo), "r"(bhi));
}
__device__ __forceinline__ void wg_ss128(float (&d)[64], uint32_t alo, uint32_t ahi, uint32_t blo, uint32_t bhi) {
    asm volatile("{\n.reg .b64 da, db;\nmov.b64 da, {%64, %65};\nmov.b64 db, {%66, %67};\n"
        "wgmma.mma_async.sync.aligned.m64n128k16.f32.bf16.bf16 {%0,%1,%2,%3,%4,%5,%6,%7,%8,%9,%10,%11,%12,%13,%14,%15,%16,%17,%18,%19,%20,%21,%22,%23,%24,%25,%26,%27,%28,%29,%30,%31,%32,%33,%34,%35,%36,%37,%38,%39,%40,%41,%42,%43,%44,%45,%46,%47,%48,%49,%50,%51,%52,%53,%54,%55,%56,%57,%58,%59,%60,%61,%62,%63}, da, db, 1, 1, 1, 0, 1;\n}\n"
        : "+f"(d[0]),"+f"(d[1]),"+f"(d[2]),"+f"(d[3]),"+f"(d[4]),"+f"(d[5]),"+f"(d[6]),"+f"(d[7]),"+f"(d[8]),"+f"(d[9]),"+f"(d[10]),"+f"(d[11]),"+f"(d[12]),"+f"(d[13]),"+f"(d[14]),"+f"(d[15]),"+f"(d[16]),"+f"(d[17]),"+f"(d[18]),"+f"(d[19]),"+f"(d[20]),"+f"(d[21]),"+f"(d[22]),"+f"(d[23]),"+f"(d[24]),"+f"(d[25]),"+f"(d[26]),"+f"(d[27]),"+f"(d[28]),"+f"(d[29]),"+f"(d[30]),"+f"(d[31]),"+f"(d[32]),"+f"(d[33]),"+f"(d[34]),"+f"(d[35]),"+f"(d[36]),"+f"(d[37]),"+f"(d[38]),"+f"(d[39]),"+f"(d[40]),"+f"(d[41]),"+f"(d[42]),"+f"(d[43]),"+f"(d[44]),"+f"(d[45]),"+f"(d[46]),"+f"(d[47]),"+f"(d[48]),"+f"(d[49]),"+f"(d[50]),"+f"(d[51]),"+f"(d[52]),"+f"(d[53]),"+f"(d[54]),"+f"(d[55]),"+f"(d[56]),"+f"(d[57]),"+f"(d[58]),"+f"(d[59]),"+f"(d[60]),"+f"(d[61]),"+f"(d[62]),"+f"(d[63])
        : "r"(alo), "r"(ahi), "r"(blo), "r"(bhi));
}
__device__ __forceinline__ void wg_ss128_z(float (&d)[64], uint32_t alo, uint32_t ahi, uint32_t blo, uint32_t bhi) {
    asm volatile("{\n.reg .b64 da, db;\nmov.b64 da, {%64, %65};\nmov.b64 db, {%66, %67};\n"
        "wgmma.mma_async.sync.aligned.m64n128k16.f32.bf16.bf16 {%0,%1,%2,%3,%4,%5,%6,%7,%8,%9,%10,%11,%12,%13,%14,%15,%16,%17,%18,%19,%20,%21,%22,%23,%24,%25,%26,%27,%28,%29,%30,%31,%32,%33,%34,%35,%36,%37,%38,%39,%40,%41,%42,%43,%44,%45,%46,%47,%48,%49,%50,%51,%52,%53,%54,%55,%56,%57,%58,%59,%60,%61,%62,%63}, da, db, 0, 1, 1, 0, 1;\n}\n"
        : "=f"(d[0]),"=f"(d[1]),"=f"(d[2]),"=f"(d[3]),"=f"(d[4]),"=f"(d[5]),"=f"(d[6]),"=f"(d[7]),"=f"(d[8]),"=f"(d[9]),"=f"(d[10]),"=f"(d[11]),"=f"(d[12]),"=f"(d[13]),"=f"(d[14]),"=f"(d[15]),"=f"(d[16]),"=f"(d[17]),"=f"(d[18]),"=f"(d[19]),"=f"(d[20]),"=f"(d[21]),"=f"(d[22]),"=f"(d[23]),"=f"(d[24]),"=f"(d[25]),"=f"(d[26]),"=f"(d[27]),"=f"(d[28]),"=f"(d[29]),"=f"(d[30]),"=f"(d[31]),"=f"(d[32]),"=f"(d[33]),"=f"(d[34]),"=f"(d[35]),"=f"(d[36]),"=f"(d[37]),"=f"(d[38]),"=f"(d[39]),"=f"(d[40]),"=f"(d[41]),"=f"(d[42]),"=f"(d[43]),"=f"(d[44]),"=f"(d[45]),"=f"(d[46]),"=f"(d[47]),"=f"(d[48]),"=f"(d[49]),"=f"(d[50]),"=f"(d[51]),"=f"(d[52]),"=f"(d[53]),"=f"(d[54]),"=f"(d[55]),"=f"(d[56]),"=f"(d[57]),"=f"(d[58]),"=f"(d[59]),"=f"(d[60]),"=f"(d[61]),"=f"(d[62]),"=f"(d[63])
        : "r"(alo), "r"(ahi), "r"(blo), "r"(bhi));
}
__device__ __forceinline__ void wg_ss64(float (&d)[32], uint32_t alo, uint32_t ahi, uint32_t blo, uint32_t bhi) {
    asm volatile("{\n.reg .b64 da, db;\nmov.b64 da, {%32, %33};\nmov.b64 db, {%34, %35};\n"
        "wgmma.mma_async.sync.aligned.m64n64k16.f32.bf16.bf16 {%0,%1,%2,%3,%4,%5,%6,%7,%8,%9,%10,%11,%12,%13,%14,%15,%16,%17,%18,%19,%20,%21,%22,%23,%24,%25,%26,%27,%28,%29,%30,%31}, da, db, 1, 1, 1, 0, 1;\n}\n"
        : "+f"(d[0]),"+f"(d[1]),"+f"(d[2]),"+f"(d[3]),"+f"(d[4]),"+f"(d[5]),"+f"(d[6]),"+f"(d[7]),"+f"(d[8]),"+f"(d[9]),"+f"(d[10]),"+f"(d[11]),"+f"(d[12]),"+f"(d[13]),"+f"(d[14]),"+f"(d[15]),"+f"(d[16]),"+f"(d[17]),"+f"(d[18]),"+f"(d[19]),"+f"(d[20]),"+f"(d[21]),"+f"(d[22]),"+f"(d[23]),"+f"(d[24]),"+f"(d[25]),"+f"(d[26]),"+f"(d[27]),"+f"(d[28]),"+f"(d[29]),"+f"(d[30]),"+f"(d[31])
        : "r"(alo), "r"(ahi), "r"(blo), "r"(bhi));
}
__device__ __forceinline__ void wg_ss64_z(float (&d)[32], uint32_t alo, uint32_t ahi, uint32_t blo, uint32_t bhi) {
    asm volatile("{\n.reg .b64 da, db;\nmov.b64 da, {%32, %33};\nmov.b64 db, {%34, %35};\n"
        "wgmma.mma_async.sync.aligned.m64n64k16.f32.bf16.bf16 {%0,%1,%2,%3,%4,%5,%6,%7,%8,%9,%10,%11,%12,%13,%14,%15,%16,%17,%18,%19,%20,%21,%22,%23,%24,%25,%26,%27,%28,%29,%30,%31}, da, db, 0, 1, 1, 0, 1;\n}\n"
        : "=f"(d[0]),"=f"(d[1]),"=f"(d[2]),"=f"(d[3]),"=f"(d[4]),"=f"(d[5]),"=f"(d[6]),"=f"(d[7]),"=f"(d[8]),"=f"(d[9]),"=f"(d[10]),"=f"(d[11]),"=f"(d[12]),"=f"(d[13]),"=f"(d[14]),"=f"(d[15]),"=f"(d[16]),"=f"(d[17]),"=f"(d[18]),"=f"(d[19]),"=f"(d[20]),"=f"(d[21]),"=f"(d[22]),"=f"(d[23]),"=f"(d[24]),"=f"(d[25]),"=f"(d[26]),"=f"(d[27]),"=f"(d[28]),"=f"(d[29]),"=f"(d[30]),"=f"(d[31])
        : "r"(alo), "r"(ahi), "r"(blo), "r"(bhi));
}
__device__ __forceinline__ void wg_ss64t(float (&d)[32], uint32_t alo, uint32_t ahi, uint32_t blo, uint32_t bhi) {
    asm volatile("{\n.reg .b64 da, db;\nmov.b64 da, {%32, %33};\nmov.b64 db, {%34, %35};\n"
        "wgmma.mma_async.sync.aligned.m64n64k16.f32.bf16.bf16 {%0,%1,%2,%3,%4,%5,%6,%7,%8,%9,%10,%11,%12,%13,%14,%15,%16,%17,%18,%19,%20,%21,%22,%23,%24,%25,%26,%27,%28,%29,%30,%31}, da, db, 1, 1, 1, 1, 1;\n}\n"
        : "+f"(d[0]),"+f"(d[1]),"+f"(d[2]),"+f"(d[3]),"+f"(d[4]),"+f"(d[5]),"+f"(d[6]),"+f"(d[7]),"+f"(d[8]),"+f"(d[9]),"+f"(d[10]),"+f"(d[11]),"+f"(d[12]),"+f"(d[13]),"+f"(d[14]),"+f"(d[15]),"+f"(d[16]),"+f"(d[17]),"+f"(d[18]),"+f"(d[19]),"+f"(d[20]),"+f"(d[21]),"+f"(d[22]),"+f"(d[23]),"+f"(d[24]),"+f"(d[25]),"+f"(d[26]),"+f"(d[27]),"+f"(d[28]),"+f"(d[29]),"+f"(d[30]),"+f"(d[31])
        : "r"(alo), "r"(ahi), "r"(blo), "r"(bhi));
}
__device__ __forceinline__ void wg_ss64t_z(float (&d)[32], uint32_t alo, uint32_t ahi, uint32_t blo, uint32_t bhi) {
    asm volatile("{\n.reg .b64 da, db;\nmov.b64 da, {%32, %33};\nmov.b64 db, {%34, %35};\n"
        "wgmma.mma_async.sync.aligned.m64n64k16.f32.bf16.bf16 {%0,%1,%2,%3,%4,%5,%6,%7,%8,%9,%10,%11,%12,%13,%14,%15,%16,%17,%18,%19,%20,%21,%22,%23,%24,%25,%26,%27,%28,%29,%30,%31}, da, db, 0, 1, 1, 1, 1;\n}\n"
        : "=f"(d[0]),"=f"(d[1]),"=f"(d[2]),"=f"(d[3]),"=f"(d[4]),"=f"(d[5]),"=f"(d[6]),"=f"(d[7]),"=f"(d[8]),"=f"(d[9]),"=f"(d[10]),"=f"(d[11]),"=f"(d[12]),"=f"(d[13]),"=f"(d[14]),"=f"(d[15]),"=f"(d[16]),"=f"(d[17]),"=f"(d[18]),"=f"(d[19]),"=f"(d[20]),"=f"(d[21]),"=f"(d[22]),"=f"(d[23]),"=f"(d[24]),"=f"(d[25]),"=f"(d[26]),"=f"(d[27]),"=f"(d[28]),"=f"(d[29]),"=f"(d[30]),"=f"(d[31])
        : "r"(alo), "r"(ahi), "r"(blo), "r"(bhi));
}
__device__ __forceinline__ void wg_ss8t(float (&d)[4], uint32_t alo, uint32_t ahi, uint32_t blo, uint32_t bhi) {
    asm volatile("{\n.reg .b64 da, db;\nmov.b64 da, {%4, %5};\nmov.b64 db, {%6, %7};\n"
        "wgmma.mma_async.sync.aligned.m64n8k16.f32.bf16.bf16 {%0,%1,%2,%3}, da, db, 1, 1, 1, 1, 0;\n}\n"
        : "+f"(d[0]),"+f"(d[1]),"+f"(d[2]),"+f"(d[3])
        : "r"(alo), "r"(ahi), "r"(blo), "r"(bhi));
}
__device__ __forceinline__ void wg_ss8t_z(float (&d)[4], uint32_t alo, uint32_t ahi, uint32_t blo, uint32_t bhi) {
    asm volatile("{\n.reg .b64 da, db;\nmov.b64 da, {%4, %5};\nmov.b64 db, {%6, %7};\n"
        "wgmma.mma_async.sync.aligned.m64n8k16.f32.bf16.bf16 {%0,%1,%2,%3}, da, db, 0, 1, 1, 1, 0;\n}\n"
        : "=f"(d[0]),"=f"(d[1]),"=f"(d[2]),"=f"(d[3])
        : "r"(alo), "r"(ahi), "r"(blo), "r"(bhi));
}
__device__ __forceinline__ void wg_rs24_z(float (&d)[12], uint32_t a0, uint32_t a1, uint32_t a2, uint32_t a3, uint32_t blo, uint32_t bhi) {
    asm volatile("{\n.reg .b64 db;\nmov.b64 db, {%16, %17};\n"
        "wgmma.mma_async.sync.aligned.m64n24k16.f32.bf16.bf16 {%0,%1,%2,%3,%4,%5,%6,%7,%8,%9,%10,%11}, {%12,%13,%14,%15}, db, 0, 1, 1, 0;\n}\n"
        : "=f"(d[0]),"=f"(d[1]),"=f"(d[2]),"=f"(d[3]),"=f"(d[4]),"=f"(d[5]),"=f"(d[6]),"=f"(d[7]),"=f"(d[8]),"=f"(d[9]),"=f"(d[10]),"=f"(d[11])
        : "r"(a0), "r"(a1), "r"(a2), "r"(a3), "r"(blo), "r"(bhi));
}

constexpr uint32_t DH128 = 64u | 0x40000000u;
constexpr uint32_t DH64 = 32u | 0x80000000u;
constexpr uint32_t LBO4K = (4096u >> 4) << 16, LBO8K = (8192u >> 4) << 16, LBO1 = 1u << 16;

template <bool SW64, bool FIRST> __device__ __forceinline__ void g1_issue(float (&acc)[64], uint32_t alo, uint32_t blo) {
    wg_fence();
#pragma unroll
    for (int k = 0; k < 4; k++) {
        if (FIRST && k == 0) wg_ss128_z(acc, alo, DH128, blo, SW64 ? DH64 : DH128);
        else wg_ss128(acc, alo + 2 * k, DH128, blo + (SW64 ? 64 * k : 128 * k), SW64 ? DH64 : DH128);
    }
    wg_commit();
}

template <int N> __device__ __forceinline__ void stash(uint32_t base, uint32_t sw, const uint32_t (&f)[N]) {
#pragma unroll
    for (int t = 0; t < N / 4; t++) stsm4(base + ((sw ^ (2 * t)) << 4), f[4 * t], f[4 * t + 1], f[4 * t + 2], f[4 * t + 3]);
}

template <int V0, int V1, int N> __device__ __forceinline__ void send_frag(const uint32_t (&f)[N], uint4* p, uint32_t tag) {
#pragma unroll
    for (int v = V0; v < V1; v++) st_pkt(p + v * 32, (f[4 * v] & ~1u) | tag, f[4 * v + 1], f[4 * v + 2], f[4 * v + 3]);
}
template <int H0, int H1, int N> __device__ __forceinline__ void send_h(const uint32_t (&f)[N], uint4* p) {
#pragma unroll
    for (int h = H0; h < H1; h++) {
        p[4 * h] = make_uint4(f[8 * h], f[8 * h + 2], f[8 * h + 4], f[8 * h + 6]);
        p[4 * h + 64] = make_uint4(f[8 * h + 1], f[8 * h + 3], f[8 * h + 5], f[8 * h + 7]);
    }
}
template <int O, int N, int M> __device__ __forceinline__ void pack_sub(uint32_t (&f)[N], const float (&acc)[M]) {
#pragma unroll
    for (int i = 0; i < N; i++) f[i] = keep(pack2(acc[O + 2 * i], acc[O + 2 * i + 1]));
}
template <int N> __device__ __forceinline__ void recv_issue(uint32_t (&q)[N], const uint4* p) {
#pragma unroll
    for (int v = 0; v < N / 4; v++) ld_pkt(p + v * 32, q[4 * v], q[4 * v + 1], q[4 * v + 2], q[4 * v + 3]);
}
template <int N> __device__ __forceinline__ void recv_check(uint32_t (&q)[N], const uint4* p, uint32_t tag) {
    uint32_t it = 0;
    while (true) {
        uint32_t bad = 0;
#pragma unroll
        for (int v = 0; v < N / 4; v++) bad |= q[4 * v] ^ tag;
        if (__all_sync(0xffffffffu, (bad & 1u) == 0) || ++it > SPIN_GLOBAL) break;
        recv_issue(q, p);
    }
}
__device__ __forceinline__ void accum(const uint32_t (&q)[32], float (&sum)[64]) {
#pragma unroll
    for (int i = 0; i < 32; i++) { sum[2 * i] += bf_lo(q[i]); sum[2 * i + 1] += bf_hi(q[i]); }
}

}

__global__ void __launch_bounds__(384, 1)
fused_kernel(const __grid_constant__ Maps maps, const __nv_bfloat16* __restrict__ xg, const __nv_bfloat16* __restrict__ gate_w,
             const char* __restrict__ pf_qkv, const char* __restrict__ pf_g, const char* __restrict__ pf_u,
             const char* __restrict__ pf_d, const char* __restrict__ pf_o, __nv_bfloat16* __restrict__ out) {
    extern __shared__ __align__(1024) uint8_t smem_raw[];
    const uint32_t sb = (uint32_t)__cvta_generic_to_shared(smem_raw);
    const int tid = threadIdx.x, lane = tid & 31;
    const int warp = __shfl_sync(0xffffffffu, tid >> 5, 0);
    const int j = (blockIdx.x >> 1) & 7;
    const int r = ((blockIdx.x >> 4) << 1) | (blockIdx.x & 1);
    const uint32_t rank = blockIdx.x & 1;

    if (warp == 0) { TSG(0, 30); TS(0, 0); }
    if (tid == 256) {
        for (int i = 0; i < 5; i++) { mbar_init(sb + B_FULL + 8 * i, 1); mbar_init(sb + B_EMPTY + 8 * i, MC ? 4 : 2); }
        for (int i = 0; i < 9; i++) mbar_init(sb + B_XFULL + 8 * i, 1);
        asm volatile("fence.mbarrier_init.release.cluster;" ::: "memory");
        mbar_expect(sb + B_XFULL, 16384);
        tma2(sb + OFF_X, &maps.x, 0, r * 128, sb + B_XFULL);
        TS2(0);
        mbar_expect(sb + B_FULL, 16384);
        tmaw3(sb + OFF_RING, &maps.gu, 224 * j, 0, 0, sb + B_FULL);
        TS2(1);
        mbar_expect(sb + B_FULL + 8, 16384);
        tmaw3(sb + OFF_RING + 16384, &maps.kv, 64 * j, 0, 1, sb + B_FULL + 8);
    } else if (tid == 288) {
        for (int i = 0; i < 3; i++) mbar_init(sb + B_HSENT + 8 * i, 8);
        for (int i = 0; i < 4; i++) { mbar_init(sb + B_EFULL + 8 * i, 1); mbar_init(sb + B_EEMPTY + 8 * i, MC ? 4 : 2); }
        mbar_init(sb + B_XFREE, 2); mbar_init(sb + B_XFREE + 8, 2); mbar_init(sb + B_XFREE + 16, 2);
        mbar_init(sb + B_AHEAD, 1); mbar_init(sb + B_GRDY, 1); mbar_init(sb + B_KVDONE, 8); mbar_init(sb + B_KVRDY, 2);
        asm volatile("fence.mbarrier_init.release.cluster;" ::: "memory");
    } else if (warp == 10 && lane < 10) {
        asm volatile("prefetch.tensormap [%0];" :: "l"(&maps.gu + lane) : "memory");
    }
    __syncthreads();

    if (warp >= 8) {
        asm volatile("setmaxnreg.dec.sync.aligned.u32 56;");
        if (warp == 8) {
            if (lane == 0) {
                int slot = MC ? 0 : 2, ph = 1;
                uint32_t full, dst;
                if (!MC) { mbar_expect(sb + B_XFULL + 8, 16384); tma2(sb + OFF_X + 16384, &maps.x, 64, r * 128, sb + B_XFULL + 8); }
#define P_BEGIN(S, BYTES) full = sb + B_FULL + 8 * slot; dst = sb + OFF_RING + slot * 16384; \
                mbar_wait(sb + B_EMPTY + 8 * slot, ph); TS2(S); mbar_expect(full, BYTES); if (!MC || (((S) ^ rank) & 1) == 0)
#define P_END() if (++slot == 5) { slot = 0; ph ^= 1; }
                for (int s = MC ? 0 : 2; s < 16; s++) {
                    P_BEGIN(s, 16384) {
                        const int sw = s == 13 ? 14 : s == 14 ? 13 : s;
                        if (sw & 1) tmaw3(dst, &maps.kv, 64 * j, 32 * (sw - 1), 1, full);
                        else tmaw3(dst, &maps.gu, 224 * j, 32 * sw, 0, full);
                    }
                    const int xb = (s == 4) ? 3 : (s == 10) ? 7 : !(s & 1) ? 0 : (s < 5) ? (s + 1) / 2 : (s <= 9) ? (s + 3) / 2 : 0;
                    if (xb) { mbar_expect(sb + B_XFULL + 8 * xb, 16384); tma2(sb + OFF_X + xb * 16384, &maps.x, 64 * xb, r * 128, sb + B_XFULL + 8 * xb); }
                    P_END()
                }
                for (int s = 0; s < 24; s++) {
                    P_BEGIN(16 + s, 16384) {
                        if ((s >> 3) == 1) {
                            tmaw3(dst, &maps.q64, 0, 64 * (s & 7), 2 * j, full);
                            tmaw3(dst + 8192, &maps.gu64, 224 * j + 192, 64 * (s & 7), 0, full);
                        } else {
                            tmaw3(dst, &maps.gu, 224 * j + 64 + 4 * (s & 16), 64 * (s & 7), 0, full);
                        }
                    }
                    P_END()
                }
                const int p = j >> 1;
#pragma unroll 1
                for (int t = 0; t < 18; t++) {
                    const int u = (int)((t < 16 ? 0x2187658704653210ull >> (4 * t) : 0x43ull >> (4 * (t - 16))) & 15);
                    const int q = t >= 9, sl = t - 9 * q;
                    const int cw = (j & 1) * 4 + ((p & 2) ^ ((t == 7 || t > 9) ? 0 : 2)), cc = 64 * cw;
                    if (sl < 5) {
                        full = sb + B_FULL + 8 * sl; dst = sb + OFF_RING + sl * 16384;
                        mbar_wait(sb + B_EMPTY + 8 * sl, q ^ 1);
                    } else {
                        full = sb + B_EFULL + 8 * (sl - 5); dst = sb + OFF_X + (sl == 7 ? 8 : sl == 8 ? 7 : sl) * 16384;
                        mbar_wait(sb + B_EEMPTY + 8 * (sl - 5), q);
                    }
                    TS2(40 + t);
                    mbar_expect(full, 16384);
                    if (!MC || ((t ^ rank) & 1) == 0) {
                        if (u == 4) {
                            tmaw5(dst, &maps.wdph, cc, 14 * p + 6, full); tmaw5(dst + 4096, &maps.wdph, cc, 14 * p + 13, full);
                            tmaw5(dst + 8192, &maps.wdph, cc + 64, 14 * p + 6, full); tmaw5(dst + 12288, &maps.wdph, cc + 64, 14 * p + 13, full);
                        } else if (u > 4) {
                            const int js = u > 6 ? j ^ 1 : j;
                            tmaw3(dst, (u & 1) ? &maps.wow : &maps.wdw, 0, (u & 1) ? 64 * js : 224 * js + 128, cw, full);
                        } else {
                            const int g = 14 * p + 7 * (u & 1) + (u & 2);
                            tmaw5(dst, &maps.wdp, cc, g, full); tmaw5(dst + 8192, &maps.wdp, cc + 64, g, full);
                        }
                    }
                }
            }
        } else if (warp < 11) {
            const int hx = warp - 9;
            uint32_t epoch;
            asm volatile("ld.relaxed.gpu.global.u32 %0, [%1];" : "=r"(epoch) : "l"(g_epoch + blockIdx.x) : "memory");
            {
                const uint4* xr = (const uint4*)(xg + (size_t)(r * 128 + j * 16 + hx * 8) * kD) + lane;
                const uint4 wa = __ldg((const uint4*)gate_w + lane), wb = __ldg((const uint4*)gate_w + 32 + lane);
                const uint32_t tag = (epoch + 1) & 1;
                uint4* gp = g_gx + r * 32;
                if (lane < 2) st_pkt(gp + j * 4 + hx * 2 + lane, tag ^ 1, 0, 0, 0);
                float s[8];
#pragma unroll
                for (int i0 = 0; i0 < 8; i0 += 4) {
                    uint4 va[4], vb[4];
#pragma unroll
                    for (int i = 0; i < 4; i++) { va[i] = __ldg(xr + (i0 + i) * 64); vb[i] = __ldg(xr + (i0 + i) * 64 + 32); }
#pragma unroll
                    for (int i = 0; i < 4; i++) {
                        float t0 = bf_lo(va[i].x) * bf_lo(wa.x), t1 = bf_hi(va[i].x) * bf_hi(wa.x);
                        t0 = fmaf(bf_lo(va[i].y), bf_lo(wa.y), t0); t1 = fmaf(bf_hi(va[i].y), bf_hi(wa.y), t1);
                        t0 = fmaf(bf_lo(va[i].z), bf_lo(wa.z), t0); t1 = fmaf(bf_hi(va[i].z), bf_hi(wa.z), t1);
                        t0 = fmaf(bf_lo(va[i].w), bf_lo(wa.w), t0); t1 = fmaf(bf_hi(va[i].w), bf_hi(wa.w), t1);
                        t0 = fmaf(bf_lo(vb[i].x), bf_lo(wb.x), t0); t1 = fmaf(bf_hi(vb[i].x), bf_hi(wb.x), t1);
                        t0 = fmaf(bf_lo(vb[i].y), bf_lo(wb.y), t0); t1 = fmaf(bf_hi(vb[i].y), bf_hi(wb.y), t1);
                        t0 = fmaf(bf_lo(vb[i].z), bf_lo(wb.z), t0); t1 = fmaf(bf_hi(vb[i].z), bf_hi(wb.z), t1);
                        t0 = fmaf(bf_lo(vb[i].w), bf_lo(wb.w), t0); t1 = fmaf(bf_hi(vb[i].w), bf_hi(wb.w), t1);
                        s[i0 + i] = t0 + t1;
                    }
                }
#pragma unroll
                for (int i = 0; i < 8; i++) {
#pragma unroll
                    for (int o = 16; o; o >>= 1) s[i] += __shfl_xor_sync(0xffffffffu, s[i], o);
                    s[i] = 1.f / (1.f + __expf(-s[i]));
                }
                if (lane < 2) {
                    const float v0 = lane ? s[4] : s[0], v1 = lane ? s[5] : s[1], v2 = lane ? s[6] : s[2], v3 = lane ? s[7] : s[3];
                    st_pkt(gp + j * 4 + hx * 2 + lane, (__float_as_uint(v0) & ~1u) | tag, __float_as_uint(v1), __float_as_uint(v2), __float_as_uint(v3));
                }
                if (hx == 1) {
                    asm volatile("st.shared.u32 [%0], %1;" :: "r"(sb + OFF_ONES + lane * 4), "r"(0x3f803f80u) : "memory");
                    asm volatile("fence.proxy.async.shared::cta;" ::: "memory");
                }
                asm volatile("bar.sync 3, 96;" ::: "memory");
                if (hx == 0) {
                    uint32_t q[4];
                    recv_issue(q, gp + lane);
                    recv_check(q, gp + lane, tag);
                    asm volatile("st.shared.v4.u32 [%0], {%1,%2,%3,%4};" :: "r"(sb + OFF_G + lane * 16), "r"(q[0]), "r"(q[1]), "r"(q[2]), "r"(q[3]) : "memory");
                    if (lane == 0) {
                        asm volatile("st.shared.u32 [%0], %1;" :: "r"(sb + OFF_EPOCH), "r"(epoch) : "memory");
                        g_epoch[blockIdx.x] = epoch + 1;
                    }
                    __syncwarp();
                    if (lane == 0) mbar_arrive(sb + B_GRDY);
                } else {
                    if (r == 0) {
                        float4* zp = (float4*)(g_kvacc + (((epoch & 1) ^ 1) * 8 + j) * 4 * 272);
                        for (int i = lane; i < 272; i += 32) zp[i] = make_float4(0.f, 0.f, 0.f, 0.f);
                    }
                }
            }
            TS(2 + hx, 1);
#define PUBLISH_H(B) do { mbar_wait(sb + B_HSENT + 8 * (B), 0); if (lane == 0) { \
                asm volatile("st.release.gpu.global.u32 [%0], %1;" :: "l"(g_hflag + (r * 8 + j) * 8 + (B)), "r"(epoch + 1) : "memory"); } __syncwarp(); } while (0)
            if (hx == 1) {
#pragma unroll 1
                for (int b = 0; b < 3; b++) { PUBLISH_H(b); TS(3, 5 + b); }
            } else {
                const float* accp = g_kvacc + ((epoch & 1) * 8 + j) * 4 * 272;
                unsigned* cnt = g_kvcnt + j * 32;
                mbar_wait(sb + B_KVDONE, 0);
                TS(2, 5);
                if (lane == 0) asm volatile("red.release.gpu.global.add.u32 [%0], 1;" :: "l"(cnt) : "memory");
                __syncwarp();
                TS(2, 2);
                {
                    const unsigned target = 16u * (epoch + 1);
                    uint32_t it = 0, v;
                    do {
                        asm volatile("ld.acquire.gpu.global.u32 %0, [%1];" : "=r"(v) : "l"(cnt) : "memory");
                    } while ((int)(v - target) < 0 && ++it < SPIN_GLOBAL);
                }
                TS(2, 3);
#pragma unroll
                for (int h = 0; h < 4; h++) {
                    const float4 d0 = __ldcg((const float4*)(accp + h * 272) + lane);
                    const float4 d1 = __ldcg((const float4*)(accp + h * 272 + 128) + lane);
                    const float2 z0 = __ldcg((const float2*)(accp + h * 272 + 256) + (lane & 3));
                    const float2 z1 = __ldcg((const float2*)(accp + h * 272 + 264) + (lane & 3));
                    const uint32_t ba = sb + OFF_STG + h * 768 + lane * 4;
                    asm volatile("st.shared.u32 [%0], %1;" :: "r"(ba), "r"(pack2(d0.x, d0.y)) : "memory");
                    asm volatile("st.shared.u32 [%0], %1;" :: "r"(ba + 128), "r"(pack2(d1.x, d1.y)) : "memory");
                    asm volatile("st.shared.u32 [%0], %1;" :: "r"(ba + 256), "r"(pack2(d0.z, d0.w)) : "memory");
                    asm volatile("st.shared.u32 [%0], %1;" :: "r"(ba + 384), "r"(pack2(d1.z, d1.w)) : "memory");
                    asm volatile("st.shared.u32 [%0], %1;" :: "r"(ba + 512), "r"(pack2(z0.x, z0.y)) : "memory");
                    asm volatile("st.shared.u32 [%0], %1;" :: "r"(ba + 640), "r"(pack2(z1.x, z1.y)) : "memory");
                }
                asm volatile("fence.proxy.async.shared::cta;" ::: "memory");
                __syncwarp();
                if (lane == 0) mbar_arrive(sb + B_KVRDY);
                TS(2, 4);
            }
        } else {
            uint32_t epoch;
            asm volatile("ld.relaxed.gpu.global.u32 %0, [%1];" : "=r"(epoch) : "l"(g_epoch + blockIdx.x) : "memory");
            asm volatile("bar.arrive 3, 96;" :: "r"(epoch) : "memory");
            const int b = blockIdx.x, p = j >> 1;
            mbar_wait(sb + B_XFULL, 0);
#pragma unroll 1
            for (int kb = 1; kb < 8; kb++) {
                mbar_wait(sb + B_XFULL + 8 * kb, 0);
                const char* base = kb < 3 ? pf_g : kb < 5 ? pf_u : kb == 5 ? pf_qkv : pf_d;
                const int off = kb == 5 ? b * 12288 : b * 14336 + ((kb < 5 ? kb - 1 : kb) & 1) * 7168;
                asm volatile("prefetch.global.L2 [%0];" :: "l"(base + off + lane * 128));
                if (kb == 5 || lane < 24) asm volatile("prefetch.global.L2 [%0];" :: "l"(base + off + 4096 + lane * 128));
                if (kb == 5) asm volatile("prefetch.global.L2 [%0];" :: "l"(base + off + 8192 + lane * 128));
                if (kb == 7) asm volatile("prefetch.global.L2 [%0];" :: "l"(pf_o + b * 4096 + lane * 128));
            }
            {
                uint4* mb = g_part + (size_t)(r * 2 + (j & 1)) * 16384 + (((p ^ 1) * 4 + p) << 10) + lane;
#pragma unroll 1
                for (int i = 0; i < 32; i++) { st_pkt(mb + i * 32, epoch & 1, 0, 0, 0); __nanosleep(40); }
                __syncwarp();
                if (lane == 0) mbar_arrive(sb + B_KVRDY);
            }
            {
                const uint32_t want = epoch + 1;
                const int hrow = (r * 4 + p) * 5 * 128;
                const unsigned* fl = g_hflag + (r * 8 + (j & 6)) * 8 + (lane & 15);
                uint32_t it = 0;
                int i = 0;
                mbar_wait(sb + B_HSENT + 8, 0);
#pragma unroll 1
                while (i < 3 && ++it < SPIN_GLOBAL) {
                    uint32_t v;
                    asm volatile("ld.acquire.gpu.global.u32 %0, [%1];" : "=r"(v) : "l"(fl) : "memory");
                    const uint32_t rdy = __ballot_sync(0xffffffffu, v == want);
#pragma unroll 1
                    while (i < 3 && ((rdy >> i) & 0x101u) == 0x101u) {
                        mbar_wait(sb + B_XFREE + 8 * i, 0);
                        if (lane == 0) {
                            asm volatile("fence.proxy.async.global;" ::: "memory");
                            TS2(140 + i);
                            mbar_expect(sb + B_XFULL + 16 * i, i < 2 ? 32768 : 16384);
                            tma2(sb + OFF_X + i * 32768, i < 2 ? &maps.hx2 : &maps.hx, 0, hrow + i * 256, sb + B_XFULL + 16 * i);
                        }
                        i++;
                    }
                }
            }
        }
    } else {
        asm volatile("setmaxnreg.inc.sync.aligned.u32 224;");
        const int wg = warp >> 2;
        const bool elect = (tid & 127) == 0;
        const uint32_t xlo = ((sb + OFF_X + wg * 8192) >> 4) | LBO1;
        const uint32_t ringlo = (sb + OFF_RING) >> 4;
        auto release = [&](uint32_t bar) {
            if (elect) {
                mbar_arrive(sb + bar);
            }
        };
#define S_SL(S) ((S) < 40 ? (S) % 5 : ((S) - 40) % 9)
#define S_WAIT(S) do { mbar_wait(sb + (S_SL(S) < 5 ? B_FULL + 8 * S_SL(S) : B_EFULL + 8 * (S_SL(S) - 5)), (S) < 40 ? ((S) / 5) & 1 : (S) >= 49); \
            if (PROF && tid == 0) TS2(64 + (S)); } while (0)
#define S_B(S) (S_SL(S) < 5 ? ringlo + S_SL(S) * 1024 : ((sb + OFF_X) >> 4) + (S_SL(S) == 7 ? 8 : S_SL(S) == 8 ? 7 : S_SL(S)) * 1024)
#define S_REL(S) do { if ((S) < 49) release(S_SL(S) < 5 ? B_EMPTY + 8 * S_SL(S) : B_EEMPTY + 8 * (S_SL(S) - 5)); } while (0)
#define G1(S, acc, SW, KB) g1_issue<SW, (KB) == 0>(acc, xlo + (KB) * 1024, S_B(S) | (SW ? LBO4K : LBO8K))
#define RET(S) do { S_WAIT((S) + 1); wg_wait<1>(); S_REL((S) - 1); } while (0)
#define RET2(S) do { S_WAIT((S) + 1); wg_wait<2>(); S_REL((S) - 1); } while (0)
#define SCHED() mbar_wait(sb + B_GRDY, 0)
#define A2_SYNC() do { asm volatile("fence.proxy.async.shared::cta;" ::: "memory"); asm volatile("bar.sync %0, 128;" :: "r"(wg + 1) : "memory"); } while (0)
#define H_EPI(acc, F, I0, I1, OG, OU) _Pragma("unroll") for (int i = (I0); i < (I1); i++) \
            F[i] = keep(hmul2(pack2(acc[(OG) + 2 * i] * acc[(OU) + 2 * i], acc[(OG) + 2 * i + 1] * acc[(OU) + 2 * i + 1]), (i & 1) ? m_hi : m_lo))
#define PHI(acc, F, I0, I1) _Pragma("unroll") for (int i = (I0); i < (I1); i++) F[i] = keep(phi2(acc[2 * i], acc[2 * i + 1]))

        float a0[64], b0[64], a1[64], a2_[64], a3[64];
        mbar_wait(sb + B_XFULL, 0);
        S_WAIT(0); G1(0, a0, false, 0);
        if ((warp & 3) == 0) TS(wg, 1);
        S_WAIT(1); G1(1, b0, false, 0); RET(1);
#define C0(KB) mbar_wait(sb + B_XFULL + 8 * (KB), 0); if (PROF && tid == 0) TS2(128 + (KB)); \
        G1(2 * (KB), a0, false, KB); RET(2 * (KB)); G1(2 * (KB) + 1, b0, false, KB); RET(2 * (KB) + 1)
        C0(1); C0(2); C0(3); C0(4); C0(5);
        mbar_wait(sb + B_XFULL + 8 * 6, 0);
        G1(12, a0, false, 6); RET(12);
        mbar_wait(sb + B_XFULL + 8 * 7, 0);
        G1(13, a0, false, 7); RET(13);
        G1(14, b0, false, 6);
        mbar_wait(sb + B_GRDY, 0);
        float g_lo, g_hi;
        uint32_t tag;
        {
            const uint32_t ga = sb + OFF_G + (warp * 16 + (lane >> 2)) * 4;
            asm volatile("ld.shared.f32 %0, [%1];" : "=f"(g_lo) : "r"(ga) : "memory");
            asm volatile("ld.shared.f32 %0, [%1];" : "=f"(g_hi) : "r"(ga + 32) : "memory");
            asm volatile("ld.shared.u32 %0, [%1];" : "=r"(tag) : "r"(sb + OFF_EPOCH) : "memory");
        }
        float* const kvp = g_kvacc + (((tag & 1) * 8 + j) * 4 + (warp & 3)) * 272;
        tag = (tag + 1) & 1;
        const uint32_t m_lo = pack2(1.f - g_lo, 1.f - g_lo), m_hi = pack2(1.f - g_hi, 1.f - g_hi);
        const uint32_t lrow = ((lane & 7) + 8 * ((lane >> 3) & 1)) * 128;
        const uint32_t srow = (warp & 3) * 2048 + lrow;
        const uint32_t ssw = (lane >> 4) ^ (lane & 7);
        uint4* const hsend = g_hx + (size_t)((r * 4 + (j >> 1)) * 5 + (j & 1)) * 1024 + warp * 128 + (lane >> 2) * 8 + (lane & 3);
#define SENT_H(B) do { __syncwarp(); if (lane == 0) mbar_arrive(sb + B_HSENT + 8 * (B)); } while (0)
        RET(14);
        pin(a0);
        uint32_t fh0[16], fh1[16], fh2[16], fh3[8], fo[16];
        G1(15, b0, false, 7); SCHED(); H_EPI(a0, fh0, 0, 16, 0, 32); RET(15);
        if ((warp & 3) == 0) TS(wg, 2);

        float kv[32], zs[4];
        uint32_t pk[16], pv[16];
        const uint32_t stg = sb + OFF_STG + wg * 8192, stl = stg + (warp & 1) * 2048 + lrow;
        const uint32_t klo = (stg >> 4) | LBO1, vlo = klo + 256, olo = (sb + OFF_ONES) >> 4;
        G1(16, a1, false, 0); RET(16);
        pin(b0);
        G1(17, a1, false, 1); send_h<0, 1>(fh0, hsend); SCHED(); PHI(b0, pk, 0, 6); RET(17);
        G1(18, a1, false, 2); send_h<1, 2>(fh0, hsend); SENT_H(0); SCHED(); PHI(b0, pk, 6, 12); RET(18);
        G1(19, a1, false, 3); SCHED(); PHI(b0, pk, 12, 16); pack_sub<32>(pv, b0); RET(19);
#define KV_ROUND(Z) do { A2_SYNC(); wg_fence(); \
            wg_ss64t##Z(kv, vlo, DH128, klo, DH128); wg_ss64t(kv, vlo + 128, DH128, klo + 128, DH128); \
            wg_ss8t##Z(zs, klo, DH128, olo, 0); wg_ss8t(zs, klo + 128, DH128, olo, 0); wg_commit(); } while (0)
        G1(20, a1, false, 4); if (!(warp & 2)) { stash<16>(stl, ssw, pk); stash<16>(stl + 4096, ssw, pv); } RET(20);
        G1(21, a1, false, 5); KV_ROUND(_z); RET2(21);
        G1(22, a1, false, 6); RET(22);
        G1(23, a1, false, 7); if (warp & 2) { stash<16>(stl, ssw, pk); stash<16>(stl + 4096, ssw, pv); } RET(23);
        if ((warp & 3) == 0) TS(wg, 3);

        G1(24, a2_, true, 0); KV_ROUND(); RET2(24);
        pin(a1);
        G1(25, a2_, true, 1); RET(25);
        pin(kv); pin(zs);
        G1(26, a2_, true, 2);
#define KV_RED(W) do { asm volatile("red.global.add.v4.f32 [%0], {%1,%2,%3,%4};" :: "l"(kvp + lane * 4), "f"(kv[8 * W]), "f"(kv[8 * W + 1]), "f"(kv[8 * W + 2]), "f"(kv[8 * W + 3]) : "memory"); \
                       asm volatile("red.global.add.v4.f32 [%0], {%1,%2,%3,%4};" :: "l"(kvp + 128 + lane * 4), "f"(kv[8 * W + 4]), "f"(kv[8 * W + 5]), "f"(kv[8 * W + 6]), "f"(kv[8 * W + 7]) : "memory"); } while (0)
        if ((warp & 3) == 0) KV_RED(0); else if ((warp & 3) == 1) KV_RED(1); else if ((warp & 3) == 2) KV_RED(2); else KV_RED(3);
        if ((lane & 3) == 0) {
            asm volatile("red.global.add.f32 [%0], %1;" :: "l"(kvp + 256 + (lane >> 2)), "f"(zs[0]) : "memory");
            asm volatile("red.global.add.f32 [%0], %1;" :: "l"(kvp + 264 + (lane >> 2)), "f"(zs[2]) : "memory");
        }
        __syncwarp();
        if (lane == 0) mbar_arrive(sb + B_KVDONE);
        RET(26);
        G1(27, a2_, true, 3); SCHED(); H_EPI(a1, fh1, 0, 16, 0, 32); RET(27);
        G1(28, a2_, true, 4); RET(28);
        G1(29, a2_, true, 5); RET(29);
        G1(30, a2_, true, 6); send_h<0, 1>(fh1, hsend + 2 * 1024); RET(30);
        G1(31, a2_, true, 7); send_h<1, 2>(fh1, hsend + 2 * 1024); SENT_H(1); RET(31);
        if ((warp & 3) == 0) TS(wg, 4);

        float on[4][12];
#define O_SCALE(h) do { const float s_lo = __fdividef(g_lo, on[h][8] + 1e-6f), s_hi = __fdividef(g_hi, on[h][10] + 1e-6f); \
            const uint32_t sl_ = pack2(s_lo, s_lo), sh_ = pack2(s_hi, s_hi); \
            fo[4 * h] = hmul2(pack2(on[h][0], on[h][1]), sl_); fo[4 * h + 1] = hmul2(pack2(on[h][2], on[h][3]), sh_); \
            fo[4 * h + 2] = hmul2(pack2(on[h][4], on[h][5]), sl_); fo[4 * h + 3] = hmul2(pack2(on[h][6], on[h][7]), sh_); } while (0)
        G1(32, a3, false, 0); RET(32);
        pin(a2_);
        G1(33, a3, false, 1); SCHED(); H_EPI(a2_, fh3, 0, 8, 32, 48);
        send_h<0, 1>(fh3, hsend + 4 * 1024 - (j & 1) * 1020); SENT_H(2); PHI(a2_, fo, 0, 2); RET(33);
        G1(34, a3, false, 2); SCHED(); PHI(a2_, fo, 2, 7); RET(34);
        if (elect) mbar_arrive(sb + B_XFREE);
        G1(35, a3, false, 3); SCHED(); PHI(a2_, fo, 7, 12); RET(35);
        G1(36, a3, false, 4); SCHED(); PHI(a2_, fo, 12, 16); RET(36);
        if (elect) mbar_arrive(sb + B_XFREE + 8);
        G1(37, a3, false, 5);
        if ((warp & 3) == 0) TS(wg, 5);
        mbar_wait(sb + B_KVRDY, 0);
        if ((warp & 3) == 0) TS(wg, 6);
        wg_fence();
#pragma unroll
        for (int h = 0; h < 4; h++)
            wg_rs24_z(on[h], fo[4 * h], fo[4 * h + 1], fo[4 * h + 2], fo[4 * h + 3], (((sb + OFF_STG) >> 4) + h * 48) | (8u << 16), 16u);
        wg_commit();
        RET2(37);
        G1(38, a3, false, 6); RET(38);
        release(B_EEMPTY); release(B_EEMPTY + 16);
        pin(on[0]); pin(on[1]); pin(on[2]); pin(on[3]);
        uint4* const lsend = g_lx + (size_t)(r * 8 + j) * 2048 + warp * 128 + lane;
        const uint4* const lrecv = g_lx + (size_t)(r * 8 + (j ^ 1)) * 2048 + warp * 128 + lane;
        G1(39, a3, false, 7); SCHED();
        O_SCALE(0); O_SCALE(1); send_frag<0, 2>(fo, lsend, tag);
        O_SCALE(2); O_SCALE(3);
        RET(39);
        release(B_EEMPTY + 8);
        if ((warp & 3) == 0) TS(wg, 7);

#define G2S(S, acc, U) do { wg_fence(); _Pragma("unroll") for (int k = 0; k < 4; k++) { \
            if (((S) == 40 || (S) == 47) && k == 0) wg_ss128_z(acc, xlo, DH128, S_B(S) | LBO8K, DH128); \
            else wg_ss128(acc, xlo + (U) * 1024 + 2 * k, DH128, (S_B(S) | LBO8K) + 128 * k, DH128); } wg_commit(); } while (0)
#define G2R(S, acc, F) do { wg_fence(); _Pragma("unroll") for (int k = 0; k < 4; k++) { \
            wg_rs128(acc, F[4 * k], F[4 * k + 1], F[4 * k + 2], F[4 * k + 3], (S_B(S) | LBO8K) + 128 * k, DH128); } wg_commit(); } while (0)
#define H_WAIT(P) do { mbar_wait(sb + B_XFULL + 8 * (P), 1); if (PROF && tid == 0) TS2(150 + (P)); } while (0)
        const int p = j >> 1, pw = (p & 2) ^ 2;
        const bool own = wg == (p & 1);
        uint4* const pbase = g_part + (size_t)(r * 2 + (j & 1)) * 16384 + (warp & 3) * 256 + lane;

        float p1[64], p2[64];
        uint32_t po[16], ph2[16];
        H_WAIT(0); G2S(40, p1, 0); send_frag<2, 4>(fo, lsend, tag); RET(40);
        release(B_EEMPTY + 24);
        if (elect) mbar_arrive(sb + B_XFREE + 16);
        pin(a3);
        G2S(41, p1, 1); SCHED(); H_EPI(a3, fh2, 0, 16, 0, 32); send_frag<0, 2>(fh2, lsend + 1024, tag); RET(41);
        H_WAIT(2); G2S(42, p1, 2); send_frag<2, 4>(fh2, lsend + 1024, tag); RET(42);
        G2S(43, p1, 3); recv_issue(po, lrecv); RET(43);
        G2R(44, p1, fo); RET(44);
        G2R(45, p1, fh2); SCHED(); recv_check(po, lrecv, tag); recv_issue(ph2, lrecv + 1024); RET(45);
        H_WAIT(4); G2S(46, p1, 4); RET(46);
        G2S(47, p2, 0); RET(47);
        G2R(48, p1, po); SCHED(); recv_check(ph2, lrecv + 1024, tag); RET(48);
        G2R(49, p1, ph2); RET(49);
        if ((warp & 3) == 0) TS(wg, 8);
        uint32_t sp[32], qa[32], qb[32];
        uint4* const s1 = pbase + (((pw + wg) * 4 + p) << 10);
        G2R(50, p2, fo); RET(50);
        pin(p1);
        G2R(51, p2, fh2); SCHED(); pack_sub<0>(sp, p1); send_frag<0, 2>(sp, s1, tag); RET(51);
        G2R(52, p2, po); send_frag<2, 5>(sp, s1, tag); RET(52);
        G2R(53, p2, ph2); send_frag<5, 8>(sp, s1, tag); RET(53);
        const uint4* ra = pbase + ((p * 4 + pw) << 10);
        const uint4* rc = pbase + ((p * 4 + (p ^ 1)) << 10);
        if (own) {
            wg_wait<0>();
            pin(p2);
            __nanosleep(PAUSE_NS);
            recv_issue(qa, ra); recv_issue(qb, ra + 1024);
            recv_check(qa, ra, tag); accum(qa, p2);
            recv_check(qb, ra + 1024, tag); accum(qb, p2);
            pin(p2);
            if ((warp & 3) == 0) TS(wg, 10);
            mbar_wait(sb + B_AHEAD, 0);
        }
        G2S(54, p2, 1); RET(54);
        G2S(55, p2, 2); RET(55);
        G2S(56, p2, 3); RET(56);
        G2S(57, p2, 4);
        if ((warp & 3) == 0) TS(wg, 9);
        if (!own) {
            if (elect) mbar_arrive(sb + B_AHEAD);
        } else {
            recv_issue(sp, rc);
        }
        wg_wait<0>();
        pin(p2);
        if ((warp & 3) == 0) TS(wg, 11);
        if (!own) {
            pack_sub<0>(sp, p2); send_frag<0, 8>(sp, pbase + (((p ^ 1) * 4 + p) << 10), tag);
        } else {
            if ((warp & 3) == 0) TS(wg, 12);
            recv_check(sp, rc, tag); accum(sp, p2);
            if ((warp & 3) == 0) TS(wg, 13);
            uint32_t f0[16], f1[16];
            pack_sub<0>(f0, p2); pack_sub<32>(f1, p2);
            const uint32_t slab = sb + OFF_X + 2 * 16384 + wg * 8192;
            stash<16>(slab + srow, ssw, f0); stash<16>(slab + 16384 + srow, ssw, f1);
            __syncwarp();
            __nv_bfloat16* op = out + (size_t)(r * 128 + warp * 16 + (lane >> 4)) * kD + (j & 1) * 256 + (p & 2) * 64 + (lane & 15) * 8;
#pragma unroll
            for (int i = 0; i < 8; i++) {
                const int row = i * 2 + (lane >> 4);
                uint4 v;
                asm volatile("ld.shared.v4.u32 {%0,%1,%2,%3}, [%4];" : "=r"(v.x), "=r"(v.y), "=r"(v.z), "=r"(v.w)
                             : "r"(slab + (lane & 8) * 2048 + ((warp & 3) * 16 + row) * 128 + (((lane & 7) ^ (row & 7)) << 4)) : "memory");
                *(uint4*)(op + i * 2 * kD) = v;
            }
        }
        if ((warp & 3) == 0) { TS(wg, 14); TSG(wg, 31); }
    }
}

typedef CUresult (*EncodeFn)(CUtensorMap*, CUtensorMapDataType, cuuint32_t, void*, const cuuint64_t*, const cuuint64_t*, const cuuint32_t*,
                             const cuuint32_t*, CUtensorMapInterleave, CUtensorMapSwizzle, CUtensorMapL2promotion, CUtensorMapFloatOOBfill);

static void encode(EncodeFn fn, CUtensorMap* m, int rank, const void* base, const cuuint64_t (&gd)[5], const cuuint64_t (&gs)[4],
                   const cuuint32_t (&bd)[5], CUtensorMapSwizzle sw) {
    cuuint32_t es[5] = {1, 1, 1, 1, 1};
    fn(m, CU_TENSOR_MAP_DATA_TYPE_BFLOAT16, rank, const_cast<void*>(base), gd, gs, bd, es, CU_TENSOR_MAP_INTERLEAVE_NONE, sw,
       CU_TENSOR_MAP_L2_PROMOTION_L2_128B, CU_TENSOR_MAP_FLOAT_OOB_FILL_NONE);
}

extern "C" void kernel_launch(void* const* d_in, const int* in_sizes, int n_in, void* d_out, int out_size) {
    const char* x = (const char*)d_in[0];
    const char* wqkv = (const char*)d_in[1];
    const char* wo = (const char*)d_in[2];
    const char* wg = (const char*)d_in[4];
    const char* wu = (const char*)d_in[5];
    const char* wd = (const char*)d_in[6];
    void* fnp = nullptr;
    cudaDriverEntryPointQueryResult qr;
    cudaGetDriverEntryPoint("cuTensorMapEncodeTiled", &fnp, cudaEnableDefault, &qr);
    EncodeFn fn = (EncodeFn)fnp;
    Maps maps;
    const char* lo = wg < wu ? wg : wu;
    const uint64_t diff = wg < wu ? (uint64_t)(wu - wg) : (uint64_t)(wg - wu);
    const CUtensorMapSwizzle S128 = CU_TENSOR_MAP_SWIZZLE_128B, S64 = CU_TENSOR_MAP_SWIZZLE_64B;
    encode(fn, &maps.x, 2, x, {512, 2048, 1, 1}, {1024, 0, 0}, {64, 128, 1, 1}, S128);
    encode(fn, &maps.gu, 3, lo, {1792, 512, 2, 1}, {3584, diff, 0}, {64, 64, 2, 1}, S128);
    encode(fn, &maps.kv, 3, wqkv, {512, 512, 3, 1}, {3072, 1024, 0}, {64, 64, 2, 1}, S128);
    encode(fn, &maps.q64, 3, wqkv, {32, 512, 48, 1}, {3072, 64, 0}, {32, 64, 2, 1}, S64);
    encode(fn, &maps.gu64, 3, lo, {1792, 512, 2, 1}, {3584, diff, 0}, {32, 64, 2, 1}, S64);
    encode(fn, &maps.wdw, 3, wd, {64, 1792, 8, 1}, {1024, 128, 0}, {64, 64, 2, 1}, S128);
    encode(fn, &maps.wow, 3, wo, {64, 512, 8}, {1024, 128}, {64, 64, 2}, S128);
    encode(fn, &maps.wdp, 5, wd, {512, 2, 4, 4, 56}, {1024, 8192, 2048, 32768}, {64, 2, 4, 4, 2}, S128);
    encode(fn, &maps.wdph, 5, wd, {512, 2, 4, 4, 56}, {1024, 8192, 2048, 32768}, {64, 2, 4, 4, 1}, S128);
    void* hx = nullptr;
    cudaGetSymbolAddress(&hx, g_hx);
    encode(fn, &maps.hx, 2, hx, {64, 16 * 4 * 5 * 128}, {128}, {64, 128}, S128);
    encode(fn, &maps.hx2, 2, hx, {64, 16 * 4 * 5 * 128}, {128}, {64, 256}, S128);
    cudaFuncSetAttribute(fused_kernel, cudaFuncAttributeMaxDynamicSharedMemorySize, SMEM_BYTES);
    cudaLaunchConfig_t cfg = {};
    cfg.gridDim = dim3(128);
    cfg.blockDim = dim3(384);
    cfg.dynamicSmemBytes = SMEM_BYTES;
    cfg.stream = cudaStreamPerThread;
    cudaLaunchAttribute at[1];
    at[0].id = cudaLaunchAttributeClusterDimension;
    at[0].val.clusterDim.x = 2; at[0].val.clusterDim.y = 1; at[0].val.clusterDim.z = 1;
    cfg.attrs = at;
    cfg.numAttrs = MC ? 1 : 0;
    cudaLaunchKernelEx(&cfg, fused_kernel, maps, (const __nv_bfloat16*)d_in[0], (const __nv_bfloat16*)d_in[7], wqkv, wg, wu, wd, wo, (__nv_bfloat16*)d_out);
}
```

```cpp
#include <cuda_runtime.h>
#include <cuda.h>
#include <cuda_bf16.h>
#include <stdint.h>

#define MC 0
#define PFMODE 1
#define PROF 0

namespace {

constexpr int kD = 512;
constexpr uint32_t OFF_X = 0, OFF_STG = 131072, OFF_RING = 147456, OFF_MISC = 229376;
constexpr uint32_t B_FULL = OFF_MISC, B_EMPTY = OFF_MISC + 40, B_XFULL = OFF_MISC + 80;
constexpr uint32_t B_GRDY = OFF_MISC + 152, B_KVDONE = OFF_MISC + 160, B_KVRDY = OFF_MISC + 168;
constexpr uint32_t B_HSENT = OFF_MISC + 176, B_XFREE = OFF_MISC + 200;
constexpr uint32_t OFF_EPOCH = OFF_MISC + 240, OFF_G = OFF_MISC + 256;
constexpr uint32_t B_AHEAD = OFF_MISC + 248;
constexpr uint32_t OFF_ONES = OFF_MISC + 768;
constexpr uint32_t B_EFULL = OFF_MISC + 896, B_EEMPTY = OFF_MISC + 928;
constexpr uint32_t SMEM_BYTES = OFF_MISC + 960;
constexpr uint32_t SPIN_GLOBAL = 1u << 14;

struct alignas(64) Maps { CUtensorMap x, gu, kv, q64, gu64, wdw, wow, wdp, wdph, hx, hx2; };

}

__device__ uint4 g_part[16 * 2 * 4 * 4 * 1024];
__device__ uint4 g_hx[16 * 4 * 5 * 1024];
__device__ uint4 g_lx[16 * 8 * 2 * 1024];
__device__ unsigned g_hflag[128 * 8];
__device__ uint4 g_gx[16 * 32];
__device__ float g_kvacc[2 * 8 * 4 * 272];
__device__ unsigned g_kvcnt[8 * 32];
__device__ unsigned g_epoch[128];
#define TS(role, idx)
#define TS2(idx)
#define TSG(role, idx)

namespace {

__device__ __forceinline__ void mbar_init(uint32_t bar, uint32_t cnt) { asm volatile("mbarrier.init.shared::cta.b64 [%0], %1;" :: "r"(bar), "r"(cnt) : "memory"); }
__device__ __forceinline__ void mbar_expect(uint32_t bar, uint32_t bytes) { asm volatile("mbarrier.arrive.expect_tx.shared::cta.b64 _, [%0], %1;" :: "r"(bar), "r"(bytes) : "memory"); }
__device__ __forceinline__ void mbar_arrive(uint32_t bar) { asm volatile("mbarrier.arrive.shared::cta.b64 _, [%0];" :: "r"(bar) : "memory"); }
__device__ __forceinline__ void mbar_arrive_cta(uint32_t bar, uint32_t cta) {
    asm volatile("{\n.reg .b32 ra;\nmapa.shared::cluster.u32 ra, %0, %1;\nmbarrier.arrive.shared::cluster.b64 _, [ra];\n}" :: "r"(bar), "r"(cta) : "memory");
}
__device__ __forceinline__ void mbar_wait(uint32_t bar, uint32_t parity) {
    asm volatile("{\n.reg .pred p;\n.reg .u32 c;\n"
                 "mbarrier.try_wait.parity.shared::cta.b64 p, [%0], %1;\n@p bra DONE;\n"
                 "mov.u32 c, 0;\nLAB_WAIT:\nmbarrier.try_wait.parity.shared::cta.b64 p, [%0], %1;\n@p bra DONE;\n"
                 "add.u32 c, c, 1;\nsetp.lt.u32 p, c, 65536;\n@p bra LAB_WAIT;\nDONE:\n}" :: "r"(bar), "r"(parity) : "memory");
}
__device__ __forceinline__ void tma2(uint32_t dst, const CUtensorMap* m, int c0, int c1, uint32_t bar) {
    asm volatile("cp.async.bulk.tensor.2d.shared::cluster.global.mbarrier::complete_tx::bytes [%0], [%1, {%3, %4}], [%2];"
        :: "r"(dst), "l"(m), "r"(bar), "r"(c0), "r"(c1) : "memory");
}
__device__ __forceinline__ void tmaw2(uint32_t dst, const CUtensorMap* m, int c0, int c1, uint32_t bar) {
    tma2(dst, m, c0, c1, bar);
}
__device__ __forceinline__ void tmaw3(uint32_t dst, const CUtensorMap* m, int c0, int c1, int c2, uint32_t bar) {
    asm volatile("cp.async.bulk.tensor.3d.shared::cluster.global.mbarrier::complete_tx::bytes [%0], [%1, {%3, %4, %5}], [%2];"
        :: "r"(dst), "l"(m), "r"(bar), "r"(c0), "r"(c1), "r"(c2) : "memory");
}
__device__ __forceinline__ void tmaw5(uint32_t dst, const CUtensorMap* m, int c0, int c4, uint32_t bar) {
    asm volatile("cp.async.bulk.tensor.5d.shared::cluster.global.mbarrier::complete_tx::bytes [%0], [%1, {%3, %5, %5, %5, %4}], [%2];"
        :: "r"(dst), "l"(m), "r"(bar), "r"(c0), "r"(c4), "r"(0) : "memory");
}
__device__ __forceinline__ void wg_fence() { asm volatile("wgmma.fence.sync.aligned;" ::: "memory"); }
__device__ __forceinline__ void wg_commit() { asm volatile("wgmma.commit_group.sync.aligned;" ::: "memory"); }
template <int N> __device__ __forceinline__ void wg_wait() { asm volatile("wgmma.wait_group.sync.aligned %0;" :: "n"(N) : "memory"); }
template <int N> __device__ __forceinline__ void pin(float (&d)[N]) {
#pragma unroll
    for (int i = 0; i < N; i++) asm volatile("" : "+f"(d[i]) :: "memory");
}
__device__ __forceinline__ uint32_t pack2(float lo, float hi) { uint32_t r; asm("cvt.rn.bf16x2.f32 %0, %1, %2;" : "=r"(r) : "f"(hi), "f"(lo)); return r; }
__device__ __forceinline__ uint32_t keep(uint32_t v) { asm volatile("" : "+r"(v)); return v; }
__device__ __forceinline__ uint32_t hadd2(uint32_t a, uint32_t b) { uint32_t r; asm("add.bf16x2 %0, %1, %2;" : "=r"(r) : "r"(a), "r"(b)); return r; }
__device__ __forceinline__ uint32_t hmul2(uint32_t a, uint32_t b) { uint32_t r; asm("mul.bf16x2 %0, %1, %2;" : "=r"(r) : "r"(a), "r"(b)); return r; }
__device__ __forceinline__ uint32_t phi2(float t0, float t1) {
    float e0, e1;
    asm("ex2.approx.ftz.f32 %0, %1;" : "=f"(e0) : "f"(t0 * 1.4426950408889634f));
    asm("ex2.approx.ftz.f32 %0, %1;" : "=f"(e1) : "f"(t1 * 1.4426950408889634f));
    uint32_t e = pack2(e0, e1), t = pack2(t0, t1), r;
    asm("min.bf16x2 %0, %0, %1;" : "+r"(e) : "r"(0x3f803f80u));
    asm("max.bf16x2 %0, %0, %1;" : "+r"(t) : "r"(0x35863586u));
    asm("add.bf16x2 %0, %1, %2;" : "=r"(r) : "r"(e), "r"(t));
    return r;
}
__device__ __forceinline__ void stsm4(uint32_t a, uint32_t r0, uint32_t r1, uint32_t r2, uint32_t r3) {
    asm volatile("stmatrix.sync.aligned.m8n8.x4.shared.b16 [%0], {%1,%2,%3,%4};" :: "r"(a), "r"(r0), "r"(r1), "r"(r2), "r"(r3) : "memory");
}
__device__ __forceinline__ float bf_lo(uint32_t w) { return __uint_as_float(w << 16); }
__device__ __forceinline__ float bf_hi(uint32_t w) { return __uint_as_float(w & 0xffff0000u); }
__device__ __forceinline__ void st_pkt(uint4* p, uint32_t w0, uint32_t w1, uint32_t w2, uint32_t w3) {
    asm volatile("{\n.reg .b64 lo, hi;\n.reg .b128 v;\nmov.b64 lo, {%1, %2};\nmov.b64 hi, {%3, %4};\nmov.b128 v, {lo, hi};\nst.relaxed.gpu.global.b128 [%0], v;\n}"
        :: "l"(p), "r"(w0), "r"(w1), "r"(w2), "r"(w3) : "memory");
}
__device__ __forceinline__ void ld_pkt(const uint4* p, uint32_t& w0, uint32_t& w1, uint32_t& w2, uint32_t& w3) {
    asm volatile("{\n.reg .b64 lo, hi;\n.reg .b128 v;\nld.relaxed.gpu.global.b128 v, [%4];\nmov.b128 {lo, hi}, v;\nmov.b64 {%0, %1}, lo;\nmov.b64 {%2, %3}, hi;\n}"
        : "=r"(w0), "=r"(w1), "=r"(w2), "=r"(w3) : "l"(p) : "memory");
}

__device__ __forceinline__ void wg_rs128(float (&d)[64], uint32_t a0, uint32_t a1, uint32_t a2, uint32_t a3, uint32_t blo, uint32_t bhi) {
    asm volatile("{\n.reg .b64 db;\nmov.b64 db, {%68, %69};\n"
        "wgmma.mma_async.sync.aligned.m64n128k16.f32.bf16.bf16 {%0,%1,%2,%3,%4,%5,%6,%7,%8,%9,%10,%11,%12,%13,%14,%15,%16,%17,%18,%19,%20,%21,%22,%23,%24,%25,%26,%27,%28,%29,%30,%31,%32,%33,%34,%35,%36,%37,%38,%39,%40,%41,%42,%43,%44,%45,%46,%47,%48,%49,%50,%51,%52,%53,%54,%55,%56,%57,%58,%59,%60,%61,%62,%63}, {%64,%65,%66,%67}, db, 1, 1, 1, 1;\n}\n"
        : "+f"(d[0]),"+f"(d[1]),"+f"(d[2]),"+f"(d[3]),"+f"(d[4]),"+f"(d[5]),"+f"(d[6]),"+f"(d[7]),"+f"(d[8]),"+f"(d[9]),"+f"(d[10]),"+f"(d[11]),"+f"(d[12]),"+f"(d[13]),"+f"(d[14]),"+f"(d[15]),"+f"(d[16]),"+f"(d[17]),"+f"(d[18]),"+f"(d[19]),"+f"(d[20]),"+f"(d[21]),"+f"(d[22]),"+f"(d[23]),"+f"(d[24]),"+f"(d[25]),"+f"(d[26]),"+f"(d[27]),"+f"(d[28]),"+f"(d[29]),"+f"(d[30]),"+f"(d[31]),"+f"(d[32]),"+f"(d[33]),"+f"(d[34]),"+f"(d[35]),"+f"(d[36]),"+f"(d[37]),"+f"(d[38]),"+f"(d[39]),"+f"(d[40]),"+f"(d[41]),"+f"(d[42]),"+f"(d[43]),"+f"(d[44]),"+f"(d[45]),"+f"(d[46]),"+f"(d[47]),"+f"(d[48]),"+f"(d[49]),"+f"(d[50]),"+f"(d[51]),"+f"(d[52]),"+f"(d[53]),"+f"(d[54]),"+f"(d[55]),"+f"(d[56]),"+f"(d[57]),"+f"(d[58]),"+f"(d[59]),"+f"(d[60]),"+f"(d[61]),"+f"(d[62]),"+f"(d[63])
        : "r"(a0), "r"(a1), "r"(a2), "r"(a3), "r"(blo), "r"(bhi));
}
__device__ __forceinline__ void wg_ss128(float (&d)[64], uint32_t alo, uint32_t ahi, uint32_t blo, uint32_t bhi) {
    asm volatile("{\n.reg .b64 da, db;\nmov.b64 da, {%64, %65};\nmov.b64 db, {%66, %67};\n"
        "wgmma.mma_async.sync.aligned.m64n128k16.f32.bf16.bf16 {%0,%1,%2,%3,%4,%5,%6,%7,%8,%9,%10,%11,%12,%13,%14,%15,%16,%17,%18,%19,%20,%21,%22,%23,%24,%25,%26,%27,%28,%29,%30,%31,%32,%33,%34,%35,%36,%37,%38,%39,%40,%41,%42,%43,%44,%45,%46,%47,%48,%49,%50,%51,%52,%53,%54,%55,%56,%57,%58,%59,%60,%61,%62,%63}, da, db, 1, 1, 1, 0, 1;\n}\n"
        : "+f"(d[0]),"+f"(d[1]),"+f"(d[2]),"+f"(d[3]),"+f"(d[4]),"+f"(d[5]),"+f"(d[6]),"+f"(d[7]),"+f"(d[8]),"+f"(d[9]),"+f"(d[10]),"+f"(d[11]),"+f"(d[12]),"+f"(d[13]),"+f"(d[14]),"+f"(d[15]),"+f"(d[16]),"+f"(d[17]),"+f"(d[18]),"+f"(d[19]),"+f"(d[20]),"+f"(d[21]),"+f"(d[22]),"+f"(d[23]),"+f"(d[24]),"+f"(d[25]),"+f"(d[26]),"+f"(d[27]),"+f"(d[28]),"+f"(d[29]),"+f"(d[30]),"+f"(d[31]),"+f"(d[32]),"+f"(d[33]),"+f"(d[34]),"+f"(d[35]),"+f"(d[36]),"+f"(d[37]),"+f"(d[38]),"+f"(d[39]),"+f"(d[40]),"+f"(d[41]),"+f"(d[42]),"+f"(d[43]),"+f"(d[44]),"+f"(d[45]),"+f"(d[46]),"+f"(d[47]),"+f"(d[48]),"+f"(d[49]),"+f"(d[50]),"+f"(d[51]),"+f"(d[52]),"+f"(d[53]),"+f"(d[54]),"+f"(d[55]),"+f"(d[56]),"+f"(d[57]),"+f"(d[58]),"+f"(d[59]),"+f"(d[60]),"+f"(d[61]),"+f"(d[62]),"+f"(d[63])
        : "r"(alo), "r"(ahi), "r"(blo), "r"(bhi));
}
__device__ __forceinline__ void wg_ss128_z(float (&d)[64], uint32_t alo, uint32_t ahi, uint32_t blo, uint32_t bhi) {
    asm volatile("{\n.reg .b64 da, db;\nmov.b64 da, {%64, %65};\nmov.b64 db, {%66, %67};\n"
        "wgmma.mma_async.sync.aligned.m64n128k16.f32.bf16.bf16 {%0,%1,%2,%3,%4,%5,%6,%7,%8,%9,%10,%11,%12,%13,%14,%15,%16,%17,%18,%19,%20,%21,%22,%23,%24,%25,%26,%27,%28,%29,%30,%31,%32,%33,%34,%35,%36,%37,%38,%39,%40,%41,%42,%43,%44,%45,%46,%47,%48,%49,%50,%51,%52,%53,%54,%55,%56,%57,%58,%59,%60,%61,%62,%63}, da, db, 0, 1, 1, 0, 1;\n}\n"
        : "=f"(d[0]),"=f"(d[1]),"=f"(d[2]),"=f"(d[3]),"=f"(d[4]),"=f"(d[5]),"=f"(d[6]),"=f"(d[7]),"=f"(d[8]),"=f"(d[9]),"=f"(d[10]),"=f"(d[11]),"=f"(d[12]),"=f"(d[13]),"=f"(d[14]),"=f"(d[15]),"=f"(d[16]),"=f"(d[17]),"=f"(d[18]),"=f"(d[19]),"=f"(d[20]),"=f"(d[21]),"=f"(d[22]),"=f"(d[23]),"=f"(d[24]),"=f"(d[25]),"=f"(d[26]),"=f"(d[27]),"=f"(d[28]),"=f"(d[29]),"=f"(d[30]),"=f"(d[31]),"=f"(d[32]),"=f"(d[33]),"=f"(d[34]),"=f"(d[35]),"=f"(d[36]),"=f"(d[37]),"=f"(d[38]),"=f"(d[39]),"=f"(d[40]),"=f"(d[41]),"=f"(d[42]),"=f"(d[43]),"=f"(d[44]),"=f"(d[45]),"=f"(d[46]),"=f"(d[47]),"=f"(d[48]),"=f"(d[49]),"=f"(d[50]),"=f"(d[51]),"=f"(d[52]),"=f"(d[53]),"=f"(d[54]),"=f"(d[55]),"=f"(d[56]),"=f"(d[57]),"=f"(d[58]),"=f"(d[59]),"=f"(d[60]),"=f"(d[61]),"=f"(d[62]),"=f"(d[63])
        : "r"(alo), "r"(ahi), "r"(blo), "r"(bhi));
}
__device__ __forceinline__ void wg_ss64(float (&d)[32], uint32_t alo, uint32_t ahi, uint32_t blo, uint32_t bhi) {
    asm volatile("{\n.reg .b64 da, db;\nmov.b64 da, {%32, %33};\nmov.b64 db, {%34, %35};\n"
        "wgmma.mma_async.sync.aligned.m64n64k16.f32.bf16.bf16 {%0,%1,%2,%3,%4,%5,%6,%7,%8,%9,%10,%11,%12,%13,%14,%15,%16,%17,%18,%19,%20,%21,%22,%23,%24,%25,%26,%27,%28,%29,%30,%31}, da, db, 1, 1, 1, 0, 1;\n}\n"
        : "+f"(d[0]),"+f"(d[1]),"+f"(d[2]),"+f"(d[3]),"+f"(d[4]),"+f"(d[5]),"+f"(d[6]),"+f"(d[7]),"+f"(d[8]),"+f"(d[9]),"+f"(d[10]),"+f"(d[11]),"+f"(d[12]),"+f"(d[13]),"+f"(d[14]),"+f"(d[15]),"+f"(d[16]),"+f"(d[17]),"+f"(d[18]),"+f"(d[19]),"+f"(d[20]),"+f"(d[21]),"+f"(d[22]),"+f"(d[23]),"+f"(d[24]),"+f"(d[25]),"+f"(d[26]),"+f"(d[27]),"+f"(d[28]),"+f"(d[29]),"+f"(d[30]),"+f"(d[31])
        : "r"(alo), "r"(ahi), "r"(blo), "r"(bhi));
}
__device__ __forceinline__ void wg_ss64_z(float (&d)[32], uint32_t alo, uint32_t ahi, uint32_t blo, uint32_t bhi) {
    asm volatile("{\n.reg .b64 da, db;\nmov.b64 da, {%32, %33};\nmov.b64 db, {%34, %35};\n"
        "wgmma.mma_async.sync.aligned.m64n64k16.f32.bf16.bf16 {%0,%1,%2,%3,%4,%5,%6,%7,%8,%9,%10,%11,%12,%13,%14,%15,%16,%17,%18,%19,%20,%21,%22,%23,%24,%25,%26,%27,%28,%29,%30,%31}, da, db, 0, 1, 1, 0, 1;\n}\n"
        : "=f"(d[0]),"=f"(d[1]),"=f"(d[2]),"=f"(d[3]),"=f"(d[4]),"=f"(d[5]),"=f"(d[6]),"=f"(d[7]),"=f"(d[8]),"=f"(d[9]),"=f"(d[10]),"=f"(d[11]),"=f"(d[12]),"=f"(d[13]),"=f"(d[14]),"=f"(d[15]),"=f"(d[16]),"=f"(d[17]),"=f"(d[18]),"=f"(d[19]),"=f"(d[20]),"=f"(d[21]),"=f"(d[22]),"=f"(d[23]),"=f"(d[24]),"=f"(d[25]),"=f"(d[26]),"=f"(d[27]),"=f"(d[28]),"=f"(d[29]),"=f"(d[30]),"=f"(d[31])
        : "r"(alo), "r"(ahi), "r"(blo), "r"(bhi));
}
__device__ __forceinline__ void wg_ss64t(float (&d)[32], uint32_t alo, uint32_t ahi, uint32_t blo, uint32_t bhi) {
    asm volatile("{\n.reg .b64 da, db;\nmov.b64 da, {%32, %33};\nmov.b64 db, {%34, %35};\n"
        "wgmma.mma_async.sync.aligned.m64n64k16.f32.bf16.bf16 {%0,%1,%2,%3,%4,%5,%6,%7,%8,%9,%10,%11,%12,%13,%14,%15,%16,%17,%18,%19,%20,%21,%22,%23,%24,%25,%26,%27,%28,%29,%30,%31}, da, db, 1, 1, 1, 1, 1;\n}\n"
        : "+f"(d[0]),"+f"(d[1]),"+f"(d[2]),"+f"(d[3]),"+f"(d[4]),"+f"(d[5]),"+f"(d[6]),"+f"(d[7]),"+f"(d[8]),"+f"(d[9]),"+f"(d[10]),"+f"(d[11]),"+f"(d[12]),"+f"(d[13]),"+f"(d[14]),"+f"(d[15]),"+f"(d[16]),"+f"(d[17]),"+f"(d[18]),"+f"(d[19]),"+f"(d[20]),"+f"(d[21]),"+f"(d[22]),"+f"(d[23]),"+f"(d[24]),"+f"(d[25]),"+f"(d[26]),"+f"(d[27]),"+f"(d[28]),"+f"(d[29]),"+f"(d[30]),"+f"(d[31])
        : "r"(alo), "r"(ahi), "r"(blo), "r"(bhi));
}
__device__ __forceinline__ void wg_ss64t_z(float (&d)[32], uint32_t alo, uint32_t ahi, uint32_t blo, uint32_t bhi) {
    asm volatile("{\n.reg .b64 da, db;\nmov.b64 da, {%32, %33};\nmov.b64 db, {%34, %35};\n"
        "wgmma.mma_async.sync.aligned.m64n64k16.f32.bf16.bf16 {%0,%1,%2,%3,%4,%5,%6,%7,%8,%9,%10,%11,%12,%13,%14,%15,%16,%17,%18,%19,%20,%21,%22,%23,%24,%25,%26,%27,%28,%29,%30,%31}, da, db, 0, 1, 1, 1, 1;\n}\n"
        : "=f"(d[0]),"=f"(d[1]),"=f"(d[2]),"=f"(d[3]),"=f"(d[4]),"=f"(d[5]),"=f"(d[6]),"=f"(d[7]),"=f"(d[8]),"=f"(d[9]),"=f"(d[10]),"=f"(d[11]),"=f"(d[12]),"=f"(d[13]),"=f"(d[14]),"=f"(d[15]),"=f"(d[16]),"=f"(d[17]),"=f"(d[18]),"=f"(d[19]),"=f"(d[20]),"=f"(d[21]),"=f"(d[22]),"=f"(d[23]),"=f"(d[24]),"=f"(d[25]),"=f"(d[26]),"=f"(d[27]),"=f"(d[28]),"=f"(d[29]),"=f"(d[30]),"=f"(d[31])
        : "r"(alo), "r"(ahi), "r"(blo), "r"(bhi));
}
__device__ __forceinline__ void wg_ss8t(float (&d)[4], uint32_t alo, uint32_t ahi, uint32_t blo, uint32_t bhi) {
    asm volatile("{\n.reg .b64 da, db;\nmov.b64 da, {%4, %5};\nmov.b64 db, {%6, %7};\n"
        "wgmma.mma_async.sync.aligned.m64n8k16.f32.bf16.bf16 {%0,%1,%2,%3}, da, db, 1, 1, 1, 1, 0;\n}\n"
        : "+f"(d[0]),"+f"(d[1]),"+f"(d[2]),"+f"(d[3])
        : "r"(alo), "r"(ahi), "r"(blo), "r"(bhi));
}
__device__ __forceinline__ void wg_ss8t_z(float (&d)[4], uint32_t alo, uint32_t ahi, uint32_t blo, uint32_t bhi) {
    asm volatile("{\n.reg .b64 da, db;\nmov.b64 da, {%4, %5};\nmov.b64 db, {%6, %7};\n"
        "wgmma.mma_async.sync.aligned.m64n8k16.f32.bf16.bf16 {%0,%1,%2,%3}, da, db, 0, 1, 1, 1, 0;\n}\n"
        : "=f"(d[0]),"=f"(d[1]),"=f"(d[2]),"=f"(d[3])
        : "r"(alo), "r"(ahi), "r"(blo), "r"(bhi));
}
__device__ __forceinline__ void wg_rs24_z(float (&d)[12], uint32_t a0, uint32_t a1, uint32_t a2, uint32_t a3, uint32_t blo, uint32_t bhi) {
    asm volatile("{\n.reg .b64 db;\nmov.b64 db, {%16, %17};\n"
        "wgmma.mma_async.sync.aligned.m64n24k16.f32.bf16.bf16 {%0,%1,%2,%3,%4,%5,%6,%7,%8,%9,%10,%11}, {%12,%13,%14,%15}, db, 0, 1, 1, 0;\n}\n"
        : "=f"(d[0]),"=f"(d[1]),"=f"(d[2]),"=f"(d[3]),"=f"(d[4]),"=f"(d[5]),"=f"(d[6]),"=f"(d[7]),"=f"(d[8]),"=f"(d[9]),"=f"(d[10]),"=f"(d[11])
        : "r"(a0), "r"(a1), "r"(a2), "r"(a3), "r"(blo), "r"(bhi));
}

constexpr uint32_t DH128 = 64u | 0x40000000u;
constexpr uint32_t DH64 = 32u | 0x80000000u;
constexpr uint32_t LBO4K = (4096u >> 4) << 16, LBO8K = (8192u >> 4) << 16, LBO1 = 1u << 16;

template <bool SW64, bool FIRST> __device__ __forceinline__ void g1_issue(float (&acc)[64], uint32_t alo, uint32_t blo) {
    wg_fence();
#pragma unroll
    for (int k = 0; k < 4; k++) {
        if (FIRST && k == 0) wg_ss128_z(acc, alo, DH128, blo, SW64 ? DH64 : DH128);
        else wg_ss128(acc, alo + 2 * k, DH128, blo + (SW64 ? 64 * k : 128 * k), SW64 ? DH64 : DH128);
    }
    wg_commit();
}

template <int N> __device__ __forceinline__ void stash(uint32_t base, uint32_t sw, const uint32_t (&f)[N]) {
#pragma unroll
    for (int t = 0; t < N / 4; t++) stsm4(base + ((sw ^ (2 * t)) << 4), f[4 * t], f[4 * t + 1], f[4 * t + 2], f[4 * t + 3]);
}

template <int V0, int V1, int N> __device__ __forceinline__ void send_frag(const uint32_t (&f)[N], uint4* p, uint32_t tag) {
#pragma unroll
    for (int v = V0; v < V1; v++) st_pkt(p + v * 32, (f[4 * v] & ~1u) | tag, f[4 * v + 1], f[4 * v + 2], f[4 * v + 3]);
}
template <int H0, int H1, int N> __device__ __forceinline__ void send_h(const uint32_t (&f)[N], uint4* p) {
#pragma unroll
    for (int h = H0; h < H1; h++) {
        p[4 * h] = make_uint4(f[8 * h], f[8 * h + 2], f[8 * h + 4], f[8 * h + 6]);
        p[4 * h + 64] = make_uint4(f[8 * h + 1], f[8 * h + 3], f[8 * h + 5], f[8 * h + 7]);
    }
}
template <int O, int N, int M> __device__ __forceinline__ void pack_sub(uint32_t (&f)[N], const float (&acc)[M]) {
#pragma unroll
    for (int i = 0; i < N; i++) f[i] = keep(pack2(acc[O + 2 * i], acc[O + 2 * i + 1]));
}
template <int N> __device__ __forceinline__ void recv_issue(uint32_t (&q)[N], const uint4* p) {
#pragma unroll
    for (int v = 0; v < N / 4; v++) ld_pkt(p + v * 32, q[4 * v], q[4 * v + 1], q[4 * v + 2], q[4 * v + 3]);
}
template <int N> __device__ __forceinline__ void recv_check(uint32_t (&q)[N], const uint4* p, uint32_t tag) {
    uint32_t it = 0;
    while (true) {
        uint32_t bad = 0;
#pragma unroll
        for (int v = 0; v < N / 4; v++) bad |= q[4 * v] ^ tag;
        if (__all_sync(0xffffffffu, (bad & 1u) == 0) || ++it > SPIN_GLOBAL) break;
        recv_issue(q, p);
    }
}
__device__ __forceinline__ void accum(const uint32_t (&q)[32], float (&sum)[64]) {
#pragma unroll
    for (int i = 0; i < 32; i++) { sum[2 * i] += bf_lo(q[i]); sum[2 * i + 1] += bf_hi(q[i]); }
}

}

__global__ void __launch_bounds__(384, 1)
fused_kernel(const __grid_constant__ Maps maps, const __nv_bfloat16* __restrict__ xg, const __nv_bfloat16* __restrict__ gate_w,
             const char* __restrict__ pf_qkv, const char* __restrict__ pf_g, const char* __restrict__ pf_u,
             const char* __restrict__ pf_d, const char* __restrict__ pf_o, __nv_bfloat16* __restrict__ out) {
    extern __shared__ __align__(1024) uint8_t smem_raw[];
    const uint32_t sb = (uint32_t)__cvta_generic_to_shared(smem_raw);
    const int tid = threadIdx.x, lane = tid & 31;
    const int warp = __shfl_sync(0xffffffffu, tid >> 5, 0);
    const int j = (blockIdx.x >> 1) & 7;
    const int r = ((blockIdx.x >> 4) << 1) | (blockIdx.x & 1);
    const uint32_t rank = blockIdx.x & 1;

    if (warp == 0) { TSG(0, 30); TS(0, 0); }
    if (tid == 256) {
        for (int i = 0; i < 5; i++) { mbar_init(sb + B_FULL + 8 * i, 1); mbar_init(sb + B_EMPTY + 8 * i, MC ? 4 : 2); }
        for (int i = 0; i < 9; i++) mbar_init(sb + B_XFULL + 8 * i, 1);
        asm volatile("fence.mbarrier_init.release.cluster;" ::: "memory");
        mbar_expect(sb + B_XFULL, 16384);
        tma2(sb + OFF_X, &maps.x, 0, r * 128, sb + B_XFULL);
        TS2(0);
        mbar_expect(sb + B_FULL, 16384);
        tmaw3(sb + OFF_RING, &maps.gu, 224 * j, 0, 0, sb + B_FULL);
        TS2(1);
        mbar_expect(sb + B_FULL + 8, 16384);
        tmaw3(sb + OFF_RING + 16384, &maps.kv, 64 * j, 0, 1, sb + B_FULL + 8);
    } else if (tid == 288) {
        for (int i = 0; i < 3; i++) mbar_init(sb + B_HSENT + 8 * i, 8);
        for (int i = 0; i < 4; i++) { mbar_init(sb + B_EFULL + 8 * i, 1); mbar_init(sb + B_EEMPTY + 8 * i, MC ? 4 : 2); }
        mbar_init(sb + B_XFREE, 2); mbar_init(sb + B_XFREE + 8, 2); mbar_init(sb + B_XFREE + 16, 2);
        mbar_init(sb + B_AHEAD, 1); mbar_init(sb + B_GRDY, 1); mbar_init(sb + B_KVDONE, 8); mbar_init(sb + B_KVRDY, 2);
        asm volatile("fence.mbarrier_init.release.cluster;" ::: "memory");
    } else if (warp == 10 && lane < 10) {
        asm volatile("prefetch.tensormap [%0];" :: "l"(&maps.gu + lane) : "memory");
    }
    __syncthreads();

    if (warp >= 8) {
        asm volatile("setmaxnreg.dec.sync.aligned.u32 56;");
        if (warp == 8) {
            if (lane == 0) {
                int slot = MC ? 0 : 2, ph = 1;
                uint32_t full, dst;
                if (!MC) { mbar_expect(sb + B_XFULL + 8, 16384); tma2(sb + OFF_X + 16384, &maps.x, 64, r * 128, sb + B_XFULL + 8); }
#define P_BEGIN(S, BYTES) full = sb + B_FULL + 8 * slot; dst = sb + OFF_RING + slot * 16384; \
                mbar_wait(sb + B_EMPTY + 8 * slot, ph); TS2(S); mbar_expect(full, BYTES); if (!MC || (((S) ^ rank) & 1) == 0)
#define P_END() if (++slot == 5) { slot = 0; ph ^= 1; }
                for (int s = MC ? 0 : 2; s < 16; s++) {
                    P_BEGIN(s, 16384) {
                        const int sw = s == 13 ? 14 : s == 14 ? 13 : s;
                        if (sw & 1) tmaw3(dst, &maps.kv, 64 * j, 32 * (sw - 1), 1, full);
                        else tmaw3(dst, &maps.gu, 224 * j, 32 * sw, 0, full);
                    }
                    const int xb = (s == 4) ? 3 : (s == 10) ? 7 : !(s & 1) ? 0 : (s < 5) ? (s + 1) / 2 : (s <= 9) ? (s + 3) / 2 : 0;
                    if (xb) { mbar_expect(sb + B_XFULL + 8 * xb, 16384); tma2(sb + OFF_X + xb * 16384, &maps.x, 64 * xb, r * 128, sb + B_XFULL + 8 * xb); }
                    P_END()
                }
                for (int s = 0; s < 24; s++) {
                    P_BEGIN(16 + s, 16384) {
                        if ((s >> 3) == 1) {
                            tmaw3(dst, &maps.q64, 0, 64 * (s & 7), 2 * j, full);
                            tmaw3(dst + 8192, &maps.gu64, 224 * j + 192, 64 * (s & 7), 0, full);
                        } else {
                            tmaw3(dst, &maps.gu, 224 * j + 64 + 4 * (s & 16), 64 * (s & 7), 0, full);
                        }
                    }
                    P_END()
                }
                const int p = j >> 1;
#pragma unroll 1
                for (int t = 0; t < 18; t++) {
                    const int u = (int)((t < 16 ? 0x2187658704653210ull >> (4 * t) : 0x43ull >> (4 * (t - 16))) & 15);
                    const int q = t >= 9, sl = t - 9 * q;
                    const int cw = (j & 1) * 4 + ((p & 2) ^ ((t == 7 || t > 9) ? 0 : 2)), cc = 64 * cw;
                    if (sl < 5) {
                        full = sb + B_FULL + 8 * sl; dst = sb + OFF_RING + sl * 16384;
                        mbar_wait(sb + B_EMPTY + 8 * sl, q ^ 1);
                    } else {
                        full = sb + B_EFULL + 8 * (sl - 5); dst = sb + OFF_X + (sl == 7 ? 8 : sl == 8 ? 7 : sl) * 16384;
                        mbar_wait(sb + B_EEMPTY + 8 * (sl - 5), q);
                    }
                    TS2(40 + t);
                    mbar_expect(full, 16384);
                    if (!MC || ((t ^ rank) & 1) == 0) {
                        if (u == 4) {
                            tmaw5(dst, &maps.wdph, cc, 14 * p + 6, full); tmaw5(dst + 4096, &maps.wdph, cc, 14 * p + 13, full);
                            tmaw5(dst + 8192, &maps.wdph, cc + 64, 14 * p + 6, full); tmaw5(dst + 12288, &maps.wdph, cc + 64, 14 * p + 13, full);
                        } else if (u > 4) {
                            const int js = u > 6 ? j ^ 1 : j;
                            tmaw3(dst, (u & 1) ? &maps.wow : &maps.wdw, 0, (u & 1) ? 64 * js : 224 * js + 128, cw, full);
                        } else {
                            const int g = 14 * p + 7 * (u & 1) + (u & 2);
                            tmaw5(dst, &maps.wdp, cc, g, full); tmaw5(dst + 8192, &maps.wdp, cc + 64, g, full);
                        }
                    }
                }
            }
        } else if (warp < 11) {
            const int hx = warp - 9;
            uint32_t epoch;
            asm volatile("ld.relaxed.gpu.global.u32 %0, [%1];" : "=r"(epoch) : "l"(g_epoch + blockIdx.x) : "memory");
            {
                const uint4* xr = (const uint4*)(xg + (size_t)(r * 128 + j * 16 + hx * 8) * kD) + lane;
                const uint4 wa = __ldg((const uint4*)gate_w + lane), wb = __ldg((const uint4*)gate_w + 32 + lane);
                const uint32_t tag = (epoch + 1) & 1;
                uint4* gp = g_gx + r * 32;
                if (lane < 2) st_pkt(gp + j * 4 + hx * 2 + lane, tag ^ 1, 0, 0, 0);
                float s[8];
#pragma unroll
                for (int i0 = 0; i0 < 8; i0 += 4) {
                    uint4 va[4], vb[4];
#pragma unroll
                    for (int i = 0; i < 4; i++) { va[i] = __ldg(xr + (i0 + i) * 64); vb[i] = __ldg(xr + (i0 + i) * 64 + 32); }
#pragma unroll
                    for (int i = 0; i < 4; i++) {
                        float t0 = bf_lo(va[i].x) * bf_lo(wa.x), t1 = bf_hi(va[i].x) * bf_hi(wa.x);
                        t0 = fmaf(bf_lo(va[i].y), bf_lo(wa.y), t0); t1 = fmaf(bf_hi(va[i].y), bf_hi(wa.y), t1);
                        t0 = fmaf(bf_lo(va[i].z), bf_lo(wa.z), t0); t1 = fmaf(bf_hi(va[i].z), bf_hi(wa.z), t1);
                        t0 = fmaf(bf_lo(va[i].w), bf_lo(wa.w), t0); t1 = fmaf(bf_hi(va[i].w), bf_hi(wa.w), t1);
                        t0 = fmaf(bf_lo(vb[i].x), bf_lo(wb.x), t0); t1 = fmaf(bf_hi(vb[i].x), bf_hi(wb.x), t1);
                        t0 = fmaf(bf_lo(vb[i].y), bf_lo(wb.y), t0); t1 = fmaf(bf_hi(vb[i].y), bf_hi(wb.y), t1);
                        t0 = fmaf(bf_lo(vb[i].z), bf_lo(wb.z), t0); t1 = fmaf(bf_hi(vb[i].z), bf_hi(wb.z), t1);
                        t0 = fmaf(bf_lo(vb[i].w), bf_lo(wb.w), t0); t1 = fmaf(bf_hi(vb[i].w), bf_hi(wb.w), t1);
                        s[i0 + i] = t0 + t1;
                    }
                }
#pragma unroll
                for (int i = 0; i < 8; i++) {
#pragma unroll
                    for (int o = 16; o; o >>= 1) s[i] += __shfl_xor_sync(0xffffffffu, s[i], o);
                    s[i] = 1.f / (1.f + __expf(-s[i]));
                }
                if (lane < 2) {
                    const float v0 = lane ? s[4] : s[0], v1 = lane ? s[5] : s[1], v2 = lane ? s[6] : s[2], v3 = lane ? s[7] : s[3];
                    st_pkt(gp + j * 4 + hx * 2 + lane, (__float_as_uint(v0) & ~1u) | tag, __float_as_uint(v1), __float_as_uint(v2), __float_as_uint(v3));
                }
                if (hx == 1) {
                    asm volatile("st.shared.u32 [%0], %1;" :: "r"(sb + OFF_ONES + lane * 4), "r"(0x3f803f80u) : "memory");
                    asm volatile("fence.proxy.async.shared::cta;" ::: "memory");
                }
                asm volatile("bar.sync 3, 96;" ::: "memory");
                if (hx == 0) {
                    uint32_t q[4];
                    recv_issue(q, gp + lane);
                    recv_check(q, gp + lane, tag);
                    asm volatile("st.shared.v4.u32 [%0], {%1,%2,%3,%4};" :: "r"(sb + OFF_G + lane * 16), "r"(q[0]), "r"(q[1]), "r"(q[2]), "r"(q[3]) : "memory");
                    if (lane == 0) {
                        asm volatile("st.shared.u32 [%0], %1;" :: "r"(sb + OFF_EPOCH), "r"(epoch) : "memory");
                        g_epoch[blockIdx.x] = epoch + 1;
                    }
                    __syncwarp();
                    if (lane == 0) mbar_arrive(sb + B_GRDY);
                } else {
                    if (r == 0) {
                        float4* zp = (float4*)(g_kvacc + (((epoch & 1) ^ 1) * 8 + j) * 4 * 272);
                        for (int i = lane; i < 272; i += 32) zp[i] = make_float4(0.f, 0.f, 0.f, 0.f);
                    }
                }
            }
            TS(2 + hx, 1);
#define PUBLISH_H(B) do { mbar_wait(sb + B_HSENT + 8 * (B), 0); if (lane == 0) { \
                asm volatile("st.release.gpu.global.u32 [%0], %1;" :: "l"(g_hflag + (r * 8 + j) * 8 + (B)), "r"(epoch + 1) : "memory"); } __syncwarp(); } while (0)
            if (hx == 1) {
#pragma unroll 1
                for (int b = 0; b < 3; b++) { PUBLISH_H(b); TS(3, 5 + b); }
            } else {
                const float* accp = g_kvacc + ((epoch & 1) * 8 + j) * 4 * 272;
                unsigned* cnt = g_kvcnt + j * 32;
                mbar_wait(sb + B_KVDONE, 0);
                TS(2, 5);
                if (lane == 0) asm volatile("red.release.gpu.global.add.u32 [%0], 1;" :: "l"(cnt) : "memory");
                __syncwarp();
                TS(2, 2);
                {
                    const unsigned target = 16u * (epoch + 1);
                    uint32_t it = 0, v;
                    do {
                        asm volatile("ld.acquire.gpu.global.u32 %0, [%1];" : "=r"(v) : "l"(cnt) : "memory");
                    } while ((int)(v - target) < 0 && ++it < SPIN_GLOBAL);
                }
                TS(2, 3);
#pragma unroll
                for (int h = 0; h < 4; h++) {
                    const float4 d0 = __ldcg((const float4*)(accp + h * 272) + lane);
                    const float4 d1 = __ldcg((const float4*)(accp + h * 272 + 128) + lane);
                    const float2 z0 = __ldcg((const float2*)(accp + h * 272 + 256) + (lane & 3));
                    const float2 z1 = __ldcg((const float2*)(accp + h * 272 + 264) + (lane & 3));
                    const uint32_t ba = sb + OFF_STG + h * 768 + lane * 4;
                    asm volatile("st.shared.u32 [%0], %1;" :: "r"(ba), "r"(pack2(d0.x, d0.y)) : "memory");
                    asm volatile("st.shared.u32 [%0], %1;" :: "r"(ba + 128), "r"(pack2(d1.x, d1.y)) : "memory");
                    asm volatile("st.shared.u32 [%0], %1;" :: "r"(ba + 256), "r"(pack2(d0.z, d0.w)) : "memory");
                    asm volatile("st.shared.u32 [%0], %1;" :: "r"(ba + 384), "r"(pack2(d1.z, d1.w)) : "memory");
                    asm volatile("st.shared.u32 [%0], %1;" :: "r"(ba + 512), "r"(pack2(z0.x, z0.y)) : "memory");
                    asm volatile("st.shared.u32 [%0], %1;" :: "r"(ba + 640), "r"(pack2(z1.x, z1.y)) : "memory");
                }
                asm volatile("fence.proxy.async.shared::cta;" ::: "memory");
                __syncwarp();
                if (lane == 0) mbar_arrive(sb + B_KVRDY);
                TS(2, 4);
            }
        } else {
            uint32_t epoch;
            asm volatile("ld.relaxed.gpu.global.u32 %0, [%1];" : "=r"(epoch) : "l"(g_epoch + blockIdx.x) : "memory");
            asm volatile("bar.arrive 3, 96;" :: "r"(epoch) : "memory");
            const int b = blockIdx.x, p = j >> 1;
            mbar_wait(sb + B_XFULL, 0);
#pragma unroll 1
            for (int kb = 1; kb < 8; kb++) {
                mbar_wait(sb + B_XFULL + 8 * kb, 0);
                const char* base = kb < 3 ? pf_g : kb < 5 ? pf_u : kb == 5 ? pf_qkv : pf_d;
                const int off = kb == 5 ? b * 12288 : b * 14336 + ((kb < 5 ? kb - 1 : kb) & 1) * 7168;
                asm volatile("prefetch.global.L2 [%0];" :: "l"(base + off + lane * 128));
                if (kb == 5 || lane < 24) asm volatile("prefetch.global.L2 [%0];" :: "l"(base + off + 4096 + lane * 128));
                if (kb == 5) asm volatile("prefetch.global.L2 [%0];" :: "l"(base + off + 8192 + lane * 128));
                if (kb == 7) asm volatile("prefetch.global.L2 [%0];" :: "l"(pf_o + b * 4096 + lane * 128));
            }
            {
                uint4* mb = g_part + (size_t)(r * 2 + (j & 1)) * 16384 + (((p ^ 1) * 4 + p) << 10) + lane;
#pragma unroll 1
                for (int i = 0; i < 32; i++) { st_pkt(mb + i * 32, epoch & 1, 0, 0, 0); __nanosleep(40); }
                __syncwarp();
                if (lane == 0) mbar_arrive(sb + B_KVRDY);
            }
            {
                const uint32_t want = epoch + 1;
                const int hrow = (r * 4 + p) * 5 * 128;
                const unsigned* fl = g_hflag + (r * 8 + (j & 6)) * 8 + (lane & 15);
                uint32_t it = 0;
                int i = 0;
                mbar_wait(sb + B_HSENT + 8, 0);
#pragma unroll 1
                while (i < 3 && ++it < SPIN_GLOBAL) {
                    uint32_t v;
                    asm volatile("ld.acquire.gpu.global.u32 %0, [%1];" : "=r"(v) : "l"(fl) : "memory");
                    const uint32_t rdy = __ballot_sync(0xffffffffu, v == want);
#pragma unroll 1
                    while (i < 3 && ((rdy >> i) & 0x101u) == 0x101u) {
                        mbar_wait(sb + B_XFREE + 8 * i, 0);
                        if (lane == 0) {
                            asm volatile("fence.proxy.async.global;" ::: "memory");
                            TS2(140 + i);
                            mbar_expect(sb + B_XFULL + 16 * i, i < 2 ? 32768 : 16384);
                            tma2(sb + OFF_X + i * 32768, i < 2 ? &maps.hx2 : &maps.hx, 0, hrow + i * 256, sb + B_XFULL + 16 * i);
                        }
                        i++;
                    }
                }
            }
        }
    } else {
        asm volatile("setmaxnreg.inc.sync.aligned.u32 224;");
        const int wg = warp >> 2;
        const bool elect = (tid & 127) == 0;
        const uint32_t xlo = ((sb + OFF_X + wg * 8192) >> 4) | LBO1;
        const uint32_t ringlo = (sb + OFF_RING) >> 4;
        auto release = [&](uint32_t bar) {
            if (elect) {
                mbar_arrive(sb + bar);
            }
        };
#define S_SL(S) ((S) < 40 ? (S) % 5 : ((S) - 40) % 9)
#define S_WAIT(S) do { mbar_wait(sb + (S_SL(S) < 5 ? B_FULL + 8 * S_SL(S) : B_EFULL + 8 * (S_SL(S) - 5)), (S) < 40 ? ((S) / 5) & 1 : (S) >= 49); \
            if (PROF && tid == 0) TS2(64 + (S)); } while (0)
#define S_B(S) (S_SL(S) < 5 ? ringlo + S_SL(S) * 1024 : ((sb + OFF_X) >> 4) + (S_SL(S) == 7 ? 8 : S_SL(S) == 8 ? 7 : S_SL(S)) * 1024)
#define S_REL(S) do { if ((S) < 49) release(S_SL(S) < 5 ? B_EMPTY + 8 * S_SL(S) : B_EEMPTY + 8 * (S_SL(S) - 5)); } while (0)
#define G1(S, acc, SW, KB) g1_issue<SW, (KB) == 0>(acc, xlo + (KB) * 1024, S_B(S) | (SW ? LBO4K : LBO8K))
#define RET(S) do { S_WAIT((S) + 1); wg_wait<1>(); S_REL((S) - 1); } while (0)
#define RET2(S) do { S_WAIT((S) + 1); wg_wait<2>(); S_REL((S) - 1); } while (0)
#define SCHED() mbar_wait(sb + B_GRDY, 0)
#define A2_SYNC() do { asm volatile("fence.proxy.async.shared::cta;" ::: "memory"); asm volatile("bar.sync %0, 128;" :: "r"(wg + 1) : "memory"); } while (0)
#define H_EPI(acc, F, I0, I1, OG, OU) _Pragma("unroll") for (int i = (I0); i < (I1); i++) \
            F[i] = keep(hmul2(pack2(acc[(OG) + 2 * i] * acc[(OU) + 2 * i], acc[(OG) + 2 * i + 1] * acc[(OU) + 2 * i + 1]), (i & 1) ? m_hi : m_lo))
#define PHI(acc, F, I0, I1) _Pragma("unroll") for (int i = (I0); i < (I1); i++) F[i] = keep(phi2(acc[2 * i], acc[2 * i + 1]))

        float a0[64], b0[64], a1[64], a2_[64], a3[64];
        mbar_wait(sb + B_XFULL, 0);
        S_WAIT(0); G1(0, a0, false, 0);
        if ((warp & 3) == 0) TS(wg, 1);
        S_WAIT(1); G1(1, b0, false, 0); RET(1);
#define C0(KB) mbar_wait(sb + B_XFULL + 8 * (KB), 0); if (PROF && tid == 0) TS2(128 + (KB)); \
        G1(2 * (KB), a0, false, KB); RET(2 * (KB)); G1(2 * (KB) + 1, b0, false, KB); RET(2 * (KB) + 1)
        C0(1); C0(2); C0(3); C0(4); C0(5);
        mbar_wait(sb + B_XFULL + 8 * 6, 0);
        G1(12, a0, false, 6); RET(12);
        mbar_wait(sb + B_XFULL + 8 * 7, 0);
        G1(13, a0, false, 7); RET(13);
        G1(14, b0, false, 6);
        mbar_wait(sb + B_GRDY, 0);
        float g_lo, g_hi;
        uint32_t tag;
        {
            const uint32_t ga = sb + OFF_G + (warp * 16 + (lane >> 2)) * 4;
            asm volatile("ld.shared.f32 %0, [%1];" : "=f"(g_lo) : "r"(ga) : "memory");
            asm volatile("ld.shared.f32 %0, [%1];" : "=f"(g_hi) : "r"(ga + 32) : "memory");
            asm volatile("ld.shared.u32 %0, [%1];" : "=r"(tag) : "r"(sb + OFF_EPOCH) : "memory");
        }
        float* const kvp = g_kvacc + (((tag & 1) * 8 + j) * 4 + (warp & 3)) * 272;
        tag = (tag + 1) & 1;
        const uint32_t m_lo = pack2(1.f - g_lo, 1.f - g_lo), m_hi = pack2(1.f - g_hi, 1.f - g_hi);
        const uint32_t lrow = ((lane & 7) + 8 * ((lane >> 3) & 1)) * 128;
        const uint32_t srow = (warp & 3) * 2048 + lrow;
        const uint32_t ssw = (lane >> 4) ^ (lane & 7);
        uint4* const hsend = g_hx + (size_t)((r * 4 + (j >> 1)) * 5 + (j & 1)) * 1024 + warp * 128 + (lane >> 2) * 8 + (lane & 3);
#define SENT_H(B) do { __syncwarp(); if (lane == 0) mbar_arrive(sb + B_HSENT + 8 * (B)); } while (0)
        RET(14);
        pin(a0);
        uint32_t fh0[16], fh1[16], fh2[16], fh3[8], fo[16];
        G1(15, b0, false, 7); SCHED(); H_EPI(a0, fh0, 0, 16, 0, 32); RET(15);
        if ((warp & 3) == 0) TS(wg, 2);

        float kv[32], zs[4];
        uint32_t pk[16], pv[16];
        const uint32_t stg = sb + OFF_STG + wg * 8192, stl = stg + (warp & 1) * 2048 + lrow;
        const uint32_t klo = (stg >> 4) | LBO1, vlo = klo + 256, olo = (sb + OFF_ONES) >> 4;
        G1(16, a1, false, 0); RET(16);
        pin(b0);
        G1(17, a1, false, 1); send_h<0, 1>(fh0, hsend); SCHED(); PHI(b0, pk, 0, 6); RET(17);
        G1(18, a1, false, 2); send_h<1, 2>(fh0, hsend); SENT_H(0); SCHED(); PHI(b0, pk, 6, 12); RET(18);
        G1(19, a1, false, 3); SCHED(); PHI(b0, pk, 12, 16); pack_sub<32>(pv, b0); RET(19);
#define KV_ROUND(Z) do { A2_SYNC(); wg_fence(); \
            wg_ss64t##Z(kv, vlo, DH128, klo, DH128); wg_ss64t(kv, vlo + 128, DH128, klo + 128, DH128); \
            wg_ss8t##Z(zs, klo, DH128, olo, 0); wg_ss8t(zs, klo + 128, DH128, olo, 0); wg_commit(); } while (0)
        G1(20, a1, false, 4); if (!(warp & 2)) { stash<16>(stl, ssw, pk); stash<16>(stl + 4096, ssw, pv); } RET(20);
        G1(21, a1, false, 5); KV_ROUND(_z); RET2(21);
        G1(22, a1, false, 6); RET(22);
        G1(23, a1, false, 7); if (warp & 2) { stash<16>(stl, ssw, pk); stash<16>(stl + 4096, ssw, pv); } RET(23);
        if ((warp & 3) == 0) TS(wg, 3);

        G1(24, a2_, true, 0); KV_ROUND(); RET2(24);
        pin(a1);
        G1(25, a2_, true, 1); RET(25);
        pin(kv); pin(zs);
        G1(26, a2_, true, 2);
#define KV_RED(W) do { asm volatile("red.global.add.v4.f32 [%0], {%1,%2,%3,%4};" :: "l"(kvp + lane * 4), "f"(kv[8 * W]), "f"(kv[8 * W + 1]), "f"(kv[8 * W + 2]), "f"(kv[8 * W + 3]) : "memory"); \
                       asm volatile("red.global.add.v4.f32 [%0], {%1,%2,%3,%4};" :: "l"(kvp + 128 + lane * 4), "f"(kv[8 * W + 4]), "f"(kv[8 * W + 5]), "f"(kv[8 * W + 6]), "f"(kv[8 * W + 7]) : "memory"); } while (0)
        if ((warp & 3) == 0) KV_RED(0); else if ((warp & 3) == 1) KV_RED(1); else if ((warp & 3) == 2) KV_RED(2); else KV_RED(3);
        if ((lane & 3) == 0) {
            asm volatile("red.global.add.f32 [%0], %1;" :: "l"(kvp + 256 + (lane >> 2)), "f"(zs[0]) : "memory");
            asm volatile("red.global.add.f32 [%0], %1;" :: "l"(kvp + 264 + (lane >> 2)), "f"(zs[2]) : "memory");
        }
        __syncwarp();
        if (lane == 0) mbar_arrive(sb + B_KVDONE);
        RET(26);
        G1(27, a2_, true, 3); SCHED(); H_EPI(a1, fh1, 0, 16, 0, 32); RET(27);
        G1(28, a2_, true, 4); RET(28);
        G1(29, a2_, true, 5); RET(29);
        G1(30, a2_, true, 6); send_h<0, 1>(fh1, hsend + 2 * 1024); RET(30);
        G1(31, a2_, true, 7); send_h<1, 2>(fh1, hsend + 2 * 1024); SENT_H(1); RET(31);
        if ((warp & 3) == 0) TS(wg, 4);

        float on[4][12];
#define O_SCALE(h) do { const float s_lo = __fdividef(g_lo, on[h][8] + 1e-6f), s_hi = __fdividef(g_hi, on[h][10] + 1e-6f); \
            const uint32_t sl_ = pack2(s_lo, s_lo), sh_ = pack2(s_hi, s_hi); \
            fo[4 * h] = hmul2(pack2(on[h][0], on[h][1]), sl_); fo[4 * h + 1] = hmul2(pack2(on[h][2], on[h][3]), sh_); \
            fo[4 * h + 2] = hmul2(pack2(on[h][4], on[h][5]), sl_); fo[4 * h + 3] = hmul2(pack2(on[h][6], on[h][7]), sh_); } while (0)
        G1(32, a3, false, 0); RET(32);
        pin(a2_);
        G1(33, a3, false, 1); SCHED(); H_EPI(a2_, fh3, 0, 8, 32, 48);
        send_h<0, 1>(fh3, hsend + 4 * 1024 - (j & 1) * 1020); SENT_H(2); PHI(a2_, fo, 0, 2); RET(33);
        G1(34, a3, false, 2); SCHED(); PHI(a2_, fo, 2, 7); RET(34);
        if (elect) mbar_arrive(sb + B_XFREE);
        G1(35, a3, false, 3); SCHED(); PHI(a2_, fo, 7, 12); RET(35);
        G1(36, a3, false, 4); SCHED(); PHI(a2_, fo, 12, 16); RET(36);
        if (elect) mbar_arrive(sb + B_XFREE + 8);
        G1(37, a3, false, 5);
        if ((warp & 3) == 0) TS(wg, 5);
        mbar_wait(sb + B_KVRDY, 0);
        if ((warp & 3) == 0) TS(wg, 6);
        wg_fence();
#pragma unroll
        for (int h = 0; h < 4; h++)
            wg_rs24_z(on[h], fo[4 * h], fo[4 * h + 1], fo[4 * h + 2], fo[4 * h + 3], (((sb + OFF_STG) >> 4) + h * 48) | (8u << 16), 16u);
        wg_commit();
        RET2(37);
        G1(38, a3, false, 6); RET(38);
        release(B_EEMPTY); release(B_EEMPTY + 16);
        pin(on[0]); pin(on[1]); pin(on[2]); pin(on[3]);
        uint4* const lsend = g_lx + (size_t)(r * 8 + j) * 2048 + warp * 128 + lane;
        const uint4* const lrecv = g_lx + (size_t)(r * 8 + (j ^ 1)) * 2048 + warp * 128 + lane;
        G1(39, a3, false, 7); SCHED();
        O_SCALE(0); O_SCALE(1); send_frag<0, 2>(fo, lsend, tag);
        O_SCALE(2); O_SCALE(3);
        RET(39);
        release(B_EEMPTY + 8);
        if ((warp & 3) == 0) TS(wg, 7);

#define G2S(S, acc, U) do { wg_fence(); _Pragma("unroll") for (int k = 0; k < 4; k++) { \
            if (((S) == 40 || (S) == 47) && k == 0) wg_ss128_z(acc, xlo, DH128, S_B(S) | LBO8K, DH128); \
            else wg_ss128(acc, xlo + (U) * 1024 + 2 * k, DH128, (S_B(S) | LBO8K) + 128 * k, DH128); } wg_commit(); } while (0)
#define G2R(S, acc, F) do { wg_fence(); _Pragma("unroll") for (int k = 0; k < 4; k++) { \
            wg_rs128(acc, F[4 * k], F[4 * k + 1], F[4 * k + 2], F[4 * k + 3], (S_B(S) | LBO8K) + 128 * k, DH128); } wg_commit(); } while (0)
#define H_WAIT(P) do { mbar_wait(sb + B_XFULL + 8 * (P), 1); if (PROF && tid == 0) TS2(150 + (P)); } while (0)
        const int p = j >> 1, pw = (p & 2) ^ 2;
        const bool own = wg == (p & 1);
        uint4* const pbase = g_part + (size_t)(r * 2 + (j & 1)) * 16384 + (warp & 3) * 256 + lane;

        float p1[64], p2[64];
        uint32_t po[16], ph2[16];
        H_WAIT(0); G2S(40, p1, 0); send_frag<2, 4>(fo, lsend, tag); RET(40);
        release(B_EEMPTY + 24);
        if (elect) mbar_arrive(sb + B_XFREE + 16);
        pin(a3);
        G2S(41, p1, 1); SCHED(); H_EPI(a3, fh2, 0, 16, 0, 32); send_frag<0, 2>(fh2, lsend + 1024, tag); RET(41);
        H_WAIT(2); G2S(42, p1, 2); send_frag<2, 4>(fh2, lsend + 1024, tag); RET(42);
        G2S(43, p1, 3); recv_issue(po, lrecv); RET(43);
        G2R(44, p1, fo); RET(44);
        G2R(45, p1, fh2); SCHED(); recv_check(po, lrecv, tag); recv_issue(ph2, lrecv + 1024); RET(45);
        H_WAIT(4); G2S(46, p1, 4); RET(46);
        G2S(47, p2, 0); RET(47);
        G2R(48, p1, po); SCHED(); recv_check(ph2, lrecv + 1024, tag); RET(48);
        G2R(49, p1, ph2); RET(49);
        if ((warp & 3) == 0) TS(wg, 8);
        uint32_t sp[32], qa[32], qb[32];
        uint4* const s1 = pbase + (((pw + wg) * 4 + p) << 10);
        G2R(50, p2, fo); RET(50);
        pin(p1);
        G2R(51, p2, fh2); SCHED(); pack_sub<0>(sp, p1); send_frag<0, 2>(sp, s1, tag); RET(51);
        G2R(52, p2, po); send_frag<2, 5>(sp, s1, tag); RET(52);
        G2R(53, p2, ph2); send_frag<5, 8>(sp, s1, tag); RET(53);
        const uint4* ra = pbase + ((p * 4 + pw) << 10);
        const uint4* rc = pbase + ((p * 4 + (p ^ 1)) << 10);
        if (own) { mbar_wait(sb + B_AHEAD, 0); recv_issue(qa, ra); recv_issue(qb, ra + 1024); }
        G2S(54, p2, 1); RET(54);
        G2S(55, p2, 2); RET(55);
        G2S(56, p2, 3); RET(56);
        G2S(57, p2, 4);
        if ((warp & 3) == 0) TS(wg, 9);
        if (!own) {
            if (elect) mbar_arrive(sb + B_AHEAD);
        } else {
            recv_issue(sp, rc);
            recv_check(qa, ra, tag); recv_check(qb, ra + 1024, tag);
#pragma unroll
            for (int i = 0; i < 32; i++) qa[i] = keep(hadd2(qa[i], qb[i]));
        }
        wg_wait<0>();
        pin(p2);
        if ((warp & 3) == 0) TS(wg, 11);
        if (!own) {
            pack_sub<0>(sp, p2); send_frag<0, 8>(sp, pbase + (((p ^ 1) * 4 + p) << 10), tag);
        } else {
            if ((warp & 3) == 0) TS(wg, 12);
            recv_check(sp, rc, tag);
#pragma unroll
            for (int i = 0; i < 32; i++) qa[i] = hadd2(qa[i], sp[i]);
            accum(qa, p2);
            if ((warp & 3) == 0) TS(wg, 13);
            uint32_t f0[16], f1[16];
            pack_sub<0>(f0, p2); pack_sub<32>(f1, p2);
            const uint32_t slab = sb + OFF_X + 2 * 16384 + wg * 8192;
            stash<16>(slab + srow, ssw, f0); stash<16>(slab + 16384 + srow, ssw, f1);
            __syncwarp();
            __nv_bfloat16* op = out + (size_t)(r * 128 + warp * 16 + (lane >> 4)) * kD + (j & 1) * 256 + (p & 2) * 64 + (lane & 15) * 8;
#pragma unroll
            for (int i = 0; i < 8; i++) {
                const int row = i * 2 + (lane >> 4);
                uint4 v;
                asm volatile("ld.shared.v4.u32 {%0,%1,%2,%3}, [%4];" : "=r"(v.x), "=r"(v.y), "=r"(v.z), "=r"(v.w)
                             : "r"(slab + (lane & 8) * 2048 + ((warp & 3) * 16 + row) * 128 + (((lane & 7) ^ (row & 7)) << 4)) : "memory");
                *(uint4*)(op + i * 2 * kD) = v;
            }
        }
        if ((warp & 3) == 0) { TS(wg, 14); TSG(wg, 31); }
    }
}

typedef CUresult (*EncodeFn)(CUtensorMap*, CUtensorMapDataType, cuuint32_t, void*, const cuuint64_t*, const cuuint64_t*, const cuuint32_t*,
                             const cuuint32_t*, CUtensorMapInterleave, CUtensorMapSwizzle, CUtensorMapL2promotion, CUtensorMapFloatOOBfill);

static void encode(EncodeFn fn, CUtensorMap* m, int rank, const void* base, const cuuint64_t (&gd)[5], const cuuint64_t (&gs)[4],
                   const cuuint32_t (&bd)[5], CUtensorMapSwizzle sw) {
    cuuint32_t es[5] = {1, 1, 1, 1, 1};
    fn(m, CU_TENSOR_MAP_DATA_TYPE_BFLOAT16, rank, const_cast<void*>(base), gd, gs, bd, es, CU_TENSOR_MAP_INTERLEAVE_NONE, sw,
       CU_TENSOR_MAP_L2_PROMOTION_L2_128B, CU_TENSOR_MAP_FLOAT_OOB_FILL_NONE);
}

extern "C" void kernel_launch(void* const* d_in, const int* in_sizes, int n_in, void* d_out, int out_size) {
    const char* x = (const char*)d_in[0];
    const char* wqkv = (const char*)d_in[1];
    const char* wo = (const char*)d_in[2];
    const char* wg = (const char*)d_in[4];
    const char* wu = (const char*)d_in[5];
    const char* wd = (const char*)d_in[6];
    void* fnp = nullptr;
    cudaDriverEntryPointQueryResult qr;
    cudaGetDriverEntryPoint("cuTensorMapEncodeTiled", &fnp, cudaEnableDefault, &qr);
    EncodeFn fn = (EncodeFn)fnp;
    Maps maps;
    const char* lo = wg < wu ? wg : wu;
    const uint64_t diff = wg < wu ? (uint64_t)(wu - wg) : (uint64_t)(wg - wu);
    const CUtensorMapSwizzle S128 = CU_TENSOR_MAP_SWIZZLE_128B, S64 = CU_TENSOR_MAP_SWIZZLE_64B;
    encode(fn, &maps.x, 2, x, {512, 2048, 1, 1}, {1024, 0, 0}, {64, 128, 1, 1}, S128);
    encode(fn, &maps.gu, 3, lo, {1792, 512, 2, 1}, {3584, diff, 0}, {64, 64, 2, 1}, S128);
    encode(fn, &maps.kv, 3, wqkv, {512, 512, 3, 1}, {3072, 1024, 0}, {64, 64, 2, 1}, S128);
    encode(fn, &maps.q64, 3, wqkv, {32, 512, 48, 1}, {3072, 64, 0}, {32, 64, 2, 1}, S64);
    encode(fn, &maps.gu64, 3, lo, {1792, 512, 2, 1}, {3584, diff, 0}, {32, 64, 2, 1}, S64);
    encode(fn, &maps.wdw, 3, wd, {64, 1792, 8, 1}, {1024, 128, 0}, {64, 64, 2, 1}, S128);
    encode(fn, &maps.wow, 3, wo, {64, 512, 8}, {1024, 128}, {64, 64, 2}, S128);
    encode(fn, &maps.wdp, 5, wd, {512, 2, 4, 4, 56}, {1024, 8192, 2048, 32768}, {64, 2, 4, 4, 2}, S128);
    encode(fn, &maps.wdph, 5, wd, {512, 2, 4, 4, 56}, {1024, 8192, 2048, 32768}, {64, 2, 4, 4, 1}, S128);
    void* hx = nullptr;
    cudaGetSymbolAddress(&hx, g_hx);
    encode(fn, &maps.hx, 2, hx, {64, 16 * 4 * 5 * 128}, {128}, {64, 128}, S128);
    encode(fn, &maps.hx2, 2, hx, {64, 16 * 4 * 5 * 128}, {128}, {64, 256}, S128);
    cudaFuncSetAttribute(fused_kernel, cudaFuncAttributeMaxDynamicSharedMemorySize, SMEM_BYTES);
    cudaLaunchConfig_t cfg = {};
    cfg.gridDim = dim3(128);
    cfg.blockDim = dim3(384);
    cfg.dynamicSmemBytes = SMEM_BYTES;
    cfg.stream = cudaStreamPerThread;
    cudaLaunchAttribute at[1];
    at[0].id = cudaLaunchAttributeClusterDimension;
    at[0].val.clusterDim.x = 2; at[0].val.clusterDim.y = 1; at[0].val.clusterDim.z = 1;
    cfg.attrs = at;
    cfg.numAttrs = MC ? 1 : 0;
    cudaLaunchKernelEx(&cfg, fused_kernel, maps, (const __nv_bfloat16*)d_in[0], (const __nv_bfloat16*)d_in[7], wqkv, wg, wu, wd, wo, (__nv_bfloat16*)d_out);
}
```

```cpp
#include <cuda_runtime.h>
#include <cuda.h>
#include <cuda_bf16.h>
#include <stdint.h>

#define MC 0
#define PFMODE 1
#define PROF 0

namespace {

constexpr int kD = 512;
constexpr uint32_t OFF_X = 0, OFF_STG = 131072, OFF_RING = 147456, OFF_MISC = 229376;
constexpr uint32_t B_FULL = OFF_MISC, B_EMPTY = OFF_MISC + 40, B_XFULL = OFF_MISC + 80;
constexpr uint32_t B_GRDY = OFF_MISC + 152, B_KVDONE = OFF_MISC + 160, B_KVRDY = OFF_MISC + 168;
constexpr uint32_t B_HSENT = OFF_MISC + 176, B_XFREE = OFF_MISC + 200;
constexpr uint32_t OFF_EPOCH = OFF_MISC + 240, OFF_G = OFF_MISC + 256;
constexpr uint32_t B_AHEAD = OFF_MISC + 248;
constexpr uint32_t OFF_ONES = OFF_MISC + 768;
constexpr uint32_t B_EFULL = OFF_MISC + 896, B_EEMPTY = OFF_MISC + 928;
constexpr uint32_t SMEM_BYTES = OFF_MISC + 960;
constexpr uint32_t SPIN_GLOBAL = 1u << 14;

struct alignas(64) Maps { CUtensorMap x, gu, kv, q64, gu64, wdw, wow, wdp, wdph, hx, hx2; };

}

__device__ uint4 g_part[16 * 2 * 4 * 4 * 1024];
__device__ uint4 g_hx[16 * 4 * 5 * 1024];
__device__ uint4 g_lx[16 * 8 * 2 * 1024];
__device__ unsigned g_hflag[128 * 8];
__device__ uint4 g_gx[16 * 32];
__device__ float g_kvacc[2 * 8 * 4 * 272];
__device__ unsigned g_kvcnt[8 * 32];
__device__ unsigned g_epoch[128];
#define TS(role, idx)
#define TS2(idx)
#define TSG(role, idx)

namespace {

__device__ __forceinline__ void mbar_init(uint32_t bar, uint32_t cnt) { asm volatile("mbarrier.init.shared::cta.b64 [%0], %1;" :: "r"(bar), "r"(cnt) : "memory"); }
__device__ __forceinline__ void mbar_expect(uint32_t bar, uint32_t bytes) { asm volatile("mbarrier.arrive.expect_tx.shared::cta.b64 _, [%0], %1;" :: "r"(bar), "r"(bytes) : "memory"); }
__device__ __forceinline__ void mbar_arrive(uint32_t bar) { asm volatile("mbarrier.arrive.shared::cta.b64 _, [%0];" :: "r"(bar) : "memory"); }
__device__ __forceinline__ void mbar_arrive_cta(uint32_t bar, uint32_t cta) {
    asm volatile("{\n.reg .b32 ra;\nmapa.shared::cluster.u32 ra, %0, %1;\nmbarrier.arrive.shared::cluster.b64 _, [ra];\n}" :: "r"(bar), "r"(cta) : "memory");
}
__device__ __forceinline__ void mbar_wait(uint32_t bar, uint32_t parity) {
    asm volatile("{\n.reg .pred p;\n.reg .u32 c;\n"
                 "mbarrier.try_wait.parity.shared::cta.b64 p, [%0], %1;\n@p bra DONE;\n"
                 "mov.u32 c, 0;\nLAB_WAIT:\nmbarrier.try_wait.parity.shared::cta.b64 p, [%0], %1;\n@p bra DONE;\n"
                 "add.u32 c, c, 1;\nsetp.lt.u32 p, c, 65536;\n@p bra LAB_WAIT;\nDONE:\n}" :: "r"(bar), "r"(parity) : "memory");
}
__device__ __forceinline__ void tma2(uint32_t dst, const CUtensorMap* m, int c0, int c1, uint32_t bar) {
    asm volatile("cp.async.bulk.tensor.2d.shared::cluster.global.mbarrier::complete_tx::bytes [%0], [%1, {%3, %4}], [%2];"
        :: "r"(dst), "l"(m), "r"(bar), "r"(c0), "r"(c1) : "memory");
}
__device__ __forceinline__ void tmaw2(uint32_t dst, const CUtensorMap* m, int c0, int c1, uint32_t bar) {
    tma2(dst, m, c0, c1, bar);
}
__device__ __forceinline__ void tmaw3(uint32_t dst, const CUtensorMap* m, int c0, int c1, int c2, uint32_t bar) {
    asm volatile("cp.async.bulk.tensor.3d.shared::cluster.global.mbarrier::complete_tx::bytes [%0], [%1, {%3, %4, %5}], [%2];"
        :: "r"(dst), "l"(m), "r"(bar), "r"(c0), "r"(c1), "r"(c2) : "memory");
}
__device__ __forceinline__ void tmaw5(uint32_t dst, const CUtensorMap* m, int c0, int c4, uint32_t bar) {
    asm volatile("cp.async.bulk.tensor.5d.shared::cluster.global.mbarrier::complete_tx::bytes [%0], [%1, {%3, %5, %5, %5, %4}], [%2];"
        :: "r"(dst), "l"(m), "r"(bar), "r"(c0), "r"(c4), "r"(0) : "memory");
}
__device__ __forceinline__ void wg_fence() { asm volatile("wgmma.fence.sync.aligned;" ::: "memory"); }
__device__ __forceinline__ void wg_commit() { asm volatile("wgmma.commit_group.sync.aligned;" ::: "memory"); }
template <int N> __device__ __forceinline__ void wg_wait() { asm volatile("wgmma.wait_group.sync.aligned %0;" :: "n"(N) : "memory"); }
template <int N> __device__ __forceinline__ void pin(float (&d)[N]) {
#pragma unroll
    for (int i = 0; i < N; i++) asm volatile("" : "+f"(d[i]) :: "memory");
}
__device__ __forceinline__ uint32_t pack2(float lo, float hi) { uint32_t r; asm("cvt.rn.bf16x2.f32 %0, %1, %2;" : "=r"(r) : "f"(hi), "f"(lo)); return r; }
__device__ __forceinline__ uint32_t keep(uint32_t v) { asm volatile("" : "+r"(v)); return v; }
__device__ __forceinline__ uint32_t hadd2(uint32_t a, uint32_t b) { uint32_t r; asm("add.bf16x2 %0, %1, %2;" : "=r"(r) : "r"(a), "r"(b)); return r; }
__device__ __forceinline__ uint32_t hmul2(uint32_t a, uint32_t b) { uint32_t r; asm("mul.bf16x2 %0, %1, %2;" : "=r"(r) : "r"(a), "r"(b)); return r; }
__device__ __forceinline__ uint32_t phi2(float t0, float t1) {
    float e0, e1;
    asm("ex2.approx.ftz.f32 %0, %1;" : "=f"(e0) : "f"(t0 * 1.4426950408889634f));
    asm("ex2.approx.ftz.f32 %0, %1;" : "=f"(e1) : "f"(t1 * 1.4426950408889634f));
    uint32_t e = pack2(e0, e1), t = pack2(t0, t1), r;
    asm("min.bf16x2 %0, %0, %1;" : "+r"(e) : "r"(0x3f803f80u));
    asm("max.bf16x2 %0, %0, %1;" : "+r"(t) : "r"(0x35863586u));
    asm("add.bf16x2 %0, %1, %2;" : "=r"(r) : "r"(e), "r"(t));
    return r;
}
__device__ __forceinline__ void stsm4(uint32_t a, uint32_t r0, uint32_t r1, uint32_t r2, uint32_t r3) {
    asm volatile("stmatrix.sync.aligned.m8n8.x4.shared.b16 [%0], {%1,%2,%3,%4};" :: "r"(a), "r"(r0), "r"(r1), "r"(r2), "r"(r3) : "memory");
}
__device__ __forceinline__ float bf_lo(uint32_t w) { return __uint_as_float(w << 16); }
__device__ __forceinline__ float bf_hi(uint32_t w) { return __uint_as_float(w & 0xffff0000u); }
__device__ __forceinline__ void st_pkt(uint4* p, uint32_t w0, uint32_t w1, uint32_t w2, uint32_t w3) {
    asm volatile("{\n.reg .b64 lo, hi;\n.reg .b128 v;\nmov.b64 lo, {%1, %2};\nmov.b64 hi, {%3, %4};\nmov.b128 v, {lo, hi};\nst.relaxed.gpu.global.b128 [%0], v;\n}"
        :: "l"(p), "r"(w0), "r"(w1), "r"(w2), "r"(w3) : "memory");
}
__device__ __forceinline__ void ld_pkt(const uint4* p, uint32_t& w0, uint32_t& w1, uint32_t& w2, uint32_t& w3) {
    asm volatile("{\n.reg .b64 lo, hi;\n.reg .b128 v;\nld.relaxed.gpu.global.b128 v, [%4];\nmov.b128 {lo, hi}, v;\nmov.b64 {%0, %1}, lo;\nmov.b64 {%2, %3}, hi;\n}"
        : "=r"(w0), "=r"(w1), "=r"(w2), "=r"(w3) : "l"(p) : "memory");
}

__device__ __forceinline__ void wg_rs128(float (&d)[64], uint32_t a0, uint32_t a1, uint32_t a2, uint32_t a3, uint32_t blo, uint32_t bhi) {
    asm volatile("{\n.reg .b64 db;\nmov.b64 db, {%68, %69};\n"
        "wgmma.mma_async.sync.aligned.m64n128k16.f32.bf16.bf16 {%0,%1,%2,%3,%4,%5,%6,%7,%8,%9,%10,%11,%12,%13,%14,%15,%16,%17,%18,%19,%20,%21,%22,%23,%24,%25,%26,%27,%28,%29,%30,%31,%32,%33,%34,%35,%36,%37,%38,%39,%40,%41,%42,%43,%44,%45,%46,%47,%48,%49,%50,%51,%52,%53,%54,%55,%56,%57,%58,%59,%60,%61,%62,%63}, {%64,%65,%66,%67}, db, 1, 1, 1, 1;\n}\n"
        : "+f"(d[0]),"+f"(d[1]),"+f"(d[2]),"+f"(d[3]),"+f"(d[4]),"+f"(d[5]),"+f"(d[6]),"+f"(d[7]),"+f"(d[8]),"+f"(d[9]),"+f"(d[10]),"+f"(d[11]),"+f"(d[12]),"+f"(d[13]),"+f"(d[14]),"+f"(d[15]),"+f"(d[16]),"+f"(d[17]),"+f"(d[18]),"+f"(d[19]),"+f"(d[20]),"+f"(d[21]),"+f"(d[22]),"+f"(d[23]),"+f"(d[24]),"+f"(d[25]),"+f"(d[26]),"+f"(d[27]),"+f"(d[28]),"+f"(d[29]),"+f"(d[30]),"+f"(d[31]),"+f"(d[32]),"+f"(d[33]),"+f"(d[34]),"+f"(d[35]),"+f"(d[36]),"+f"(d[37]),"+f"(d[38]),"+f"(d[39]),"+f"(d[40]),"+f"(d[41]),"+f"(d[42]),"+f"(d[43]),"+f"(d[44]),"+f"(d[45]),"+f"(d[46]),"+f"(d[47]),"+f"(d[48]),"+f"(d[49]),"+f"(d[50]),"+f"(d[51]),"+f"(d[52]),"+f"(d[53]),"+f"(d[54]),"+f"(d[55]),"+f"(d[56]),"+f"(d[57]),"+f"(d[58]),"+f"(d[59]),"+f"(d[60]),"+f"(d[61]),"+f"(d[62]),"+f"(d[63])
        : "r"(a0), "r"(a1), "r"(a2), "r"(a3), "r"(blo), "r"(bhi));
}
__device__ __forceinline__ void wg_rs128_z(float (&d)[64], uint32_t a0, uint32_t a1, uint32_t a2, uint32_t a3, uint32_t blo, uint32_t bhi) {
    asm volatile("{\n.reg .b64 db;\nmov.b64 db, {%68, %69};\n"
        "wgmma.mma_async.sync.aligned.m64n128k16.f32.bf16.bf16 {%0,%1,%2,%3,%4,%5,%6,%7,%8,%9,%10,%11,%12,%13,%14,%15,%16,%17,%18,%19,%20,%21,%22,%23,%24,%25,%26,%27,%28,%29,%30,%31,%32,%33,%34,%35,%36,%37,%38,%39,%40,%41,%42,%43,%44,%45,%46,%47,%48,%49,%50,%51,%52,%53,%54,%55,%56,%57,%58,%59,%60,%61,%62,%63}, {%64,%65,%66,%67}, db, 0, 1, 1, 1;\n}\n"
        : "=f"(d[0]),"=f"(d[1]),"=f"(d[2]),"=f"(d[3]),"=f"(d[4]),"=f"(d[5]),"=f"(d[6]),"=f"(d[7]),"=f"(d[8]),"=f"(d[9]),"=f"(d[10]),"=f"(d[11]),"=f"(d[12]),"=f"(d[13]),"=f"(d[14]),"=f"(d[15]),"=f"(d[16]),"=f"(d[17]),"=f"(d[18]),"=f"(d[19]),"=f"(d[20]),"=f"(d[21]),"=f"(d[22]),"=f"(d[23]),"=f"(d[24]),"=f"(d[25]),"=f"(d[26]),"=f"(d[27]),"=f"(d[28]),"=f"(d[29]),"=f"(d[30]),"=f"(d[31]),"=f"(d[32]),"=f"(d[33]),"=f"(d[34]),"=f"(d[35]),"=f"(d[36]),"=f"(d[37]),"=f"(d[38]),"=f"(d[39]),"=f"(d[40]),"=f"(d[41]),"=f"(d[42]),"=f"(d[43]),"=f"(d[44]),"=f"(d[45]),"=f"(d[46]),"=f"(d[47]),"=f"(d[48]),"=f"(d[49]),"=f"(d[50]),"=f"(d[51]),"=f"(d[52]),"=f"(d[53]),"=f"(d[54]),"=f"(d[55]),"=f"(d[56]),"=f"(d[57]),"=f"(d[58]),"=f"(d[59]),"=f"(d[60]),"=f"(d[61]),"=f"(d[62]),"=f"(d[63])
        : "r"(a0), "r"(a1), "r"(a2), "r"(a3), "r"(blo), "r"(bhi));
}
__device__ __forceinline__ void wg_ss128(float (&d)[64], uint32_t alo, uint32_t ahi, uint32_t blo, uint32_t bhi) {
    asm volatile("{\n.reg .b64 da, db;\nmov.b64 da, {%64, %65};\nmov.b64 db, {%66, %67};\n"
        "wgmma.mma_async.sync.aligned.m64n128k16.f32.bf16.bf16 {%0,%1,%2,%3,%4,%5,%6,%7,%8,%9,%10,%11,%12,%13,%14,%15,%16,%17,%18,%19,%20,%21,%22,%23,%24,%25,%26,%27,%28,%29,%30,%31,%32,%33,%34,%35,%36,%37,%38,%39,%40,%41,%42,%43,%44,%45,%46,%47,%48,%49,%50,%51,%52,%53,%54,%55,%56,%57,%58,%59,%60,%61,%62,%63}, da, db, 1, 1, 1, 0, 1;\n}\n"
        : "+f"(d[0]),"+f"(d[1]),"+f"(d[2]),"+f"(d[3]),"+f"(d[4]),"+f"(d[5]),"+f"(d[6]),"+f"(d[7]),"+f"(d[8]),"+f"(d[9]),"+f"(d[10]),"+f"(d[11]),"+f"(d[12]),"+f"(d[13]),"+f"(d[14]),"+f"(d[15]),"+f"(d[16]),"+f"(d[17]),"+f"(d[18]),"+f"(d[19]),"+f"(d[20]),"+f"(d[21]),"+f"(d[22]),"+f"(d[23]),"+f"(d[24]),"+f"(d[25]),"+f"(d[26]),"+f"(d[27]),"+f"(d[28]),"+f"(d[29]),"+f"(d[30]),"+f"(d[31]),"+f"(d[32]),"+f"(d[33]),"+f"(d[34]),"+f"(d[35]),"+f"(d[36]),"+f"(d[37]),"+f"(d[38]),"+f"(d[39]),"+f"(d[40]),"+f"(d[41]),"+f"(d[42]),"+f"(d[43]),"+f"(d[44]),"+f"(d[45]),"+f"(d[46]),"+f"(d[47]),"+f"(d[48]),"+f"(d[49]),"+f"(d[50]),"+f"(d[51]),"+f"(d[52]),"+f"(d[53]),"+f"(d[54]),"+f"(d[55]),"+f"(d[56]),"+f"(d[57]),"+f"(d[58]),"+f"(d[59]),"+f"(d[60]),"+f"(d[61]),"+f"(d[62]),"+f"(d[63])
        : "r"(alo), "r"(ahi), "r"(blo), "r"(bhi));
}
__device__ __forceinline__ void wg_ss128_z(float (&d)[64], uint32_t alo, uint32_t ahi, uint32_t blo, uint32_t bhi) {
    asm volatile("{\n.reg .b64 da, db;\nmov.b64 da, {%64, %65};\nmov.b64 db, {%66, %67};\n"
        "wgmma.mma_async.sync.aligned.m64n128k16.f32.bf16.bf16 {%0,%1,%2,%3,%4,%5,%6,%7,%8,%9,%10,%11,%12,%13,%14,%15,%16,%17,%18,%19,%20,%21,%22,%23,%24,%25,%26,%27,%28,%29,%30,%31,%32,%33,%34,%35,%36,%37,%38,%39,%40,%41,%42,%43,%44,%45,%46,%47,%48,%49,%50,%51,%52,%53,%54,%55,%56,%57,%58,%59,%60,%61,%62,%63}, da, db, 0, 1, 1, 0, 1;\n}\n"
        : "=f"(d[0]),"=f"(d[1]),"=f"(d[2]),"=f"(d[3]),"=f"(d[4]),"=f"(d[5]),"=f"(d[6]),"=f"(d[7]),"=f"(d[8]),"=f"(d[9]),"=f"(d[10]),"=f"(d[11]),"=f"(d[12]),"=f"(d[13]),"=f"(d[14]),"=f"(d[15]),"=f"(d[16]),"=f"(d[17]),"=f"(d[18]),"=f"(d[19]),"=f"(d[20]),"=f"(d[21]),"=f"(d[22]),"=f"(d[23]),"=f"(d[24]),"=f"(d[25]),"=f"(d[26]),"=f"(d[27]),"=f"(d[28]),"=f"(d[29]),"=f"(d[30]),"=f"(d[31]),"=f"(d[32]),"=f"(d[33]),"=f"(d[34]),"=f"(d[35]),"=f"(d[36]),"=f"(d[37]),"=f"(d[38]),"=f"(d[39]),"=f"(d[40]),"=f"(d[41]),"=f"(d[42]),"=f"(d[43]),"=f"(d[44]),"=f"(d[45]),"=f"(d[46]),"=f"(d[47]),"=f"(d[48]),"=f"(d[49]),"=f"(d[50]),"=f"(d[51]),"=f"(d[52]),"=f"(d[53]),"=f"(d[54]),"=f"(d[55]),"=f"(d[56]),"=f"(d[57]),"=f"(d[58]),"=f"(d[59]),"=f"(d[60]),"=f"(d[61]),"=f"(d[62]),"=f"(d[63])
        : "r"(alo), "r"(ahi), "r"(blo), "r"(bhi));
}
__device__ __forceinline__ void wg_ss64(float (&d)[32], uint32_t alo, uint32_t ahi, uint32_t blo, uint32_t bhi) {
    asm volatile("{\n.reg .b64 da, db;\nmov.b64 da, {%32, %33};\nmov.b64 db, {%34, %35};\n"
        "wgmma.mma_async.sync.aligned.m64n64k16.f32.bf16.bf16 {%0,%1,%2,%3,%4,%5,%6,%7,%8,%9,%10,%11,%12,%13,%14,%15,%16,%17,%18,%19,%20,%21,%22,%23,%24,%25,%26,%27,%28,%29,%30,%31}, da, db, 1, 1, 1, 0, 1;\n}\n"
        : "+f"(d[0]),"+f"(d[1]),"+f"(d[2]),"+f"(d[3]),"+f"(d[4]),"+f"(d[5]),"+f"(d[6]),"+f"(d[7]),"+f"(d[8]),"+f"(d[9]),"+f"(d[10]),"+f"(d[11]),"+f"(d[12]),"+f"(d[13]),"+f"(d[14]),"+f"(d[15]),"+f"(d[16]),"+f"(d[17]),"+f"(d[18]),"+f"(d[19]),"+f"(d[20]),"+f"(d[21]),"+f"(d[22]),"+f"(d[23]),"+f"(d[24]),"+f"(d[25]),"+f"(d[26]),"+f"(d[27]),"+f"(d[28]),"+f"(d[29]),"+f"(d[30]),"+f"(d[31])
        : "r"(alo), "r"(ahi), "r"(blo), "r"(bhi));
}
__device__ __forceinline__ void wg_ss64_z(float (&d)[32], uint32_t alo, uint32_t ahi, uint32_t blo, uint32_t bhi) {
    asm volatile("{\n.reg .b64 da, db;\nmov.b64 da, {%32, %33};\nmov.b64 db, {%34, %35};\n"
        "wgmma.mma_async.sync.aligned.m64n64k16.f32.bf16.bf16 {%0,%1,%2,%3,%4,%5,%6,%7,%8,%9,%10,%11,%12,%13,%14,%15,%16,%17,%18,%19,%20,%21,%22,%23,%24,%25,%26,%27,%28,%29,%30,%31}, da, db, 0, 1, 1, 0, 1;\n}\n"
        : "=f"(d[0]),"=f"(d[1]),"=f"(d[2]),"=f"(d[3]),"=f"(d[4]),"=f"(d[5]),"=f"(d[6]),"=f"(d[7]),"=f"(d[8]),"=f"(d[9]),"=f"(d[10]),"=f"(d[11]),"=f"(d[12]),"=f"(d[13]),"=f"(d[14]),"=f"(d[15]),"=f"(d[16]),"=f"(d[17]),"=f"(d[18]),"=f"(d[19]),"=f"(d[20]),"=f"(d[21]),"=f"(d[22]),"=f"(d[23]),"=f"(d[24]),"=f"(d[25]),"=f"(d[26]),"=f"(d[27]),"=f"(d[28]),"=f"(d[29]),"=f"(d[30]),"=f"(d[31])
        : "r"(alo), "r"(ahi), "r"(blo), "r"(bhi));
}
__device__ __forceinline__ void wg_ss64t(float (&d)[32], uint32_t alo, uint32_t ahi, uint32_t blo, uint32_t bhi) {
    asm volatile("{\n.reg .b64 da, db;\nmov.b64 da, {%32, %33};\nmov.b64 db, {%34, %35};\n"
        "wgmma.mma_async.sync.aligned.m64n64k16.f32.bf16.bf16 {%0,%1,%2,%3,%4,%5,%6,%7,%8,%9,%10,%11,%12,%13,%14,%15,%16,%17,%18,%19,%20,%21,%22,%23,%24,%25,%26,%27,%28,%29,%30,%31}, da, db, 1, 1, 1, 1, 1;\n}\n"
        : "+f"(d[0]),"+f"(d[1]),"+f"(d[2]),"+f"(d[3]),"+f"(d[4]),"+f"(d[5]),"+f"(d[6]),"+f"(d[7]),"+f"(d[8]),"+f"(d[9]),"+f"(d[10]),"+f"(d[11]),"+f"(d[12]),"+f"(d[13]),"+f"(d[14]),"+f"(d[15]),"+f"(d[16]),"+f"(d[17]),"+f"(d[18]),"+f"(d[19]),"+f"(d[20]),"+f"(d[21]),"+f"(d[22]),"+f"(d[23]),"+f"(d[24]),"+f"(d[25]),"+f"(d[26]),"+f"(d[27]),"+f"(d[28]),"+f"(d[29]),"+f"(d[30]),"+f"(d[31])
        : "r"(alo), "r"(ahi), "r"(blo), "r"(bhi));
}
__device__ __forceinline__ void wg_ss64t_z(float (&d)[32], uint32_t alo, uint32_t ahi, uint32_t blo, uint32_t bhi) {
    asm volatile("{\n.reg .b64 da, db;\nmov.b64 da, {%32, %33};\nmov.b64 db, {%34, %35};\n"
        "wgmma.mma_async.sync.aligned.m64n64k16.f32.bf16.bf16 {%0,%1,%2,%3,%4,%5,%6,%7,%8,%9,%10,%11,%12,%13,%14,%15,%16,%17,%18,%19,%20,%21,%22,%23,%24,%25,%26,%27,%28,%29,%30,%31}, da, db, 0, 1, 1, 1, 1;\n}\n"
        : "=f"(d[0]),"=f"(d[1]),"=f"(d[2]),"=f"(d[3]),"=f"(d[4]),"=f"(d[5]),"=f"(d[6]),"=f"(d[7]),"=f"(d[8]),"=f"(d[9]),"=f"(d[10]),"=f"(d[11]),"=f"(d[12]),"=f"(d[13]),"=f"(d[14]),"=f"(d[15]),"=f"(d[16]),"=f"(d[17]),"=f"(d[18]),"=f"(d[19]),"=f"(d[20]),"=f"(d[21]),"=f"(d[22]),"=f"(d[23]),"=f"(d[24]),"=f"(d[25]),"=f"(d[26]),"=f"(d[27]),"=f"(d[28]),"=f"(d[29]),"=f"(d[30]),"=f"(d[31])
        : "r"(alo), "r"(ahi), "r"(blo), "r"(bhi));
}
__device__ __forceinline__ void wg_ss8t(float (&d)[4], uint32_t alo, uint32_t ahi, uint32_t blo, uint32_t bhi) {
    asm volatile("{\n.reg .b64 da, db;\nmov.b64 da, {%4, %5};\nmov.b64 db, {%6, %7};\n"
        "wgmma.mma_async.sync.aligned.m64n8k16.f32.bf16.bf16 {%0,%1,%2,%3}, da, db, 1, 1, 1, 1, 0;\n}\n"
        : "+f"(d[0]),"+f"(d[1]),"+f"(d[2]),"+f"(d[3])
        : "r"(alo), "r"(ahi), "r"(blo), "r"(bhi));
}
__device__ __forceinline__ void wg_ss8t_z(float (&d)[4], uint32_t alo, uint32_t ahi, uint32_t blo, uint32_t bhi) {
    asm volatile("{\n.reg .b64 da, db;\nmov.b64 da, {%4, %5};\nmov.b64 db, {%6, %7};\n"
        "wgmma.mma_async.sync.aligned.m64n8k16.f32.bf16.bf16 {%0,%1,%2,%3}, da, db, 0, 1, 1, 1, 0;\n}\n"
        : "=f"(d[0]),"=f"(d[1]),"=f"(d[2]),"=f"(d[3])
        : "r"(alo), "r"(ahi), "r"(blo), "r"(bhi));
}
__device__ __forceinline__ void wg_rs24_z(float (&d)[12], uint32_t a0, uint32_t a1, uint32_t a2, uint32_t a3, uint32_t blo, uint32_t bhi) {
    asm volatile("{\n.reg .b64 db;\nmov.b64 db, {%16, %17};\n"
        "wgmma.mma_async.sync.aligned.m64n24k16.f32.bf16.bf16 {%0,%1,%2,%3,%4,%5,%6,%7,%8,%9,%10,%11}, {%12,%13,%14,%15}, db, 0, 1, 1, 0;\n}\n"
        : "=f"(d[0]),"=f"(d[1]),"=f"(d[2]),"=f"(d[3]),"=f"(d[4]),"=f"(d[5]),"=f"(d[6]),"=f"(d[7]),"=f"(d[8]),"=f"(d[9]),"=f"(d[10]),"=f"(d[11])
        : "r"(a0), "r"(a1), "r"(a2), "r"(a3), "r"(blo), "r"(bhi));
}

constexpr uint32_t DH128 = 64u | 0x40000000u;
constexpr uint32_t DH64 = 32u | 0x80000000u;
constexpr uint32_t LBO4K = (4096u >> 4) << 16, LBO8K = (8192u >> 4) << 16, LBO1 = 1u << 16;

template <bool SW64, bool FIRST> __device__ __forceinline__ void g1_issue(float (&acc)[64], uint32_t alo, uint32_t blo) {
    wg_fence();
#pragma unroll
    for (int k = 0; k < 4; k++) {
        if (FIRST && k == 0) wg_ss128_z(acc, alo, DH128, blo, SW64 ? DH64 : DH128);
        else wg_ss128(acc, alo + 2 * k, DH128, blo + (SW64 ? 64 * k : 128 * k), SW64 ? DH64 : DH128);
    }
    wg_commit();
}

template <int N> __device__ __forceinline__ void stash(uint32_t base, uint32_t sw, const uint32_t (&f)[N]) {
#pragma unroll
    for (int t = 0; t < N / 4; t++) stsm4(base + ((sw ^ (2 * t)) << 4), f[4 * t], f[4 * t + 1], f[4 * t + 2], f[4 * t + 3]);
}

template <int V0, int V1, int N> __device__ __forceinline__ void send_frag(const uint32_t (&f)[N], uint4* p, uint32_t tag) {
#pragma unroll
    for (int v = V0; v < V1; v++) st_pkt(p + v * 32, (f[4 * v] & ~1u) | tag, f[4 * v + 1], f[4 * v + 2], f[4 * v + 3]);
}
template <int V0, int V1, int N> __device__ __forceinline__ void send_h(const uint32_t (&f)[N], uint4* p) {
#pragma unroll
    for (int v = V0; v < V1; v++) {
        const int h = v >> 1, hi = v & 1;
        asm volatile("st.global.v4.u32 [%0], {%1,%2,%3,%4};" :: "l"(p + 4 * h + 64 * hi),
                     "r"(f[8 * h + hi]), "r"(f[8 * h + 2 + hi]), "r"(f[8 * h + 4 + hi]), "r"(f[8 * h + 6 + hi]) : "memory");
    }
}
template <int O, int N, int M> __device__ __forceinline__ void pack_sub(uint32_t (&f)[N], const float (&acc)[M]) {
#pragma unroll
    for (int i = 0; i < N; i++) f[i] = keep(pack2(acc[O + 2 * i], acc[O + 2 * i + 1]));
}
template <int N> __device__ __forceinline__ void recv_issue(uint32_t (&q)[N], const uint4* p) {
#pragma unroll
    for (int v = 0; v < N / 4; v++) ld_pkt(p + v * 32, q[4 * v], q[4 * v + 1], q[4 * v + 2], q[4 * v + 3]);
}
template <int N> __device__ __forceinline__ void recv_check(uint32_t (&q)[N], const uint4* p, uint32_t tag) {
    uint32_t it = 0;
    while (true) {
        uint32_t bad = 0;
#pragma unroll
        for (int v = 0; v < N / 4; v++) bad |= q[4 * v] ^ tag;
        if (__all_sync(0xffffffffu, (bad & 1u) == 0) || ++it > SPIN_GLOBAL) break;
        recv_issue(q, p);
    }
}
__device__ __forceinline__ void accum(const uint32_t (&q)[32], float (&sum)[64]) {
#pragma unroll
    for (int i = 0; i < 32; i++) { sum[2 * i] += bf_lo(q[i]); sum[2 * i + 1] += bf_hi(q[i]); }
}

}

__global__ void __launch_bounds__(384, 1)
fused_kernel(const __grid_constant__ Maps maps, const __nv_bfloat16* __restrict__ xg, const __nv_bfloat16* __restrict__ gate_w,
             const char* __restrict__ pf_qkv, const char* __restrict__ pf_g, const char* __restrict__ pf_u,
             const char* __restrict__ pf_d, const char* __restrict__ pf_o, __nv_bfloat16* __restrict__ out) {
    extern __shared__ __align__(1024) uint8_t smem_raw[];
    const uint32_t sb = (uint32_t)__cvta_generic_to_shared(smem_raw);
    const int tid = threadIdx.x, lane = tid & 31;
    const int warp = __shfl_sync(0xffffffffu, tid >> 5, 0);
    const int j = (blockIdx.x >> 1) & 7;
    const int r = ((blockIdx.x >> 4) << 1) | (blockIdx.x & 1);
    const uint32_t rank = blockIdx.x & 1;

    if (warp == 0) { TSG(0, 30); TS(0, 0); }
    if (tid == 256) {
        for (int i = 0; i < 5; i++) { mbar_init(sb + B_FULL + 8 * i, 1); mbar_init(sb + B_EMPTY + 8 * i, MC ? 4 : 2); }
        for (int i = 0; i < 9; i++) mbar_init(sb + B_XFULL + 8 * i, 1);
        asm volatile("fence.mbarrier_init.release.cluster;" ::: "memory");
        mbar_expect(sb + B_XFULL, 16384);
        tma2(sb + OFF_X, &maps.x, 0, r * 128, sb + B_XFULL);
        TS2(0);
        mbar_expect(sb + B_FULL, 16384);
        tmaw3(sb + OFF_RING, &maps.kv, 64 * j, 0, 1, sb + B_FULL);
        TS2(1);
        mbar_expect(sb + B_FULL + 8, 16384);
        tmaw3(sb + OFF_RING + 16384, &maps.gu, 224 * j, 0, 0, sb + B_FULL + 8);
    } else if (tid == 288) {
        for (int i = 0; i < 3; i++) mbar_init(sb + B_HSENT + 8 * i, 8);
        for (int i = 0; i < 4; i++) { mbar_init(sb + B_EFULL + 8 * i, 1); mbar_init(sb + B_EEMPTY + 8 * i, MC ? 4 : 2); }
        mbar_init(sb + B_XFREE, 2); mbar_init(sb + B_XFREE + 8, 2); mbar_init(sb + B_XFREE + 16, 2);
        mbar_init(sb + B_AHEAD, 1); mbar_init(sb + B_GRDY, 1); mbar_init(sb + B_KVDONE, 8); mbar_init(sb + B_KVRDY, 2);
        asm volatile("fence.mbarrier_init.release.cluster;" ::: "memory");
    } else if (warp == 10 && lane < 10) {
        asm volatile("prefetch.tensormap [%0];" :: "l"(&maps.gu + lane) : "memory");
    }
    __syncthreads();

    if (warp >= 8) {
        asm volatile("setmaxnreg.dec.sync.aligned.u32 56;");
        if (warp == 8) {
            if (lane == 0) {
                int slot = MC ? 0 : 2, ph = 1;
                uint32_t full, dst;
                if (!MC) { mbar_expect(sb + B_XFULL + 8, 16384); tma2(sb + OFF_X + 16384, &maps.x, 64, r * 128, sb + B_XFULL + 8); }
#define P_BEGIN(S, BYTES) full = sb + B_FULL + 8 * slot; dst = sb + OFF_RING + slot * 16384; \
                mbar_wait(sb + B_EMPTY + 8 * slot, ph); TS2(S); mbar_expect(full, BYTES); if (!MC || (((S) ^ rank) & 1) == 0)
#define P_END() if (++slot == 5) { slot = 0; ph ^= 1; }
                for (int s = MC ? 0 : 2; s < 16; s++) {
                    const int kb = (int)(0x7654763542312100ull >> (4 * s)) & 15;
                    P_BEGIN(s, 16384) {
                        if ((0x0DADu >> s) & 1) tmaw3(dst, &maps.kv, 64 * j, 64 * kb, 1, full);
                        else tmaw3(dst, &maps.gu, 224 * j, 64 * kb, 0, full);
                    }
                    const int xb = (int)(0x0000000765403210ull >> (4 * s)) & 15;
                    if (xb) { mbar_expect(sb + B_XFULL + 8 * xb, 16384); tma2(sb + OFF_X + xb * 16384, &maps.x, 64 * xb, r * 128, sb + B_XFULL + 8 * xb); }
                    P_END()
                }
                for (int s = 0; s < 24; s++) {
                    P_BEGIN(16 + s, 16384) {
                        if (s < 8) {
                            tmaw3(dst, &maps.q64, 0, 64 * s, 2 * j, full);
                            tmaw3(dst + 8192, &maps.gu64, 224 * j + 192, 64 * s, 0, full);
                        } else {
                            tmaw3(dst, &maps.gu, 224 * j + 64 * (s >> 3), 64 * (s & 7), 0, full);
                        }
                    }
                    P_END()
                }
                const int p = j >> 1;
#pragma unroll 1
                for (int t = 0; t < 18; t++) {
                    const int q = t >= 9, sl = t - 9 * q;
                    const int u = (int)((q ? 0x432108675ull : 0x867325410ull) >> (4 * sl)) & 15;
                    const int cw = (j & 1) * 4 + ((p & 2) ^ (q ? 0 : 2)), cc = 64 * cw;
                    if (sl < 5) {
                        full = sb + B_FULL + 8 * sl; dst = sb + OFF_RING + sl * 16384;
                        mbar_wait(sb + B_EMPTY + 8 * sl, q ^ 1);
                    } else {
                        full = sb + B_EFULL + 8 * (sl - 5); dst = sb + OFF_X + (sl == 7 ? 8 : sl == 8 ? 7 : sl) * 16384;
                        mbar_wait(sb + B_EEMPTY + 8 * (sl - 5), q);
                    }
                    TS2(40 + t);
                    mbar_expect(full, 16384);
                    if (!MC || ((t ^ rank) & 1) == 0) {
                        if (u == 4) {
                            tmaw5(dst, &maps.wdph, cc, 14 * p + 6, full); tmaw5(dst + 4096, &maps.wdph, cc, 14 * p + 13, full);
                            tmaw5(dst + 8192, &maps.wdph, cc + 64, 14 * p + 6, full); tmaw5(dst + 12288, &maps.wdph, cc + 64, 14 * p + 13, full);
                        } else if (u > 4) {
                            const int js = u > 6 ? j ^ 1 : j;
                            tmaw3(dst, (u & 1) ? &maps.wow : &maps.wdw, 0, (u & 1) ? 64 * js : 224 * js + 128, cw, full);
                        } else {
                            const int g = 14 * p + 7 * (u & 1) + (u & 2);
                            tmaw5(dst, &maps.wdp, cc, g, full); tmaw5(dst + 8192, &maps.wdp, cc + 64, g, full);
                        }
                    }
                }
            }
        } else if (warp < 11) {
            const int hx = warp - 9;
            uint32_t epoch;
            asm volatile("ld.relaxed.gpu.global.u32 %0, [%1];" : "=r"(epoch) : "l"(g_epoch + blockIdx.x) : "memory");
            {
                const uint4* xr = (const uint4*)(xg + (size_t)(r * 128 + j * 16 + hx * 8) * kD) + lane;
                const uint4 wa = __ldg((const uint4*)gate_w + lane), wb = __ldg((const uint4*)gate_w + 32 + lane);
                const uint32_t tag = (epoch + 1) & 1;
                uint4* gp = g_gx + r * 32;
                if (lane < 2) st_pkt(gp + j * 4 + hx * 2 + lane, tag ^ 1, 0, 0, 0);
                float s[8];
#pragma unroll
                for (int i0 = 0; i0 < 8; i0 += 4) {
                    uint4 va[4], vb[4];
#pragma unroll
                    for (int i = 0; i < 4; i++) { va[i] = __ldg(xr + (i0 + i) * 64); vb[i] = __ldg(xr + (i0 + i) * 64 + 32); }
#pragma unroll
                    for (int i = 0; i < 4; i++) {
                        float t0 = bf_lo(va[i].x) * bf_lo(wa.x), t1 = bf_hi(va[i].x) * bf_hi(wa.x);
                        t0 = fmaf(bf_lo(va[i].y), bf_lo(wa.y), t0); t1 = fmaf(bf_hi(va[i].y), bf_hi(wa.y), t1);
                        t0 = fmaf(bf_lo(va[i].z), bf_lo(wa.z), t0); t1 = fmaf(bf_hi(va[i].z), bf_hi(wa.z), t1);
                        t0 = fmaf(bf_lo(va[i].w), bf_lo(wa.w), t0); t1 = fmaf(bf_hi(va[i].w), bf_hi(wa.w), t1);
                        t0 = fmaf(bf_lo(vb[i].x), bf_lo(wb.x), t0); t1 = fmaf(bf_hi(vb[i].x), bf_hi(wb.x), t1);
                        t0 = fmaf(bf_lo(vb[i].y), bf_lo(wb.y), t0); t1 = fmaf(bf_hi(vb[i].y), bf_hi(wb.y), t1);
                        t0 = fmaf(bf_lo(vb[i].z), bf_lo(wb.z), t0); t1 = fmaf(bf_hi(vb[i].z), bf_hi(wb.z), t1);
                        t0 = fmaf(bf_lo(vb[i].w), bf_lo(wb.w), t0); t1 = fmaf(bf_hi(vb[i].w), bf_hi(wb.w), t1);
                        s[i0 + i] = t0 + t1;
                    }
                }
#pragma unroll
                for (int i = 0; i < 8; i++) {
#pragma unroll
                    for (int o = 16; o; o >>= 1) s[i] += __shfl_xor_sync(0xffffffffu, s[i], o);
                    s[i] = 1.f / (1.f + __expf(-s[i]));
                }
                if (lane < 2) {
                    const float v0 = lane ? s[4] : s[0], v1 = lane ? s[5] : s[1], v2 = lane ? s[6] : s[2], v3 = lane ? s[7] : s[3];
                    st_pkt(gp + j * 4 + hx * 2 + lane, (__float_as_uint(v0) & ~1u) | tag, __float_as_uint(v1), __float_as_uint(v2), __float_as_uint(v3));
                }
                if (hx == 1) {
                    asm volatile("st.shared.u32 [%0], %1;" :: "r"(sb + OFF_ONES + lane * 4), "r"(0x3f803f80u) : "memory");
                    asm volatile("fence.proxy.async.shared::cta;" ::: "memory");
                }
                asm volatile("bar.sync 3, 96;" ::: "memory");
                if (hx == 0) {
                    uint32_t q[4];
                    recv_issue(q, gp + lane);
                    recv_check(q, gp + lane, tag);
                    asm volatile("st.shared.v4.u32 [%0], {%1,%2,%3,%4};" :: "r"(sb + OFF_G + lane * 16), "r"(q[0]), "r"(q[1]), "r"(q[2]), "r"(q[3]) : "memory");
                    if (lane == 0) {
                        asm volatile("st.shared.u32 [%0], %1;" :: "r"(sb + OFF_EPOCH), "r"(epoch) : "memory");
                        g_epoch[blockIdx.x] = epoch + 1;
                    }
                    __syncwarp();
                    if (lane == 0) mbar_arrive(sb + B_GRDY);
                } else {
                    if (r == 0) {
                        float4* zp = (float4*)(g_kvacc + (((epoch & 1) ^ 1) * 8 + j) * 4 * 272);
                        for (int i = lane; i < 272; i += 32) zp[i] = make_float4(0.f, 0.f, 0.f, 0.f);
                    }
                }
            }
            TS(2 + hx, 1);
#define PUBLISH_H(B) do { mbar_wait(sb + B_HSENT + 8 * (B), 0); if (lane == 0) { \
                asm volatile("st.release.gpu.global.u32 [%0], %1;" :: "l"(g_hflag + (r * 8 + j) * 8 + (B)), "r"(epoch + 1) : "memory"); } __syncwarp(); } while (0)
            if (hx == 1) {
#pragma unroll 1
                for (int b = 0; b < 3; b++) { PUBLISH_H(b); TS(3, 5 + b); }
            } else {
                const float* accp = g_kvacc + ((epoch & 1) * 8 + j) * 4 * 272;
                unsigned* cnt = g_kvcnt + j * 32;
                mbar_wait(sb + B_KVDONE, 0);
                TS(2, 5);
                if (lane == 0) asm volatile("red.release.gpu.global.add.u32 [%0], 1;" :: "l"(cnt) : "memory");
                __syncwarp();
                TS(2, 2);
                {
                    const unsigned target = 16u * (epoch + 1);
                    uint32_t it = 0, v;
                    do {
                        asm volatile("ld.acquire.gpu.global.u32 %0, [%1];" : "=r"(v) : "l"(cnt) : "memory");
                    } while ((int)(v - target) < 0 && ++it < SPIN_GLOBAL);
                }
                TS(2, 3);
#pragma unroll
                for (int h = 0; h < 4; h++) {
                    const float4 d0 = __ldcg((const float4*)(accp + h * 272) + lane);
                    const float4 d1 = __ldcg((const float4*)(accp + h * 272 + 128) + lane);
                    const float2 z0 = __ldcg((const float2*)(accp + h * 272 + 256) + (lane & 3));
                    const float2 z1 = __ldcg((const float2*)(accp + h * 272 + 264) + (lane & 3));
                    const uint32_t ba = sb + OFF_STG + h * 768 + lane * 4;
                    asm volatile("st.shared.u32 [%0], %1;" :: "r"(ba), "r"(pack2(d0.x, d0.y)) : "memory");
                    asm volatile("st.shared.u32 [%0], %1;" :: "r"(ba + 128), "r"(pack2(d1.x, d1.y)) : "memory");
                    asm volatile("st.shared.u32 [%0], %1;" :: "r"(ba + 256), "r"(pack2(d0.z, d0.w)) : "memory");
                    asm volatile("st.shared.u32 [%0], %1;" :: "r"(ba + 384), "r"(pack2(d1.z, d1.w)) : "memory");
                    asm volatile("st.shared.u32 [%0], %1;" :: "r"(ba + 512), "r"(pack2(z0.x, z0.y)) : "memory");
                    asm volatile("st.shared.u32 [%0], %1;" :: "r"(ba + 640), "r"(pack2(z1.x, z1.y)) : "memory");
                }
                asm volatile("fence.proxy.async.shared::cta;" ::: "memory");
                __syncwarp();
                if (lane == 0) mbar_arrive(sb + B_KVRDY);
                TS(2, 4);
            }
        } else {
            uint32_t epoch;
            asm volatile("ld.relaxed.gpu.global.u32 %0, [%1];" : "=r"(epoch) : "l"(g_epoch + blockIdx.x) : "memory");
            asm volatile("bar.arrive 3, 96;" :: "r"(epoch) : "memory");
            const int b = blockIdx.x, p = j >> 1;
            mbar_wait(sb + B_XFULL, 0);
#pragma unroll 1
            for (int kb = 1; kb < 8; kb++) {
                mbar_wait(sb + B_XFULL + 8 * kb, 0);
                const char* base = kb < 3 ? pf_g : kb < 5 ? pf_u : kb == 5 ? pf_qkv : pf_d;
                const int off = kb == 5 ? b * 12288 : b * 14336 + ((kb < 5 ? kb - 1 : kb) & 1) * 7168;
                if (kb == 5) {
                    asm volatile("prefetch.global.L2 [%0];" :: "l"(base + off + (lane >> 3) * 3072 + (lane & 7) * 128));
                } else {
                    asm volatile("prefetch.global.L2 [%0];" :: "l"(base + off + lane * 128));
                    if (lane < 24) asm volatile("prefetch.global.L2 [%0];" :: "l"(base + off + 4096 + lane * 128));
                }
                if (kb == 7) asm volatile("prefetch.global.L2 [%0];" :: "l"(pf_o + b * 4096 + lane * 128));
            }
            {
                uint4* mb = g_part + (size_t)(r * 2 + (j & 1)) * 16384 + (((p ^ 1) * 4 + p) << 10) + lane;
#pragma unroll 1
                for (int i = 0; i < 32; i++) { st_pkt(mb + i * 32, epoch & 1, 0, 0, 0); __nanosleep(40); }
                __syncwarp();
                if (lane == 0) mbar_arrive(sb + B_KVRDY);
            }
            {
                const uint32_t want = epoch + 1;
                const int hrow = (r * 4 + p) * 5 * 128;
                const unsigned* fl = g_hflag + (r * 8 + (j & 6)) * 8 + (lane & 15);
                uint32_t it = 0;
                int i = 0;
                mbar_wait(sb + B_HSENT + 8, 0);
#pragma unroll 1
                while (i < 3 && ++it < SPIN_GLOBAL) {
                    uint32_t v;
                    asm volatile("ld.acquire.gpu.global.u32 %0, [%1];" : "=r"(v) : "l"(fl) : "memory");
                    const uint32_t rdy = __ballot_sync(0xffffffffu, v == want);
#pragma unroll 1
                    while (i < 3 && ((rdy >> i) & 0x101u) == 0x101u) {
                        if (i < 2) mbar_wait(sb + B_XFREE + 8 * i, 0);
                        if (lane == 0) {
                            const int pc = (6 - 2 * i) % 6;
                            asm volatile("fence.proxy.async.global;" ::: "memory");
                            TS2(140 + i);
                            mbar_expect(sb + B_XFULL + 8 * pc, i != 1 ? 32768 : 16384);
                            tma2(sb + OFF_X + pc * 16384, i != 1 ? &maps.hx2 : &maps.hx, 0, hrow + pc * 128, sb + B_XFULL + 8 * pc);
                        }
                        i++;
                    }
                }
            }
        }
    } else {
        asm volatile("setmaxnreg.inc.sync.aligned.u32 224;");
        const int wg = warp >> 2;
        const bool elect = (tid & 127) == 0;
        const uint32_t xlo = ((sb + OFF_X + wg * 8192) >> 4) | LBO1;
        const uint32_t ringlo = (sb + OFF_RING) >> 4;
        auto release = [&](uint32_t bar) {
            if (elect) {
                mbar_arrive(sb + bar);
            }
        };
#define S_SL(S) ((S) < 40 ? (S) % 5 : ((S) - 40) % 9)
#define S_WAIT(S) do { mbar_wait(sb + (S_SL(S) < 5 ? B_FULL + 8 * S_SL(S) : B_EFULL + 8 * (S_SL(S) - 5)), (S) < 40 ? ((S) / 5) & 1 : (S) >= 49); \
            if (PROF && tid == 0) TS2(64 + (S)); } while (0)
#define S_B(S) (S_SL(S) < 5 ? ringlo + S_SL(S) * 1024 : ((sb + OFF_X) >> 4) + (S_SL(S) == 7 ? 8 : S_SL(S) == 8 ? 7 : S_SL(S)) * 1024)
#define S_REL(S) do { if ((S) < 49) release(S_SL(S) < 5 ? B_EMPTY + 8 * S_SL(S) : B_EEMPTY + 8 * (S_SL(S) - 5)); } while (0)
#define G1(S, acc, SW, KB) g1_issue<SW, (KB) == 0>(acc, xlo + (KB) * 1024, S_B(S) | (SW ? LBO4K : LBO8K))
#define RET(S) do { S_WAIT((S) + 1); wg_wait<1>(); S_REL((S) - 1); } while (0)
#define RET2(S) do { S_WAIT((S) + 1); wg_wait<2>(); S_REL((S) - 1); } while (0)
#define SCHED() mbar_wait(sb + B_GRDY, 0)
#define A2_SYNC() do { asm volatile("fence.proxy.async.shared::cta;" ::: "memory"); asm volatile("bar.sync %0, 128;" :: "r"(wg + 1) : "memory"); } while (0)
#define H_EPI(acc, F, I0, I1, OG, OU) _Pragma("unroll") for (int i = (I0); i < (I1); i++) \
            F[i] = keep(hmul2(pack2(acc[(OG) + 2 * i] * acc[(OU) + 2 * i], acc[(OG) + 2 * i + 1] * acc[(OU) + 2 * i + 1]), (i & 1) ? m_hi : m_lo))
#define PHI(acc, F, I0, I1) _Pragma("unroll") for (int i = (I0); i < (I1); i++) F[i] = keep(phi2(acc[2 * i], acc[2 * i + 1]))

        float a0[64], b0[64], a1[64], a2_[64], a3[64];
        mbar_wait(sb + B_XFULL, 0);
#define X_WAIT(KB) do { mbar_wait(sb + B_XFULL + 8 * (KB), 0); if (PROF && tid == 0) TS2(128 + (KB)); } while (0)
        S_WAIT(0); G1(0, b0, false, 0);
        if ((warp & 3) == 0) TS(wg, 1);
        S_WAIT(1); G1(1, a0, false, 0); RET(1);
        X_WAIT(1); G1(2, b0, false, 1); RET(2);
        X_WAIT(2); G1(3, b0, false, 2); RET(3);
        G1(4, a0, false, 1); RET(4);
        X_WAIT(3); G1(5, b0, false, 3); RET(5);
        G1(6, a0, false, 2); RET(6);
        X_WAIT(4); G1(7, b0, false, 4); RET(7);
        X_WAIT(5); G1(8, b0, false, 5); RET(8);
        G1(9, a0, false, 3); RET(9);
        X_WAIT(6); G1(10, b0, false, 6); RET(10);
        X_WAIT(7); G1(11, b0, false, 7); RET(11);
        G1(12, a0, false, 4);
        mbar_wait(sb + B_GRDY, 0);
        float g_lo, g_hi;
        uint32_t tag;
        {
            const uint32_t ga = sb + OFF_G + (warp * 16 + (lane >> 2)) * 4;
            asm volatile("ld.shared.f32 %0, [%1];" : "=f"(g_lo) : "r"(ga) : "memory");
            asm volatile("ld.shared.f32 %0, [%1];" : "=f"(g_hi) : "r"(ga + 32) : "memory");
            asm volatile("ld.shared.u32 %0, [%1];" : "=r"(tag) : "r"(sb + OFF_EPOCH) : "memory");
        }
        float* const kvp = g_kvacc + (((tag & 1) * 8 + j) * 4 + (warp & 3)) * 272;
        tag = (tag + 1) & 1;
        const uint32_t m_lo = pack2(1.f - g_lo, 1.f - g_lo), m_hi = pack2(1.f - g_hi, 1.f - g_hi);
        const uint32_t lrow = ((lane & 7) + 8 * ((lane >> 3) & 1)) * 128;
        const uint32_t srow = (warp & 3) * 2048 + lrow;
        const uint32_t ssw = (lane >> 4) ^ (lane & 7);
        uint4* const hsend = g_hx + (size_t)((r * 4 + (j >> 1)) * 5 + (j & 1)) * 1024 + warp * 128 + (lane >> 2) * 8 + (lane & 3);
#define SENT_H(B) do { __syncwarp(); if (lane == 0) mbar_arrive(sb + B_HSENT + 8 * (B)); } while (0)
        RET(12);
        pin(b0);
        uint32_t fh0[16], fh1[16], fh2[16], fh3[8], fo[16], pk[16], pv[16];
        float kv[32], zs[4];
        const uint32_t stg = sb + OFF_STG + wg * 8192, stl = stg + (warp & 1) * 2048 + lrow;
        const uint32_t klo = (stg >> 4) | LBO1, vlo = klo + 256, olo = (sb + OFF_ONES) >> 4;
#define KV_ROUND(Z) do { A2_SYNC(); wg_fence(); \
            wg_ss64t##Z(kv, vlo, DH128, klo, DH128); wg_ss64t(kv, vlo + 128, DH128, klo + 128, DH128); \
            wg_ss8t##Z(zs, klo, DH128, olo, 0); wg_ss8t(zs, klo + 128, DH128, olo, 0); wg_commit(); } while (0)
        G1(13, a0, false, 5); SCHED(); pack_sub<32>(pv, b0); PHI(b0, pk, 0, 4); RET(13);
        G1(14, a0, false, 6); if (!(warp & 2)) stash<16>(stl + 4096, ssw, pv); SCHED(); PHI(b0, pk, 4, 10); RET(14);
        G1(15, a0, false, 7); SCHED(); PHI(b0, pk, 10, 16); RET(15);
        if ((warp & 3) == 0) TS(wg, 2);

        G1(16, a1, true, 0); if (!(warp & 2)) stash<16>(stl, ssw, pk); RET(16);
        pin(a0);
        G1(17, a1, true, 1); SCHED(); H_EPI(a0, fh0, 0, 16, 0, 32); RET(17);
        G1(18, a1, true, 2); KV_ROUND(_z); RET2(18);
        G1(19, a1, true, 3); send_h<0, 1>(fh0, hsend); RET(19);
        G1(20, a1, true, 4); if (warp & 2) { stash<16>(stl, ssw, pk); stash<16>(stl + 4096, ssw, pv); } RET(20);
        G1(21, a1, true, 5); RET(21);
        G1(22, a1, true, 6); KV_ROUND(); RET2(22);
        G1(23, a1, true, 7); send_h<1, 2>(fh0, hsend); RET(23);
        pin(kv); pin(zs);
        if ((warp & 3) == 0) TS(wg, 3);

        G1(24, a2_, false, 0);
#define KV_RED(W) do { asm volatile("red.global.add.v4.f32 [%0], {%1,%2,%3,%4};" :: "l"(kvp + lane * 4), "f"(kv[8 * W]), "f"(kv[8 * W + 1]), "f"(kv[8 * W + 2]), "f"(kv[8 * W + 3]) : "memory"); \
                       asm volatile("red.global.add.v4.f32 [%0], {%1,%2,%3,%4};" :: "l"(kvp + 128 + lane * 4), "f"(kv[8 * W + 4]), "f"(kv[8 * W + 5]), "f"(kv[8 * W + 6]), "f"(kv[8 * W + 7]) : "memory"); } while (0)
        if ((warp & 3) == 0) KV_RED(0); else if ((warp & 3) == 1) KV_RED(1); else if ((warp & 3) == 2) KV_RED(2); else KV_RED(3);
        if ((lane & 3) == 0) {
            asm volatile("red.global.add.f32 [%0], %1;" :: "l"(kvp + 256 + (lane >> 2)), "f"(zs[0]) : "memory");
            asm volatile("red.global.add.f32 [%0], %1;" :: "l"(kvp + 264 + (lane >> 2)), "f"(zs[2]) : "memory");
        }
        __syncwarp();
        if (lane == 0) mbar_arrive(sb + B_KVDONE);
        RET(24);
        pin(a1);
        G1(25, a2_, false, 1); send_h<2, 3>(fh0, hsend); SCHED(); H_EPI(a1, fh3, 0, 8, 32, 48); RET(25);
        G1(26, a2_, false, 2); send_h<3, 4>(fh0, hsend); SENT_H(0); SCHED(); PHI(a1, fo, 0, 4); RET(26);
        G1(27, a2_, false, 3); send_h<0, 1>(fh3, hsend + 4 * 1024 - (j & 1) * 1020); SCHED(); PHI(a1, fo, 4, 8); RET(27);
        G1(28, a2_, false, 4); send_h<1, 2>(fh3, hsend + 4 * 1024 - (j & 1) * 1020); SENT_H(1); SCHED(); PHI(a1, fo, 8, 12); RET(28);
        G1(29, a2_, false, 5); SCHED(); PHI(a1, fo, 12, 16); RET(29);
        G1(30, a2_, false, 6); RET(30);
        G1(31, a2_, false, 7); RET(31);
        if ((warp & 3) == 0) TS(wg, 4);

        float on[4][12];
#define O_SCALE(h) do { const float s_lo = __fdividef(g_lo, on[h][8] + 1e-6f), s_hi = __fdividef(g_hi, on[h][10] + 1e-6f); \
            const uint32_t sl_ = pack2(s_lo, s_lo), sh_ = pack2(s_hi, s_hi); \
            fo[4 * h] = keep(hmul2(pack2(on[h][0], on[h][1]), sl_)); fo[4 * h + 1] = keep(hmul2(pack2(on[h][2], on[h][3]), sh_)); \
            fo[4 * h + 2] = keep(hmul2(pack2(on[h][4], on[h][5]), sl_)); fo[4 * h + 3] = keep(hmul2(pack2(on[h][6], on[h][7]), sh_)); } while (0)
        uint4* const lsend = g_lx + (size_t)(r * 8 + j) * 2048 + warp * 128 + lane;
        const uint4* const lrecv = g_lx + (size_t)(r * 8 + (j ^ 1)) * 2048 + warp * 128 + lane;
        G1(32, a3, false, 0); RET(32);
        pin(a2_);
        G1(33, a3, false, 1); SCHED(); H_EPI(a2_, fh1, 0, 16, 0, 32); send_h<0, 1>(fh1, hsend + 2 * 1024); RET(33);
        G1(34, a3, false, 2); send_h<1, 3>(fh1, hsend + 2 * 1024);
        if ((warp & 3) == 0) TS(wg, 5);
        mbar_wait(sb + B_KVRDY, 0);
        if ((warp & 3) == 0) TS(wg, 6);
        wg_fence();
#pragma unroll
        for (int h = 0; h < 4; h++)
            wg_rs24_z(on[h], fo[4 * h], fo[4 * h + 1], fo[4 * h + 2], fo[4 * h + 3], (((sb + OFF_STG) >> 4) + h * 48) | (8u << 16), 16u);
        wg_commit();
        RET2(34);
        if (elect) mbar_arrive(sb + B_XFREE);
        G1(35, a3, false, 3); send_h<3, 4>(fh1, hsend + 2 * 1024); SENT_H(2); RET(35);
        pin(on[0]); pin(on[1]); pin(on[2]); pin(on[3]);
        release(B_EEMPTY + 16);
        G1(36, a3, false, 4); SCHED(); O_SCALE(0); O_SCALE(1); O_SCALE(2); O_SCALE(3); RET(36);
        G1(37, a3, false, 5); send_frag<0, 2>(fo, lsend, tag); RET(37);
        if (elect) mbar_arrive(sb + B_XFREE + 8);
        G1(38, a3, false, 6); send_frag<2, 4>(fo, lsend, tag); RET(38);
        release(B_EEMPTY);
        G1(39, a3, false, 7); RET(39);
        release(B_EEMPTY + 8);
        if ((warp & 3) == 0) TS(wg, 7);

#define G2S(S, acc, U) do { wg_fence(); _Pragma("unroll") for (int k = 0; k < 4; k++) { \
            if ((S) == 40 && k == 0) wg_ss128_z(acc, xlo, DH128, S_B(S) | LBO8K, DH128); \
            else wg_ss128(acc, xlo + (U) * 1024 + 2 * k, DH128, (S_B(S) | LBO8K) + 128 * k, DH128); } wg_commit(); } while (0)
#define G2R(S, acc, F) do { wg_fence(); _Pragma("unroll") for (int k = 0; k < 4; k++) { \
            if ((S) == 49 && k == 0) wg_rs128_z(acc, F[0], F[1], F[2], F[3], S_B(S) | LBO8K, DH128); \
            else wg_rs128(acc, F[4 * k], F[4 * k + 1], F[4 * k + 2], F[4 * k + 3], (S_B(S) | LBO8K) + 128 * k, DH128); } wg_commit(); } while (0)
#define H_WAIT(P) do { mbar_wait(sb + B_XFULL + 8 * (P), 1); if (PROF && tid == 0) TS2(150 + (P)); } while (0)
        const int p = j >> 1, pw = (p & 2) ^ 2;
        const bool own = wg == (p & 1);
        uint4* const pbase = g_part + (size_t)(r * 2 + (j & 1)) * 16384 + (warp & 3) * 256 + lane;

        float p1[64], p2[64];
        uint32_t po[16], ph2[16];
        H_WAIT(0); G2S(40, p1, 0); RET(40);
        release(B_EEMPTY + 24);
        pin(a3);
        G2S(41, p1, 1); SCHED(); H_EPI(a3, fh2, 0, 16, 0, 32); send_frag<0, 2>(fh2, lsend + 1024, tag); RET(41);
        H_WAIT(4); G2S(42, p1, 4); send_frag<2, 4>(fh2, lsend + 1024, tag); RET(42);
        G2R(43, p1, fo); recv_issue(po, lrecv); RET(43);
        H_WAIT(2); G2S(44, p1, 2); RET(44);
        G2S(45, p1, 3); SCHED(); recv_check(po, lrecv, tag); recv_issue(ph2, lrecv + 1024); RET(45);
        G2R(46, p1, po); RET(46);
        G2R(47, p1, fh2); SCHED(); recv_check(ph2, lrecv + 1024, tag); RET(47);
        G2R(48, p1, ph2); RET(48);
        if ((warp & 3) == 0) TS(wg, 8);
        uint32_t sp[32], qa[32], qb[32];
        uint4* const s1 = pbase + (((pw + wg) * 4 + p) << 10);
        G2R(49, p2, fo); RET(49);
        pin(p1);
        G2R(50, p2, po); SCHED(); pack_sub<0>(sp, p1); send_frag<0, 2>(sp, s1, tag); RET(50);
        G2R(51, p2, fh2); send_frag<2, 4>(sp, s1, tag); RET(51);
        G2R(52, p2, ph2); send_frag<4, 6>(sp, s1, tag); RET(52);
        G2S(53, p2, 0); send_frag<6, 8>(sp, s1, tag); RET(53);
        const uint4* ra = pbase + ((p * 4 + pw) << 10);
        const uint4* rc = pbase + ((p * 4 + (p ^ 1)) << 10);
        if (own) { mbar_wait(sb + B_AHEAD, 0); recv_issue(qa, ra); recv_issue(qb, ra + 1024); }
        G2S(54, p2, 1); RET(54);
        G2S(55, p2, 2); RET(55);
        G2S(56, p2, 3); RET(56);
        G2S(57, p2, 4);
        if ((warp & 3) == 0) TS(wg, 9);
        if (!own) {
            if (elect) mbar_arrive(sb + B_AHEAD);
        } else {
            recv_issue(sp, rc);
            recv_check(qa, ra, tag); recv_check(qb, ra + 1024, tag);
#pragma unroll
            for (int i = 0; i < 32; i++) qa[i] = keep(hadd2(qa[i], qb[i]));
        }
        wg_wait<0>();
        pin(p2);
        if ((warp & 3) == 0) TS(wg, 11);
        if (!own) {
            pack_sub<0>(sp, p2); send_frag<0, 8>(sp, pbase + (((p ^ 1) * 4 + p) << 10), tag);
        } else {
            if ((warp & 3) == 0) TS(wg, 12);
            recv_check(sp, rc, tag);
#pragma unroll
            for (int i = 0; i < 32; i++) qa[i] = hadd2(qa[i], sp[i]);
            accum(qa, p2);
            if ((warp & 3) == 0) TS(wg, 13);
            uint32_t f0[16], f1[16];
            pack_sub<0>(f0, p2); pack_sub<32>(f1, p2);
            const uint32_t slab = sb + OFF_X + 2 * 16384 + wg * 8192;
            stash<16>(slab + srow, ssw, f0); stash<16>(slab + 16384 + srow, ssw, f1);
            __syncwarp();
            __nv_bfloat16* op = out + (size_t)(r * 128 + warp * 16 + (lane >> 4)) * kD + (j & 1) * 256 + (p & 2) * 64 + (lane & 15) * 8;
#pragma unroll
            for (int i = 0; i < 8; i++) {
                const int row = i * 2 + (lane >> 4);
                uint4 v;
                asm volatile("ld.shared.v4.u32 {%0,%1,%2,%3}, [%4];" : "=r"(v.x), "=r"(v.y), "=r"(v.z), "=r"(v.w)
                             : "r"(slab + (lane & 8) * 2048 + ((warp & 3) * 16 + row) * 128 + (((lane & 7) ^ (row & 7)) << 4)) : "memory");
                *(uint4*)(op + i * 2 * kD) = v;
            }
        }
        if ((warp & 3) == 0) { TS(wg, 14); TSG(wg, 31); }
    }
}

typedef CUresult (*EncodeFn)(CUtensorMap*, CUtensorMapDataType, cuuint32_t, void*, const cuuint64_t*, const cuuint64_t*, const cuuint32_t*,
                             const cuuint32_t*, CUtensorMapInterleave, CUtensorMapSwizzle, CUtensorMapL2promotion, CUtensorMapFloatOOBfill);

static void encode(EncodeFn fn, CUtensorMap* m, int rank, const void* base, const cuuint64_t (&gd)[5], const cuuint64_t (&gs)[4],
                   const cuuint32_t (&bd)[5], CUtensorMapSwizzle sw) {
    cuuint32_t es[5] = {1, 1, 1, 1, 1};
    fn(m, CU_TENSOR_MAP_DATA_TYPE_BFLOAT16, rank, const_cast<void*>(base), gd, gs, bd, es, CU_TENSOR_MAP_INTERLEAVE_NONE, sw,
       CU_TENSOR_MAP_L2_PROMOTION_L2_128B, CU_TENSOR_MAP_FLOAT_OOB_FILL_NONE);
}

extern "C" void kernel_launch(void* const* d_in, const int* in_sizes, int n_in, void* d_out, int out_size) {
    const char* x = (const char*)d_in[0];
    const char* wqkv = (const char*)d_in[1];
    const char* wo = (const char*)d_in[2];
    const char* wg = (const char*)d_in[4];
    const char* wu = (const char*)d_in[5];
    const char* wd = (const char*)d_in[6];
    void* fnp = nullptr;
    cudaDriverEntryPointQueryResult qr;
    cudaGetDriverEntryPoint("cuTensorMapEncodeTiled", &fnp, cudaEnableDefault, &qr);
    EncodeFn fn = (EncodeFn)fnp;
    Maps maps;
    const char* lo = wg < wu ? wg : wu;
    const uint64_t diff = wg < wu ? (uint64_t)(wu - wg) : (uint64_t)(wg - wu);
    const CUtensorMapSwizzle S128 = CU_TENSOR_MAP_SWIZZLE_128B, S64 = CU_TENSOR_MAP_SWIZZLE_64B;
    encode(fn, &maps.x, 2, x, {512, 2048, 1, 1}, {1024, 0, 0}, {64, 128, 1, 1}, S128);
    encode(fn, &maps.gu, 3, lo, {1792, 512, 2, 1}, {3584, diff, 0}, {64, 64, 2, 1}, S128);
    encode(fn, &maps.kv, 3, wqkv, {512, 512, 3, 1}, {3072, 1024, 0}, {64, 64, 2, 1}, S128);
    encode(fn, &maps.q64, 3, wqkv, {32, 512, 48, 1}, {3072, 64, 0}, {32, 64, 2, 1}, S64);
    encode(fn, &maps.gu64, 3, lo, {1792, 512, 2, 1}, {3584, diff, 0}, {32, 64, 2, 1}, S64);
    encode(fn, &maps.wdw, 3, wd, {64, 1792, 8, 1}, {1024, 128, 0}, {64, 64, 2, 1}, S128);
    encode(fn, &maps.wow, 3, wo, {64, 512, 8}, {1024, 128}, {64, 64, 2}, S128);
    encode(fn, &maps.wdp, 5, wd, {512, 2, 4, 4, 56}, {1024, 8192, 2048, 32768}, {64, 2, 4, 4, 2}, S128);
    encode(fn, &maps.wdph, 5, wd, {512, 2, 4, 4, 56}, {1024, 8192, 2048, 32768}, {64, 2, 4, 4, 1}, S128);
    void* hx = nullptr;
    cudaGetSymbolAddress(&hx, g_hx);
    encode(fn, &maps.hx, 2, hx, {64, 16 * 4 * 5 * 128}, {128}, {64, 128}, S128);
    encode(fn, &maps.hx2, 2, hx, {64, 16 * 4 * 5 * 128}, {128}, {64, 256}, S128);
    cudaFuncSetAttribute(fused_kernel, cudaFuncAttributeMaxDynamicSharedMemorySize, SMEM_BYTES);
    cudaLaunchConfig_t cfg = {};
    cfg.gridDim = dim3(128);
    cfg.blockDim = dim3(384);
    cfg.dynamicSmemBytes = SMEM_BYTES;
    cfg.stream = cudaStreamPerThread;
    cudaLaunchAttribute at[1];
    at[0].id = cudaLaunchAttributeClusterDimension;
    at[0].val.clusterDim.x = 2; at[0].val.clusterDim.y = 1; at[0].val.clusterDim.z = 1;
    cfg.attrs = at;
    cfg.numAttrs = MC ? 1 : 0;
    cudaLaunchKernelEx(&cfg, fused_kernel, maps, (const __nv_bfloat16*)d_in[0], (const __nv_bfloat16*)d_in[7], wqkv, wg, wu, wd, wo, (__nv_bfloat16*)d_out);
}
```

```cpp
#include <cuda_runtime.h>
#include <cuda.h>
#include <cuda_bf16.h>
#include <stdint.h>

#define MC 0
#define PFMODE 1
#define PROF 0

namespace {

constexpr int kD = 512;
constexpr uint32_t OFF_X = 0, OFF_STG = 131072, OFF_RING = 147456, OFF_MISC = 229376;
constexpr uint32_t B_FULL = OFF_MISC, B_EMPTY = OFF_MISC + 40, B_XFULL = OFF_MISC + 80;
constexpr uint32_t B_GRDY = OFF_MISC + 152, B_KVDONE = OFF_MISC + 160, B_KVRDY = OFF_MISC + 168;
constexpr uint32_t B_HSENT = OFF_MISC + 176, B_XFREE = OFF_MISC + 200;
constexpr uint32_t OFF_EPOCH = OFF_MISC + 240, OFF_G = OFF_MISC + 256;
constexpr uint32_t B_AHEAD = OFF_MISC + 248;
constexpr uint32_t OFF_ONES = OFF_MISC + 768;
constexpr uint32_t B_EFULL = OFF_MISC + 896, B_EEMPTY = OFF_MISC + 928;
constexpr uint32_t SMEM_BYTES = OFF_MISC + 960;
constexpr uint32_t SPIN_GLOBAL = 1u << 14;

struct alignas(64) Maps { CUtensorMap x, gu, kv, q64, gu64, wdw, wow, wdp, wdph, hx, hx2; };

}

__device__ uint4 g_part[16 * 2 * 4 * 4 * 1024];
__device__ uint4 g_hx[16 * 4 * 5 * 1024];
__device__ uint4 g_lx[16 * 8 * 2 * 1024];
__device__ unsigned g_hflag[128 * 8];
__device__ uint4 g_gx[16 * 32];
__device__ float g_kvacc[2 * 8 * 4 * 272];
__device__ unsigned g_kvcnt[8 * 32];
__device__ unsigned g_epoch[128];
#define TS(role, idx)
#define TS2(idx)
#define TSG(role, idx)

namespace {

__device__ __forceinline__ void mbar_init(uint32_t bar, uint32_t cnt) { asm volatile("mbarrier.init.shared::cta.b64 [%0], %1;" :: "r"(bar), "r"(cnt) : "memory"); }
__device__ __forceinline__ void mbar_expect(uint32_t bar, uint32_t bytes) { asm volatile("mbarrier.arrive.expect_tx.shared::cta.b64 _, [%0], %1;" :: "r"(bar), "r"(bytes) : "memory"); }
__device__ __forceinline__ void mbar_arrive(uint32_t bar) { asm volatile("mbarrier.arrive.shared::cta.b64 _, [%0];" :: "r"(bar) : "memory"); }
__device__ __forceinline__ void mbar_arrive_cta(uint32_t bar, uint32_t cta) {
    asm volatile("{\n.reg .b32 ra;\nmapa.shared::cluster.u32 ra, %0, %1;\nmbarrier.arrive.shared::cluster.b64 _, [ra];\n}" :: "r"(bar), "r"(cta) : "memory");
}
__device__ __forceinline__ void mbar_wait(uint32_t bar, uint32_t parity) {
    asm volatile("{\n.reg .pred p;\n.reg .u32 c;\n"
                 "mbarrier.try_wait.parity.shared::cta.b64 p, [%0], %1;\n@p bra DONE;\n"
                 "mov.u32 c, 0;\nLAB_WAIT:\nmbarrier.try_wait.parity.shared::cta.b64 p, [%0], %1;\n@p bra DONE;\n"
                 "add.u32 c, c, 1;\nsetp.lt.u32 p, c, 65536;\n@p bra LAB_WAIT;\nDONE:\n}" :: "r"(bar), "r"(parity) : "memory");
}
__device__ __forceinline__ void tma2(uint32_t dst, const CUtensorMap* m, int c0, int c1, uint32_t bar) {
    asm volatile("cp.async.bulk.tensor.2d.shared::cluster.global.mbarrier::complete_tx::bytes [%0], [%1, {%3, %4}], [%2];"
        :: "r"(dst), "l"(m), "r"(bar), "r"(c0), "r"(c1) : "memory");
}
__device__ __forceinline__ void tmaw2(uint32_t dst, const CUtensorMap* m, int c0, int c1, uint32_t bar) {
    tma2(dst, m, c0, c1, bar);
}
__device__ __forceinline__ void tmaw3(uint32_t dst, const CUtensorMap* m, int c0, int c1, int c2, uint32_t bar) {
    asm volatile("cp.async.bulk.tensor.3d.shared::cluster.global.mbarrier::complete_tx::bytes [%0], [%1, {%3, %4, %5}], [%2];"
        :: "r"(dst), "l"(m), "r"(bar), "r"(c0), "r"(c1), "r"(c2) : "memory");
}
__device__ __forceinline__ void tmaw5(uint32_t dst, const CUtensorMap* m, int c0, int c4, uint32_t bar) {
    asm volatile("cp.async.bulk.tensor.5d.shared::cluster.global.mbarrier::complete_tx::bytes [%0], [%1, {%3, %5, %5, %5, %4}], [%2];"
        :: "r"(dst), "l"(m), "r"(bar), "r"(c0), "r"(c4), "r"(0) : "memory");
}
__device__ __forceinline__ void wg_fence() { asm volatile("wgmma.fence.sync.aligned;" ::: "memory"); }
__device__ __forceinline__ void wg_commit() { asm volatile("wgmma.commit_group.sync.aligned;" ::: "memory"); }
template <int N> __device__ __forceinline__ void wg_wait() { asm volatile("wgmma.wait_group.sync.aligned %0;" :: "n"(N) : "memory"); }
template <int N> __device__ __forceinline__ void pin(float (&d)[N]) {
#pragma unroll
    for (int i = 0; i < N; i++) asm volatile("" : "+f"(d[i]) :: "memory");
}
__device__ __forceinline__ uint32_t pack2(float lo, float hi) { uint32_t r; asm("cvt.rn.bf16x2.f32 %0, %1, %2;" : "=r"(r) : "f"(hi), "f"(lo)); return r; }
__device__ __forceinline__ uint32_t keep(uint32_t v) { asm volatile("" : "+r"(v)); return v; }
__device__ __forceinline__ uint32_t hadd2(uint32_t a, uint32_t b) { uint32_t r; asm("add.bf16x2 %0, %1, %2;" : "=r"(r) : "r"(a), "r"(b)); return r; }
__device__ __forceinline__ uint32_t hmul2(uint32_t a, uint32_t b) { uint32_t r; asm("mul.bf16x2 %0, %1, %2;" : "=r"(r) : "r"(a), "r"(b)); return r; }
__device__ __forceinline__ uint32_t phi2(float t0, float t1) {
    float e0, e1;
    asm("ex2.approx.ftz.f32 %0, %1;" : "=f"(e0) : "f"(t0 * 1.4426950408889634f));
    asm("ex2.approx.ftz.f32 %0, %1;" : "=f"(e1) : "f"(t1 * 1.4426950408889634f));
    uint32_t e = pack2(e0, e1), t = pack2(t0, t1), r;
    asm("min.bf16x2 %0, %0, %1;" : "+r"(e) : "r"(0x3f803f80u));
    asm("max.bf16x2 %0, %0, %1;" : "+r"(t) : "r"(0x35863586u));
    asm("add.bf16x2 %0, %1, %2;" : "=r"(r) : "r"(e), "r"(t));
    return r;
}
__device__ __forceinline__ void stsm4(uint32_t a, uint32_t r0, uint32_t r1, uint32_t r2, uint32_t r3) {
    asm volatile("stmatrix.sync.aligned.m8n8.x4.shared.b16 [%0], {%1,%2,%3,%4};" :: "r"(a), "r"(r0), "r"(r1), "r"(r2), "r"(r3) : "memory");
}
__device__ __forceinline__ float bf_lo(uint32_t w) { return __uint_as_float(w << 16); }
__device__ __forceinline__ float bf_hi(uint32_t w) { return __uint_as_float(w & 0xffff0000u); }
__device__ __forceinline__ void st_pkt(uint4* p, uint32_t w0, uint32_t w1, uint32_t w2, uint32_t w3) {
    asm volatile("{\n.reg .b64 lo, hi;\n.reg .b128 v;\nmov.b64 lo, {%1, %2};\nmov.b64 hi, {%3, %4};\nmov.b128 v, {lo, hi};\nst.relaxed.gpu.global.b128 [%0], v;\n}"
        :: "l"(p), "r"(w0), "r"(w1), "r"(w2), "r"(w3) : "memory");
}
__device__ __forceinline__ void ld_pkt(const uint4* p, uint32_t& w0, uint32_t& w1, uint32_t& w2, uint32_t& w3) {
    asm volatile("{\n.reg .b64 lo, hi;\n.reg .b128 v;\nld.relaxed.gpu.global.b128 v, [%4];\nmov.b128 {lo, hi}, v;\nmov.b64 {%0, %1}, lo;\nmov.b64 {%2, %3}, hi;\n}"
        : "=r"(w0), "=r"(w1), "=r"(w2), "=r"(w3) : "l"(p) : "memory");
}

template <uint32_t AO, uint32_t BO, uint32_t BH> __device__ __forceinline__ void wg_ss128(float (&d)[64], uint32_t ab, uint32_t bb) {
    asm volatile("{\n.reg .b64 da, db;\n.reg .b32 ta, tb, th, ah;\nadd.u32 ta, %64, %66;\nadd.u32 tb, %65, %67;\nmov.b32 th, %68;\nmov.b32 ah, 0x40000040;\nmov.b64 da, {ta, ah};\nmov.b64 db, {tb, th};\n"
        "wgmma.mma_async.sync.aligned.m64n128k16.f32.bf16.bf16 {%0,%1,%2,%3,%4,%5,%6,%7,%8,%9,%10,%11,%12,%13,%14,%15,%16,%17,%18,%19,%20,%21,%22,%23,%24,%25,%26,%27,%28,%29,%30,%31,%32,%33,%34,%35,%36,%37,%38,%39,%40,%41,%42,%43,%44,%45,%46,%47,%48,%49,%50,%51,%52,%53,%54,%55,%56,%57,%58,%59,%60,%61,%62,%63}, da, db, 1, 1, 1, 0, 1;\n}\n"
        : "+f"(d[0]),"+f"(d[1]),"+f"(d[2]),"+f"(d[3]),"+f"(d[4]),"+f"(d[5]),"+f"(d[6]),"+f"(d[7]),"+f"(d[8]),"+f"(d[9]),"+f"(d[10]),"+f"(d[11]),"+f"(d[12]),"+f"(d[13]),"+f"(d[14]),"+f"(d[15]),"+f"(d[16]),"+f"(d[17]),"+f"(d[18]),"+f"(d[19]),"+f"(d[20]),"+f"(d[21]),"+f"(d[22]),"+f"(d[23]),"+f"(d[24]),"+f"(d[25]),"+f"(d[26]),"+f"(d[27]),"+f"(d[28]),"+f"(d[29]),"+f"(d[30]),"+f"(d[31]),"+f"(d[32]),"+f"(d[33]),"+f"(d[34]),"+f"(d[35]),"+f"(d[36]),"+f"(d[37]),"+f"(d[38]),"+f"(d[39]),"+f"(d[40]),"+f"(d[41]),"+f"(d[42]),"+f"(d[43]),"+f"(d[44]),"+f"(d[45]),"+f"(d[46]),"+f"(d[47]),"+f"(d[48]),"+f"(d[49]),"+f"(d[50]),"+f"(d[51]),"+f"(d[52]),"+f"(d[53]),"+f"(d[54]),"+f"(d[55]),"+f"(d[56]),"+f"(d[57]),"+f"(d[58]),"+f"(d[59]),"+f"(d[60]),"+f"(d[61]),"+f"(d[62]),"+f"(d[63])
        : "r"(ab), "r"(bb), "n"(AO), "n"(BO), "n"(BH));
}
template <uint32_t AO, uint32_t BO, uint32_t BH> __device__ __forceinline__ void wg_ss128_z(float (&d)[64], uint32_t ab, uint32_t bb) {
    asm volatile("{\n.reg .b64 da, db;\n.reg .b32 ta, tb, th, ah;\nadd.u32 ta, %64, %66;\nadd.u32 tb, %65, %67;\nmov.b32 th, %68;\nmov.b32 ah, 0x40000040;\nmov.b64 da, {ta, ah};\nmov.b64 db, {tb, th};\n"
        "wgmma.mma_async.sync.aligned.m64n128k16.f32.bf16.bf16 {%0,%1,%2,%3,%4,%5,%6,%7,%8,%9,%10,%11,%12,%13,%14,%15,%16,%17,%18,%19,%20,%21,%22,%23,%24,%25,%26,%27,%28,%29,%30,%31,%32,%33,%34,%35,%36,%37,%38,%39,%40,%41,%42,%43,%44,%45,%46,%47,%48,%49,%50,%51,%52,%53,%54,%55,%56,%57,%58,%59,%60,%61,%62,%63}, da, db, 0, 1, 1, 0, 1;\n}\n"
        : "=f"(d[0]),"=f"(d[1]),"=f"(d[2]),"=f"(d[3]),"=f"(d[4]),"=f"(d[5]),"=f"(d[6]),"=f"(d[7]),"=f"(d[8]),"=f"(d[9]),"=f"(d[10]),"=f"(d[11]),"=f"(d[12]),"=f"(d[13]),"=f"(d[14]),"=f"(d[15]),"=f"(d[16]),"=f"(d[17]),"=f"(d[18]),"=f"(d[19]),"=f"(d[20]),"=f"(d[21]),"=f"(d[22]),"=f"(d[23]),"=f"(d[24]),"=f"(d[25]),"=f"(d[26]),"=f"(d[27]),"=f"(d[28]),"=f"(d[29]),"=f"(d[30]),"=f"(d[31]),"=f"(d[32]),"=f"(d[33]),"=f"(d[34]),"=f"(d[35]),"=f"(d[36]),"=f"(d[37]),"=f"(d[38]),"=f"(d[39]),"=f"(d[40]),"=f"(d[41]),"=f"(d[42]),"=f"(d[43]),"=f"(d[44]),"=f"(d[45]),"=f"(d[46]),"=f"(d[47]),"=f"(d[48]),"=f"(d[49]),"=f"(d[50]),"=f"(d[51]),"=f"(d[52]),"=f"(d[53]),"=f"(d[54]),"=f"(d[55]),"=f"(d[56]),"=f"(d[57]),"=f"(d[58]),"=f"(d[59]),"=f"(d[60]),"=f"(d[61]),"=f"(d[62]),"=f"(d[63])
        : "r"(ab), "r"(bb), "n"(AO), "n"(BO), "n"(BH));
}
template <uint32_t BO, uint32_t BH> __device__ __forceinline__ void wg_rs128(float (&d)[64], uint32_t a0, uint32_t a1, uint32_t a2, uint32_t a3, uint32_t bb) {
    asm volatile("{\n.reg .b64 db;\n.reg .b32 tb, th;\nadd.u32 tb, %68, %69;\nmov.b32 th, %70;\nmov.b64 db, {tb, th};\n"
        "wgmma.mma_async.sync.aligned.m64n128k16.f32.bf16.bf16 {%0,%1,%2,%3,%4,%5,%6,%7,%8,%9,%10,%11,%12,%13,%14,%15,%16,%17,%18,%19,%20,%21,%22,%23,%24,%25,%26,%27,%28,%29,%30,%31,%32,%33,%34,%35,%36,%37,%38,%39,%40,%41,%42,%43,%44,%45,%46,%47,%48,%49,%50,%51,%52,%53,%54,%55,%56,%57,%58,%59,%60,%61,%62,%63}, {%64,%65,%66,%67}, db, 1, 1, 1, 1;\n}\n"
        : "+f"(d[0]),"+f"(d[1]),"+f"(d[2]),"+f"(d[3]),"+f"(d[4]),"+f"(d[5]),"+f"(d[6]),"+f"(d[7]),"+f"(d[8]),"+f"(d[9]),"+f"(d[10]),"+f"(d[11]),"+f"(d[12]),"+f"(d[13]),"+f"(d[14]),"+f"(d[15]),"+f"(d[16]),"+f"(d[17]),"+f"(d[18]),"+f"(d[19]),"+f"(d[20]),"+f"(d[21]),"+f"(d[22]),"+f"(d[23]),"+f"(d[24]),"+f"(d[25]),"+f"(d[26]),"+f"(d[27]),"+f"(d[28]),"+f"(d[29]),"+f"(d[30]),"+f"(d[31]),"+f"(d[32]),"+f"(d[33]),"+f"(d[34]),"+f"(d[35]),"+f"(d[36]),"+f"(d[37]),"+f"(d[38]),"+f"(d[39]),"+f"(d[40]),"+f"(d[41]),"+f"(d[42]),"+f"(d[43]),"+f"(d[44]),"+f"(d[45]),"+f"(d[46]),"+f"(d[47]),"+f"(d[48]),"+f"(d[49]),"+f"(d[50]),"+f"(d[51]),"+f"(d[52]),"+f"(d[53]),"+f"(d[54]),"+f"(d[55]),"+f"(d[56]),"+f"(d[57]),"+f"(d[58]),"+f"(d[59]),"+f"(d[60]),"+f"(d[61]),"+f"(d[62]),"+f"(d[63])
        : "r"(a0), "r"(a1), "r"(a2), "r"(a3), "r"(bb), "n"(BO), "n"(BH));
}
template <uint32_t BO, uint32_t BH> __device__ __forceinline__ void wg_rs128_z(float (&d)[64], uint32_t a0, uint32_t a1, uint32_t a2, uint32_t a3, uint32_t bb) {
    asm volatile("{\n.reg .b64 db;\n.reg .b32 tb, th;\nadd.u32 tb, %68, %69;\nmov.b32 th, %70;\nmov.b64 db, {tb, th};\n"
        "wgmma.mma_async.sync.aligned.m64n128k16.f32.bf16.bf16 {%0,%1,%2,%3,%4,%5,%6,%7,%8,%9,%10,%11,%12,%13,%14,%15,%16,%17,%18,%19,%20,%21,%22,%23,%24,%25,%26,%27,%28,%29,%30,%31,%32,%33,%34,%35,%36,%37,%38,%39,%40,%41,%42,%43,%44,%45,%46,%47,%48,%49,%50,%51,%52,%53,%54,%55,%56,%57,%58,%59,%60,%61,%62,%63}, {%64,%65,%66,%67}, db, 0, 1, 1, 1;\n}\n"
        : "=f"(d[0]),"=f"(d[1]),"=f"(d[2]),"=f"(d[3]),"=f"(d[4]),"=f"(d[5]),"=f"(d[6]),"=f"(d[7]),"=f"(d[8]),"=f"(d[9]),"=f"(d[10]),"=f"(d[11]),"=f"(d[12]),"=f"(d[13]),"=f"(d[14]),"=f"(d[15]),"=f"(d[16]),"=f"(d[17]),"=f"(d[18]),"=f"(d[19]),"=f"(d[20]),"=f"(d[21]),"=f"(d[22]),"=f"(d[23]),"=f"(d[24]),"=f"(d[25]),"=f"(d[26]),"=f"(d[27]),"=f"(d[28]),"=f"(d[29]),"=f"(d[30]),"=f"(d[31]),"=f"(d[32]),"=f"(d[33]),"=f"(d[34]),"=f"(d[35]),"=f"(d[36]),"=f"(d[37]),"=f"(d[38]),"=f"(d[39]),"=f"(d[40]),"=f"(d[41]),"=f"(d[42]),"=f"(d[43]),"=f"(d[44]),"=f"(d[45]),"=f"(d[46]),"=f"(d[47]),"=f"(d[48]),"=f"(d[49]),"=f"(d[50]),"=f"(d[51]),"=f"(d[52]),"=f"(d[53]),"=f"(d[54]),"=f"(d[55]),"=f"(d[56]),"=f"(d[57]),"=f"(d[58]),"=f"(d[59]),"=f"(d[60]),"=f"(d[61]),"=f"(d[62]),"=f"(d[63])
        : "r"(a0), "r"(a1), "r"(a2), "r"(a3), "r"(bb), "n"(BO), "n"(BH));
}
template <uint32_t AO, uint32_t BO, uint32_t BH> __device__ __forceinline__ void wg_ss64t(float (&d)[32], uint32_t ab, uint32_t bb) {
    asm volatile("{\n.reg .b64 da, db;\n.reg .b32 ta, tb, th, ah;\nadd.u32 ta, %32, %34;\nadd.u32 tb, %33, %35;\nmov.b32 th, %36;\nmov.b32 ah, 0x40000040;\nmov.b64 da, {ta, ah};\nmov.b64 db, {tb, th};\n"
        "wgmma.mma_async.sync.aligned.m64n64k16.f32.bf16.bf16 {%0,%1,%2,%3,%4,%5,%6,%7,%8,%9,%10,%11,%12,%13,%14,%15,%16,%17,%18,%19,%20,%21,%22,%23,%24,%25,%26,%27,%28,%29,%30,%31}, da, db, 1, 1, 1, 1, 1;\n}\n"
        : "+f"(d[0]),"+f"(d[1]),"+f"(d[2]),"+f"(d[3]),"+f"(d[4]),"+f"(d[5]),"+f"(d[6]),"+f"(d[7]),"+f"(d[8]),"+f"(d[9]),"+f"(d[10]),"+f"(d[11]),"+f"(d[12]),"+f"(d[13]),"+f"(d[14]),"+f"(d[15]),"+f"(d[16]),"+f"(d[17]),"+f"(d[18]),"+f"(d[19]),"+f"(d[20]),"+f"(d[21]),"+f"(d[22]),"+f"(d[23]),"+f"(d[24]),"+f"(d[25]),"+f"(d[26]),"+f"(d[27]),"+f"(d[28]),"+f"(d[29]),"+f"(d[30]),"+f"(d[31])
        : "r"(ab), "r"(bb), "n"(AO), "n"(BO), "n"(BH));
}
template <uint32_t AO, uint32_t BO, uint32_t BH> __device__ __forceinline__ void wg_ss64t_z(float (&d)[32], uint32_t ab, uint32_t bb) {
    asm volatile("{\n.reg .b64 da, db;\n.reg .b32 ta, tb, th, ah;\nadd.u32 ta, %32, %34;\nadd.u32 tb, %33, %35;\nmov.b32 th, %36;\nmov.b32 ah, 0x40000040;\nmov.b64 da, {ta, ah};\nmov.b64 db, {tb, th};\n"
        "wgmma.mma_async.sync.aligned.m64n64k16.f32.bf16.bf16 {%0,%1,%2,%3,%4,%5,%6,%7,%8,%9,%10,%11,%12,%13,%14,%15,%16,%17,%18,%19,%20,%21,%22,%23,%24,%25,%26,%27,%28,%29,%30,%31}, da, db, 0, 1, 1, 1, 1;\n}\n"
        : "=f"(d[0]),"=f"(d[1]),"=f"(d[2]),"=f"(d[3]),"=f"(d[4]),"=f"(d[5]),"=f"(d[6]),"=f"(d[7]),"=f"(d[8]),"=f"(d[9]),"=f"(d[10]),"=f"(d[11]),"=f"(d[12]),"=f"(d[13]),"=f"(d[14]),"=f"(d[15]),"=f"(d[16]),"=f"(d[17]),"=f"(d[18]),"=f"(d[19]),"=f"(d[20]),"=f"(d[21]),"=f"(d[22]),"=f"(d[23]),"=f"(d[24]),"=f"(d[25]),"=f"(d[26]),"=f"(d[27]),"=f"(d[28]),"=f"(d[29]),"=f"(d[30]),"=f"(d[31])
        : "r"(ab), "r"(bb), "n"(AO), "n"(BO), "n"(BH));
}
template <uint32_t AO, uint32_t BO, uint32_t BH> __device__ __forceinline__ void wg_ss8t(float (&d)[4], uint32_t ab, uint32_t bb) {
    asm volatile("{\n.reg .b64 da, db;\n.reg .b32 ta, tb, th, ah;\nadd.u32 ta, %4, %6;\nadd.u32 tb, %5, %7;\nmov.b32 th, %8;\nmov.b32 ah, 0x40000040;\nmov.b64 da, {ta, ah};\nmov.b64 db, {tb, th};\n"
        "wgmma.mma_async.sync.aligned.m64n8k16.f32.bf16.bf16 {%0,%1,%2,%3}, da, db, 1, 1, 1, 1, 0;\n}\n"
        : "+f"(d[0]),"+f"(d[1]),"+f"(d[2]),"+f"(d[3])
        : "r"(ab), "r"(bb), "n"(AO), "n"(BO), "n"(BH));
}
template <uint32_t AO, uint32_t BO, uint32_t BH> __device__ __forceinline__ void wg_ss8t_z(float (&d)[4], uint32_t ab, uint32_t bb) {
    asm volatile("{\n.reg .b64 da, db;\n.reg .b32 ta, tb, th, ah;\nadd.u32 ta, %4, %6;\nadd.u32 tb, %5, %7;\nmov.b32 th, %8;\nmov.b32 ah, 0x40000040;\nmov.b64 da, {ta, ah};\nmov.b64 db, {tb, th};\n"
        "wgmma.mma_async.sync.aligned.m64n8k16.f32.bf16.bf16 {%0,%1,%2,%3}, da, db, 0, 1, 1, 1, 0;\n}\n"
        : "=f"(d[0]),"=f"(d[1]),"=f"(d[2]),"=f"(d[3])
        : "r"(ab), "r"(bb), "n"(AO), "n"(BO), "n"(BH));
}
template <uint32_t BO, uint32_t BH> __device__ __forceinline__ void wg_rs24_z(float (&d)[12], uint32_t a0, uint32_t a1, uint32_t a2, uint32_t a3, uint32_t bb) {
    asm volatile("{\n.reg .b64 db;\n.reg .b32 tb, th;\nadd.u32 tb, %16, %17;\nmov.b32 th, %18;\nmov.b64 db, {tb, th};\n"
        "wgmma.mma_async.sync.aligned.m64n24k16.f32.bf16.bf16 {%0,%1,%2,%3,%4,%5,%6,%7,%8,%9,%10,%11}, {%12,%13,%14,%15}, db, 0, 1, 1, 0;\n}\n"
        : "=f"(d[0]),"=f"(d[1]),"=f"(d[2]),"=f"(d[3]),"=f"(d[4]),"=f"(d[5]),"=f"(d[6]),"=f"(d[7]),"=f"(d[8]),"=f"(d[9]),"=f"(d[10]),"=f"(d[11])
        : "r"(a0), "r"(a1), "r"(a2), "r"(a3), "r"(bb), "n"(BO), "n"(BH));
}

constexpr uint32_t DH128 = 64u | 0x40000000u;
constexpr uint32_t DH64 = 32u | 0x80000000u;
constexpr uint32_t LBO4K = (4096u >> 4) << 16, LBO8K = (8192u >> 4) << 16, LBO1 = 1u << 16;

template <uint32_t AO, uint32_t BO, bool SW64, bool FIRST> __device__ __forceinline__ void stage_ss(float (&acc)[64], uint32_t ab, uint32_t bb) {
    constexpr uint32_t KS = SW64 ? 64 : 128, BH = SW64 ? DH64 : DH128, B0 = BO + (SW64 ? LBO4K : LBO8K);
    wg_fence();
    if (FIRST) wg_ss128_z<AO, B0, BH>(acc, ab, bb); else wg_ss128<AO, B0, BH>(acc, ab, bb);
    wg_ss128<AO + 2, B0 + KS, BH>(acc, ab, bb);
    wg_ss128<AO + 4, B0 + 2 * KS, BH>(acc, ab, bb);
    wg_ss128<AO + 6, B0 + 3 * KS, BH>(acc, ab, bb);
    wg_commit();
}
template <uint32_t BO, bool FIRST> __device__ __forceinline__ void stage_rs(float (&acc)[64], const uint32_t (&f)[16], uint32_t bb) {
    wg_fence();
    if (FIRST) wg_rs128_z<BO + LBO8K, DH128>(acc, f[0], f[1], f[2], f[3], bb); else wg_rs128<BO + LBO8K, DH128>(acc, f[0], f[1], f[2], f[3], bb);
    wg_rs128<BO + LBO8K + 128, DH128>(acc, f[4], f[5], f[6], f[7], bb);
    wg_rs128<BO + LBO8K + 256, DH128>(acc, f[8], f[9], f[10], f[11], bb);
    wg_rs128<BO + LBO8K + 384, DH128>(acc, f[12], f[13], f[14], f[15], bb);
    wg_commit();
}

template <int N> __device__ __forceinline__ void stash(uint32_t base, uint32_t sw, const uint32_t (&f)[N]) {
#pragma unroll
    for (int t = 0; t < N / 4; t++) stsm4(base + ((sw ^ (2 * t)) << 4), f[4 * t], f[4 * t + 1], f[4 * t + 2], f[4 * t + 3]);
}

template <int V0, int V1, int N> __device__ __forceinline__ void send_frag(const uint32_t (&f)[N], uint4* p, uint32_t tag) {
#pragma unroll
    for (int v = V0; v < V1; v++) st_pkt(p + v * 32, (f[4 * v] & ~1u) | tag, f[4 * v + 1], f[4 * v + 2], f[4 * v + 3]);
}
template <int V0, int V1, int N> __device__ __forceinline__ void send_h(const uint32_t (&f)[N], uint4* p) {
#pragma unroll
    for (int v = V0; v < V1; v++) {
        const int h = v >> 1, hi = v & 1;
        asm volatile("st.global.v4.u32 [%0], {%1,%2,%3,%4};" :: "l"(p + 4 * h + 64 * hi),
                     "r"(f[8 * h + hi]), "r"(f[8 * h + 2 + hi]), "r"(f[8 * h + 4 + hi]), "r"(f[8 * h + 6 + hi]) : "memory");
    }
}
template <int O, int N, int M> __device__ __forceinline__ void pack_sub(uint32_t (&f)[N], const float (&acc)[M]) {
#pragma unroll
    for (int i = 0; i < N; i++) f[i] = keep(pack2(acc[O + 2 * i], acc[O + 2 * i + 1]));
}
template <int N> __device__ __forceinline__ void recv_issue(uint32_t (&q)[N], const uint4* p) {
#pragma unroll
    for (int v = 0; v < N / 4; v++) ld_pkt(p + v * 32, q[4 * v], q[4 * v + 1], q[4 * v + 2], q[4 * v + 3]);
}
template <int N> __device__ __forceinline__ void recv_check(uint32_t (&q)[N], const uint4* p, uint32_t tag) {
    uint32_t it = 0;
    while (true) {
        uint32_t bad = 0;
#pragma unroll
        for (int v = 0; v < N / 4; v++) bad |= q[4 * v] ^ tag;
        if (__all_sync(0xffffffffu, (bad & 1u) == 0) || ++it > SPIN_GLOBAL) break;
        recv_issue(q, p);
    }
}
__device__ __forceinline__ void accum(const uint32_t (&q)[32], float (&sum)[64]) {
#pragma unroll
    for (int i = 0; i < 32; i++) { sum[2 * i] += bf_lo(q[i]); sum[2 * i + 1] += bf_hi(q[i]); }
}

}

__global__ void __launch_bounds__(384, 1)
fused_kernel(const __grid_constant__ Maps maps, const __nv_bfloat16* __restrict__ xg, const __nv_bfloat16* __restrict__ gate_w,
             const char* __restrict__ pf_qkv, const char* __restrict__ pf_g, const char* __restrict__ pf_u,
             const char* __restrict__ pf_d, const char* __restrict__ pf_o, __nv_bfloat16* __restrict__ out) {
    extern __shared__ __align__(1024) uint8_t smem_raw[];
    const uint32_t sb = (uint32_t)__cvta_generic_to_shared(smem_raw);
    const int tid = threadIdx.x, lane = tid & 31;
    const int warp = __shfl_sync(0xffffffffu, tid >> 5, 0);
    const int j = (blockIdx.x >> 1) & 7;
    const int r = ((blockIdx.x >> 4) << 1) | (blockIdx.x & 1);
    const uint32_t rank = blockIdx.x & 1;

    if (warp == 0) { TSG(0, 30); TS(0, 0); }
    if (tid == 256) {
        for (int i = 0; i < 5; i++) { mbar_init(sb + B_FULL + 8 * i, 1); mbar_init(sb + B_EMPTY + 8 * i, MC ? 4 : 2); }
        for (int i = 0; i < 9; i++) mbar_init(sb + B_XFULL + 8 * i, 1);
        asm volatile("fence.mbarrier_init.release.cluster;" ::: "memory");
        mbar_expect(sb + B_XFULL, 16384);
        tma2(sb + OFF_X, &maps.x, 0, r * 128, sb + B_XFULL);
        TS2(0);
        mbar_expect(sb + B_FULL, 16384);
        tmaw3(sb + OFF_RING, &maps.kv, 64 * j, 0, 1, sb + B_FULL);
        TS2(1);
        mbar_expect(sb + B_FULL + 8, 16384);
        tmaw3(sb + OFF_RING + 16384, &maps.gu, 224 * j, 0, 0, sb + B_FULL + 8);
    } else if (tid == 288) {
        for (int i = 0; i < 3; i++) mbar_init(sb + B_HSENT + 8 * i, 8);
        for (int i = 0; i < 4; i++) { mbar_init(sb + B_EFULL + 8 * i, 1); mbar_init(sb + B_EEMPTY + 8 * i, MC ? 4 : 2); }
        mbar_init(sb + B_XFREE, 2); mbar_init(sb + B_XFREE + 8, 2); mbar_init(sb + B_XFREE + 16, 2);
        mbar_init(sb + B_AHEAD, 1); mbar_init(sb + B_GRDY, 1); mbar_init(sb + B_KVDONE, 8); mbar_init(sb + B_KVRDY, 2);
        asm volatile("fence.mbarrier_init.release.cluster;" ::: "memory");
    } else if (warp == 10 && lane < 10) {
        asm volatile("prefetch.tensormap [%0];" :: "l"(&maps.gu + lane) : "memory");
    }
    __syncthreads();

    if (warp >= 8) {
        asm volatile("setmaxnreg.dec.sync.aligned.u32 56;");
        if (warp == 8) {
            if (lane == 0) {
                int slot = MC ? 0 : 2, ph = 1;
                uint32_t full, dst;
                if (!MC) { mbar_expect(sb + B_XFULL + 8, 16384); tma2(sb + OFF_X + 16384, &maps.x, 64, r * 128, sb + B_XFULL + 8); }
#define P_BEGIN(S, BYTES) full = sb + B_FULL + 8 * slot; dst = sb + OFF_RING + slot * 16384; \
                mbar_wait(sb + B_EMPTY + 8 * slot, ph); TS2(S); mbar_expect(full, BYTES); if (!MC || (((S) ^ rank) & 1) == 0)
#define P_END() if (++slot == 5) { slot = 0; ph ^= 1; }
                for (int s = MC ? 0 : 2; s < 16; s++) {
                    const int kb = (int)(0x7654763542312100ull >> (4 * s)) & 15;
                    P_BEGIN(s, 16384) {
                        if ((0x0DADu >> s) & 1) tmaw3(dst, &maps.kv, 64 * j, 64 * kb, 1, full);
                        else tmaw3(dst, &maps.gu, 224 * j, 64 * kb, 0, full);
                    }
                    const int xb = (int)(0x0000000765403210ull >> (4 * s)) & 15;
                    if (xb) { mbar_expect(sb + B_XFULL + 8 * xb, 16384); tma2(sb + OFF_X + xb * 16384, &maps.x, 64 * xb, r * 128, sb + B_XFULL + 8 * xb); }
                    P_END()
                }
                for (int s = 0; s < 24; s++) {
                    P_BEGIN(16 + s, 16384) {
                        if (s < 8) {
                            tmaw3(dst, &maps.q64, 0, 64 * s, 2 * j, full);
                            tmaw3(dst + 8192, &maps.gu64, 224 * j + 192, 64 * s, 0, full);
                        } else {
                            tmaw3(dst, &maps.gu, 224 * j + 64 * (s >> 3), 64 * (s & 7), 0, full);
                        }
                    }
                    P_END()
                }
                const int p = j >> 1;
#pragma unroll 1
                for (int t = 0; t < 18; t++) {
                    const int q = t >= 9, sl = t - 9 * q;
                    const int u = (int)((q ? 0x432108675ull : 0x867325410ull) >> (4 * sl)) & 15;
                    const int cw = (j & 1) * 4 + ((p & 2) ^ (q ? 0 : 2)), cc = 64 * cw;
                    if (sl < 5) {
                        full = sb + B_FULL + 8 * sl; dst = sb + OFF_RING + sl * 16384;
                        mbar_wait(sb + B_EMPTY + 8 * sl, q ^ 1);
                    } else {
                        full = sb + B_EFULL + 8 * (sl - 5); dst = sb + OFF_X + (sl == 7 ? 8 : sl == 8 ? 7 : sl) * 16384;
                        mbar_wait(sb + B_EEMPTY + 8 * (sl - 5), q);
                    }
                    TS2(40 + t);
                    mbar_expect(full, 16384);
                    if (!MC || ((t ^ rank) & 1) == 0) {
                        if (u == 4) {
                            tmaw5(dst, &maps.wdph, cc, 14 * p + 6, full); tmaw5(dst + 4096, &maps.wdph, cc, 14 * p + 13, full);
                            tmaw5(dst + 8192, &maps.wdph, cc + 64, 14 * p + 6, full); tmaw5(dst + 12288, &maps.wdph, cc + 64, 14 * p + 13, full);
                        } else if (u > 4) {
                            const int js = u > 6 ? j ^ 1 : j;
                            tmaw3(dst, (u & 1) ? &maps.wow : &maps.wdw, 0, (u & 1) ? 64 * js : 224 * js + 128, cw, full);
                        } else {
                            const int g = 14 * p + 7 * (u & 1) + (u & 2);
                            tmaw5(dst, &maps.wdp, cc, g, full); tmaw5(dst + 8192, &maps.wdp, cc + 64, g, full);
                        }
                    }
                }
            }
        } else if (warp < 11) {
            const int hx = warp - 9;
            uint32_t epoch;
            asm volatile("ld.relaxed.gpu.global.u32 %0, [%1];" : "=r"(epoch) : "l"(g_epoch + blockIdx.x) : "memory");
            {
                const uint4* xr = (const uint4*)(xg + (size_t)(r * 128 + j * 16 + hx * 8) * kD) + lane;
                const uint4 wa = __ldg((const uint4*)gate_w + lane), wb = __ldg((const uint4*)gate_w + 32 + lane);
                const uint32_t tag = (epoch + 1) & 1;
                uint4* gp = g_gx + r * 32;
                if (lane < 2) st_pkt(gp + j * 4 + hx * 2 + lane, tag ^ 1, 0, 0, 0);
                float s[8];
#pragma unroll
                for (int i0 = 0; i0 < 8; i0 += 4) {
                    uint4 va[4], vb[4];
#pragma unroll
                    for (int i = 0; i < 4; i++) { va[i] = __ldg(xr + (i0 + i) * 64); vb[i] = __ldg(xr + (i0 + i) * 64 + 32); }
#pragma unroll
                    for (int i = 0; i < 4; i++) {
                        float t0 = bf_lo(va[i].x) * bf_lo(wa.x), t1 = bf_hi(va[i].x) * bf_hi(wa.x);
                        t0 = fmaf(bf_lo(va[i].y), bf_lo(wa.y), t0); t1 = fmaf(bf_hi(va[i].y), bf_hi(wa.y), t1);
                        t0 = fmaf(bf_lo(va[i].z), bf_lo(wa.z), t0); t1 = fmaf(bf_hi(va[i].z), bf_hi(wa.z), t1);
                        t0 = fmaf(bf_lo(va[i].w), bf_lo(wa.w), t0); t1 = fmaf(bf_hi(va[i].w), bf_hi(wa.w), t1);
                        t0 = fmaf(bf_lo(vb[i].x), bf_lo(wb.x), t0); t1 = fmaf(bf_hi(vb[i].x), bf_hi(wb.x), t1);
                        t0 = fmaf(bf_lo(vb[i].y), bf_lo(wb.y), t0); t1 = fmaf(bf_hi(vb[i].y), bf_hi(wb.y), t1);
                        t0 = fmaf(bf_lo(vb[i].z), bf_lo(wb.z), t0); t1 = fmaf(bf_hi(vb[i].z), bf_hi(wb.z), t1);
                        t0 = fmaf(bf_lo(vb[i].w), bf_lo(wb.w), t0); t1 = fmaf(bf_hi(vb[i].w), bf_hi(wb.w), t1);
                        s[i0 + i] = t0 + t1;
                    }
                }
#pragma unroll
                for (int i = 0; i < 8; i++) {
#pragma unroll
                    for (int o = 16; o; o >>= 1) s[i] += __shfl_xor_sync(0xffffffffu, s[i], o);
                    s[i] = 1.f / (1.f + __expf(-s[i]));
                }
                if (lane < 2) {
                    const float v0 = lane ? s[4] : s[0], v1 = lane ? s[5] : s[1], v2 = lane ? s[6] : s[2], v3 = lane ? s[7] : s[3];
                    st_pkt(gp + j * 4 + hx * 2 + lane, (__float_as_uint(v0) & ~1u) | tag, __float_as_uint(v1), __float_as_uint(v2), __float_as_uint(v3));
                }
                if (hx == 1) {
                    asm volatile("st.shared.u32 [%0], %1;" :: "r"(sb + OFF_ONES + lane * 4), "r"(0x3f803f80u) : "memory");
                    asm volatile("fence.proxy.async.shared::cta;" ::: "memory");
                }
                asm volatile("bar.sync 3, 96;" ::: "memory");
                if (hx == 0) {
                    uint32_t q[4];
                    recv_issue(q, gp + lane);
                    recv_check(q, gp + lane, tag);
                    asm volatile("st.shared.v4.u32 [%0], {%1,%2,%3,%4};" :: "r"(sb + OFF_G + lane * 16), "r"(q[0]), "r"(q[1]), "r"(q[2]), "r"(q[3]) : "memory");
                    if (lane == 0) {
                        asm volatile("st.shared.u32 [%0], %1;" :: "r"(sb + OFF_EPOCH), "r"(epoch) : "memory");
                        g_epoch[blockIdx.x] = epoch + 1;
                    }
                    __syncwarp();
                    if (lane == 0) mbar_arrive(sb + B_GRDY);
                } else {
                    if (r == 0) {
                        float4* zp = (float4*)(g_kvacc + (((epoch & 1) ^ 1) * 8 + j) * 4 * 272);
                        for (int i = lane; i < 272; i += 32) zp[i] = make_float4(0.f, 0.f, 0.f, 0.f);
                    }
                }
            }
            TS(2 + hx, 1);
#define PUBLISH_H(B) do { mbar_wait(sb + B_HSENT + 8 * (B), 0); if (lane == 0) { \
                asm volatile("st.release.gpu.global.u32 [%0], %1;" :: "l"(g_hflag + (r * 8 + j) * 8 + (B)), "r"(epoch + 1) : "memory"); } __syncwarp(); } while (0)
            if (hx == 1) {
#pragma unroll 1
                for (int b = 0; b < 3; b++) { PUBLISH_H(b); TS(3, 5 + b); }
            } else {
                const float* accp = g_kvacc + ((epoch & 1) * 8 + j) * 4 * 272;
                unsigned* cnt = g_kvcnt + j * 32;
                mbar_wait(sb + B_KVDONE, 0);
                TS(2, 5);
                if (lane == 0) asm volatile("red.release.gpu.global.add.u32 [%0], 1;" :: "l"(cnt) : "memory");
                __syncwarp();
                TS(2, 2);
                {
                    const unsigned target = 16u * (epoch + 1);
                    uint32_t it = 0, v;
                    do {
                        asm volatile("ld.acquire.gpu.global.u32 %0, [%1];" : "=r"(v) : "l"(cnt) : "memory");
                    } while ((int)(v - target) < 0 && ++it < SPIN_GLOBAL);
                }
                TS(2, 3);
#pragma unroll
                for (int h = 0; h < 4; h++) {
                    const float4 d0 = __ldcg((const float4*)(accp + h * 272) + lane);
                    const float4 d1 = __ldcg((const float4*)(accp + h * 272 + 128) + lane);
                    const float2 z0 = __ldcg((const float2*)(accp + h * 272 + 256) + (lane & 3));
                    const float2 z1 = __ldcg((const float2*)(accp + h * 272 + 264) + (lane & 3));
                    const uint32_t ba = sb + OFF_STG + h * 768 + lane * 4;
                    asm volatile("st.shared.u32 [%0], %1;" :: "r"(ba), "r"(pack2(d0.x, d0.y)) : "memory");
                    asm volatile("st.shared.u32 [%0], %1;" :: "r"(ba + 128), "r"(pack2(d1.x, d1.y)) : "memory");
                    asm volatile("st.shared.u32 [%0], %1;" :: "r"(ba + 256), "r"(pack2(d0.z, d0.w)) : "memory");
                    asm volatile("st.shared.u32 [%0], %1;" :: "r"(ba + 384), "r"(pack2(d1.z, d1.w)) : "memory");
                    asm volatile("st.shared.u32 [%0], %1;" :: "r"(ba + 512), "r"(pack2(z0.x, z0.y)) : "memory");
                    asm volatile("st.shared.u32 [%0], %1;" :: "r"(ba + 640), "r"(pack2(z1.x, z1.y)) : "memory");
                }
                asm volatile("fence.proxy.async.shared::cta;" ::: "memory");
                __syncwarp();
                if (lane == 0) mbar_arrive(sb + B_KVRDY);
                TS(2, 4);
            }
        } else {
            uint32_t epoch;
            asm volatile("ld.relaxed.gpu.global.u32 %0, [%1];" : "=r"(epoch) : "l"(g_epoch + blockIdx.x) : "memory");
            asm volatile("bar.arrive 3, 96;" :: "r"(epoch) : "memory");
            const int b = blockIdx.x, p = j >> 1;
            mbar_wait(sb + B_XFULL, 0);
#pragma unroll 1
            for (int kb = 1; kb < 8; kb++) {
                mbar_wait(sb + B_XFULL + 8 * kb, 0);
                const char* base = kb < 3 ? pf_g : kb < 5 ? pf_u : kb == 5 ? pf_qkv : pf_d;
                const int off = kb == 5 ? b * 12288 : b * 14336 + ((kb < 5 ? kb - 1 : kb) & 1) * 7168;
                if (kb == 5) {
                    asm volatile("prefetch.global.L2 [%0];" :: "l"(base + off + (lane >> 3) * 3072 + (lane & 7) * 128));
                } else {
                    asm volatile("prefetch.global.L2 [%0];" :: "l"(base + off + lane * 128));
                    if (lane < 24) asm volatile("prefetch.global.L2 [%0];" :: "l"(base + off + 4096 + lane * 128));
                }
                if (kb == 7) asm volatile("prefetch.global.L2 [%0];" :: "l"(pf_o + b * 4096 + lane * 128));
            }
            {
                uint4* mb = g_part + (size_t)(r * 2 + (j & 1)) * 16384 + (((p ^ 1) * 4 + p) << 10) + lane;
#pragma unroll 1
                for (int i = 0; i < 32; i++) { st_pkt(mb + i * 32, epoch & 1, 0, 0, 0); __nanosleep(40); }
                __syncwarp();
                if (lane == 0) mbar_arrive(sb + B_KVRDY);
            }
            {
                const uint32_t want = epoch + 1;
                const int hrow = (r * 4 + p) * 5 * 128;
                const unsigned* fl = g_hflag + (r * 8 + (j & 6)) * 8 + (lane & 15);
                uint32_t it = 0;
                int i = 0;
                mbar_wait(sb + B_HSENT + 8, 0);
#pragma unroll 1
                while (i < 3 && ++it < SPIN_GLOBAL) {
                    uint32_t v;
                    asm volatile("ld.acquire.gpu.global.u32 %0, [%1];" : "=r"(v) : "l"(fl) : "memory");
                    const uint32_t rdy = __ballot_sync(0xffffffffu, v == want);
#pragma unroll 1
                    while (i < 3 && ((rdy >> i) & 0x101u) == 0x101u) {
                        if (i < 2) mbar_wait(sb + B_XFREE + 8 * i, 0);
                        if (lane == 0) {
                            const int pc = (6 - 2 * i) % 6;
                            asm volatile("fence.proxy.async.global;" ::: "memory");
                            TS2(140 + i);
                            mbar_expect(sb + B_XFULL + 8 * pc, i != 1 ? 32768 : 16384);
                            tma2(sb + OFF_X + pc * 16384, i != 1 ? &maps.hx2 : &maps.hx, 0, hrow + pc * 128, sb + B_XFULL + 8 * pc);
                        }
                        i++;
                    }
                }
            }
        }
    } else {
        asm volatile("setmaxnreg.inc.sync.aligned.u32 224;");
        const int wg = warp >> 2;
        const bool elect = (tid & 127) == 0;
        const uint32_t sbd = sb >> 4, xlo = (sbd + wg * 512) | LBO1;
        auto release = [&](uint32_t bar) {
            if (elect) {
                mbar_arrive(sb + bar);
            }
        };
#define S_SL(S) ((S) < 40 ? (S) % 5 : ((S) - 40) % 9)
#define S_WAIT(S) do { mbar_wait(sb + (S_SL(S) < 5 ? B_FULL + 8 * S_SL(S) : B_EFULL + 8 * (S_SL(S) - 5)), (S) < 40 ? ((S) / 5) & 1 : (S) >= 49); \
            if (PROF && tid == 0) TS2(64 + (S)); } while (0)
#define S_B(S) (S_SL(S) < 5 ? OFF_RING / 16 + S_SL(S) * 1024 : (S_SL(S) == 7 ? 8 : S_SL(S) == 8 ? 7 : S_SL(S)) * 1024)
#define S_REL(S) do { if ((S) < 49) release(S_SL(S) < 5 ? B_EMPTY + 8 * S_SL(S) : B_EEMPTY + 8 * (S_SL(S) - 5)); } while (0)
#define G1(S, acc, SW, KB) stage_ss<(KB) * 1024, S_B(S), SW, (KB) == 0>(acc, xlo, sbd)
#define RET(S) do { S_WAIT((S) + 1); wg_wait<1>(); S_REL((S) - 1); } while (0)
#define RET2(S) do { S_WAIT((S) + 1); wg_wait<2>(); S_REL((S) - 1); } while (0)
#define SCHED() mbar_wait(sb + B_GRDY, 0)
#define A2_SYNC() do { asm volatile("fence.proxy.async.shared::cta;" ::: "memory"); asm volatile("bar.sync %0, 128;" :: "r"(wg + 1) : "memory"); } while (0)
#define H_EPI(acc, F, I0, I1, OG, OU) _Pragma("unroll") for (int i = (I0); i < (I1); i++) \
            F[i] = keep(hmul2(pack2(acc[(OG) + 2 * i] * acc[(OU) + 2 * i], acc[(OG) + 2 * i + 1] * acc[(OU) + 2 * i + 1]), (i & 1) ? m_hi : m_lo))
#define PHI(acc, F, I0, I1) _Pragma("unroll") for (int i = (I0); i < (I1); i++) F[i] = keep(phi2(acc[2 * i], acc[2 * i + 1]))

        float a0[64], b0[64], a1[64], a2_[64], a3[64];
        mbar_wait(sb + B_XFULL, 0);
#define X_WAIT(KB) do { mbar_wait(sb + B_XFULL + 8 * (KB), 0); if (PROF && tid == 0) TS2(128 + (KB)); } while (0)
        S_WAIT(0); G1(0, b0, false, 0);
        if ((warp & 3) == 0) TS(wg, 1);
        S_WAIT(1); G1(1, a0, false, 0); RET(1);
        X_WAIT(1); G1(2, b0, false, 1); RET(2);
        X_WAIT(2); G1(3, b0, false, 2); RET(3);
        G1(4, a0, false, 1); RET(4);
        X_WAIT(3); G1(5, b0, false, 3); RET(5);
        G1(6, a0, false, 2); RET(6);
        X_WAIT(4); G1(7, b0, false, 4); RET(7);
        X_WAIT(5); G1(8, b0, false, 5); RET(8);
        G1(9, a0, false, 3); RET(9);
        X_WAIT(6); G1(10, b0, false, 6); RET(10);
        X_WAIT(7); G1(11, b0, false, 7); RET(11);
        G1(12, a0, false, 4);
        mbar_wait(sb + B_GRDY, 0);
        float g_lo, g_hi;
        uint32_t tag;
        {
            const uint32_t ga = sb + OFF_G + (warp * 16 + (lane >> 2)) * 4;
            asm volatile("ld.shared.f32 %0, [%1];" : "=f"(g_lo) : "r"(ga) : "memory");
            asm volatile("ld.shared.f32 %0, [%1];" : "=f"(g_hi) : "r"(ga + 32) : "memory");
            asm volatile("ld.shared.u32 %0, [%1];" : "=r"(tag) : "r"(sb + OFF_EPOCH) : "memory");
        }
        float* const kvp = g_kvacc + (((tag & 1) * 8 + j) * 4 + (warp & 3)) * 272;
        tag = (tag + 1) & 1;
        const uint32_t m_lo = pack2(1.f - g_lo, 1.f - g_lo), m_hi = pack2(1.f - g_hi, 1.f - g_hi);
        const uint32_t lrow = ((lane & 7) + 8 * ((lane >> 3) & 1)) * 128;
        const uint32_t srow = (warp & 3) * 2048 + lrow;
        const uint32_t ssw = (lane >> 4) ^ (lane & 7);
        uint4* const hsend = g_hx + (size_t)((r * 4 + (j >> 1)) * 5 + (j & 1)) * 1024 + warp * 128 + (lane >> 2) * 8 + (lane & 3);
#define SENT_H(B) do { __syncwarp(); if (lane == 0) mbar_arrive(sb + B_HSENT + 8 * (B)); } while (0)
        RET(12);
        pin(b0);
        uint32_t fh0[16], fh1[16], fh2[16], fh3[8], fo[16], pk[16], pv[16];
        float kv[32], zs[4];
        const uint32_t stg = sb + OFF_STG + wg * 8192, stl = stg + (warp & 1) * 2048 + lrow;
#define KV_ROUND(Z) do { A2_SYNC(); wg_fence(); \
            wg_ss64t##Z<8192 + 256, 8192, DH128>(kv, xlo, xlo); wg_ss64t<8192 + 384, 8192 + 128, DH128>(kv, xlo, xlo); \
            wg_ss8t##Z<8192, OFF_ONES / 16, 0>(zs, xlo, sbd); wg_ss8t<8192 + 128, OFF_ONES / 16, 0>(zs, xlo, sbd); wg_commit(); } while (0)
        G1(13, a0, false, 5); SCHED(); pack_sub<32>(pv, b0); PHI(b0, pk, 0, 4); RET(13);
        G1(14, a0, false, 6); SCHED(); if (!(warp & 2)) stash<16>(stl + 4096, ssw, pv); PHI(b0, pk, 4, 10); RET(14);
        G1(15, a0, false, 7); SCHED(); PHI(b0, pk, 10, 16); RET(15);
        if ((warp & 3) == 0) TS(wg, 2);

        G1(16, a1, true, 0); SCHED(); if (!(warp & 2)) stash<16>(stl, ssw, pk); RET(16);
        pin(a0);
        G1(17, a1, true, 1); SCHED(); H_EPI(a0, fh0, 0, 16, 0, 32); RET(17);
        G1(18, a1, true, 2); KV_ROUND(_z); RET2(18);
        G1(19, a1, true, 3); SCHED(); send_h<0, 1>(fh0, hsend); RET(19);
        G1(20, a1, true, 4); SCHED(); if (warp & 2) { stash<16>(stl, ssw, pk); stash<16>(stl + 4096, ssw, pv); } RET(20);
        G1(21, a1, true, 5); RET(21);
        G1(22, a1, true, 6); KV_ROUND(); RET2(22);
        G1(23, a1, true, 7); SCHED(); send_h<1, 2>(fh0, hsend); RET(23);
        pin(kv); pin(zs);
        if ((warp & 3) == 0) TS(wg, 3);

        G1(24, a2_, false, 0); SCHED();
#define KV_RED(W) do { asm volatile("red.global.add.v4.f32 [%0], {%1,%2,%3,%4};" :: "l"(kvp + lane * 4), "f"(kv[8 * W]), "f"(kv[8 * W + 1]), "f"(kv[8 * W + 2]), "f"(kv[8 * W + 3]) : "memory"); \
                       asm volatile("red.global.add.v4.f32 [%0], {%1,%2,%3,%4};" :: "l"(kvp + 128 + lane * 4), "f"(kv[8 * W + 4]), "f"(kv[8 * W + 5]), "f"(kv[8 * W + 6]), "f"(kv[8 * W + 7]) : "memory"); } while (0)
        if ((warp & 3) == 0) KV_RED(0); else if ((warp & 3) == 1) KV_RED(1); else if ((warp & 3) == 2) KV_RED(2); else KV_RED(3);
        if ((lane & 3) == 0) {
            asm volatile("red.global.add.f32 [%0], %1;" :: "l"(kvp + 256 + (lane >> 2)), "f"(zs[0]) : "memory");
            asm volatile("red.global.add.f32 [%0], %1;" :: "l"(kvp + 264 + (lane >> 2)), "f"(zs[2]) : "memory");
        }
        __syncwarp();
        if (lane == 0) mbar_arrive(sb + B_KVDONE);
        RET(24);
        pin(a1);
        G1(25, a2_, false, 1); SCHED(); send_h<2, 3>(fh0, hsend); H_EPI(a1, fh3, 0, 8, 32, 48); RET(25);
        G1(26, a2_, false, 2); SCHED(); send_h<3, 4>(fh0, hsend); SENT_H(0); PHI(a1, fo, 0, 4); RET(26);
        G1(27, a2_, false, 3); SCHED(); send_h<0, 1>(fh3, hsend + 4 * 1024 - (j & 1) * 1020); PHI(a1, fo, 4, 8); RET(27);
        G1(28, a2_, false, 4); SCHED(); send_h<1, 2>(fh3, hsend + 4 * 1024 - (j & 1) * 1020); SENT_H(1); PHI(a1, fo, 8, 12); RET(28);
        G1(29, a2_, false, 5); SCHED(); PHI(a1, fo, 12, 16); RET(29);
        G1(30, a2_, false, 6); RET(30);
        G1(31, a2_, false, 7); RET(31);
        if ((warp & 3) == 0) TS(wg, 4);

        float on[4][12];
#define O_SCALE(h) do { const float s_lo = __fdividef(g_lo, on[h][8] + 1e-6f), s_hi = __fdividef(g_hi, on[h][10] + 1e-6f); \
            const uint32_t sl_ = pack2(s_lo, s_lo), sh_ = pack2(s_hi, s_hi); \
            fo[4 * h] = keep(hmul2(pack2(on[h][0], on[h][1]), sl_)); fo[4 * h + 1] = keep(hmul2(pack2(on[h][2], on[h][3]), sh_)); \
            fo[4 * h + 2] = keep(hmul2(pack2(on[h][4], on[h][5]), sl_)); fo[4 * h + 3] = keep(hmul2(pack2(on[h][6], on[h][7]), sh_)); } while (0)
        uint4* const lsend = g_lx + (size_t)(r * 8 + j) * 2048 + warp * 128 + lane;
        const uint4* const lrecv = g_lx + (size_t)(r * 8 + (j ^ 1)) * 2048 + warp * 128 + lane;
        G1(32, a3, false, 0); RET(32);
        pin(a2_);
        G1(33, a3, false, 1); SCHED(); H_EPI(a2_, fh1, 0, 16, 0, 32); send_h<0, 1>(fh1, hsend + 2 * 1024); RET(33);
        G1(34, a3, false, 2); SCHED(); send_h<1, 3>(fh1, hsend + 2 * 1024);
        if ((warp & 3) == 0) TS(wg, 5);
        mbar_wait(sb + B_KVRDY, 0);
        if ((warp & 3) == 0) TS(wg, 6);
        wg_fence();
#define O_MMA(h) wg_rs24_z<OFF_STG / 16 + (h) * 48 + (8u << 16), 16>(on[h], fo[4 * (h)], fo[4 * (h) + 1], fo[4 * (h) + 2], fo[4 * (h) + 3], sbd)
        O_MMA(0); O_MMA(1); O_MMA(2); O_MMA(3);
        wg_commit();
        RET2(34);
        if (elect) mbar_arrive(sb + B_XFREE);
        G1(35, a3, false, 3); SCHED(); send_h<3, 4>(fh1, hsend + 2 * 1024); SENT_H(2); RET(35);
        pin(on[0]); pin(on[1]); pin(on[2]); pin(on[3]);
        release(B_EEMPTY + 16);
        G1(36, a3, false, 4); SCHED(); O_SCALE(0); O_SCALE(1); O_SCALE(2); O_SCALE(3); RET(36);
        G1(37, a3, false, 5); SCHED(); send_frag<0, 2>(fo, lsend, tag); RET(37);
        if (elect) mbar_arrive(sb + B_XFREE + 8);
        G1(38, a3, false, 6); SCHED(); send_frag<2, 4>(fo, lsend, tag); RET(38);
        release(B_EEMPTY);
        G1(39, a3, false, 7); RET(39);
        release(B_EEMPTY + 8);
        if ((warp & 3) == 0) TS(wg, 7);

#define G2S(S, acc, U) stage_ss<(U) * 1024, S_B(S), false, (S) == 40>(acc, xlo, sbd)
#define G2R(S, acc, F) stage_rs<S_B(S), (S) == 49>(acc, F, sbd)
#define H_WAIT(P) do { mbar_wait(sb + B_XFULL + 8 * (P), 1); if (PROF && tid == 0) TS2(150 + (P)); } while (0)
        const int p = j >> 1, pw = (p & 2) ^ 2;
        const bool own = wg == (p & 1);
        uint4* const pbase = g_part + (size_t)(r * 2 + (j & 1)) * 16384 + (warp & 3) * 256 + lane;

        float p1[64], p2[64];
        uint32_t po[16], ph2[16];
        H_WAIT(0); G2S(40, p1, 0); RET(40);
        release(B_EEMPTY + 24);
        pin(a3);
        G2S(41, p1, 1); SCHED(); H_EPI(a3, fh2, 0, 16, 0, 32); send_frag<0, 2>(fh2, lsend + 1024, tag); RET(41);
        H_WAIT(4); G2S(42, p1, 4); SCHED(); send_frag<2, 4>(fh2, lsend + 1024, tag); RET(42);
        G2R(43, p1, fo); SCHED(); recv_issue(po, lrecv); RET(43);
        H_WAIT(2); G2S(44, p1, 2); RET(44);
        G2S(45, p1, 3); SCHED(); recv_check(po, lrecv, tag); recv_issue(ph2, lrecv + 1024); RET(45);
        G2R(46, p1, po); RET(46);
        G2R(47, p1, fh2); SCHED(); recv_check(ph2, lrecv + 1024, tag); RET(47);
        G2R(48, p1, ph2); RET(48);
        if ((warp & 3) == 0) TS(wg, 8);
        uint32_t sp[32], qa[32], qb[32];
        uint4* const s1 = pbase + (((pw + wg) * 4 + p) << 10);
        G2R(49, p2, fo); RET(49);
        pin(p1);
        G2R(50, p2, po); SCHED(); pack_sub<0>(sp, p1); send_frag<0, 2>(sp, s1, tag); RET(50);
        G2R(51, p2, fh2); SCHED(); send_frag<2, 4>(sp, s1, tag); RET(51);
        G2R(52, p2, ph2); SCHED(); send_frag<4, 6>(sp, s1, tag); RET(52);
        G2S(53, p2, 0); SCHED(); send_frag<6, 8>(sp, s1, tag); RET(53);
        const uint4* ra = pbase + ((p * 4 + pw) << 10);
        const uint4* rc = pbase + ((p * 4 + (p ^ 1)) << 10);
        if (own) { mbar_wait(sb + B_AHEAD, 0); recv_issue(qa, ra); recv_issue(qb, ra + 1024); }
        G2S(54, p2, 1); RET(54);
        G2S(55, p2, 2); RET(55);
        G2S(56, p2, 3); RET(56);
        G2S(57, p2, 4); SCHED();
        if ((warp & 3) == 0) TS(wg, 9);
        if (!own) {
            if (elect) mbar_arrive(sb + B_AHEAD);
        } else {
            recv_issue(sp, rc);
            recv_check(qa, ra, tag); recv_check(qb, ra + 1024, tag);
#pragma unroll
            for (int i = 0; i < 32; i++) qa[i] = keep(hadd2(qa[i], qb[i]));
        }
        wg_wait<0>();
        pin(p2);
        if ((warp & 3) == 0) TS(wg, 11);
        if (!own) {
            pack_sub<0>(sp, p2); send_frag<0, 8>(sp, pbase + (((p ^ 1) * 4 + p) << 10), tag);
        } else {
            if ((warp & 3) == 0) TS(wg, 12);
            recv_check(sp, rc, tag);
#pragma unroll
            for (int i = 0; i < 32; i++) qa[i] = hadd2(qa[i], sp[i]);
            accum(qa, p2);
            if ((warp & 3) == 0) TS(wg, 13);
            uint32_t f0[16], f1[16];
            pack_sub<0>(f0, p2); pack_sub<32>(f1, p2);
            const uint32_t slab = sb + OFF_X + 2 * 16384 + wg * 8192;
            stash<16>(slab + srow, ssw, f0); stash<16>(slab + 16384 + srow, ssw, f1);
            __syncwarp();
            __nv_bfloat16* op = out + (size_t)(r * 128 + warp * 16 + (lane >> 4)) * kD + (j & 1) * 256 + (p & 2) * 64 + (lane & 15) * 8;
#pragma unroll
            for (int i = 0; i < 8; i++) {
                const int row = i * 2 + (lane >> 4);
                uint4 v;
                asm volatile("ld.shared.v4.u32 {%0,%1,%2,%3}, [%4];" : "=r"(v.x), "=r"(v.y), "=r"(v.z), "=r"(v.w)
                             : "r"(slab + (lane & 8) * 2048 + ((warp & 3) * 16 + row) * 128 + (((lane & 7) ^ (row & 7)) << 4)) : "memory");
                *(uint4*)(op + i * 2 * kD) = v;
            }
        }
        if ((warp & 3) == 0) { TS(wg, 14); TSG(wg, 31); }
    }
}

typedef CUresult (*EncodeFn)(CUtensorMap*, CUtensorMapDataType, cuuint32_t, void*, const cuuint64_t*, const cuuint64_t*, const cuuint32_t*,
                             const cuuint32_t*, CUtensorMapInterleave, CUtensorMapSwizzle, CUtensorMapL2promotion, CUtensorMapFloatOOBfill);

static void encode(EncodeFn fn, CUtensorMap* m, int rank, const void* base, const cuuint64_t (&gd)[5], const cuuint64_t (&gs)[4],
                   const cuuint32_t (&bd)[5], CUtensorMapSwizzle sw) {
    cuuint32_t es[5] = {1, 1, 1, 1, 1};
    fn(m, CU_TENSOR_MAP_DATA_TYPE_BFLOAT16, rank, const_cast<void*>(base), gd, gs, bd, es, CU_TENSOR_MAP_INTERLEAVE_NONE, sw,
       CU_TENSOR_MAP_L2_PROMOTION_L2_128B, CU_TENSOR_MAP_FLOAT_OOB_FILL_NONE);
}

extern "C" void kernel_launch(void* const* d_in, const int* in_sizes, int n_in, void* d_out, int out_size) {
    const char* x = (const char*)d_in[0];
    const char* wqkv = (const char*)d_in[1];
    const char* wo = (const char*)d_in[2];
    const char* wg = (const char*)d_in[4];
    const char* wu = (const char*)d_in[5];
    const char* wd = (const char*)d_in[6];
    void* fnp = nullptr;
    cudaDriverEntryPointQueryResult qr;
    cudaGetDriverEntryPoint("cuTensorMapEncodeTiled", &fnp, cudaEnableDefault, &qr);
    EncodeFn fn = (EncodeFn)fnp;
    Maps maps;
    const char* lo = wg < wu ? wg : wu;
    const uint64_t diff = wg < wu ? (uint64_t)(wu - wg) : (uint64_t)(wg - wu);
    const CUtensorMapSwizzle S128 = CU_TENSOR_MAP_SWIZZLE_128B, S64 = CU_TENSOR_MAP_SWIZZLE_64B;
    encode(fn, &maps.x, 2, x, {512, 2048, 1, 1}, {1024, 0, 0}, {64, 128, 1, 1}, S128);
    encode(fn, &maps.gu, 3, lo, {1792, 512, 2, 1}, {3584, diff, 0}, {64, 64, 2, 1}, S128);
    encode(fn, &maps.kv, 3, wqkv, {512, 512, 3, 1}, {3072, 1024, 0}, {64, 64, 2, 1}, S128);
    encode(fn, &maps.q64, 3, wqkv, {32, 512, 48, 1}, {3072, 64, 0}, {32, 64, 2, 1}, S64);
    encode(fn, &maps.gu64, 3, lo, {1792, 512, 2, 1}, {3584, diff, 0}, {32, 64, 2, 1}, S64);
    encode(fn, &maps.wdw, 3, wd, {64, 1792, 8, 1}, {1024, 128, 0}, {64, 64, 2, 1}, S128);
    encode(fn, &maps.wow, 3, wo, {64, 512, 8}, {1024, 128}, {64, 64, 2}, S128);
    encode(fn, &maps.wdp, 5, wd, {512, 2, 4, 4, 56}, {1024, 8192, 2048, 32768}, {64, 2, 4, 4, 2}, S128);
    encode(fn, &maps.wdph, 5, wd, {512, 2, 4, 4, 56}, {1024, 8192, 2048, 32768}, {64, 2, 4, 4, 1}, S128);
    void* hx = nullptr;
    cudaGetSymbolAddress(&hx, g_hx);
    encode(fn, &maps.hx, 2, hx, {64, 16 * 4 * 5 * 128}, {128}, {64, 128}, S128);
    encode(fn, &maps.hx2, 2, hx, {64, 16 * 4 * 5 * 128}, {128}, {64, 256}, S128);
    cudaFuncSetAttribute(fused_kernel, cudaFuncAttributeMaxDynamicSharedMemorySize, SMEM_BYTES);
    cudaLaunchConfig_t cfg = {};
    cfg.gridDim = dim3(128);
    cfg.blockDim = dim3(384);
    cfg.dynamicSmemBytes = SMEM_BYTES;
    cfg.stream = cudaStreamPerThread;
    cudaLaunchAttribute at[1];
    at[0].id = cudaLaunchAttributeClusterDimension;
    at[0].val.clusterDim.x = 2; at[0].val.clusterDim.y = 1; at[0].val.clusterDim.z = 1;
    cfg.attrs = at;
    cfg.numAttrs = MC ? 1 : 0;
    cudaLaunchKernelEx(&cfg, fused_kernel, maps, (const __nv_bfloat16*)d_in[0], (const __nv_bfloat16*)d_in[7], wqkv, wg, wu, wd, wo, (__nv_bfloat16*)d_out);
}
```

```cpp
#include <cuda_runtime.h>
#include <cuda.h>
#include <cuda_bf16.h>
#include <stdint.h>

#define MC 0
#define PFMODE 1
#define PROF 0

namespace {

constexpr int kD = 512;
constexpr uint32_t OFF_X = 0, OFF_STG = 131072, OFF_RING = 147456, OFF_MISC = 229376;
constexpr uint32_t B_FULL = OFF_MISC, B_EMPTY = OFF_MISC + 40, B_XFULL = OFF_MISC + 80;
constexpr uint32_t B_GRDY = OFF_MISC + 152, B_KVDONE = OFF_MISC + 160, B_KVRDY = OFF_MISC + 168;
constexpr uint32_t B_HSENT = OFF_MISC + 176, B_XFREE = OFF_MISC + 200;
constexpr uint32_t OFF_EPOCH = OFF_MISC + 240, OFF_G = OFF_MISC + 256;
constexpr uint32_t B_AHEAD = OFF_MISC + 248;
constexpr uint32_t OFF_ONES = OFF_MISC + 768;
constexpr uint32_t B_EFULL = OFF_MISC + 896, B_EEMPTY = OFF_MISC + 928;
constexpr uint32_t SMEM_BYTES = OFF_MISC + 960;
constexpr uint32_t SPIN_GLOBAL = 1u << 14;

struct alignas(64) Maps { CUtensorMap x, gu, kv, q64, gu64, wdw, wow, wdp, wdph, hx, hx2; };

}

__device__ uint4 g_part[16 * 2 * 4 * 4 * 1024];
__device__ uint4 g_hx[16 * 4 * 5 * 1024];
__device__ uint4 g_lx[16 * 8 * 2 * 1024];
__device__ unsigned g_hflag[128 * 8];
__device__ uint4 g_gx[16 * 32];
__device__ float g_kvacc[2 * 8 * 4 * 272];
__device__ unsigned g_kvcnt[8 * 32];
__device__ unsigned g_epoch[128];
#define TS(role, idx)
#define TS2(idx)
#define TSG(role, idx)

namespace {

__device__ __forceinline__ void mbar_init(uint32_t bar, uint32_t cnt) { asm volatile("mbarrier.init.shared::cta.b64 [%0], %1;" :: "r"(bar), "r"(cnt) : "memory"); }
__device__ __forceinline__ void mbar_expect(uint32_t bar, uint32_t bytes) { asm volatile("mbarrier.arrive.expect_tx.shared::cta.b64 _, [%0], %1;" :: "r"(bar), "r"(bytes) : "memory"); }
__device__ __forceinline__ void mbar_arrive(uint32_t bar) { asm volatile("mbarrier.arrive.shared::cta.b64 _, [%0];" :: "r"(bar) : "memory"); }
__device__ __forceinline__ void mbar_arrive_cta(uint32_t bar, uint32_t cta) {
    asm volatile("{\n.reg .b32 ra;\nmapa.shared::cluster.u32 ra, %0, %1;\nmbarrier.arrive.shared::cluster.b64 _, [ra];\n}" :: "r"(bar), "r"(cta) : "memory");
}
__device__ __forceinline__ void mbar_wait(uint32_t bar, uint32_t parity) {
    asm volatile("{\n.reg .pred p;\n.reg .u32 c;\n"
                 "mbarrier.try_wait.parity.shared::cta.b64 p, [%0], %1;\n@p bra DONE;\n"
                 "mov.u32 c, 0;\nLAB_WAIT:\nmbarrier.try_wait.parity.shared::cta.b64 p, [%0], %1;\n@p bra DONE;\n"
                 "add.u32 c, c, 1;\nsetp.lt.u32 p, c, 65536;\n@p bra LAB_WAIT;\nDONE:\n}" :: "r"(bar), "r"(parity) : "memory");
}
__device__ __forceinline__ void tma2(uint32_t dst, const CUtensorMap* m, int c0, int c1, uint32_t bar) {
    asm volatile("cp.async.bulk.tensor.2d.shared::cluster.global.mbarrier::complete_tx::bytes [%0], [%1, {%3, %4}], [%2];"
        :: "r"(dst), "l"(m), "r"(bar), "r"(c0), "r"(c1) : "memory");
}
__device__ __forceinline__ void tmaw2(uint32_t dst, const CUtensorMap* m, int c0, int c1, uint32_t bar) {
    tma2(dst, m, c0, c1, bar);
}
__device__ __forceinline__ void tmaw3(uint32_t dst, const CUtensorMap* m, int c0, int c1, int c2, uint32_t bar) {
    asm volatile("cp.async.bulk.tensor.3d.shared::cluster.global.mbarrier::complete_tx::bytes [%0], [%1, {%3, %4, %5}], [%2];"
        :: "r"(dst), "l"(m), "r"(bar), "r"(c0), "r"(c1), "r"(c2) : "memory");
}
__device__ __forceinline__ void tmaw5(uint32_t dst, const CUtensorMap* m, int c0, int c4, uint32_t bar) {
    asm volatile("cp.async.bulk.tensor.5d.shared::cluster.global.mbarrier::complete_tx::bytes [%0], [%1, {%3, %5, %5, %5, %4}], [%2];"
        :: "r"(dst), "l"(m), "r"(bar), "r"(c0), "r"(c4), "r"(0) : "memory");
}
__device__ __forceinline__ void wg_fence() { asm volatile("wgmma.fence.sync.aligned;" ::: "memory"); }
__device__ __forceinline__ void wg_commit() { asm volatile("wgmma.commit_group.sync.aligned;" ::: "memory"); }
template <int N> __device__ __forceinline__ void wg_wait() { asm volatile("wgmma.wait_group.sync.aligned %0;" :: "n"(N) : "memory"); }
template <int N> __device__ __forceinline__ void pin(float (&d)[N]) {
#pragma unroll
    for (int i = 0; i < N; i++) asm volatile("" : "+f"(d[i]) :: "memory");
}
__device__ __forceinline__ uint32_t pack2(float lo, float hi) { uint32_t r; asm("cvt.rn.bf16x2.f32 %0, %1, %2;" : "=r"(r) : "f"(hi), "f"(lo)); return r; }
__device__ __forceinline__ uint32_t keep(uint32_t v) { asm volatile("" : "+r"(v)); return v; }
__device__ __forceinline__ uint32_t hadd2(uint32_t a, uint32_t b) { uint32_t r; asm("add.bf16x2 %0, %1, %2;" : "=r"(r) : "r"(a), "r"(b)); return r; }
__device__ __forceinline__ uint32_t hmul2(uint32_t a, uint32_t b) { uint32_t r; asm("mul.bf16x2 %0, %1, %2;" : "=r"(r) : "r"(a), "r"(b)); return r; }
__device__ __forceinline__ uint32_t phi2(float t0, float t1) {
    float e0, e1;
    asm("ex2.approx.ftz.f32 %0, %1;" : "=f"(e0) : "f"(t0 * 1.4426950408889634f));
    asm("ex2.approx.ftz.f32 %0, %1;" : "=f"(e1) : "f"(t1 * 1.4426950408889634f));
    uint32_t e = pack2(e0, e1), t = pack2(t0, t1), r;
    asm("min.bf16x2 %0, %0, %1;" : "+r"(e) : "r"(0x3f803f80u));
    asm("max.bf16x2 %0, %0, %1;" : "+r"(t) : "r"(0x35863586u));
    asm("add.bf16x2 %0, %1, %2;" : "=r"(r) : "r"(e), "r"(t));
    return r;
}
__device__ __forceinline__ void stsm4(uint32_t a, uint32_t r0, uint32_t r1, uint32_t r2, uint32_t r3) {
    asm volatile("stmatrix.sync.aligned.m8n8.x4.shared.b16 [%0], {%1,%2,%3,%4};" :: "r"(a), "r"(r0), "r"(r1), "r"(r2), "r"(r3) : "memory");
}
__device__ __forceinline__ float bf_lo(uint32_t w) { return __uint_as_float(w << 16); }
__device__ __forceinline__ float bf_hi(uint32_t w) { return __uint_as_float(w & 0xffff0000u); }
__device__ __forceinline__ void st_pkt(uint4* p, uint32_t w0, uint32_t w1, uint32_t w2, uint32_t w3) {
    asm volatile("{\n.reg .b64 lo, hi;\n.reg .b128 v;\nmov.b64 lo, {%1, %2};\nmov.b64 hi, {%3, %4};\nmov.b128 v, {lo, hi};\nst.relaxed.gpu.global.b128 [%0], v;\n}"
        :: "l"(p), "r"(w0), "r"(w1), "r"(w2), "r"(w3) : "memory");
}
__device__ __forceinline__ void ld_pkt(const uint4* p, uint32_t& w0, uint32_t& w1, uint32_t& w2, uint32_t& w3) {
    asm volatile("{\n.reg .b64 lo, hi;\n.reg .b128 v;\nld.relaxed.gpu.global.b128 v, [%4];\nmov.b128 {lo, hi}, v;\nmov.b64 {%0, %1}, lo;\nmov.b64 {%2, %3}, hi;\n}"
        : "=r"(w0), "=r"(w1), "=r"(w2), "=r"(w3) : "l"(p) : "memory");
}

template <uint32_t AO, uint32_t BO, uint32_t BH> __device__ __forceinline__ void wg_ss128(float (&d)[64], uint32_t ab, uint32_t bb) {
    asm volatile("{\n.reg .b64 da, db;\n.reg .b32 ta, tb, th, ah;\nadd.u32 ta, %64, %66;\nadd.u32 tb, %65, %67;\nmov.b32 th, %68;\nmov.b32 ah, 0x40000040;\nmov.b64 da, {ta, ah};\nmov.b64 db, {tb, th};\n"
        "wgmma.mma_async.sync.aligned.m64n128k16.f32.bf16.bf16 {%0,%1,%2,%3,%4,%5,%6,%7,%8,%9,%10,%11,%12,%13,%14,%15,%16,%17,%18,%19,%20,%21,%22,%23,%24,%25,%26,%27,%28,%29,%30,%31,%32,%33,%34,%35,%36,%37,%38,%39,%40,%41,%42,%43,%44,%45,%46,%47,%48,%49,%50,%51,%52,%53,%54,%55,%56,%57,%58,%59,%60,%61,%62,%63}, da, db, 1, 1, 1, 0, 1;\n}\n"
        : "+f"(d[0]),"+f"(d[1]),"+f"(d[2]),"+f"(d[3]),"+f"(d[4]),"+f"(d[5]),"+f"(d[6]),"+f"(d[7]),"+f"(d[8]),"+f"(d[9]),"+f"(d[10]),"+f"(d[11]),"+f"(d[12]),"+f"(d[13]),"+f"(d[14]),"+f"(d[15]),"+f"(d[16]),"+f"(d[17]),"+f"(d[18]),"+f"(d[19]),"+f"(d[20]),"+f"(d[21]),"+f"(d[22]),"+f"(d[23]),"+f"(d[24]),"+f"(d[25]),"+f"(d[26]),"+f"(d[27]),"+f"(d[28]),"+f"(d[29]),"+f"(d[30]),"+f"(d[31]),"+f"(d[32]),"+f"(d[33]),"+f"(d[34]),"+f"(d[35]),"+f"(d[36]),"+f"(d[37]),"+f"(d[38]),"+f"(d[39]),"+f"(d[40]),"+f"(d[41]),"+f"(d[42]),"+f"(d[43]),"+f"(d[44]),"+f"(d[45]),"+f"(d[46]),"+f"(d[47]),"+f"(d[48]),"+f"(d[49]),"+f"(d[50]),"+f"(d[51]),"+f"(d[52]),"+f"(d[53]),"+f"(d[54]),"+f"(d[55]),"+f"(d[56]),"+f"(d[57]),"+f"(d[58]),"+f"(d[59]),"+f"(d[60]),"+f"(d[61]),"+f"(d[62]),"+f"(d[63])
        : "r"(ab), "r"(bb), "n"(AO), "n"(BO), "n"(BH));
}
template <uint32_t AO, uint32_t BO, uint32_t BH> __device__ __forceinline__ void wg_ss128_z(float (&d)[64], uint32_t ab, uint32_t bb) {
    asm volatile("{\n.reg .b64 da, db;\n.reg .b32 ta, tb, th, ah;\nadd.u32 ta, %64, %66;\nadd.u32 tb, %65, %67;\nmov.b32 th, %68;\nmov.b32 ah, 0x40000040;\nmov.b64 da, {ta, ah};\nmov.b64 db, {tb, th};\n"
        "wgmma.mma_async.sync.aligned.m64n128k16.f32.bf16.bf16 {%0,%1,%2,%3,%4,%5,%6,%7,%8,%9,%10,%11,%12,%13,%14,%15,%16,%17,%18,%19,%20,%21,%22,%23,%24,%25,%26,%27,%28,%29,%30,%31,%32,%33,%34,%35,%36,%37,%38,%39,%40,%41,%42,%43,%44,%45,%46,%47,%48,%49,%50,%51,%52,%53,%54,%55,%56,%57,%58,%59,%60,%61,%62,%63}, da, db, 0, 1, 1, 0, 1;\n}\n"
        : "=f"(d[0]),"=f"(d[1]),"=f"(d[2]),"=f"(d[3]),"=f"(d[4]),"=f"(d[5]),"=f"(d[6]),"=f"(d[7]),"=f"(d[8]),"=f"(d[9]),"=f"(d[10]),"=f"(d[11]),"=f"(d[12]),"=f"(d[13]),"=f"(d[14]),"=f"(d[15]),"=f"(d[16]),"=f"(d[17]),"=f"(d[18]),"=f"(d[19]),"=f"(d[20]),"=f"(d[21]),"=f"(d[22]),"=f"(d[23]),"=f"(d[24]),"=f"(d[25]),"=f"(d[26]),"=f"(d[27]),"=f"(d[28]),"=f"(d[29]),"=f"(d[30]),"=f"(d[31]),"=f"(d[32]),"=f"(d[33]),"=f"(d[34]),"=f"(d[35]),"=f"(d[36]),"=f"(d[37]),"=f"(d[38]),"=f"(d[39]),"=f"(d[40]),"=f"(d[41]),"=f"(d[42]),"=f"(d[43]),"=f"(d[44]),"=f"(d[45]),"=f"(d[46]),"=f"(d[47]),"=f"(d[48]),"=f"(d[49]),"=f"(d[50]),"=f"(d[51]),"=f"(d[52]),"=f"(d[53]),"=f"(d[54]),"=f"(d[55]),"=f"(d[56]),"=f"(d[57]),"=f"(d[58]),"=f"(d[59]),"=f"(d[60]),"=f"(d[61]),"=f"(d[62]),"=f"(d[63])
        : "r"(ab), "r"(bb), "n"(AO), "n"(BO), "n"(BH));
}
template <uint32_t BO, uint32_t BH> __device__ __forceinline__ void wg_rs128(float (&d)[64], uint32_t a0, uint32_t a1, uint32_t a2, uint32_t a3, uint32_t bb) {
    asm volatile("{\n.reg .b64 db;\n.reg .b32 tb, th;\nadd.u32 tb, %68, %69;\nmov.b32 th, %70;\nmov.b64 db, {tb, th};\n"
        "wgmma.mma_async.sync.aligned.m64n128k16.f32.bf16.bf16 {%0,%1,%2,%3,%4,%5,%6,%7,%8,%9,%10,%11,%12,%13,%14,%15,%16,%17,%18,%19,%20,%21,%22,%23,%24,%25,%26,%27,%28,%29,%30,%31,%32,%33,%34,%35,%36,%37,%38,%39,%40,%41,%42,%43,%44,%45,%46,%47,%48,%49,%50,%51,%52,%53,%54,%55,%56,%57,%58,%59,%60,%61,%62,%63}, {%64,%65,%66,%67}, db, 1, 1, 1, 1;\n}\n"
        : "+f"(d[0]),"+f"(d[1]),"+f"(d[2]),"+f"(d[3]),"+f"(d[4]),"+f"(d[5]),"+f"(d[6]),"+f"(d[7]),"+f"(d[8]),"+f"(d[9]),"+f"(d[10]),"+f"(d[11]),"+f"(d[12]),"+f"(d[13]),"+f"(d[14]),"+f"(d[15]),"+f"(d[16]),"+f"(d[17]),"+f"(d[18]),"+f"(d[19]),"+f"(d[20]),"+f"(d[21]),"+f"(d[22]),"+f"(d[23]),"+f"(d[24]),"+f"(d[25]),"+f"(d[26]),"+f"(d[27]),"+f"(d[28]),"+f"(d[29]),"+f"(d[30]),"+f"(d[31]),"+f"(d[32]),"+f"(d[33]),"+f"(d[34]),"+f"(d[35]),"+f"(d[36]),"+f"(d[37]),"+f"(d[38]),"+f"(d[39]),"+f"(d[40]),"+f"(d[41]),"+f"(d[42]),"+f"(d[43]),"+f"(d[44]),"+f"(d[45]),"+f"(d[46]),"+f"(d[47]),"+f"(d[48]),"+f"(d[49]),"+f"(d[50]),"+f"(d[51]),"+f"(d[52]),"+f"(d[53]),"+f"(d[54]),"+f"(d[55]),"+f"(d[56]),"+f"(d[57]),"+f"(d[58]),"+f"(d[59]),"+f"(d[60]),"+f"(d[61]),"+f"(d[62]),"+f"(d[63])
        : "r"(a0), "r"(a1), "r"(a2), "r"(a3), "r"(bb), "n"(BO), "n"(BH));
}
template <uint32_t BO, uint32_t BH> __device__ __forceinline__ void wg_rs128_z(float (&d)[64], uint32_t a0, uint32_t a1, uint32_t a2, uint32_t a3, uint32_t bb) {
    asm volatile("{\n.reg .b64 db;\n.reg .b32 tb, th;\nadd.u32 tb, %68, %69;\nmov.b32 th, %70;\nmov.b64 db, {tb, th};\n"
        "wgmma.mma_async.sync.aligned.m64n128k16.f32.bf16.bf16 {%0,%1,%2,%3,%4,%5,%6,%7,%8,%9,%10,%11,%12,%13,%14,%15,%16,%17,%18,%19,%20,%21,%22,%23,%24,%25,%26,%27,%28,%29,%30,%31,%32,%33,%34,%35,%36,%37,%38,%39,%40,%41,%42,%43,%44,%45,%46,%47,%48,%49,%50,%51,%52,%53,%54,%55,%56,%57,%58,%59,%60,%61,%62,%63}, {%64,%65,%66,%67}, db, 0, 1, 1, 1;\n}\n"
        : "=f"(d[0]),"=f"(d[1]),"=f"(d[2]),"=f"(d[3]),"=f"(d[4]),"=f"(d[5]),"=f"(d[6]),"=f"(d[7]),"=f"(d[8]),"=f"(d[9]),"=f"(d[10]),"=f"(d[11]),"=f"(d[12]),"=f"(d[13]),"=f"(d[14]),"=f"(d[15]),"=f"(d[16]),"=f"(d[17]),"=f"(d[18]),"=f"(d[19]),"=f"(d[20]),"=f"(d[21]),"=f"(d[22]),"=f"(d[23]),"=f"(d[24]),"=f"(d[25]),"=f"(d[26]),"=f"(d[27]),"=f"(d[28]),"=f"(d[29]),"=f"(d[30]),"=f"(d[31]),"=f"(d[32]),"=f"(d[33]),"=f"(d[34]),"=f"(d[35]),"=f"(d[36]),"=f"(d[37]),"=f"(d[38]),"=f"(d[39]),"=f"(d[40]),"=f"(d[41]),"=f"(d[42]),"=f"(d[43]),"=f"(d[44]),"=f"(d[45]),"=f"(d[46]),"=f"(d[47]),"=f"(d[48]),"=f"(d[49]),"=f"(d[50]),"=f"(d[51]),"=f"(d[52]),"=f"(d[53]),"=f"(d[54]),"=f"(d[55]),"=f"(d[56]),"=f"(d[57]),"=f"(d[58]),"=f"(d[59]),"=f"(d[60]),"=f"(d[61]),"=f"(d[62]),"=f"(d[63])
        : "r"(a0), "r"(a1), "r"(a2), "r"(a3), "r"(bb), "n"(BO), "n"(BH));
}
template <uint32_t AO, uint32_t BO, uint32_t BH> __device__ __forceinline__ void wg_ss64t(float (&d)[32], uint32_t ab, uint32_t bb) {
    asm volatile("{\n.reg .b64 da, db;\n.reg .b32 ta, tb, th, ah;\nadd.u32 ta, %32, %34;\nadd.u32 tb, %33, %35;\nmov.b32 th, %36;\nmov.b32 ah, 0x40000040;\nmov.b64 da, {ta, ah};\nmov.b64 db, {tb, th};\n"
        "wgmma.mma_async.sync.aligned.m64n64k16.f32.bf16.bf16 {%0,%1,%2,%3,%4,%5,%6,%7,%8,%9,%10,%11,%12,%13,%14,%15,%16,%17,%18,%19,%20,%21,%22,%23,%24,%25,%26,%27,%28,%29,%30,%31}, da, db, 1, 1, 1, 1, 1;\n}\n"
        : "+f"(d[0]),"+f"(d[1]),"+f"(d[2]),"+f"(d[3]),"+f"(d[4]),"+f"(d[5]),"+f"(d[6]),"+f"(d[7]),"+f"(d[8]),"+f"(d[9]),"+f"(d[10]),"+f"(d[11]),"+f"(d[12]),"+f"(d[13]),"+f"(d[14]),"+f"(d[15]),"+f"(d[16]),"+f"(d[17]),"+f"(d[18]),"+f"(d[19]),"+f"(d[20]),"+f"(d[21]),"+f"(d[22]),"+f"(d[23]),"+f"(d[24]),"+f"(d[25]),"+f"(d[26]),"+f"(d[27]),"+f"(d[28]),"+f"(d[29]),"+f"(d[30]),"+f"(d[31])
        : "r"(ab), "r"(bb), "n"(AO), "n"(BO), "n"(BH));
}
template <uint32_t AO, uint32_t BO, uint32_t BH> __device__ __forceinline__ void wg_ss64t_z(float (&d)[32], uint32_t ab, uint32_t bb) {
    asm volatile("{\n.reg .b64 da, db;\n.reg .b32 ta, tb, th, ah;\nadd.u32 ta, %32, %34;\nadd.u32 tb, %33, %35;\nmov.b32 th, %36;\nmov.b32 ah, 0x40000040;\nmov.b64 da, {ta, ah};\nmov.b64 db, {tb, th};\n"
        "wgmma.mma_async.sync.aligned.m64n64k16.f32.bf16.bf16 {%0,%1,%2,%3,%4,%5,%6,%7,%8,%9,%10,%11,%12,%13,%14,%15,%16,%17,%18,%19,%20,%21,%22,%23,%24,%25,%26,%27,%28,%29,%30,%31}, da, db, 0, 1, 1, 1, 1;\n}\n"
        : "=f"(d[0]),"=f"(d[1]),"=f"(d[2]),"=f"(d[3]),"=f"(d[4]),"=f"(d[5]),"=f"(d[6]),"=f"(d[7]),"=f"(d[8]),"=f"(d[9]),"=f"(d[10]),"=f"(d[11]),"=f"(d[12]),"=f"(d[13]),"=f"(d[14]),"=f"(d[15]),"=f"(d[16]),"=f"(d[17]),"=f"(d[18]),"=f"(d[19]),"=f"(d[20]),"=f"(d[21]),"=f"(d[22]),"=f"(d[23]),"=f"(d[24]),"=f"(d[25]),"=f"(d[26]),"=f"(d[27]),"=f"(d[28]),"=f"(d[29]),"=f"(d[30]),"=f"(d[31])
        : "r"(ab), "r"(bb), "n"(AO), "n"(BO), "n"(BH));
}
template <uint32_t AO, uint32_t BO, uint32_t BH> __device__ __forceinline__ void wg_ss8t(float (&d)[4], uint32_t ab, uint32_t bb) {
    asm volatile("{\n.reg .b64 da, db;\n.reg .b32 ta, tb, th, ah;\nadd.u32 ta, %4, %6;\nadd.u32 tb, %5, %7;\nmov.b32 th, %8;\nmov.b32 ah, 0x40000040;\nmov.b64 da, {ta, ah};\nmov.b64 db, {tb, th};\n"
        "wgmma.mma_async.sync.aligned.m64n8k16.f32.bf16.bf16 {%0,%1,%2,%3}, da, db, 1, 1, 1, 1, 0;\n}\n"
        : "+f"(d[0]),"+f"(d[1]),"+f"(d[2]),"+f"(d[3])
        : "r"(ab), "r"(bb), "n"(AO), "n"(BO), "n"(BH));
}
template <uint32_t AO, uint32_t BO, uint32_t BH> __device__ __forceinline__ void wg_ss8t_z(float (&d)[4], uint32_t ab, uint32_t bb) {
    asm volatile("{\n.reg .b64 da, db;\n.reg .b32 ta, tb, th, ah;\nadd.u32 ta, %4, %6;\nadd.u32 tb, %5, %7;\nmov.b32 th, %8;\nmov.b32 ah, 0x40000040;\nmov.b64 da, {ta, ah};\nmov.b64 db, {tb, th};\n"
        "wgmma.mma_async.sync.aligned.m64n8k16.f32.bf16.bf16 {%0,%1,%2,%3}, da, db, 0, 1, 1, 1, 0;\n}\n"
        : "=f"(d[0]),"=f"(d[1]),"=f"(d[2]),"=f"(d[3])
        : "r"(ab), "r"(bb), "n"(AO), "n"(BO), "n"(BH));
}
template <uint32_t BO, uint32_t BH> __device__ __forceinline__ void wg_rs24_z(float (&d)[12], uint32_t a0, uint32_t a1, uint32_t a2, uint32_t a3, uint32_t bb) {
    asm volatile("{\n.reg .b64 db;\n.reg .b32 tb, th;\nadd.u32 tb, %16, %17;\nmov.b32 th, %18;\nmov.b64 db, {tb, th};\n"
        "wgmma.mma_async.sync.aligned.m64n24k16.f32.bf16.bf16 {%0,%1,%2,%3,%4,%5,%6,%7,%8,%9,%10,%11}, {%12,%13,%14,%15}, db, 0, 1, 1, 0;\n}\n"
        : "=f"(d[0]),"=f"(d[1]),"=f"(d[2]),"=f"(d[3]),"=f"(d[4]),"=f"(d[5]),"=f"(d[6]),"=f"(d[7]),"=f"(d[8]),"=f"(d[9]),"=f"(d[10]),"=f"(d[11])
        : "r"(a0), "r"(a1), "r"(a2), "r"(a3), "r"(bb), "n"(BO), "n"(BH));
}

constexpr uint32_t DH128 = 64u | 0x40000000u;
constexpr uint32_t DH64 = 32u | 0x80000000u;
constexpr uint32_t LBO4K = (4096u >> 4) << 16, LBO8K = (8192u >> 4) << 16, LBO1 = 1u << 16;

template <uint32_t AO, uint32_t BO, bool SW64, bool FIRST> __device__ __forceinline__ void stage_ss(float (&acc)[64], uint32_t ab, uint32_t bb) {
    constexpr uint32_t KS = SW64 ? 64 : 128, BH = SW64 ? DH64 : DH128, B0 = BO + (SW64 ? LBO4K : LBO8K);
    wg_fence();
    if (FIRST) wg_ss128_z<AO, B0, BH>(acc, ab, bb); else wg_ss128<AO, B0, BH>(acc, ab, bb);
    wg_ss128<AO + 2, B0 + KS, BH>(acc, ab, bb);
    wg_ss128<AO + 4, B0 + 2 * KS, BH>(acc, ab, bb);
    wg_ss128<AO + 6, B0 + 3 * KS, BH>(acc, ab, bb);
    wg_commit();
}
template <uint32_t BO, bool FIRST> __device__ __forceinline__ void stage_rs(float (&acc)[64], const uint32_t (&f)[16], uint32_t bb) {
    wg_fence();
    if (FIRST) wg_rs128_z<BO + LBO8K, DH128>(acc, f[0], f[1], f[2], f[3], bb); else wg_rs128<BO + LBO8K, DH128>(acc, f[0], f[1], f[2], f[3], bb);
    wg_rs128<BO + LBO8K + 128, DH128>(acc, f[4], f[5], f[6], f[7], bb);
    wg_rs128<BO + LBO8K + 256, DH128>(acc, f[8], f[9], f[10], f[11], bb);
    wg_rs128<BO + LBO8K + 384, DH128>(acc, f[12], f[13], f[14], f[15], bb);
    wg_commit();
}

template <int N> __device__ __forceinline__ void stash(uint32_t base, uint32_t sw, const uint32_t (&f)[N]) {
#pragma unroll
    for (int t = 0; t < N / 4; t++) stsm4(base + ((sw ^ (2 * t)) << 4), f[4 * t], f[4 * t + 1], f[4 * t + 2], f[4 * t + 3]);
}

template <int V0, int V1, int N> __device__ __forceinline__ void send_frag(const uint32_t (&f)[N], uint4* p, uint32_t tag) {
#pragma unroll
    for (int v = V0; v < V1; v++) st_pkt(p + v * 32, (f[4 * v] & ~1u) | tag, f[4 * v + 1], f[4 * v + 2], f[4 * v + 3]);
}
template <int V0, int V1, int N> __device__ __forceinline__ void send_h(const uint32_t (&f)[N], uint4* p) {
#pragma unroll
    for (int v = V0; v < V1; v++) {
        const int h = v >> 1, hi = v & 1;
        asm volatile("st.global.v4.u32 [%0], {%1,%2,%3,%4};" :: "l"(p + 4 * h + 64 * hi),
                     "r"(f[8 * h + hi]), "r"(f[8 * h + 2 + hi]), "r"(f[8 * h + 4 + hi]), "r"(f[8 * h + 6 + hi]) : "memory");
    }
}
template <int O, int N, int M> __device__ __forceinline__ void pack_sub(uint32_t (&f)[N], const float (&acc)[M]) {
#pragma unroll
    for (int i = 0; i < N; i++) f[i] = keep(pack2(acc[O + 2 * i], acc[O + 2 * i + 1]));
}
template <int N> __device__ __forceinline__ void recv_issue(uint32_t (&q)[N], const uint4* p) {
#pragma unroll
    for (int v = 0; v < N / 4; v++) ld_pkt(p + v * 32, q[4 * v], q[4 * v + 1], q[4 * v + 2], q[4 * v + 3]);
}
template <int N> __device__ __forceinline__ void recv_check(uint32_t (&q)[N], const uint4* p, uint32_t tag) {
    uint32_t it = 0;
    while (true) {
        uint32_t bad = 0;
#pragma unroll
        for (int v = 0; v < N / 4; v++) bad |= q[4 * v] ^ tag;
        if (__all_sync(0xffffffffu, (bad & 1u) == 0) || ++it > SPIN_GLOBAL) break;
        recv_issue(q, p);
    }
}
__device__ __forceinline__ void accum(const uint32_t (&q)[32], float (&sum)[64]) {
#pragma unroll
    for (int i = 0; i < 32; i++) { sum[2 * i] += bf_lo(q[i]); sum[2 * i + 1] += bf_hi(q[i]); }
}

}

__global__ void __launch_bounds__(384, 1)
fused_kernel(const __grid_constant__ Maps maps, const __nv_bfloat16* __restrict__ xg, const __nv_bfloat16* __restrict__ gate_w,
             const char* __restrict__ pf_qkv, const char* __restrict__ pf_g, const char* __restrict__ pf_u,
             const char* __restrict__ pf_d, const char* __restrict__ pf_o, __nv_bfloat16* __restrict__ out) {
    extern __shared__ __align__(1024) uint8_t smem_raw[];
    const uint32_t sb = (uint32_t)__cvta_generic_to_shared(smem_raw);
    const int tid = threadIdx.x, lane = tid & 31;
    const int warp = __shfl_sync(0xffffffffu, tid >> 5, 0);
    const int j = (blockIdx.x >> 1) & 7;
    const int r = ((blockIdx.x >> 4) << 1) | (blockIdx.x & 1);
    const uint32_t rank = blockIdx.x & 1;

    if (warp == 0) { TSG(0, 30); TS(0, 0); }
    if (tid == 256) {
        for (int i = 0; i < 5; i++) { mbar_init(sb + B_FULL + 8 * i, 1); mbar_init(sb + B_EMPTY + 8 * i, MC ? 4 : 2); }
        for (int i = 0; i < 9; i++) mbar_init(sb + B_XFULL + 8 * i, 1);
        asm volatile("fence.mbarrier_init.release.cluster;" ::: "memory");
        mbar_expect(sb + B_XFULL, 16384);
        tma2(sb + OFF_X, &maps.x, 0, r * 128, sb + B_XFULL);
        TS2(0);
        mbar_expect(sb + B_FULL, 16384);
        tmaw3(sb + OFF_RING, &maps.kv, 64 * j, 0, 1, sb + B_FULL);
        TS2(1);
        mbar_expect(sb + B_FULL + 8, 16384);
        tmaw3(sb + OFF_RING + 16384, &maps.gu, 224 * j, 0, 0, sb + B_FULL + 8);
    } else if (tid == 288) {
        for (int i = 0; i < 3; i++) mbar_init(sb + B_HSENT + 8 * i, 8);
        for (int i = 0; i < 4; i++) { mbar_init(sb + B_EFULL + 8 * i, 1); mbar_init(sb + B_EEMPTY + 8 * i, MC ? 4 : 2); }
        mbar_init(sb + B_XFREE, 2); mbar_init(sb + B_XFREE + 8, 2); mbar_init(sb + B_XFREE + 16, 2);
        mbar_init(sb + B_AHEAD, 1); mbar_init(sb + B_GRDY, 1); mbar_init(sb + B_KVDONE, 8); mbar_init(sb + B_KVRDY, 2);
        asm volatile("fence.mbarrier_init.release.cluster;" ::: "memory");
    } else if (warp == 10 && lane < 10) {
        asm volatile("prefetch.tensormap [%0];" :: "l"(&maps.gu + lane) : "memory");
    }
    __syncthreads();

    if (warp >= 8) {
        asm volatile("setmaxnreg.dec.sync.aligned.u32 56;");
        if (warp == 8) {
            if (lane == 0) {
                int slot = MC ? 0 : 2, ph = 1;
                uint32_t full, dst;
                if (!MC) { mbar_expect(sb + B_XFULL + 8, 16384); tma2(sb + OFF_X + 16384, &maps.x, 64, r * 128, sb + B_XFULL + 8); }
#define P_BEGIN(S, BYTES) full = sb + B_FULL + 8 * slot; dst = sb + OFF_RING + slot * 16384; \
                mbar_wait(sb + B_EMPTY + 8 * slot, ph); TS2(S); mbar_expect(full, BYTES); if (!MC || (((S) ^ rank) & 1) == 0)
#define P_END() if (++slot == 5) { slot = 0; ph ^= 1; }
                for (int s = MC ? 0 : 2; s < 16; s++) {
                    const int kb = (int)(0x7654763542312100ull >> (4 * s)) & 15;
                    P_BEGIN(s, 16384) {
                        if ((0x0DADu >> s) & 1) tmaw3(dst, &maps.kv, 64 * j, 64 * kb, 1, full);
                        else tmaw3(dst, &maps.gu, 224 * j, 64 * kb, 0, full);
                    }
                    const int xb = (int)(0x0000000765403210ull >> (4 * s)) & 15;
                    if (xb) { mbar_expect(sb + B_XFULL + 8 * xb, 16384); tma2(sb + OFF_X + xb * 16384, &maps.x, 64 * xb, r * 128, sb + B_XFULL + 8 * xb); }
                    P_END()
                }
                for (int s = 0; s < 24; s++) {
                    P_BEGIN(16 + s, 16384) {
                        if (s < 8) {
                            tmaw3(dst, &maps.q64, 0, 64 * s, 2 * j, full);
                            tmaw3(dst + 8192, &maps.gu64, 224 * j + 192, 64 * s, 0, full);
                        } else {
                            tmaw3(dst, &maps.gu, 224 * j + 64 * (s >> 3), 64 * (s & 7), 0, full);
                        }
                    }
                    P_END()
                }
                const int p = j >> 1;
#pragma unroll 1
                for (int t = 0; t < 18; t++) {
                    const int q = t >= 9, sl = t - 9 * q;
                    const int u = (int)((q ? 0x432186758ull : 0x032675410ull) >> (4 * sl)) & 15;
                    const int cw = (j & 1) * 4 + ((p & 2) ^ ((t == 8 || t > 9) ? 0 : 2)), cc = 64 * cw;
                    if (sl < 5) {
                        full = sb + B_FULL + 8 * sl; dst = sb + OFF_RING + sl * 16384;
                        mbar_wait(sb + B_EMPTY + 8 * sl, q ^ 1);
                    } else {
                        full = sb + B_EFULL + 8 * (sl - 5); dst = sb + OFF_X + (sl == 7 ? 8 : sl == 8 ? 7 : sl) * 16384;
                        mbar_wait(sb + B_EEMPTY + 8 * (sl - 5), q);
                    }
                    TS2(40 + t);
                    mbar_expect(full, 16384);
                    if (!MC || ((t ^ rank) & 1) == 0) {
                        if (u == 4) {
                            tmaw5(dst, &maps.wdph, cc, 14 * p + 6, full); tmaw5(dst + 4096, &maps.wdph, cc, 14 * p + 13, full);
                            tmaw5(dst + 8192, &maps.wdph, cc + 64, 14 * p + 6, full); tmaw5(dst + 12288, &maps.wdph, cc + 64, 14 * p + 13, full);
                        } else if (u > 4) {
                            const int js = u > 6 ? j ^ 1 : j;
                            tmaw3(dst, (u & 1) ? &maps.wow : &maps.wdw, 0, (u & 1) ? 64 * js : 224 * js + 128, cw, full);
                        } else {
                            const int g = 14 * p + 7 * (u & 1) + (u & 2);
                            tmaw5(dst, &maps.wdp, cc, g, full); tmaw5(dst + 8192, &maps.wdp, cc + 64, g, full);
                        }
                    }
                }
            }
        } else if (warp < 11) {
            const int hx = warp - 9;
            uint32_t epoch;
            asm volatile("ld.relaxed.gpu.global.u32 %0, [%1];" : "=r"(epoch) : "l"(g_epoch + blockIdx.x) : "memory");
            {
                const uint4* xr = (const uint4*)(xg + (size_t)(r * 128 + j * 16 + hx * 8) * kD) + lane;
                const uint4 wa = __ldg((const uint4*)gate_w + lane), wb = __ldg((const uint4*)gate_w + 32 + lane);
                const uint32_t tag = (epoch + 1) & 1;
                uint4* gp = g_gx + r * 32;
                if (lane < 2) st_pkt(gp + j * 4 + hx * 2 + lane, tag ^ 1, 0, 0, 0);
                float s[8];
#pragma unroll
                for (int i0 = 0; i0 < 8; i0 += 4) {
                    uint4 va[4], vb[4];
#pragma unroll
                    for (int i = 0; i < 4; i++) { va[i] = __ldg(xr + (i0 + i) * 64); vb[i] = __ldg(xr + (i0 + i) * 64 + 32); }
#pragma unroll
                    for (int i = 0; i < 4; i++) {
                        float t0 = bf_lo(va[i].x) * bf_lo(wa.x), t1 = bf_hi(va[i].x) * bf_hi(wa.x);
                        t0 = fmaf(bf_lo(va[i].y), bf_lo(wa.y), t0); t1 = fmaf(bf_hi(va[i].y), bf_hi(wa.y), t1);
                        t0 = fmaf(bf_lo(va[i].z), bf_lo(wa.z), t0); t1 = fmaf(bf_hi(va[i].z), bf_hi(wa.z), t1);
                        t0 = fmaf(bf_lo(va[i].w), bf_lo(wa.w), t0); t1 = fmaf(bf_hi(va[i].w), bf_hi(wa.w), t1);
                        t0 = fmaf(bf_lo(vb[i].x), bf_lo(wb.x), t0); t1 = fmaf(bf_hi(vb[i].x), bf_hi(wb.x), t1);
                        t0 = fmaf(bf_lo(vb[i].y), bf_lo(wb.y), t0); t1 = fmaf(bf_hi(vb[i].y), bf_hi(wb.y), t1);
                        t0 = fmaf(bf_lo(vb[i].z), bf_lo(wb.z), t0); t1 = fmaf(bf_hi(vb[i].z), bf_hi(wb.z), t1);
                        t0 = fmaf(bf_lo(vb[i].w), bf_lo(wb.w), t0); t1 = fmaf(bf_hi(vb[i].w), bf_hi(wb.w), t1);
                        s[i0 + i] = t0 + t1;
                    }
                }
#pragma unroll
                for (int i = 0; i < 8; i++) {
#pragma unroll
                    for (int o = 16; o; o >>= 1) s[i] += __shfl_xor_sync(0xffffffffu, s[i], o);
                    s[i] = 1.f / (1.f + __expf(-s[i]));
                }
                if (lane < 2) {
                    const float v0 = lane ? s[4] : s[0], v1 = lane ? s[5] : s[1], v2 = lane ? s[6] : s[2], v3 = lane ? s[7] : s[3];
                    st_pkt(gp + j * 4 + hx * 2 + lane, (__float_as_uint(v0) & ~1u) | tag, __float_as_uint(v1), __float_as_uint(v2), __float_as_uint(v3));
                }
                if (hx == 1) {
                    asm volatile("st.shared.u32 [%0], %1;" :: "r"(sb + OFF_ONES + lane * 4), "r"(0x3f803f80u) : "memory");
                    asm volatile("fence.proxy.async.shared::cta;" ::: "memory");
                }
                asm volatile("bar.sync 3, 96;" ::: "memory");
                if (hx == 0) {
                    uint32_t q[4];
                    recv_issue(q, gp + lane);
                    recv_check(q, gp + lane, tag);
                    asm volatile("st.shared.v4.u32 [%0], {%1,%2,%3,%4};" :: "r"(sb + OFF_G + lane * 16), "r"(q[0]), "r"(q[1]), "r"(q[2]), "r"(q[3]) : "memory");
                    if (lane == 0) {
                        asm volatile("st.shared.u32 [%0], %1;" :: "r"(sb + OFF_EPOCH), "r"(epoch) : "memory");
                        g_epoch[blockIdx.x] = epoch + 1;
                    }
                    __syncwarp();
                    if (lane == 0) mbar_arrive(sb + B_GRDY);
                } else {
                    if (r == 0) {
                        float4* zp = (float4*)(g_kvacc + (((epoch & 1) ^ 1) * 8 + j) * 4 * 272);
                        for (int i = lane; i < 272; i += 32) zp[i] = make_float4(0.f, 0.f, 0.f, 0.f);
                    }
                }
            }
            TS(2 + hx, 1);
#define PUBLISH_H(B) do { mbar_wait(sb + B_HSENT + 8 * (B), 0); if (lane == 0) { \
                asm volatile("st.release.gpu.global.u32 [%0], %1;" :: "l"(g_hflag + (r * 8 + j) * 8 + (B)), "r"(epoch + 1) : "memory"); } __syncwarp(); } while (0)
            if (hx == 1) {
#pragma unroll 1
                for (int b = 0; b < 3; b++) { PUBLISH_H(b); TS(3, 5 + b); }
            } else {
                const float* accp = g_kvacc + ((epoch & 1) * 8 + j) * 4 * 272;
                unsigned* cnt = g_kvcnt + j * 32;
                mbar_wait(sb + B_KVDONE, 0);
                TS(2, 5);
                if (lane == 0) asm volatile("red.release.gpu.global.add.u32 [%0], 1;" :: "l"(cnt) : "memory");
                __syncwarp();
                TS(2, 2);
                {
                    const unsigned target = 16u * (epoch + 1);
                    uint32_t it = 0, v;
                    do {
                        asm volatile("ld.acquire.gpu.global.u32 %0, [%1];" : "=r"(v) : "l"(cnt) : "memory");
                    } while ((int)(v - target) < 0 && ++it < SPIN_GLOBAL);
                }
                TS(2, 3);
#pragma unroll
                for (int h = 0; h < 4; h++) {
                    const float4 d0 = __ldcg((const float4*)(accp + h * 272) + lane);
                    const float4 d1 = __ldcg((const float4*)(accp + h * 272 + 128) + lane);
                    const float2 z0 = __ldcg((const float2*)(accp + h * 272 + 256) + (lane & 3));
                    const float2 z1 = __ldcg((const float2*)(accp + h * 272 + 264) + (lane & 3));
                    const uint32_t ba = sb + OFF_STG + h * 768 + lane * 4;
                    asm volatile("st.shared.u32 [%0], %1;" :: "r"(ba), "r"(pack2(d0.x, d0.y)) : "memory");
                    asm volatile("st.shared.u32 [%0], %1;" :: "r"(ba + 128), "r"(pack2(d1.x, d1.y)) : "memory");
                    asm volatile("st.shared.u32 [%0], %1;" :: "r"(ba + 256), "r"(pack2(d0.z, d0.w)) : "memory");
                    asm volatile("st.shared.u32 [%0], %1;" :: "r"(ba + 384), "r"(pack2(d1.z, d1.w)) : "memory");
                    asm volatile("st.shared.u32 [%0], %1;" :: "r"(ba + 512), "r"(pack2(z0.x, z0.y)) : "memory");
                    asm volatile("st.shared.u32 [%0], %1;" :: "r"(ba + 640), "r"(pack2(z1.x, z1.y)) : "memory");
                }
                asm volatile("fence.proxy.async.shared::cta;" ::: "memory");
                __syncwarp();
                if (lane == 0) mbar_arrive(sb + B_KVRDY);
                TS(2, 4);
            }
        } else {
            uint32_t epoch;
            asm volatile("ld.relaxed.gpu.global.u32 %0, [%1];" : "=r"(epoch) : "l"(g_epoch + blockIdx.x) : "memory");
            asm volatile("bar.arrive 3, 96;" :: "r"(epoch) : "memory");
            const int b = blockIdx.x, p = j >> 1;
            mbar_wait(sb + B_XFULL, 0);
#pragma unroll 1
            for (int kb = 1; kb < 8; kb++) {
                mbar_wait(sb + B_XFULL + 8 * kb, 0);
                const char* base = kb < 3 ? pf_g : kb < 5 ? pf_u : kb == 5 ? pf_qkv : pf_d;
                const int off = kb == 5 ? b * 12288 : b * 14336 + ((kb < 5 ? kb - 1 : kb) & 1) * 7168;
                if (kb == 5) {
                    asm volatile("prefetch.global.L2 [%0];" :: "l"(base + off + (lane >> 3) * 3072 + (lane & 7) * 128));
                } else {
                    asm volatile("prefetch.global.L2 [%0];" :: "l"(base + off + lane * 128));
                    if (lane < 24) asm volatile("prefetch.global.L2 [%0];" :: "l"(base + off + 4096 + lane * 128));
                }
                if (kb == 7) asm volatile("prefetch.global.L2 [%0];" :: "l"(pf_o + b * 4096 + lane * 128));
            }
            {
                uint4* mb = g_part + (size_t)(r * 2 + (j & 1)) * 16384 + (((p ^ 1) * 4 + p) << 10) + lane;
#pragma unroll 1
                for (int i = 0; i < 32; i++) { st_pkt(mb + i * 32, epoch & 1, 0, 0, 0); __nanosleep(40); }
                __syncwarp();
                if (lane == 0) mbar_arrive(sb + B_KVRDY);
            }
            {
                const uint32_t want = epoch + 1;
                const int hrow = (r * 4 + p) * 5 * 128;
                const unsigned* fl = g_hflag + (r * 8 + (j & 6)) * 8 + (lane & 15);
                uint32_t it = 0;
                int i = 0;
                mbar_wait(sb + B_HSENT + 8, 0);
#pragma unroll 1
                while (i < 3 && ++it < SPIN_GLOBAL) {
                    uint32_t v;
                    asm volatile("ld.acquire.gpu.global.u32 %0, [%1];" : "=r"(v) : "l"(fl) : "memory");
                    const uint32_t rdy = __ballot_sync(0xffffffffu, v == want);
#pragma unroll 1
                    while (i < 3 && ((rdy >> i) & 0x101u) == 0x101u) {
                        if (i < 2) mbar_wait(sb + B_XFREE + 8 * i, 0);
                        if (lane == 0) {
                            const int pc = (6 - 2 * i) % 6;
                            asm volatile("fence.proxy.async.global;" ::: "memory");
                            TS2(140 + i);
                            mbar_expect(sb + B_XFULL + 8 * pc, i != 1 ? 32768 : 16384);
                            tma2(sb + OFF_X + pc * 16384, i != 1 ? &maps.hx2 : &maps.hx, 0, hrow + pc * 128, sb + B_XFULL + 8 * pc);
                        }
                        i++;
                    }
                }
            }
        }
    } else {
        asm volatile("setmaxnreg.inc.sync.aligned.u32 224;");
        const int wg = warp >> 2;
        const bool elect = (tid & 127) == 0;
        const uint32_t sbd = sb >> 4, xlo = (sbd + wg * 512) | LBO1;
        auto release = [&](uint32_t bar) {
            if (elect) {
                mbar_arrive(sb + bar);
            }
        };
#define S_SL(S) ((S) < 40 ? (S) % 5 : ((S) - 40) % 9)
#define S_WAIT(S) do { mbar_wait(sb + (S_SL(S) < 5 ? B_FULL + 8 * S_SL(S) : B_EFULL + 8 * (S_SL(S) - 5)), (S) < 40 ? ((S) / 5) & 1 : (S) >= 49); \
            if (PROF && tid == 0) TS2(64 + (S)); } while (0)
#define S_B(S) (S_SL(S) < 5 ? OFF_RING / 16 + S_SL(S) * 1024 : (S_SL(S) == 7 ? 8 : S_SL(S) == 8 ? 7 : S_SL(S)) * 1024)
#define S_REL(S) do { if ((S) < 49) release(S_SL(S) < 5 ? B_EMPTY + 8 * S_SL(S) : B_EEMPTY + 8 * (S_SL(S) - 5)); } while (0)
#define G1(S, acc, SW, KB) stage_ss<(KB) * 1024, S_B(S), SW, (KB) == 0>(acc, xlo, sbd)
#define RET(S) do { S_WAIT((S) + 1); wg_wait<1>(); S_REL((S) - 1); } while (0)
#define RET2(S) do { S_WAIT((S) + 1); wg_wait<2>(); S_REL((S) - 1); } while (0)
#define SCHED() mbar_wait(sb + B_XFULL + 8 * 7, 0)
#define A2_SYNC() do { asm volatile("fence.proxy.async.shared::cta;" ::: "memory"); asm volatile("bar.sync %0, 128;" :: "r"(wg + 1) : "memory"); } while (0)
#define H_EPI(acc, F, I0, I1, OG, OU) _Pragma("unroll") for (int i = (I0); i < (I1); i++) \
            F[i] = keep(hmul2(pack2(acc[(OG) + 2 * i] * acc[(OU) + 2 * i], acc[(OG) + 2 * i + 1] * acc[(OU) + 2 * i + 1]), (i & 1) ? m_hi : m_lo))
#define PHI(acc, F, I0, I1) _Pragma("unroll") for (int i = (I0); i < (I1); i++) F[i] = keep(phi2(acc[2 * i], acc[2 * i + 1]))

        float a0[64], b0[64], a1[64], a2_[64], a3[64];
        mbar_wait(sb + B_XFULL, 0);
#define X_WAIT(KB) do { mbar_wait(sb + B_XFULL + 8 * (KB), 0); if (PROF && tid == 0) TS2(128 + (KB)); } while (0)
        S_WAIT(0); G1(0, b0, false, 0);
        if ((warp & 3) == 0) TS(wg, 1);
        S_WAIT(1); G1(1, a0, false, 0); RET(1);
        X_WAIT(1); G1(2, b0, false, 1); RET(2);
        X_WAIT(2); G1(3, b0, false, 2); RET(3);
        G1(4, a0, false, 1); RET(4);
        X_WAIT(3); G1(5, b0, false, 3); RET(5);
        G1(6, a0, false, 2); RET(6);
        X_WAIT(4); G1(7, b0, false, 4); RET(7);
        X_WAIT(5); G1(8, b0, false, 5); RET(8);
        G1(9, a0, false, 3); RET(9);
        X_WAIT(6); G1(10, b0, false, 6); RET(10);
        X_WAIT(7); G1(11, b0, false, 7); RET(11);
        G1(12, a0, false, 4);
        const uint32_t lrow = ((lane & 7) + 8 * ((lane >> 3) & 1)) * 128;
        const uint32_t srow = (warp & 3) * 2048 + lrow;
        const uint32_t ssw = (lane >> 4) ^ (lane & 7);
        uint4* const hsend = g_hx + (size_t)((r * 4 + (j >> 1)) * 5 + (j & 1)) * 1024 + warp * 128 + (lane >> 2) * 8 + (lane & 3);
#define SENT_H(B) do { __syncwarp(); if (lane == 0) mbar_arrive(sb + B_HSENT + 8 * (B)); } while (0)
        RET(12);
        pin(b0);
        uint32_t fh0[16], fh1[16], fh2[16], fh3[8], fo[16], pk[16], pv[16];
        float kv[32], zs[4];
        const uint32_t stg = sb + OFF_STG + wg * 8192, stl = stg + (warp & 1) * 2048 + lrow;
#define KV_ROUND(Z) do { A2_SYNC(); wg_fence(); \
            wg_ss64t##Z<8192 + 256, 8192, DH128>(kv, xlo, xlo); wg_ss64t<8192 + 384, 8192 + 128, DH128>(kv, xlo, xlo); \
            wg_ss8t##Z<8192, OFF_ONES / 16, 0>(zs, xlo, sbd); wg_ss8t<8192 + 128, OFF_ONES / 16, 0>(zs, xlo, sbd); wg_commit(); } while (0)
        G1(13, a0, false, 5); SCHED(); pack_sub<32>(pv, b0); PHI(b0, pk, 0, 4); RET(13);
        G1(14, a0, false, 6); SCHED(); if (!(warp & 2)) stash<16>(stl + 4096, ssw, pv); PHI(b0, pk, 4, 10); RET(14);
        G1(15, a0, false, 7); SCHED(); PHI(b0, pk, 10, 16); RET(15);
        if ((warp & 3) == 0) TS(wg, 2);

        G1(16, a1, true, 0); SCHED(); if (!(warp & 2)) stash<16>(stl, ssw, pk);
        mbar_wait(sb + B_GRDY, 0);
        float g_lo, g_hi;
        uint32_t tag;
        {
            const uint32_t ga = sb + OFF_G + (warp * 16 + (lane >> 2)) * 4;
            asm volatile("ld.shared.f32 %0, [%1];" : "=f"(g_lo) : "r"(ga) : "memory");
            asm volatile("ld.shared.f32 %0, [%1];" : "=f"(g_hi) : "r"(ga + 32) : "memory");
            asm volatile("ld.shared.u32 %0, [%1];" : "=r"(tag) : "r"(sb + OFF_EPOCH) : "memory");
        }
        float* const kvp = g_kvacc + (((tag & 1) * 8 + j) * 4 + (warp & 3)) * 272;
        tag = (tag + 1) & 1;
        const uint32_t m_lo = pack2(1.f - g_lo, 1.f - g_lo), m_hi = pack2(1.f - g_hi, 1.f - g_hi);
        RET(16);
        pin(a0);
        G1(17, a1, true, 1); SCHED(); H_EPI(a0, fh0, 0, 16, 0, 32); RET(17);
        G1(18, a1, true, 2); KV_ROUND(_z); RET2(18);
        G1(19, a1, true, 3); SCHED(); send_h<0, 1>(fh0, hsend); RET(19);
        G1(20, a1, true, 4); SCHED(); if (warp & 2) { stash<16>(stl, ssw, pk); stash<16>(stl + 4096, ssw, pv); } RET(20);
        G1(21, a1, true, 5); RET(21);
        G1(22, a1, true, 6); KV_ROUND(); RET2(22);
        G1(23, a1, true, 7); SCHED(); send_h<1, 2>(fh0, hsend); RET(23);
        pin(kv); pin(zs);
        if ((warp & 3) == 0) TS(wg, 3);

        G1(24, a2_, false, 0); SCHED();
#define KV_RED(W) do { asm volatile("red.global.add.v4.f32 [%0], {%1,%2,%3,%4};" :: "l"(kvp + lane * 4), "f"(kv[8 * W]), "f"(kv[8 * W + 1]), "f"(kv[8 * W + 2]), "f"(kv[8 * W + 3]) : "memory"); \
                       asm volatile("red.global.add.v4.f32 [%0], {%1,%2,%3,%4};" :: "l"(kvp + 128 + lane * 4), "f"(kv[8 * W + 4]), "f"(kv[8 * W + 5]), "f"(kv[8 * W + 6]), "f"(kv[8 * W + 7]) : "memory"); } while (0)
        if ((warp & 3) == 0) KV_RED(0); else if ((warp & 3) == 1) KV_RED(1); else if ((warp & 3) == 2) KV_RED(2); else KV_RED(3);
        if ((lane & 3) == 0) {
            asm volatile("red.global.add.f32 [%0], %1;" :: "l"(kvp + 256 + (lane >> 2)), "f"(zs[0]) : "memory");
            asm volatile("red.global.add.f32 [%0], %1;" :: "l"(kvp + 264 + (lane >> 2)), "f"(zs[2]) : "memory");
        }
        __syncwarp();
        if (lane == 0) mbar_arrive(sb + B_KVDONE);
        RET(24);
        pin(a1);
        G1(25, a2_, false, 1); SCHED(); send_h<2, 3>(fh0, hsend); H_EPI(a1, fh3, 0, 8, 32, 48); RET(25);
        G1(26, a2_, false, 2); SCHED(); send_h<3, 4>(fh0, hsend); SENT_H(0); PHI(a1, fo, 0, 4); RET(26);
        G1(27, a2_, false, 3); SCHED(); send_h<0, 1>(fh3, hsend + 4 * 1024 - (j & 1) * 1020); PHI(a1, fo, 4, 8); RET(27);
        G1(28, a2_, false, 4); SCHED(); send_h<1, 2>(fh3, hsend + 4 * 1024 - (j & 1) * 1020); SENT_H(1); PHI(a1, fo, 8, 12); RET(28);
        G1(29, a2_, false, 5); SCHED(); PHI(a1, fo, 12, 16); RET(29);
        G1(30, a2_, false, 6); RET(30);
        G1(31, a2_, false, 7); RET(31);
        if ((warp & 3) == 0) TS(wg, 4);

        float on[4][12];
#define O_SCALE(h) do { const float s_lo = __fdividef(g_lo, on[h][8] + 1e-6f), s_hi = __fdividef(g_hi, on[h][10] + 1e-6f); \
            const uint32_t sl_ = pack2(s_lo, s_lo), sh_ = pack2(s_hi, s_hi); \
            fo[4 * h] = keep(hmul2(pack2(on[h][0], on[h][1]), sl_)); fo[4 * h + 1] = keep(hmul2(pack2(on[h][2], on[h][3]), sh_)); \
            fo[4 * h + 2] = keep(hmul2(pack2(on[h][4], on[h][5]), sl_)); fo[4 * h + 3] = keep(hmul2(pack2(on[h][6], on[h][7]), sh_)); } while (0)
        uint4* const lsend = g_lx + (size_t)(r * 8 + j) * 2048 + warp * 128 + lane;
        const uint4* const lrecv = g_lx + (size_t)(r * 8 + (j ^ 1)) * 2048 + warp * 128 + lane;
        G1(32, a3, false, 0); RET(32);
        pin(a2_);
        G1(33, a3, false, 1); SCHED(); H_EPI(a2_, fh1, 0, 16, 0, 32); send_h<0, 1>(fh1, hsend + 2 * 1024); RET(33);
        G1(34, a3, false, 2); SCHED(); send_h<1, 3>(fh1, hsend + 2 * 1024);
        if ((warp & 3) == 0) TS(wg, 5);
        mbar_wait(sb + B_KVRDY, 0);
        if ((warp & 3) == 0) TS(wg, 6);
        wg_fence();
#define O_MMA(h) wg_rs24_z<OFF_STG / 16 + (h) * 48 + (8u << 16), 16>(on[h], fo[4 * (h)], fo[4 * (h) + 1], fo[4 * (h) + 2], fo[4 * (h) + 3], sbd)
        O_MMA(0); O_MMA(1); O_MMA(2); O_MMA(3);
        wg_commit();
        RET2(34);
        if (elect) mbar_arrive(sb + B_XFREE);
        G1(35, a3, false, 3); SCHED(); send_h<3, 4>(fh1, hsend + 2 * 1024); SENT_H(2); RET(35);
        pin(on[0]); pin(on[1]); pin(on[2]); pin(on[3]);
        release(B_EEMPTY + 16);
        G1(36, a3, false, 4); SCHED(); O_SCALE(0); O_SCALE(1); O_SCALE(2); O_SCALE(3); RET(36);
        G1(37, a3, false, 5); SCHED(); send_frag<0, 2>(fo, lsend, tag); RET(37);
        if (elect) mbar_arrive(sb + B_XFREE + 8);
        G1(38, a3, false, 6); SCHED(); send_frag<2, 4>(fo, lsend, tag); RET(38);
        release(B_EEMPTY);
        G1(39, a3, false, 7); RET(39);
        release(B_EEMPTY + 8);
        if ((warp & 3) == 0) TS(wg, 7);

#define G2S(S, acc, U) stage_ss<(U) * 1024, S_B(S), false, (S) == 40 || (S) == 48>(acc, xlo, sbd)
#define G2R(S, acc, F) stage_rs<S_B(S), false>(acc, F, sbd)
#define H_WAIT(P) do { mbar_wait(sb + B_XFULL + 8 * (P), 1); if (PROF && tid == 0) TS2(150 + (P)); } while (0)
        const int p = j >> 1, pw = (p & 2) ^ 2;
        const bool own = wg == (p & 1);
        uint4* const pbase = g_part + (size_t)(r * 2 + (j & 1)) * 16384 + (warp & 3) * 256 + lane;

        float p1[64], p2[64];
        uint32_t po[16], ph2[16];
        H_WAIT(0); G2S(40, p1, 0); SCHED(); recv_issue(po, lrecv); RET(40);
        release(B_EEMPTY + 24);
        pin(a3);
        G2S(41, p1, 1); SCHED(); H_EPI(a3, fh2, 0, 16, 0, 32); send_frag<0, 2>(fh2, lsend + 1024, tag); RET(41);
        H_WAIT(4); G2S(42, p1, 4); SCHED(); send_frag<2, 4>(fh2, lsend + 1024, tag); RET(42);
        G2R(43, p1, fo); SCHED(); recv_check(po, lrecv, tag); RET(43);
        G2R(44, p1, po); RET(44);
        G2R(45, p1, fh2); SCHED(); recv_issue(ph2, lrecv + 1024); RET(45);
        H_WAIT(2); G2S(46, p1, 2); RET(46);
        G2S(47, p1, 3); RET(47);
        G2S(48, p2, 0); SCHED(); recv_check(ph2, lrecv + 1024, tag); RET(48);
        G2R(49, p1, ph2); RET(49);
        if ((warp & 3) == 0) TS(wg, 8);
        uint32_t sp[32], qa[32], qb[32];
        uint4* const s1 = pbase + (((pw + wg) * 4 + p) << 10);
        G2R(50, p2, fo); RET(50);
        pin(p1);
        G2R(51, p2, po); SCHED(); pack_sub<0>(sp, p1); send_frag<0, 2>(sp, s1, tag); RET(51);
        G2R(52, p2, fh2); SCHED(); send_frag<2, 5>(sp, s1, tag); RET(52);
        G2R(53, p2, ph2); SCHED(); send_frag<5, 8>(sp, s1, tag); RET(53);
        const uint4* ra = pbase + ((p * 4 + pw) << 10);
        const uint4* rc = pbase + ((p * 4 + (p ^ 1)) << 10);
        if (own) { mbar_wait(sb + B_AHEAD, 0); recv_issue(qa, ra); recv_issue(qb, ra + 1024); }
        G2S(54, p2, 1); RET(54);
        G2S(55, p2, 2); RET(55);
        G2S(56, p2, 3); RET(56);
        G2S(57, p2, 4); SCHED();
        if ((warp & 3) == 0) TS(wg, 9);
        if (!own) {
            if (elect) mbar_arrive(sb + B_AHEAD);
        } else {
            recv_issue(sp, rc);
            recv_check(qa, ra, tag); recv_check(qb, ra + 1024, tag);
#pragma unroll
            for (int i = 0; i < 32; i++) qa[i] = keep(hadd2(qa[i], qb[i]));
        }
        wg_wait<0>();
        pin(p2);
        if ((warp & 3) == 0) TS(wg, 11);
        if (!own) {
            pack_sub<0>(sp, p2); send_frag<0, 8>(sp, pbase + (((p ^ 1) * 4 + p) << 10), tag);
        } else {
            if ((warp & 3) == 0) TS(wg, 12);
            recv_check(sp, rc, tag);
#pragma unroll
            for (int i = 0; i < 32; i++) qa[i] = hadd2(qa[i], sp[i]);
            accum(qa, p2);
            if ((warp & 3) == 0) TS(wg, 13);
            uint32_t f0[16], f1[16];
            pack_sub<0>(f0, p2); pack_sub<32>(f1, p2);
            const uint32_t slab = sb + OFF_X + 2 * 16384 + wg * 8192;
            stash<16>(slab + srow, ssw, f0); stash<16>(slab + 16384 + srow, ssw, f1);
            __syncwarp();
            __nv_bfloat16* op = out + (size_t)(r * 128 + warp * 16 + (lane >> 4)) * kD + (j & 1) * 256 + (p & 2) * 64 + (lane & 15) * 8;
#pragma unroll
            for (int i = 0; i < 8; i++) {
                const int row = i * 2 + (lane >> 4);
                uint4 v;
                asm volatile("ld.shared.v4.u32 {%0,%1,%2,%3}, [%4];" : "=r"(v.x), "=r"(v.y), "=r"(v.z), "=r"(v.w)
                             : "r"(slab + (lane & 8) * 2048 + ((warp & 3) * 16 + row) * 128 + (((lane & 7) ^ (row & 7)) << 4)) : "memory");
                *(uint4*)(op + i * 2 * kD) = v;
            }
        }
        if ((warp & 3) == 0) { TS(wg, 14); TSG(wg, 31); }
    }
}

typedef CUresult (*EncodeFn)(CUtensorMap*, CUtensorMapDataType, cuuint32_t, void*, const cuuint64_t*, const cuuint64_t*, const cuuint32_t*,
                             const cuuint32_t*, CUtensorMapInterleave, CUtensorMapSwizzle, CUtensorMapL2promotion, CUtensorMapFloatOOBfill);

static void encode(EncodeFn fn, CUtensorMap* m, int rank, const void* base, const cuuint64_t (&gd)[5], const cuuint64_t (&gs)[4],
                   const cuuint32_t (&bd)[5], CUtensorMapSwizzle sw) {
    cuuint32_t es[5] = {1, 1, 1, 1, 1};
    fn(m, CU_TENSOR_MAP_DATA_TYPE_BFLOAT16, rank, const_cast<void*>(base), gd, gs, bd, es, CU_TENSOR_MAP_INTERLEAVE_NONE, sw,
       CU_TENSOR_MAP_L2_PROMOTION_L2_128B, CU_TENSOR_MAP_FLOAT_OOB_FILL_NONE);
}

extern "C" void kernel_launch(void* const* d_in, const int* in_sizes, int n_in, void* d_out, int out_size) {
    const char* x = (const char*)d_in[0];
    const char* wqkv = (const char*)d_in[1];
    const char* wo = (const char*)d_in[2];
    const char* wg = (const char*)d_in[4];
    const char* wu = (const char*)d_in[5];
    const char* wd = (const char*)d_in[6];
    void* fnp = nullptr;
    cudaDriverEntryPointQueryResult qr;
    cudaGetDriverEntryPoint("cuTensorMapEncodeTiled", &fnp, cudaEnableDefault, &qr);
    EncodeFn fn = (EncodeFn)fnp;
    Maps maps;
    const char* lo = wg < wu ? wg : wu;
    const uint64_t diff = wg < wu ? (uint64_t)(wu - wg) : (uint64_t)(wg - wu);
    const CUtensorMapSwizzle S128 = CU_TENSOR_MAP_SWIZZLE_128B, S64 = CU_TENSOR_MAP_SWIZZLE_64B;
    encode(fn, &maps.x, 2, x, {512, 2048, 1, 1}, {1024, 0, 0}, {64, 128, 1, 1}, S128);
    encode(fn, &maps.gu, 3, lo, {1792, 512, 2, 1}, {3584, diff, 0}, {64, 64, 2, 1}, S128);
    encode(fn, &maps.kv, 3, wqkv, {512, 512, 3, 1}, {3072, 1024, 0}, {64, 64, 2, 1}, S128);
    encode(fn, &maps.q64, 3, wqkv, {32, 512, 48, 1}, {3072, 64, 0}, {32, 64, 2, 1}, S64);
    encode(fn, &maps.gu64, 3, lo, {1792, 512, 2, 1}, {3584, diff, 0}, {32, 64, 2, 1}, S64);
    encode(fn, &maps.wdw, 3, wd, {64, 1792, 8, 1}, {1024, 128, 0}, {64, 64, 2, 1}, S128);
    encode(fn, &maps.wow, 3, wo, {64, 512, 8}, {1024, 128}, {64, 64, 2}, S128);
    encode(fn, &maps.wdp, 5, wd, {512, 2, 4, 4, 56}, {1024, 8192, 2048, 32768}, {64, 2, 4, 4, 2}, S128);
    encode(fn, &maps.wdph, 5, wd, {512, 2, 4, 4, 56}, {1024, 8192, 2048, 32768}, {64, 2, 4, 4, 1}, S128);
    void* hx = nullptr;
    cudaGetSymbolAddress(&hx, g_hx);
    encode(fn, &maps.hx, 2, hx, {64, 16 * 4 * 5 * 128}, {128}, {64, 128}, S128);
    encode(fn, &maps.hx2, 2, hx, {64, 16 * 4 * 5 * 128}, {128}, {64, 256}, S128);
    cudaFuncSetAttribute(fused_kernel, cudaFuncAttributeMaxDynamicSharedMemorySize, SMEM_BYTES);
    cudaLaunchConfig_t cfg = {};
    cfg.gridDim = dim3(128);
    cfg.blockDim = dim3(384);
    cfg.dynamicSmemBytes = SMEM_BYTES;
    cfg.stream = cudaStreamPerThread;
    cudaLaunchAttribute at[1];
    at[0].id = cudaLaunchAttributeClusterDimension;
    at[0].val.clusterDim.x = 2; at[0].val.clusterDim.y = 1; at[0].val.clusterDim.z = 1;
    cfg.attrs = at;
    cfg.numAttrs = MC ? 1 : 0;
    cudaLaunchKernelEx(&cfg, fused_kernel, maps, (const __nv_bfloat16*)d_in[0], (const __nv_bfloat16*)d_in[7], wqkv, wg, wu, wd, wo, (__nv_bfloat16*)d_out);
}
```

```cpp
#include <cuda_runtime.h>
#include <cuda.h>
#include <cuda_bf16.h>
#include <stdint.h>

#define MC 0
#define PFMODE 1
#define PHI_SAT 0
#define PROF 0

namespace {

constexpr int kD = 512;
constexpr uint32_t OFF_X = 0, OFF_STG = 131072, OFF_RING = 147456, OFF_MISC = 229376;
constexpr uint32_t B_FULL = OFF_MISC, B_EMPTY = OFF_MISC + 40, B_XFULL = OFF_MISC + 80;
constexpr uint32_t B_GRDY = OFF_MISC + 152, B_KVDONE = OFF_MISC + 160, B_KVRDY = OFF_MISC + 168;
constexpr uint32_t B_HSENT = OFF_MISC + 176, B_XFREE = OFF_MISC + 200;
constexpr uint32_t OFF_EPOCH = OFF_MISC + 240, OFF_G = OFF_MISC + 256;
constexpr uint32_t B_AHEAD = OFF_MISC + 248, B_PART = OFF_MISC + 232;
constexpr uint32_t OFF_ONES = OFF_MISC + 768;
constexpr uint32_t B_EFULL = OFF_MISC + 896, B_EEMPTY = OFF_MISC + 928;
constexpr uint32_t SMEM_BYTES = OFF_MISC + 960;
constexpr uint32_t SPIN_GLOBAL = 1u << 14;

struct alignas(64) Maps { CUtensorMap x, gu, kv, q64, gu64, wdw, wow, wdp, wdph, hx, hx2; };

}

__device__ uint4 g_part[16 * 2 * 4 * 4 * 1024];
__device__ uint4 g_hx[16 * 4 * 5 * 1024];
__device__ uint4 g_lx[16 * 8 * 2 * 1024];
__device__ unsigned g_hflag[128 * 8];
__device__ uint4 g_gx[16 * 32];
__device__ float g_kvacc[2 * 8 * 4 * 272];
__device__ unsigned g_kvcnt[8 * 32];
__device__ unsigned g_epoch[128];
#define TS(role, idx)
#define TS2(idx)
#define TSG(role, idx)

namespace {

__device__ __forceinline__ void mbar_init(uint32_t bar, uint32_t cnt) { asm volatile("mbarrier.init.shared::cta.b64 [%0], %1;" :: "r"(bar), "r"(cnt) : "memory"); }
__device__ __forceinline__ void mbar_expect(uint32_t bar, uint32_t bytes) { asm volatile("mbarrier.arrive.expect_tx.shared::cta.b64 _, [%0], %1;" :: "r"(bar), "r"(bytes) : "memory"); }
__device__ __forceinline__ void mbar_arrive(uint32_t bar) { asm volatile("mbarrier.arrive.shared::cta.b64 _, [%0];" :: "r"(bar) : "memory"); }
__device__ __forceinline__ void mbar_arrive_cta(uint32_t bar, uint32_t cta) {
    asm volatile("{\n.reg .b32 ra;\nmapa.shared::cluster.u32 ra, %0, %1;\nmbarrier.arrive.shared::cluster.b64 _, [ra];\n}" :: "r"(bar), "r"(cta) : "memory");
}
__device__ __forceinline__ void mbar_wait(uint32_t bar, uint32_t parity) {
    asm volatile("{\n.reg .pred p;\n.reg .u32 c;\n"
                 "mbarrier.try_wait.parity.shared::cta.b64 p, [%0], %1;\n@p bra DONE;\n"
                 "mov.u32 c, 0;\nLAB_WAIT:\nmbarrier.try_wait.parity.shared::cta.b64 p, [%0], %1;\n@p bra DONE;\n"
                 "add.u32 c, c, 1;\nsetp.lt.u32 p, c, 65536;\n@p bra LAB_WAIT;\nDONE:\n}" :: "r"(bar), "r"(parity) : "memory");
}
__device__ __forceinline__ void tma2(uint32_t dst, const CUtensorMap* m, int c0, int c1, uint32_t bar) {
    asm volatile("cp.async.bulk.tensor.2d.shared::cluster.global.mbarrier::complete_tx::bytes [%0], [%1, {%3, %4}], [%2];"
        :: "r"(dst), "l"(m), "r"(bar), "r"(c0), "r"(c1) : "memory");
}
__device__ __forceinline__ void tmaw2(uint32_t dst, const CUtensorMap* m, int c0, int c1, uint32_t bar) {
    tma2(dst, m, c0, c1, bar);
}
__device__ __forceinline__ void tmaw3(uint32_t dst, const CUtensorMap* m, int c0, int c1, int c2, uint32_t bar) {
    asm volatile("cp.async.bulk.tensor.3d.shared::cluster.global.mbarrier::complete_tx::bytes [%0], [%1, {%3, %4, %5}], [%2];"
        :: "r"(dst), "l"(m), "r"(bar), "r"(c0), "r"(c1), "r"(c2) : "memory");
}
__device__ __forceinline__ void tmaw5(uint32_t dst, const CUtensorMap* m, int c0, int c4, uint32_t bar) {
    asm volatile("cp.async.bulk.tensor.5d.shared::cluster.global.mbarrier::complete_tx::bytes [%0], [%1, {%3, %5, %5, %5, %4}], [%2];"
        :: "r"(dst), "l"(m), "r"(bar), "r"(c0), "r"(c4), "r"(0) : "memory");
}
__device__ __forceinline__ void wg_fence() { asm volatile("wgmma.fence.sync.aligned;" ::: "memory"); }
__device__ __forceinline__ void wg_commit() { asm volatile("wgmma.commit_group.sync.aligned;" ::: "memory"); }
template <int N> __device__ __forceinline__ void wg_wait() { asm volatile("wgmma.wait_group.sync.aligned %0;" :: "n"(N) : "memory"); }
template <int N> __device__ __forceinline__ void pin(float (&d)[N]) {
#pragma unroll
    for (int i = 0; i < N; i++) asm volatile("" : "+f"(d[i]) :: "memory");
}
__device__ __forceinline__ uint32_t pack2(float lo, float hi) { uint32_t r; asm("cvt.rn.bf16x2.f32 %0, %1, %2;" : "=r"(r) : "f"(hi), "f"(lo)); return r; }
__device__ __forceinline__ uint32_t keep(uint32_t v) { asm volatile("" : "+r"(v)); return v; }
__device__ __forceinline__ uint32_t hadd2(uint32_t a, uint32_t b) { uint32_t r; asm("add.bf16x2 %0, %1, %2;" : "=r"(r) : "r"(a), "r"(b)); return r; }
__device__ __forceinline__ uint32_t hmul2(uint32_t a, uint32_t b) { uint32_t r; asm("mul.bf16x2 %0, %1, %2;" : "=r"(r) : "r"(a), "r"(b)); return r; }
__device__ __forceinline__ uint32_t phi2(float t0, float t1) {
    float e0, e1;
    asm("ex2.approx.ftz.f32 %0, %1;" : "=f"(e0) : "f"(t0 * 1.4426950408889634f));
    asm("ex2.approx.ftz.f32 %0, %1;" : "=f"(e1) : "f"(t1 * 1.4426950408889634f));
    uint32_t e = pack2(e0, e1), t = pack2(t0, t1), r;
    asm("min.bf16x2 %0, %0, %1;" : "+r"(e) : "r"(0x3f803f80u));
    asm("max.bf16x2 %0, %0, %1;" : "+r"(t) : "r"(0x35863586u));
    asm("add.bf16x2 %0, %1, %2;" : "=r"(r) : "r"(e), "r"(t));
    return r;
}
__device__ __forceinline__ void stsm4(uint32_t a, uint32_t r0, uint32_t r1, uint32_t r2, uint32_t r3) {
    asm volatile("stmatrix.sync.aligned.m8n8.x4.shared.b16 [%0], {%1,%2,%3,%4};" :: "r"(a), "r"(r0), "r"(r1), "r"(r2), "r"(r3) : "memory");
}
__device__ __forceinline__ float bf_lo(uint32_t w) { return __uint_as_float(w << 16); }
__device__ __forceinline__ float bf_hi(uint32_t w) { return __uint_as_float(w & 0xffff0000u); }
__device__ __forceinline__ void st_pkt(uint4* p, uint32_t w0, uint32_t w1, uint32_t w2, uint32_t w3) {
    asm volatile("{\n.reg .b64 lo, hi;\n.reg .b128 v;\nmov.b64 lo, {%1, %2};\nmov.b64 hi, {%3, %4};\nmov.b128 v, {lo, hi};\nst.relaxed.gpu.global.b128 [%0], v;\n}"
        :: "l"(p), "r"(w0), "r"(w1), "r"(w2), "r"(w3) : "memory");
}
__device__ __forceinline__ void ld_pkt(const uint4* p, uint32_t& w0, uint32_t& w1, uint32_t& w2, uint32_t& w3) {
    asm volatile("{\n.reg .b64 lo, hi;\n.reg .b128 v;\nld.relaxed.gpu.global.b128 v, [%4];\nmov.b128 {lo, hi}, v;\nmov.b64 {%0, %1}, lo;\nmov.b64 {%2, %3}, hi;\n}"
        : "=r"(w0), "=r"(w1), "=r"(w2), "=r"(w3) : "l"(p) : "memory");
}

template <uint32_t AO, uint32_t BO, uint32_t BH> __device__ __forceinline__ void wg_ss128(float (&d)[64], uint32_t ab, uint32_t bb) {
    asm volatile("{\n.reg .b64 da, db;\n.reg .b32 ta, tb, th, ah;\nadd.u32 ta, %64, %66;\nadd.u32 tb, %65, %67;\nmov.b32 th, %68;\nmov.b32 ah, 0x40000040;\nmov.b64 da, {ta, ah};\nmov.b64 db, {tb, th};\n"
        "wgmma.mma_async.sync.aligned.m64n128k16.f32.bf16.bf16 {%0,%1,%2,%3,%4,%5,%6,%7,%8,%9,%10,%11,%12,%13,%14,%15,%16,%17,%18,%19,%20,%21,%22,%23,%24,%25,%26,%27,%28,%29,%30,%31,%32,%33,%34,%35,%36,%37,%38,%39,%40,%41,%42,%43,%44,%45,%46,%47,%48,%49,%50,%51,%52,%53,%54,%55,%56,%57,%58,%59,%60,%61,%62,%63}, da, db, 1, 1, 1, 0, 1;\n}\n"
        : "+f"(d[0]),"+f"(d[1]),"+f"(d[2]),"+f"(d[3]),"+f"(d[4]),"+f"(d[5]),"+f"(d[6]),"+f"(d[7]),"+f"(d[8]),"+f"(d[9]),"+f"(d[10]),"+f"(d[11]),"+f"(d[12]),"+f"(d[13]),"+f"(d[14]),"+f"(d[15]),"+f"(d[16]),"+f"(d[17]),"+f"(d[18]),"+f"(d[19]),"+f"(d[20]),"+f"(d[21]),"+f"(d[22]),"+f"(d[23]),"+f"(d[24]),"+f"(d[25]),"+f"(d[26]),"+f"(d[27]),"+f"(d[28]),"+f"(d[29]),"+f"(d[30]),"+f"(d[31]),"+f"(d[32]),"+f"(d[33]),"+f"(d[34]),"+f"(d[35]),"+f"(d[36]),"+f"(d[37]),"+f"(d[38]),"+f"(d[39]),"+f"(d[40]),"+f"(d[41]),"+f"(d[42]),"+f"(d[43]),"+f"(d[44]),"+f"(d[45]),"+f"(d[46]),"+f"(d[47]),"+f"(d[48]),"+f"(d[49]),"+f"(d[50]),"+f"(d[51]),"+f"(d[52]),"+f"(d[53]),"+f"(d[54]),"+f"(d[55]),"+f"(d[56]),"+f"(d[57]),"+f"(d[58]),"+f"(d[59]),"+f"(d[60]),"+f"(d[61]),"+f"(d[62]),"+f"(d[63])
        : "r"(ab), "r"(bb), "n"(AO), "n"(BO), "n"(BH));
}
template <uint32_t AO, uint32_t BO, uint32_t BH> __device__ __forceinline__ void wg_ss128_z(float (&d)[64], uint32_t ab, uint32_t bb) {
    asm volatile("{\n.reg .b64 da, db;\n.reg .b32 ta, tb, th, ah;\nadd.u32 ta, %64, %66;\nadd.u32 tb, %65, %67;\nmov.b32 th, %68;\nmov.b32 ah, 0x40000040;\nmov.b64 da, {ta, ah};\nmov.b64 db, {tb, th};\n"
        "wgmma.mma_async.sync.aligned.m64n128k16.f32.bf16.bf16 {%0,%1,%2,%3,%4,%5,%6,%7,%8,%9,%10,%11,%12,%13,%14,%15,%16,%17,%18,%19,%20,%21,%22,%23,%24,%25,%26,%27,%28,%29,%30,%31,%32,%33,%34,%35,%36,%37,%38,%39,%40,%41,%42,%43,%44,%45,%46,%47,%48,%49,%50,%51,%52,%53,%54,%55,%56,%57,%58,%59,%60,%61,%62,%63}, da, db, 0, 1, 1, 0, 1;\n}\n"
        : "=f"(d[0]),"=f"(d[1]),"=f"(d[2]),"=f"(d[3]),"=f"(d[4]),"=f"(d[5]),"=f"(d[6]),"=f"(d[7]),"=f"(d[8]),"=f"(d[9]),"=f"(d[10]),"=f"(d[11]),"=f"(d[12]),"=f"(d[13]),"=f"(d[14]),"=f"(d[15]),"=f"(d[16]),"=f"(d[17]),"=f"(d[18]),"=f"(d[19]),"=f"(d[20]),"=f"(d[21]),"=f"(d[22]),"=f"(d[23]),"=f"(d[24]),"=f"(d[25]),"=f"(d[26]),"=f"(d[27]),"=f"(d[28]),"=f"(d[29]),"=f"(d[30]),"=f"(d[31]),"=f"(d[32]),"=f"(d[33]),"=f"(d[34]),"=f"(d[35]),"=f"(d[36]),"=f"(d[37]),"=f"(d[38]),"=f"(d[39]),"=f"(d[40]),"=f"(d[41]),"=f"(d[42]),"=f"(d[43]),"=f"(d[44]),"=f"(d[45]),"=f"(d[46]),"=f"(d[47]),"=f"(d[48]),"=f"(d[49]),"=f"(d[50]),"=f"(d[51]),"=f"(d[52]),"=f"(d[53]),"=f"(d[54]),"=f"(d[55]),"=f"(d[56]),"=f"(d[57]),"=f"(d[58]),"=f"(d[59]),"=f"(d[60]),"=f"(d[61]),"=f"(d[62]),"=f"(d[63])
        : "r"(ab), "r"(bb), "n"(AO), "n"(BO), "n"(BH));
}
template <uint32_t BO, uint32_t BH> __device__ __forceinline__ void wg_rs128(float (&d)[64], uint32_t a0, uint32_t a1, uint32_t a2, uint32_t a3, uint32_t bb) {
    asm volatile("{\n.reg .b64 db;\n.reg .b32 tb, th;\nadd.u32 tb, %68, %69;\nmov.b32 th, %70;\nmov.b64 db, {tb, th};\n"
        "wgmma.mma_async.sync.aligned.m64n128k16.f32.bf16.bf16 {%0,%1,%2,%3,%4,%5,%6,%7,%8,%9,%10,%11,%12,%13,%14,%15,%16,%17,%18,%19,%20,%21,%22,%23,%24,%25,%26,%27,%28,%29,%30,%31,%32,%33,%34,%35,%36,%37,%38,%39,%40,%41,%42,%43,%44,%45,%46,%47,%48,%49,%50,%51,%52,%53,%54,%55,%56,%57,%58,%59,%60,%61,%62,%63}, {%64,%65,%66,%67}, db, 1, 1, 1, 1;\n}\n"
        : "+f"(d[0]),"+f"(d[1]),"+f"(d[2]),"+f"(d[3]),"+f"(d[4]),"+f"(d[5]),"+f"(d[6]),"+f"(d[7]),"+f"(d[8]),"+f"(d[9]),"+f"(d[10]),"+f"(d[11]),"+f"(d[12]),"+f"(d[13]),"+f"(d[14]),"+f"(d[15]),"+f"(d[16]),"+f"(d[17]),"+f"(d[18]),"+f"(d[19]),"+f"(d[20]),"+f"(d[21]),"+f"(d[22]),"+f"(d[23]),"+f"(d[24]),"+f"(d[25]),"+f"(d[26]),"+f"(d[27]),"+f"(d[28]),"+f"(d[29]),"+f"(d[30]),"+f"(d[31]),"+f"(d[32]),"+f"(d[33]),"+f"(d[34]),"+f"(d[35]),"+f"(d[36]),"+f"(d[37]),"+f"(d[38]),"+f"(d[39]),"+f"(d[40]),"+f"(d[41]),"+f"(d[42]),"+f"(d[43]),"+f"(d[44]),"+f"(d[45]),"+f"(d[46]),"+f"(d[47]),"+f"(d[48]),"+f"(d[49]),"+f"(d[50]),"+f"(d[51]),"+f"(d[52]),"+f"(d[53]),"+f"(d[54]),"+f"(d[55]),"+f"(d[56]),"+f"(d[57]),"+f"(d[58]),"+f"(d[59]),"+f"(d[60]),"+f"(d[61]),"+f"(d[62]),"+f"(d[63])
        : "r"(a0), "r"(a1), "r"(a2), "r"(a3), "r"(bb), "n"(BO), "n"(BH));
}
template <uint32_t BO, uint32_t BH> __device__ __forceinline__ void wg_rs128_z(float (&d)[64], uint32_t a0, uint32_t a1, uint32_t a2, uint32_t a3, uint32_t bb) {
    asm volatile("{\n.reg .b64 db;\n.reg .b32 tb, th;\nadd.u32 tb, %68, %69;\nmov.b32 th, %70;\nmov.b64 db, {tb, th};\n"
        "wgmma.mma_async.sync.aligned.m64n128k16.f32.bf16.bf16 {%0,%1,%2,%3,%4,%5,%6,%7,%8,%9,%10,%11,%12,%13,%14,%15,%16,%17,%18,%19,%20,%21,%22,%23,%24,%25,%26,%27,%28,%29,%30,%31,%32,%33,%34,%35,%36,%37,%38,%39,%40,%41,%42,%43,%44,%45,%46,%47,%48,%49,%50,%51,%52,%53,%54,%55,%56,%57,%58,%59,%60,%61,%62,%63}, {%64,%65,%66,%67}, db, 0, 1, 1, 1;\n}\n"
        : "=f"(d[0]),"=f"(d[1]),"=f"(d[2]),"=f"(d[3]),"=f"(d[4]),"=f"(d[5]),"=f"(d[6]),"=f"(d[7]),"=f"(d[8]),"=f"(d[9]),"=f"(d[10]),"=f"(d[11]),"=f"(d[12]),"=f"(d[13]),"=f"(d[14]),"=f"(d[15]),"=f"(d[16]),"=f"(d[17]),"=f"(d[18]),"=f"(d[19]),"=f"(d[20]),"=f"(d[21]),"=f"(d[22]),"=f"(d[23]),"=f"(d[24]),"=f"(d[25]),"=f"(d[26]),"=f"(d[27]),"=f"(d[28]),"=f"(d[29]),"=f"(d[30]),"=f"(d[31]),"=f"(d[32]),"=f"(d[33]),"=f"(d[34]),"=f"(d[35]),"=f"(d[36]),"=f"(d[37]),"=f"(d[38]),"=f"(d[39]),"=f"(d[40]),"=f"(d[41]),"=f"(d[42]),"=f"(d[43]),"=f"(d[44]),"=f"(d[45]),"=f"(d[46]),"=f"(d[47]),"=f"(d[48]),"=f"(d[49]),"=f"(d[50]),"=f"(d[51]),"=f"(d[52]),"=f"(d[53]),"=f"(d[54]),"=f"(d[55]),"=f"(d[56]),"=f"(d[57]),"=f"(d[58]),"=f"(d[59]),"=f"(d[60]),"=f"(d[61]),"=f"(d[62]),"=f"(d[63])
        : "r"(a0), "r"(a1), "r"(a2), "r"(a3), "r"(bb), "n"(BO), "n"(BH));
}
template <uint32_t AO, uint32_t BO, uint32_t BH> __device__ __forceinline__ void wg_ss64t(float (&d)[32], uint32_t ab, uint32_t bb) {
    asm volatile("{\n.reg .b64 da, db;\n.reg .b32 ta, tb, th, ah;\nadd.u32 ta, %32, %34;\nadd.u32 tb, %33, %35;\nmov.b32 th, %36;\nmov.b32 ah, 0x40000040;\nmov.b64 da, {ta, ah};\nmov.b64 db, {tb, th};\n"
        "wgmma.mma_async.sync.aligned.m64n64k16.f32.bf16.bf16 {%0,%1,%2,%3,%4,%5,%6,%7,%8,%9,%10,%11,%12,%13,%14,%15,%16,%17,%18,%19,%20,%21,%22,%23,%24,%25,%26,%27,%28,%29,%30,%31}, da, db, 1, 1, 1, 1, 1;\n}\n"
        : "+f"(d[0]),"+f"(d[1]),"+f"(d[2]),"+f"(d[3]),"+f"(d[4]),"+f"(d[5]),"+f"(d[6]),"+f"(d[7]),"+f"(d[8]),"+f"(d[9]),"+f"(d[10]),"+f"(d[11]),"+f"(d[12]),"+f"(d[13]),"+f"(d[14]),"+f"(d[15]),"+f"(d[16]),"+f"(d[17]),"+f"(d[18]),"+f"(d[19]),"+f"(d[20]),"+f"(d[21]),"+f"(d[22]),"+f"(d[23]),"+f"(d[24]),"+f"(d[25]),"+f"(d[26]),"+f"(d[27]),"+f"(d[28]),"+f"(d[29]),"+f"(d[30]),"+f"(d[31])
        : "r"(ab), "r"(bb), "n"(AO), "n"(BO), "n"(BH));
}
template <uint32_t AO, uint32_t BO, uint32_t BH> __device__ __forceinline__ void wg_ss64t_z(float (&d)[32], uint32_t ab, uint32_t bb) {
    asm volatile("{\n.reg .b64 da, db;\n.reg .b32 ta, tb, th, ah;\nadd.u32 ta, %32, %34;\nadd.u32 tb, %33, %35;\nmov.b32 th, %36;\nmov.b32 ah, 0x40000040;\nmov.b64 da, {ta, ah};\nmov.b64 db, {tb, th};\n"
        "wgmma.mma_async.sync.aligned.m64n64k16.f32.bf16.bf16 {%0,%1,%2,%3,%4,%5,%6,%7,%8,%9,%10,%11,%12,%13,%14,%15,%16,%17,%18,%19,%20,%21,%22,%23,%24,%25,%26,%27,%28,%29,%30,%31}, da, db, 0, 1, 1, 1, 1;\n}\n"
        : "=f"(d[0]),"=f"(d[1]),"=f"(d[2]),"=f"(d[3]),"=f"(d[4]),"=f"(d[5]),"=f"(d[6]),"=f"(d[7]),"=f"(d[8]),"=f"(d[9]),"=f"(d[10]),"=f"(d[11]),"=f"(d[12]),"=f"(d[13]),"=f"(d[14]),"=f"(d[15]),"=f"(d[16]),"=f"(d[17]),"=f"(d[18]),"=f"(d[19]),"=f"(d[20]),"=f"(d[21]),"=f"(d[22]),"=f"(d[23]),"=f"(d[24]),"=f"(d[25]),"=f"(d[26]),"=f"(d[27]),"=f"(d[28]),"=f"(d[29]),"=f"(d[30]),"=f"(d[31])
        : "r"(ab), "r"(bb), "n"(AO), "n"(BO), "n"(BH));
}
template <uint32_t AO, uint32_t BO, uint32_t BH> __device__ __forceinline__ void wg_ss8t(float (&d)[4], uint32_t ab, uint32_t bb) {
    asm volatile("{\n.reg .b64 da, db;\n.reg .b32 ta, tb, th, ah;\nadd.u32 ta, %4, %6;\nadd.u32 tb, %5, %7;\nmov.b32 th, %8;\nmov.b32 ah, 0x40000040;\nmov.b64 da, {ta, ah};\nmov.b64 db, {tb, th};\n"
        "wgmma.mma_async.sync.aligned.m64n8k16.f32.bf16.bf16 {%0,%1,%2,%3}, da, db, 1, 1, 1, 1, 0;\n}\n"
        : "+f"(d[0]),"+f"(d[1]),"+f"(d[2]),"+f"(d[3])
        : "r"(ab), "r"(bb), "n"(AO), "n"(BO), "n"(BH));
}
template <uint32_t AO, uint32_t BO, uint32_t BH> __device__ __forceinline__ void wg_ss8t_z(float (&d)[4], uint32_t ab, uint32_t bb) {
    asm volatile("{\n.reg .b64 da, db;\n.reg .b32 ta, tb, th, ah;\nadd.u32 ta, %4, %6;\nadd.u32 tb, %5, %7;\nmov.b32 th, %8;\nmov.b32 ah, 0x40000040;\nmov.b64 da, {ta, ah};\nmov.b64 db, {tb, th};\n"
        "wgmma.mma_async.sync.aligned.m64n8k16.f32.bf16.bf16 {%0,%1,%2,%3}, da, db, 0, 1, 1, 1, 0;\n}\n"
        : "=f"(d[0]),"=f"(d[1]),"=f"(d[2]),"=f"(d[3])
        : "r"(ab), "r"(bb), "n"(AO), "n"(BO), "n"(BH));
}
template <uint32_t BO, uint32_t BH> __device__ __forceinline__ void wg_rs24_z(float (&d)[12], uint32_t a0, uint32_t a1, uint32_t a2, uint32_t a3, uint32_t bb) {
    asm volatile("{\n.reg .b64 db;\n.reg .b32 tb, th;\nadd.u32 tb, %16, %17;\nmov.b32 th, %18;\nmov.b64 db, {tb, th};\n"
        "wgmma.mma_async.sync.aligned.m64n24k16.f32.bf16.bf16 {%0,%1,%2,%3,%4,%5,%6,%7,%8,%9,%10,%11}, {%12,%13,%14,%15}, db, 0, 1, 1, 0;\n}\n"
        : "=f"(d[0]),"=f"(d[1]),"=f"(d[2]),"=f"(d[3]),"=f"(d[4]),"=f"(d[5]),"=f"(d[6]),"=f"(d[7]),"=f"(d[8]),"=f"(d[9]),"=f"(d[10]),"=f"(d[11])
        : "r"(a0), "r"(a1), "r"(a2), "r"(a3), "r"(bb), "n"(BO), "n"(BH));
}

constexpr uint32_t DH128 = 64u | 0x40000000u;
constexpr uint32_t DH64 = 32u | 0x80000000u;
constexpr uint32_t LBO4K = (4096u >> 4) << 16, LBO8K = (8192u >> 4) << 16, LBO1 = 1u << 16;

template <uint32_t AO, uint32_t BO, bool SW64, bool FIRST> __device__ __forceinline__ void stage_ss(float (&acc)[64], uint32_t ab, uint32_t bb) {
    constexpr uint32_t KS = SW64 ? 64 : 128, BH = SW64 ? DH64 : DH128, B0 = BO + (SW64 ? LBO4K : LBO8K);
    wg_fence();
    if (FIRST) wg_ss128_z<AO, B0, BH>(acc, ab, bb); else wg_ss128<AO, B0, BH>(acc, ab, bb);
    wg_ss128<AO + 2, B0 + KS, BH>(acc, ab, bb);
    wg_ss128<AO + 4, B0 + 2 * KS, BH>(acc, ab, bb);
    wg_ss128<AO + 6, B0 + 3 * KS, BH>(acc, ab, bb);
    wg_commit();
}
template <uint32_t BO, bool FIRST> __device__ __forceinline__ void stage_rs(float (&acc)[64], const uint32_t (&f)[16], uint32_t bb) {
    wg_fence();
    if (FIRST) wg_rs128_z<BO + LBO8K, DH128>(acc, f[0], f[1], f[2], f[3], bb); else wg_rs128<BO + LBO8K, DH128>(acc, f[0], f[1], f[2], f[3], bb);
    wg_rs128<BO + LBO8K + 128, DH128>(acc, f[4], f[5], f[6], f[7], bb);
    wg_rs128<BO + LBO8K + 256, DH128>(acc, f[8], f[9], f[10], f[11], bb);
    wg_rs128<BO + LBO8K + 384, DH128>(acc, f[12], f[13], f[14], f[15], bb);
    wg_commit();
}

template <int N> __device__ __forceinline__ void stash(uint32_t base, uint32_t sw, const uint32_t (&f)[N]) {
#pragma unroll
    for (int t = 0; t < N / 4; t++) stsm4(base + ((sw ^ (2 * t)) << 4), f[4 * t], f[4 * t + 1], f[4 * t + 2], f[4 * t + 3]);
}

template <int V0, int V1, int N> __device__ __forceinline__ void send_frag(const uint32_t (&f)[N], uint4* p, uint32_t tag) {
#pragma unroll
    for (int v = V0; v < V1; v++) st_pkt(p + v * 32, (f[4 * v] & ~1u) | tag, f[4 * v + 1], f[4 * v + 2], f[4 * v + 3]);
}
template <int V0, int V1, int N> __device__ __forceinline__ void send_h(const uint32_t (&f)[N], uint4* p) {
#pragma unroll
    for (int v = V0; v < V1; v++) {
        const int h = v >> 1, hi = v & 1;
        asm volatile("st.global.v4.u32 [%0], {%1,%2,%3,%4};" :: "l"(p + 4 * h + 64 * hi),
                     "r"(f[8 * h + hi]), "r"(f[8 * h + 2 + hi]), "r"(f[8 * h + 4 + hi]), "r"(f[8 * h + 6 + hi]) : "memory");
    }
}
template <int O, int N, int M> __device__ __forceinline__ void pack_sub(uint32_t (&f)[N], const float (&acc)[M]) {
#pragma unroll
    for (int i = 0; i < N; i++) f[i] = keep(pack2(acc[O + 2 * i], acc[O + 2 * i + 1]));
}
template <int N> __device__ __forceinline__ void recv_issue(uint32_t (&q)[N], const uint4* p) {
#pragma unroll
    for (int v = 0; v < N / 4; v++) ld_pkt(p + v * 32, q[4 * v], q[4 * v + 1], q[4 * v + 2], q[4 * v + 3]);
}
template <int N> __device__ __forceinline__ void recv_check(uint32_t (&q)[N], const uint4* p, uint32_t tag) {
    uint32_t it = 0;
    while (true) {
        uint32_t bad = 0;
#pragma unroll
        for (int v = 0; v < N / 4; v++) bad |= q[4 * v] ^ tag;
        if (__all_sync(0xffffffffu, (bad & 1u) == 0) || ++it > SPIN_GLOBAL) break;
        recv_issue(q, p);
    }
}
__device__ __forceinline__ void accum(const uint32_t (&q)[32], float (&sum)[64]) {
#pragma unroll
    for (int i = 0; i < 32; i++) { sum[2 * i] += bf_lo(q[i]); sum[2 * i + 1] += bf_hi(q[i]); }
}

}

__global__ void __launch_bounds__(384, 1)
fused_kernel(const __grid_constant__ Maps maps, const __nv_bfloat16* __restrict__ xg, const __nv_bfloat16* __restrict__ gate_w,
             const char* __restrict__ pf_qkv, const char* __restrict__ pf_g, const char* __restrict__ pf_u,
             const char* __restrict__ pf_d, const char* __restrict__ pf_o, __nv_bfloat16* __restrict__ out) {
    extern __shared__ __align__(1024) uint8_t smem_raw[];
    const uint32_t sb = (uint32_t)__cvta_generic_to_shared(smem_raw);
    const int tid = threadIdx.x, lane = tid & 31;
    const int warp = __shfl_sync(0xffffffffu, tid >> 5, 0);
    const int j = (blockIdx.x >> 1) & 7;
    const int r = ((blockIdx.x >> 4) << 1) | (blockIdx.x & 1);
    const uint32_t rank = blockIdx.x & 1;

    if (warp == 0) { TSG(0, 30); TS(0, 0); }
    if (tid == 256) {
        for (int i = 0; i < 5; i++) { mbar_init(sb + B_FULL + 8 * i, 1); mbar_init(sb + B_EMPTY + 8 * i, MC ? 4 : 2); }
        for (int i = 0; i < 9; i++) mbar_init(sb + B_XFULL + 8 * i, 1);
        asm volatile("fence.mbarrier_init.release.cluster;" ::: "memory");
        mbar_expect(sb + B_XFULL, 16384);
        tma2(sb + OFF_X, &maps.x, 0, r * 128, sb + B_XFULL);
        TS2(0);
        mbar_expect(sb + B_FULL, 16384);
        tmaw3(sb + OFF_RING, &maps.kv, 64 * j, 0, 1, sb + B_FULL);
        TS2(1);
        mbar_expect(sb + B_FULL + 8, 16384);
        tmaw3(sb + OFF_RING + 16384, &maps.gu, 224 * j, 0, 0, sb + B_FULL + 8);
    } else if (tid == 288) {
        for (int i = 0; i < 3; i++) mbar_init(sb + B_HSENT + 8 * i, 8);
        for (int i = 0; i < 4; i++) { mbar_init(sb + B_EFULL + 8 * i, 1); mbar_init(sb + B_EEMPTY + 8 * i, MC ? 4 : 2); }
        mbar_init(sb + B_XFREE, 2); mbar_init(sb + B_XFREE + 8, 2); mbar_init(sb + B_XFREE + 16, 2);
        mbar_init(sb + B_AHEAD, 1); mbar_init(sb + B_PART, 1); mbar_init(sb + B_GRDY, 1); mbar_init(sb + B_KVDONE, 8); mbar_init(sb + B_KVRDY, 2);
        asm volatile("fence.mbarrier_init.release.cluster;" ::: "memory");
    } else if (warp == 10 && lane < 10) {
        asm volatile("prefetch.tensormap [%0];" :: "l"(&maps.gu + lane) : "memory");
    }
    __syncthreads();

    if (warp >= 8) {
        asm volatile("setmaxnreg.dec.sync.aligned.u32 56;");
        if (warp == 8) {
            if (lane == 0) {
                int slot = MC ? 0 : 2, ph = 1;
                uint32_t full, dst;
                if (!MC) { mbar_expect(sb + B_XFULL + 8, 16384); tma2(sb + OFF_X + 16384, &maps.x, 64, r * 128, sb + B_XFULL + 8); }
#define P_BEGIN(S, BYTES) full = sb + B_FULL + 8 * slot; dst = sb + OFF_RING + slot * 16384; \
                mbar_wait(sb + B_EMPTY + 8 * slot, ph); TS2(S); mbar_expect(full, BYTES); if (!MC || (((S) ^ rank) & 1) == 0)
#define P_END() if (++slot == 5) { slot = 0; ph ^= 1; }
                for (int s = MC ? 0 : 2; s < 16; s++) {
                    const int kb = (int)(0x7654763542312100ull >> (4 * s)) & 15;
                    P_BEGIN(s, 16384) {
                        if ((0x0DADu >> s) & 1) tmaw3(dst, &maps.kv, 64 * j, 64 * kb, 1, full);
                        else tmaw3(dst, &maps.gu, 224 * j, 64 * kb, 0, full);
                    }
                    const int xb = (int)(0x0000000765403210ull >> (4 * s)) & 15;
                    if (xb) { mbar_expect(sb + B_XFULL + 8 * xb, 16384); tma2(sb + OFF_X + xb * 16384, &maps.x, 64 * xb, r * 128, sb + B_XFULL + 8 * xb); }
                    P_END()
                }
                for (int s = 0; s < 24; s++) {
                    P_BEGIN(16 + s, 16384) {
                        if (s < 8) {
                            tmaw3(dst, &maps.q64, 0, 64 * s, 2 * j, full);
                            tmaw3(dst + 8192, &maps.gu64, 224 * j + 192, 64 * s, 0, full);
                        } else {
                            tmaw3(dst, &maps.gu, 224 * j + 64 * (s >> 3), 64 * (s & 7), 0, full);
                        }
                    }
                    P_END()
                }
                const int p = j >> 1;
#pragma unroll 1
                for (int t = 0; t < 18; t++) {
                    const int q = t >= 9, sl = (int)(0x846352107ull >> (4 * (t - 9 * q))) & 15;
                    const int u = (int)((q ? 0x432186758ull : 0x327064105ull) >> (4 * (t - 9 * q))) & 15;
                    const int cw = (j & 1) * 4 + ((p & 2) ^ ((t == 5 || t > 9) ? 0 : 2)), cc = 64 * cw;
                    if (sl < 5) {
                        full = sb + B_FULL + 8 * sl; dst = sb + OFF_RING + sl * 16384;
                        mbar_wait(sb + B_EMPTY + 8 * sl, q ^ 1);
                    } else {
                        full = sb + B_EFULL + 8 * (sl - 5); dst = sb + OFF_X + (sl == 7 ? 8 : sl == 8 ? 7 : sl) * 16384;
                        mbar_wait(sb + B_EEMPTY + 8 * (sl - 5), q);
                    }
                    TS2(40 + t);
                    mbar_expect(full, 16384);
                    if (!MC || ((t ^ rank) & 1) == 0) {
                        if (u == 4) {
                            tmaw5(dst, &maps.wdph, cc, 14 * p + 6, full); tmaw5(dst + 4096, &maps.wdph, cc, 14 * p + 13, full);
                            tmaw5(dst + 8192, &maps.wdph, cc + 64, 14 * p + 6, full); tmaw5(dst + 12288, &maps.wdph, cc + 64, 14 * p + 13, full);
                        } else if (u > 4) {
                            const int js = u > 6 ? j ^ 1 : j;
                            tmaw3(dst, (u & 1) ? &maps.wow : &maps.wdw, 0, (u & 1) ? 64 * js : 224 * js + 128, cw, full);
                        } else {
                            const int g = 14 * p + 7 * (u & 1) + (u & 2);
                            tmaw5(dst, &maps.wdp, cc, g, full); tmaw5(dst + 8192, &maps.wdp, cc + 64, g, full);
                        }
                    }
                }
            }
        } else if (warp < 11) {
            const int hx = warp - 9;
            uint32_t epoch;
            asm volatile("ld.relaxed.gpu.global.u32 %0, [%1];" : "=r"(epoch) : "l"(g_epoch + blockIdx.x) : "memory");
            {
                const uint4* xr = (const uint4*)(xg + (size_t)(r * 128 + j * 16 + hx * 8) * kD) + lane;
                const uint4 wa = __ldg((const uint4*)gate_w + lane), wb = __ldg((const uint4*)gate_w + 32 + lane);
                const uint32_t tag = (epoch + 1) & 1;
                uint4* gp = g_gx + r * 32;
                if (lane < 2) st_pkt(gp + j * 4 + hx * 2 + lane, tag ^ 1, 0, 0, 0);
                float s[8];
#pragma unroll
                for (int i0 = 0; i0 < 8; i0 += 4) {
                    uint4 va[4], vb[4];
#pragma unroll
                    for (int i = 0; i < 4; i++) { va[i] = __ldg(xr + (i0 + i) * 64); vb[i] = __ldg(xr + (i0 + i) * 64 + 32); }
#pragma unroll
                    for (int i = 0; i < 4; i++) {
                        float t0 = bf_lo(va[i].x) * bf_lo(wa.x), t1 = bf_hi(va[i].x) * bf_hi(wa.x);
                        t0 = fmaf(bf_lo(va[i].y), bf_lo(wa.y), t0); t1 = fmaf(bf_hi(va[i].y), bf_hi(wa.y), t1);
                        t0 = fmaf(bf_lo(va[i].z), bf_lo(wa.z), t0); t1 = fmaf(bf_hi(va[i].z), bf_hi(wa.z), t1);
                        t0 = fmaf(bf_lo(va[i].w), bf_lo(wa.w), t0); t1 = fmaf(bf_hi(va[i].w), bf_hi(wa.w), t1);
                        t0 = fmaf(bf_lo(vb[i].x), bf_lo(wb.x), t0); t1 = fmaf(bf_hi(vb[i].x), bf_hi(wb.x), t1);
                        t0 = fmaf(bf_lo(vb[i].y), bf_lo(wb.y), t0); t1 = fmaf(bf_hi(vb[i].y), bf_hi(wb.y), t1);
                        t0 = fmaf(bf_lo(vb[i].z), bf_lo(wb.z), t0); t1 = fmaf(bf_hi(vb[i].z), bf_hi(wb.z), t1);
                        t0 = fmaf(bf_lo(vb[i].w), bf_lo(wb.w), t0); t1 = fmaf(bf_hi(vb[i].w), bf_hi(wb.w), t1);
                        s[i0 + i] = t0 + t1;
                    }
                }
#pragma unroll
                for (int i = 0; i < 8; i++) {
#pragma unroll
                    for (int o = 16; o; o >>= 1) s[i] += __shfl_xor_sync(0xffffffffu, s[i], o);
                    s[i] = 1.f / (1.f + __expf(-s[i]));
                }
                if (lane < 2) {
                    const float v0 = lane ? s[4] : s[0], v1 = lane ? s[5] : s[1], v2 = lane ? s[6] : s[2], v3 = lane ? s[7] : s[3];
                    st_pkt(gp + j * 4 + hx * 2 + lane, (__float_as_uint(v0) & ~1u) | tag, __float_as_uint(v1), __float_as_uint(v2), __float_as_uint(v3));
                }
                if (hx == 1) {
                    asm volatile("st.shared.u32 [%0], %1;" :: "r"(sb + OFF_ONES + lane * 4), "r"(0x3f803f80u) : "memory");
                    asm volatile("fence.proxy.async.shared::cta;" ::: "memory");
                }
                asm volatile("bar.sync 3, 96;" ::: "memory");
                if (hx == 0) {
                    uint32_t q[4];
                    recv_issue(q, gp + lane);
                    recv_check(q, gp + lane, tag);
                    asm volatile("st.shared.v4.u32 [%0], {%1,%2,%3,%4};" :: "r"(sb + OFF_G + lane * 16), "r"(q[0]), "r"(q[1]), "r"(q[2]), "r"(q[3]) : "memory");
                    if (lane == 0) {
                        asm volatile("st.shared.u32 [%0], %1;" :: "r"(sb + OFF_EPOCH), "r"(epoch) : "memory");
                        g_epoch[blockIdx.x] = epoch + 1;
                    }
                    __syncwarp();
                    if (lane == 0) mbar_arrive(sb + B_GRDY);
                } else {
                    if (r == 0) {
                        float4* zp = (float4*)(g_kvacc + (((epoch & 1) ^ 1) * 8 + j) * 4 * 272);
                        for (int i = lane; i < 272; i += 32) zp[i] = make_float4(0.f, 0.f, 0.f, 0.f);
                    }
                }
            }
            TS(2 + hx, 1);
#define PUBLISH_H(B) do { mbar_wait(sb + B_HSENT + 8 * (B), 0); if (lane == 0) { \
                asm volatile("st.release.gpu.global.u32 [%0], %1;" :: "l"(g_hflag + (r * 8 + j) * 8 + (B)), "r"(epoch + 1) : "memory"); } __syncwarp(); } while (0)
            if (hx == 1) {
#pragma unroll 1
                for (int b = 0; b < 3; b++) { PUBLISH_H(b); TS(3, 5 + b); }
            } else {
                const float* accp = g_kvacc + ((epoch & 1) * 8 + j) * 4 * 272;
                unsigned* cnt = g_kvcnt + j * 32;
                mbar_wait(sb + B_KVDONE, 0);
                TS(2, 5);
                if (lane == 0) asm volatile("red.release.gpu.global.add.u32 [%0], 1;" :: "l"(cnt) : "memory");
                __syncwarp();
                TS(2, 2);
                {
                    const unsigned target = 16u * (epoch + 1);
                    uint32_t it = 0, v;
                    do {
                        asm volatile("ld.acquire.gpu.global.u32 %0, [%1];" : "=r"(v) : "l"(cnt) : "memory");
                    } while ((int)(v - target) < 0 && ++it < SPIN_GLOBAL);
                }
                TS(2, 3);
#pragma unroll
                for (int h = 0; h < 4; h++) {
                    const float4 d0 = __ldcg((const float4*)(accp + h * 272) + lane);
                    const float4 d1 = __ldcg((const float4*)(accp + h * 272 + 128) + lane);
                    const float2 z0 = __ldcg((const float2*)(accp + h * 272 + 256) + (lane & 3));
                    const float2 z1 = __ldcg((const float2*)(accp + h * 272 + 264) + (lane & 3));
                    const uint32_t ba = sb + OFF_STG + h * 768 + lane * 4;
                    asm volatile("st.shared.u32 [%0], %1;" :: "r"(ba), "r"(pack2(d0.x, d0.y)) : "memory");
                    asm volatile("st.shared.u32 [%0], %1;" :: "r"(ba + 128), "r"(pack2(d1.x, d1.y)) : "memory");
                    asm volatile("st.shared.u32 [%0], %1;" :: "r"(ba + 256), "r"(pack2(d0.z, d0.w)) : "memory");
                    asm volatile("st.shared.u32 [%0], %1;" :: "r"(ba + 384), "r"(pack2(d1.z, d1.w)) : "memory");
                    asm volatile("st.shared.u32 [%0], %1;" :: "r"(ba + 512), "r"(pack2(z0.x, z0.y)) : "memory");
                    asm volatile("st.shared.u32 [%0], %1;" :: "r"(ba + 640), "r"(pack2(z1.x, z1.y)) : "memory");
                }
                asm volatile("fence.proxy.async.shared::cta;" ::: "memory");
                __syncwarp();
                if (lane == 0) mbar_arrive(sb + B_KVRDY);
                TS(2, 4);
            }
        } else {
            uint32_t epoch;
            asm volatile("ld.relaxed.gpu.global.u32 %0, [%1];" : "=r"(epoch) : "l"(g_epoch + blockIdx.x) : "memory");
            asm volatile("bar.arrive 3, 96;" :: "r"(epoch) : "memory");
            const int b = blockIdx.x, p = j >> 1;
            mbar_wait(sb + B_XFULL, 0);
#pragma unroll 1
            for (int kb = 1; kb < 8; kb++) {
                mbar_wait(sb + B_XFULL + 8 * kb, 0);
                const char* base = kb < 3 ? pf_g : kb < 5 ? pf_u : kb == 5 ? pf_qkv : pf_d;
                const int off = kb == 5 ? b * 12288 : b * 14336 + ((kb < 5 ? kb - 1 : kb) & 1) * 7168;
                if (kb == 5) {
                    asm volatile("prefetch.global.L2 [%0];" :: "l"(base + off + (lane >> 3) * 3072 + (lane & 7) * 128));
                } else {
                    asm volatile("prefetch.global.L2 [%0];" :: "l"(base + off + lane * 128));
                    if (lane < 24) asm volatile("prefetch.global.L2 [%0];" :: "l"(base + off + 4096 + lane * 128));
                }
                if (kb == 7) asm volatile("prefetch.global.L2 [%0];" :: "l"(pf_o + b * 4096 + lane * 128));
            }
            {
                uint4* mb = g_part + (size_t)(r * 2 + (j & 1)) * 16384 + (((p ^ 1) * 4 + p) << 10) + lane;
#pragma unroll 1
                for (int i = 0; i < 32; i++) { st_pkt(mb + i * 32, epoch & 1, 0, 0, 0); __nanosleep(40); }
                __syncwarp();
                if (lane == 0) mbar_arrive(sb + B_KVRDY);
            }
            {
                const uint32_t want = epoch + 1;
                const int hrow = (r * 4 + p) * 5 * 128;
                const unsigned* fl = g_hflag + (r * 8 + (j & 6)) * 8 + (lane & 15);
                uint32_t it = 0;
                int i = 0;
                mbar_wait(sb + B_HSENT + 8, 0);
#pragma unroll 1
                while (i < 3 && ++it < SPIN_GLOBAL) {
                    uint32_t v;
                    asm volatile("ld.acquire.gpu.global.u32 %0, [%1];" : "=r"(v) : "l"(fl) : "memory");
                    const uint32_t rdy = __ballot_sync(0xffffffffu, v == want);
#pragma unroll 1
                    while (i < 3 && ((rdy >> i) & 0x101u) == 0x101u) {
                        if (i < 2) mbar_wait(sb + B_XFREE + 8 * i, 0);
                        if (lane == 0) {
                            const int pc = (6 - 2 * i) % 6;
                            asm volatile("fence.proxy.async.global;" ::: "memory");
                            TS2(140 + i);
                            mbar_expect(sb + B_XFULL + 8 * pc, i != 1 ? 32768 : 16384);
                            tma2(sb + OFF_X + pc * 16384, i != 1 ? &maps.hx2 : &maps.hx, 0, hrow + pc * 128, sb + B_XFULL + 8 * pc);
                        }
                        i++;
                    }
                }
            }
        }
    } else {
        asm volatile("setmaxnreg.inc.sync.aligned.u32 224;");
        const int wg = warp >> 2;
        const bool elect = (tid & 127) == 0;
        const uint32_t sbd = sb >> 4, xlo = (sbd + wg * 512) | LBO1;
        auto release = [&](uint32_t bar) {
            if (elect) {
                mbar_arrive(sb + bar);
            }
        };
#define S_SL(S) ((S) < 40 ? (S) % 5 : (int)((0x846352107ull >> (4 * (((S) - 40) % 9))) & 15))
#define S_WAIT(S) do { mbar_wait(sb + (S_SL(S) < 5 ? B_FULL + 8 * S_SL(S) : B_EFULL + 8 * (S_SL(S) - 5)), (S) < 40 ? ((S) / 5) & 1 : (S) >= 49); \
            if (PROF && tid == 0) TS2(64 + (S)); } while (0)
#define S_B(S) (S_SL(S) < 5 ? OFF_RING / 16 + S_SL(S) * 1024 : (S_SL(S) == 7 ? 8 : S_SL(S) == 8 ? 7 : S_SL(S)) * 1024)
#define S_REL(S) do { if ((S) < 49) release(S_SL(S) < 5 ? B_EMPTY + 8 * S_SL(S) : B_EEMPTY + 8 * (S_SL(S) - 5)); } while (0)
#define G1(S, acc, SW, KB) stage_ss<(KB) * 1024, S_B(S), SW, (KB) == 0>(acc, xlo, sbd)
#define RET(S) do { S_WAIT((S) + 1); wg_wait<1>(); S_REL((S) - 1); } while (0)
#define RET2(S) do { S_WAIT((S) + 1); wg_wait<2>(); S_REL((S) - 1); } while (0)
#define SCHED() mbar_wait(sb + B_XFULL + 8 * 7, 0)
#define A2_SYNC() do { asm volatile("fence.proxy.async.shared::cta;" ::: "memory"); asm volatile("bar.sync %0, 128;" :: "r"(wg + 1) : "memory"); } while (0)
#define H_EPI(acc, F, I0, I1, OG, OU) _Pragma("unroll") for (int i = (I0); i < (I1); i++) \
            F[i] = keep(hmul2(pack2(acc[(OG) + 2 * i] * acc[(OU) + 2 * i], acc[(OG) + 2 * i + 1] * acc[(OU) + 2 * i + 1]), (i & 1) ? m_hi : m_lo))
#define PHI(acc, F, I0, I1) _Pragma("unroll") for (int i = (I0); i < (I1); i++) F[i] = keep(phi2(acc[2 * i], acc[2 * i + 1]))

        float a0[64], b0[64], a1[64], a2_[64], a3[64];
        mbar_wait(sb + B_XFULL, 0);
#define X_WAIT(KB) do { mbar_wait(sb + B_XFULL + 8 * (KB), 0); if (PROF && tid == 0) TS2(128 + (KB)); } while (0)
        S_WAIT(0); G1(0, b0, false, 0);
        if ((warp & 3) == 0) TS(wg, 1);
        S_WAIT(1); G1(1, a0, false, 0); RET(1);
        X_WAIT(1); G1(2, b0, false, 1); RET(2);
        X_WAIT(2); G1(3, b0, false, 2); RET(3);
        G1(4, a0, false, 1); RET(4);
        X_WAIT(3); G1(5, b0, false, 3); RET(5);
        G1(6, a0, false, 2); RET(6);
        X_WAIT(4); G1(7, b0, false, 4); RET(7);
        X_WAIT(5); G1(8, b0, false, 5); RET(8);
        G1(9, a0, false, 3); RET(9);
        X_WAIT(6); G1(10, b0, false, 6); RET(10);
        X_WAIT(7); G1(11, b0, false, 7); RET(11);
        G1(12, a0, false, 4);
        const uint32_t lrow = ((lane & 7) + 8 * ((lane >> 3) & 1)) * 128;
        const uint32_t srow = (warp & 3) * 2048 + lrow;
        const uint32_t ssw = (lane >> 4) ^ (lane & 7);
        uint4* const hsend = g_hx + (size_t)((r * 4 + (j >> 1)) * 5 + (j & 1)) * 1024 + warp * 128 + (lane >> 2) * 8 + (lane & 3);
#define SENT_H(B) do { __syncwarp(); if (lane == 0) mbar_arrive(sb + B_HSENT + 8 * (B)); } while (0)
        RET(12);
        pin(b0);
        uint32_t fh0[16], fh1[16], fh2[16], fh3[8], fo[16], pk[16], pv[16];
        float kv[32], zs[4];
        const uint32_t stg = sb + OFF_STG + wg * 8192, stl = stg + (warp & 1) * 2048 + lrow;
#define KV_ROUND(Z) do { A2_SYNC(); wg_fence(); \
            wg_ss64t##Z<8192 + 256, 8192, DH128>(kv, xlo, xlo); wg_ss64t<8192 + 384, 8192 + 128, DH128>(kv, xlo, xlo); \
            wg_ss8t##Z<8192, OFF_ONES / 16, 0>(zs, xlo, sbd); wg_ss8t<8192 + 128, OFF_ONES / 16, 0>(zs, xlo, sbd); wg_commit(); } while (0)
        G1(13, a0, false, 5); SCHED(); pack_sub<32>(pv, b0); PHI(b0, pk, 0, 4); RET(13);
        G1(14, a0, false, 6); SCHED(); if (!(warp & 2)) stash<16>(stl + 4096, ssw, pv); PHI(b0, pk, 4, 10); RET(14);
        G1(15, a0, false, 7); SCHED(); PHI(b0, pk, 10, 16); RET(15);
        if ((warp & 3) == 0) TS(wg, 2);

        G1(16, a1, true, 0); SCHED(); if (!(warp & 2)) stash<16>(stl, ssw, pk);
        mbar_wait(sb + B_GRDY, 0);
        float g_lo, g_hi;
        uint32_t tag;
        {
            const uint32_t ga = sb + OFF_G + (warp * 16 + (lane >> 2)) * 4;
            asm volatile("ld.shared.f32 %0, [%1];" : "=f"(g_lo) : "r"(ga) : "memory");
            asm volatile("ld.shared.f32 %0, [%1];" : "=f"(g_hi) : "r"(ga + 32) : "memory");
            asm volatile("ld.shared.u32 %0, [%1];" : "=r"(tag) : "r"(sb + OFF_EPOCH) : "memory");
        }
        float* const kvp = g_kvacc + (((tag & 1) * 8 + j) * 4 + (warp & 3)) * 272;
        tag = (tag + 1) & 1;
        const uint32_t m_lo = pack2(1.f - g_lo, 1.f - g_lo), m_hi = pack2(1.f - g_hi, 1.f - g_hi);
        RET(16);
        pin(a0);
        G1(17, a1, true, 1); SCHED(); H_EPI(a0, fh0, 0, 16, 0, 32); RET(17);
        G1(18, a1, true, 2); KV_ROUND(_z); RET2(18);
        G1(19, a1, true, 3); SCHED(); send_h<0, 1>(fh0, hsend); RET(19);
        G1(20, a1, true, 4); SCHED(); if (warp & 2) { stash<16>(stl, ssw, pk); stash<16>(stl + 4096, ssw, pv); } RET(20);
        G1(21, a1, true, 5); RET(21);
        G1(22, a1, true, 6); KV_ROUND(); RET2(22);
        G1(23, a1, true, 7); SCHED(); send_h<1, 2>(fh0, hsend); RET(23);
        pin(kv); pin(zs);
        if ((warp & 3) == 0) TS(wg, 3);

        G1(24, a2_, false, 0); SCHED();
#define KV_RED(W) do { asm volatile("red.global.add.v4.f32 [%0], {%1,%2,%3,%4};" :: "l"(kvp + lane * 4), "f"(kv[8 * W]), "f"(kv[8 * W + 1]), "f"(kv[8 * W + 2]), "f"(kv[8 * W + 3]) : "memory"); \
                       asm volatile("red.global.add.v4.f32 [%0], {%1,%2,%3,%4};" :: "l"(kvp + 128 + lane * 4), "f"(kv[8 * W + 4]), "f"(kv[8 * W + 5]), "f"(kv[8 * W + 6]), "f"(kv[8 * W + 7]) : "memory"); } while (0)
        if ((warp & 3) == 0) KV_RED(0); else if ((warp & 3) == 1) KV_RED(1); else if ((warp & 3) == 2) KV_RED(2); else KV_RED(3);
        if ((lane & 3) == 0) {
            asm volatile("red.global.add.f32 [%0], %1;" :: "l"(kvp + 256 + (lane >> 2)), "f"(zs[0]) : "memory");
            asm volatile("red.global.add.f32 [%0], %1;" :: "l"(kvp + 264 + (lane >> 2)), "f"(zs[2]) : "memory");
        }
        __syncwarp();
        if (lane == 0) mbar_arrive(sb + B_KVDONE);
        RET(24);
        pin(a1);
        G1(25, a2_, false, 1); SCHED(); send_h<2, 3>(fh0, hsend); H_EPI(a1, fh3, 0, 8, 32, 48); RET(25);
        G1(26, a2_, false, 2); SCHED(); send_h<3, 4>(fh0, hsend); SENT_H(0); PHI(a1, fo, 0, 4); RET(26);
        G1(27, a2_, false, 3); SCHED(); send_h<0, 1>(fh3, hsend + 4 * 1024 - (j & 1) * 1020); PHI(a1, fo, 4, 8); RET(27);
        G1(28, a2_, false, 4); SCHED(); send_h<1, 2>(fh3, hsend + 4 * 1024 - (j & 1) * 1020); SENT_H(1); PHI(a1, fo, 8, 12); RET(28);
        G1(29, a2_, false, 5); SCHED(); PHI(a1, fo, 12, 16); RET(29);
        G1(30, a2_, false, 6); RET(30);
        G1(31, a2_, false, 7); RET(31);
        if ((warp & 3) == 0) TS(wg, 4);

        float on[4][12];
#define O_SCALE(h) do { const float s_lo = __fdividef(g_lo, on[h][8] + 1e-6f), s_hi = __fdividef(g_hi, on[h][10] + 1e-6f); \
            const uint32_t sl_ = pack2(s_lo, s_lo), sh_ = pack2(s_hi, s_hi); \
            fo[4 * h] = keep(hmul2(pack2(on[h][0], on[h][1]), sl_)); fo[4 * h + 1] = keep(hmul2(pack2(on[h][2], on[h][3]), sh_)); \
            fo[4 * h + 2] = keep(hmul2(pack2(on[h][4], on[h][5]), sl_)); fo[4 * h + 3] = keep(hmul2(pack2(on[h][6], on[h][7]), sh_)); } while (0)
        uint4* const lsend = g_lx + (size_t)(r * 8 + j) * 2048 + warp * 128 + lane;
        const uint4* const lrecv = g_lx + (size_t)(r * 8 + (j ^ 1)) * 2048 + warp * 128 + lane;
        G1(32, a3, false, 0); RET(32);
        pin(a2_);
        G1(33, a3, false, 1); SCHED(); H_EPI(a2_, fh1, 0, 16, 0, 32); send_h<0, 1>(fh1, hsend + 2 * 1024); RET(33);
        G1(34, a3, false, 2); SCHED(); send_h<1, 3>(fh1, hsend + 2 * 1024); RET(34);
        if (elect) mbar_arrive(sb + B_XFREE);
        G1(35, a3, false, 3); SCHED(); send_h<3, 4>(fh1, hsend + 2 * 1024); SENT_H(2);
        if ((warp & 3) == 0) TS(wg, 5);
        mbar_wait(sb + B_KVRDY, 0);
        if ((warp & 3) == 0) TS(wg, 6);
        wg_fence();
#define O_MMA(h) wg_rs24_z<OFF_STG / 16 + (h) * 48 + (8u << 16), 16>(on[h], fo[4 * (h)], fo[4 * (h) + 1], fo[4 * (h) + 2], fo[4 * (h) + 3], sbd)
        O_MMA(0); O_MMA(1); O_MMA(2); O_MMA(3);
        wg_commit();
        RET2(35);
        G1(36, a3, false, 4); RET(36);
        pin(on[0]); pin(on[1]); pin(on[2]); pin(on[3]);
        release(B_EEMPTY + 16);
        G1(37, a3, false, 5); SCHED(); O_SCALE(0); O_SCALE(1); O_SCALE(2); O_SCALE(3); RET(37);
        if (elect) mbar_arrive(sb + B_XFREE + 8);
        G1(38, a3, false, 6); SCHED(); send_frag<0, 2>(fo, lsend, tag); RET(38);
        release(B_EEMPTY);
        G1(39, a3, false, 7); SCHED(); send_frag<2, 4>(fo, lsend, tag); RET(39);
        release(B_EEMPTY + 8);
        if ((warp & 3) == 0) TS(wg, 7);

#define G2S(S, acc, U) stage_ss<(U) * 1024, S_B(S), false, (S) == 45>(acc, xlo, sbd)
#define G2R(S, acc, F) stage_rs<S_B(S), (S) == 40>(acc, F, sbd)
#define H_WAIT(P) do { mbar_wait(sb + B_XFULL + 8 * (P), 1); if (PROF && tid == 0) TS2(150 + (P)); } while (0)
        const int p = j >> 1, pw = (p & 2) ^ 2;
        const bool own = wg == (p & 1);
        uint4* const pbase = g_part + (size_t)(r * 2 + (j & 1)) * 16384 + (warp & 3) * 256 + lane;

        float p1[64], p2[64];
        uint32_t po[16], ph2[16];
        G2R(40, p1, fo); RET(40);
        release(B_EEMPTY + 24);
        pin(a3);
        H_WAIT(0); G2S(41, p1, 0); SCHED(); H_EPI(a3, fh2, 0, 16, 0, 32); send_frag<0, 2>(fh2, lsend + 1024, tag); RET(41);
        G2S(42, p1, 1); SCHED(); send_frag<2, 4>(fh2, lsend + 1024, tag); RET(42);
        H_WAIT(4); G2S(43, p1, 4); SCHED(); recv_issue(po, lrecv); RET(43);
        G2R(44, p1, fh2); RET(44);
        G2S(45, p2, 0); SCHED(); recv_check(po, lrecv, tag); RET(45);
        G2R(46, p1, po); SCHED(); recv_issue(ph2, lrecv + 1024); RET(46);
        H_WAIT(2); G2S(47, p1, 2); RET(47);
        G2S(48, p1, 3); SCHED(); recv_check(ph2, lrecv + 1024, tag); RET(48);
        G2R(49, p1, ph2); RET(49);
        if ((warp & 3) == 0) TS(wg, 8);
        uint32_t sp[32], qa[32], qb[32];
        uint4* const s1 = pbase + (((pw + wg) * 4 + p) << 10);
        G2R(50, p2, fo); RET(50);
        pin(p1);
        G2R(51, p2, po); SCHED(); pack_sub<0>(sp, p1); send_frag<0, 2>(sp, s1, tag); RET(51);
        G2R(52, p2, fh2); SCHED(); send_frag<2, 5>(sp, s1, tag); RET(52);
        if (elect) mbar_arrive(sb + B_XFREE + 16);
        G2R(53, p2, ph2); SCHED(); send_frag<5, 8>(sp, s1, tag); RET(53);
        const uint4* ra = pbase + ((p * 4 + pw) << 10);
        const uint4* rc = pbase + ((p * 4 + (p ^ 1)) << 10);
        if (own) mbar_wait(sb + B_AHEAD, 0);
        G2S(54, p2, 1); RET(54);
        G2S(55, p2, 2); RET(55);
        G2S(56, p2, 3); RET(56);
        G2S(57, p2, 4); SCHED();
        if ((warp & 3) == 0) TS(wg, 9);
        if (!own && elect) mbar_arrive(sb + B_AHEAD);
        wg_wait<0>();
        pin(p2);
        if ((warp & 3) == 0) TS(wg, 11);
        if (!own) {
            if (elect) {
                mbar_wait(sb + B_XFREE + 16, 0);
                mbar_expect(sb + B_PART, 32768);
                asm volatile("cp.async.bulk.shared::cluster.global.mbarrier::complete_tx::bytes [%0], [%1], %2, [%3];"
                             :: "r"(sb + OFF_RING), "l"(ra), "r"(32768), "r"(sb + B_PART) : "memory");
            }
            pack_sub<0>(sp, p2); send_frag<0, 8>(sp, pbase + (((p ^ 1) * 4 + p) << 10), tag);
        } else {
            recv_issue(sp, rc);
            mbar_wait(sb + B_PART, 0);
            const uint32_t pa = sb + OFF_RING + (warp & 3) * 4096 + lane * 16;
#pragma unroll
            for (int v = 0; v < 8; v++) {
                asm volatile("ld.shared.v4.u32 {%0,%1,%2,%3}, [%4];" : "=r"(qa[4 * v]), "=r"(qa[4 * v + 1]), "=r"(qa[4 * v + 2]), "=r"(qa[4 * v + 3]) : "r"(pa + v * 512) : "memory");
                asm volatile("ld.shared.v4.u32 {%0,%1,%2,%3}, [%4];" : "=r"(qb[4 * v]), "=r"(qb[4 * v + 1]), "=r"(qb[4 * v + 2]), "=r"(qb[4 * v + 3]) : "r"(pa + 16384 + v * 512) : "memory");
            }
            recv_check(qa, ra, tag); recv_check(qb, ra + 1024, tag);
#pragma unroll
            for (int i = 0; i < 32; i++) qa[i] = keep(hadd2(qa[i], qb[i]));
            if ((warp & 3) == 0) TS(wg, 12);
            recv_check(sp, rc, tag);
#pragma unroll
            for (int i = 0; i < 32; i++) qa[i] = hadd2(qa[i], sp[i]);
            accum(qa, p2);
            if ((warp & 3) == 0) TS(wg, 13);
            uint32_t f0[16], f1[16];
            pack_sub<0>(f0, p2); pack_sub<32>(f1, p2);
            const uint32_t slab = sb + OFF_X + 2 * 16384 + wg * 8192;
            stash<16>(slab + srow, ssw, f0); stash<16>(slab + 16384 + srow, ssw, f1);
            __syncwarp();
            __nv_bfloat16* op = out + (size_t)(r * 128 + warp * 16 + (lane >> 4)) * kD + (j & 1) * 256 + (p & 2) * 64 + (lane & 15) * 8;
#pragma unroll
            for (int i = 0; i < 8; i++) {
                const int row = i * 2 + (lane >> 4);
                uint4 v;
                asm volatile("ld.shared.v4.u32 {%0,%1,%2,%3}, [%4];" : "=r"(v.x), "=r"(v.y), "=r"(v.z), "=r"(v.w)
                             : "r"(slab + (lane & 8) * 2048 + ((warp & 3) * 16 + row) * 128 + (((lane & 7) ^ (row & 7)) << 4)) : "memory");
                *(uint4*)(op + i * 2 * kD) = v;
            }
        }
        if ((warp & 3) == 0) { TS(wg, 14); TSG(wg, 31); }
    }
}

typedef CUresult (*EncodeFn)(CUtensorMap*, CUtensorMapDataType, cuuint32_t, void*, const cuuint64_t*, const cuuint64_t*, const cuuint32_t*,
                             const cuuint32_t*, CUtensorMapInterleave, CUtensorMapSwizzle, CUtensorMapL2promotion, CUtensorMapFloatOOBfill);

static void encode(EncodeFn fn, CUtensorMap* m, int rank, const void* base, const cuuint64_t (&gd)[5], const cuuint64_t (&gs)[4],
                   const cuuint32_t (&bd)[5], CUtensorMapSwizzle sw) {
    cuuint32_t es[5] = {1, 1, 1, 1, 1};
    fn(m, CU_TENSOR_MAP_DATA_TYPE_BFLOAT16, rank, const_cast<void*>(base), gd, gs, bd, es, CU_TENSOR_MAP_INTERLEAVE_NONE, sw,
       CU_TENSOR_MAP_L2_PROMOTION_L2_128B, CU_TENSOR_MAP_FLOAT_OOB_FILL_NONE);
}

extern "C" void kernel_launch(void* const* d_in, const int* in_sizes, int n_in, void* d_out, int out_size) {
    const char* x = (const char*)d_in[0];
    const char* wqkv = (const char*)d_in[1];
    const char* wo = (const char*)d_in[2];
    const char* wg = (const char*)d_in[4];
    const char* wu = (const char*)d_in[5];
    const char* wd = (const char*)d_in[6];
    void* fnp = nullptr;
    cudaDriverEntryPointQueryResult qr;
    cudaGetDriverEntryPoint("cuTensorMapEncodeTiled", &fnp, cudaEnableDefault, &qr);
    EncodeFn fn = (EncodeFn)fnp;
    Maps maps;
    const char* lo = wg < wu ? wg : wu;
    const uint64_t diff = wg < wu ? (uint64_t)(wu - wg) : (uint64_t)(wg - wu);
    const CUtensorMapSwizzle S128 = CU_TENSOR_MAP_SWIZZLE_128B, S64 = CU_TENSOR_MAP_SWIZZLE_64B;
    encode(fn, &maps.x, 2, x, {512, 2048, 1, 1}, {1024, 0, 0}, {64, 128, 1, 1}, S128);
    encode(fn, &maps.gu, 3, lo, {1792, 512, 2, 1}, {3584, diff, 0}, {64, 64, 2, 1}, S128);
    encode(fn, &maps.kv, 3, wqkv, {512, 512, 3, 1}, {3072, 1024, 0}, {64, 64, 2, 1}, S128);
    encode(fn, &maps.q64, 3, wqkv, {32, 512, 48, 1}, {3072, 64, 0}, {32, 64, 2, 1}, S64);
    encode(fn, &maps.gu64, 3, lo, {1792, 512, 2, 1}, {3584, diff, 0}, {32, 64, 2, 1}, S64);
    encode(fn, &maps.wdw, 3, wd, {64, 1792, 8, 1}, {1024, 128, 0}, {64, 64, 2, 1}, S128);
    encode(fn, &maps.wow, 3, wo, {64, 512, 8}, {1024, 128}, {64, 64, 2}, S128);
    encode(fn, &maps.wdp, 5, wd, {512, 2, 4, 4, 56}, {1024, 8192, 2048, 32768}, {64, 2, 4, 4, 2}, S128);
    encode(fn, &maps.wdph, 5, wd, {512, 2, 4, 4, 56}, {1024, 8192, 2048, 32768}, {64, 2, 4, 4, 1}, S128);
    void* hx = nullptr;
    cudaGetSymbolAddress(&hx, g_hx);
    encode(fn, &maps.hx, 2, hx, {64, 16 * 4 * 5 * 128}, {128}, {64, 128}, S128);
    encode(fn, &maps.hx2, 2, hx, {64, 16 * 4 * 5 * 128}, {128}, {64, 256}, S128);
    cudaFuncSetAttribute(fused_kernel, cudaFuncAttributeMaxDynamicSharedMemorySize, SMEM_BYTES);
    cudaLaunchConfig_t cfg = {};
    cfg.gridDim = dim3(128);
    cfg.blockDim = dim3(384);
    cfg.dynamicSmemBytes = SMEM_BYTES;
    cfg.stream = cudaStreamPerThread;
    cudaLaunchAttribute at[1];
    at[0].id = cudaLaunchAttributeClusterDimension;
    at[0].val.clusterDim.x = 2; at[0].val.clusterDim.y = 1; at[0].val.clusterDim.z = 1;
    cfg.attrs = at;
    cfg.numAttrs = MC ? 1 : 0;
    cudaLaunchKernelEx(&cfg, fused_kernel, maps, (const __nv_bfloat16*)d_in[0], (const __nv_bfloat16*)d_in[7], wqkv, wg, wu, wd, wo, (__nv_bfloat16*)d_out);
}
```

```cpp
#include <cuda_runtime.h>
#include <cuda.h>
#include <cuda_bf16.h>
#include <stdint.h>

#define MC 0
#define PFMODE 1
#define PHI_SAT 0
#define PROF 0

namespace {

constexpr int kD = 512;
constexpr uint32_t OFF_X = 0, OFF_STG = 131072, OFF_RING = 147456, OFF_MISC = 229376;
constexpr uint32_t B_FULL = OFF_MISC, B_EMPTY = OFF_MISC + 40, B_XFULL = OFF_MISC + 80;
constexpr uint32_t B_GRDY = OFF_MISC + 152, B_KVDONE = OFF_MISC + 160, B_KVRDY = OFF_MISC + 168;
constexpr uint32_t B_HSENT = OFF_MISC + 176, B_XFREE = OFF_MISC + 200;
constexpr uint32_t OFF_EPOCH = OFF_MISC + 240, OFF_G = OFF_MISC + 256;
constexpr uint32_t B_AHEAD = OFF_MISC + 248, B_PART = OFF_MISC + 232;
constexpr uint32_t OFF_ONES = OFF_MISC + 768;
constexpr uint32_t B_EFULL = OFF_MISC + 896, B_EEMPTY = OFF_MISC + 928;
constexpr uint32_t SMEM_BYTES = OFF_MISC + 960;
constexpr uint32_t SPIN_GLOBAL = 1u << 14;

struct alignas(64) Maps { CUtensorMap x, gu, kv, q64, gu64, wdw, wow, wdp, wdph, hx, hx2; };

}

__device__ uint4 g_part[16 * 2 * 4 * 4 * 1024];
__device__ uint4 g_hx[16 * 4 * 5 * 1024];
__device__ uint4 g_lx[16 * 8 * 2 * 1024];
__device__ unsigned g_hflag[128 * 8];
__device__ uint4 g_gx[16 * 32];
__device__ float g_kvacc[2 * 8 * 4 * 272];
__device__ unsigned g_kvcnt[8 * 32];
__device__ unsigned g_epoch[128];
#define TS(role, idx)
#define TS2(idx)
#define TSG(role, idx)

namespace {

__device__ __forceinline__ void mbar_init(uint32_t bar, uint32_t cnt) { asm volatile("mbarrier.init.shared::cta.b64 [%0], %1;" :: "r"(bar), "r"(cnt) : "memory"); }
__device__ __forceinline__ void mbar_expect(uint32_t bar, uint32_t bytes) { asm volatile("mbarrier.arrive.expect_tx.shared::cta.b64 _, [%0], %1;" :: "r"(bar), "r"(bytes) : "memory"); }
__device__ __forceinline__ void mbar_arrive(uint32_t bar) { asm volatile("mbarrier.arrive.shared::cta.b64 _, [%0];" :: "r"(bar) : "memory"); }
__device__ __forceinline__ void mbar_arrive_cta(uint32_t bar, uint32_t cta) {
    asm volatile("{\n.reg .b32 ra;\nmapa.shared::cluster.u32 ra, %0, %1;\nmbarrier.arrive.shared::cluster.b64 _, [ra];\n}" :: "r"(bar), "r"(cta) : "memory");
}
__device__ __forceinline__ void mbar_wait(uint32_t bar, uint32_t parity) {
    asm volatile("{\n.reg .pred p;\n.reg .u32 c;\n"
                 "mbarrier.try_wait.parity.shared::cta.b64 p, [%0], %1;\n@p bra DONE;\n"
                 "mov.u32 c, 0;\nLAB_WAIT:\nmbarrier.try_wait.parity.shared::cta.b64 p, [%0], %1;\n@p bra DONE;\n"
                 "add.u32 c, c, 1;\nsetp.lt.u32 p, c, 65536;\n@p bra LAB_WAIT;\nDONE:\n}" :: "r"(bar), "r"(parity) : "memory");
}
__device__ __forceinline__ void tma2(uint32_t dst, const CUtensorMap* m, int c0, int c1, uint32_t bar) {
    asm volatile("cp.async.bulk.tensor.2d.shared::cluster.global.mbarrier::complete_tx::bytes [%0], [%1, {%3, %4}], [%2];"
        :: "r"(dst), "l"(m), "r"(bar), "r"(c0), "r"(c1) : "memory");
}
__device__ __forceinline__ void tmaw2(uint32_t dst, const CUtensorMap* m, int c0, int c1, uint32_t bar) {
    tma2(dst, m, c0, c1, bar);
}
__device__ __forceinline__ void tmaw3(uint32_t dst, const CUtensorMap* m, int c0, int c1, int c2, uint32_t bar) {
    asm volatile("cp.async.bulk.tensor.3d.shared::cluster.global.mbarrier::complete_tx::bytes [%0], [%1, {%3, %4, %5}], [%2];"
        :: "r"(dst), "l"(m), "r"(bar), "r"(c0), "r"(c1), "r"(c2) : "memory");
}
__device__ __forceinline__ void tmaw5(uint32_t dst, const CUtensorMap* m, int c0, int c4, uint32_t bar) {
    asm volatile("cp.async.bulk.tensor.5d.shared::cluster.global.mbarrier::complete_tx::bytes [%0], [%1, {%3, %5, %5, %5, %4}], [%2];"
        :: "r"(dst), "l"(m), "r"(bar), "r"(c0), "r"(c4), "r"(0) : "memory");
}
__device__ __forceinline__ void wg_fence() { asm volatile("wgmma.fence.sync.aligned;" ::: "memory"); }
__device__ __forceinline__ void wg_commit() { asm volatile("wgmma.commit_group.sync.aligned;" ::: "memory"); }
template <int N> __device__ __forceinline__ void wg_wait() { asm volatile("wgmma.wait_group.sync.aligned %0;" :: "n"(N) : "memory"); }
template <int N> __device__ __forceinline__ void pin(float (&d)[N]) {
#pragma unroll
    for (int i = 0; i < N; i++) asm volatile("" : "+f"(d[i]) :: "memory");
}
__device__ __forceinline__ uint32_t pack2(float lo, float hi) { uint32_t r; asm("cvt.rn.bf16x2.f32 %0, %1, %2;" : "=r"(r) : "f"(hi), "f"(lo)); return r; }
__device__ __forceinline__ uint32_t keep(uint32_t v) { asm volatile("" : "+r"(v)); return v; }
__device__ __forceinline__ uint32_t hadd2(uint32_t a, uint32_t b) { uint32_t r; asm("add.bf16x2 %0, %1, %2;" : "=r"(r) : "r"(a), "r"(b)); return r; }
__device__ __forceinline__ uint32_t hmul2(uint32_t a, uint32_t b) { uint32_t r; asm("mul.bf16x2 %0, %1, %2;" : "=r"(r) : "r"(a), "r"(b)); return r; }
__device__ __forceinline__ uint32_t phi2(float t0, float t1) {
    float e0, e1;
    asm("ex2.approx.ftz.f32 %0, %1;" : "=f"(e0) : "f"(t0 * 1.4426950408889634f));
    asm("ex2.approx.ftz.f32 %0, %1;" : "=f"(e1) : "f"(t1 * 1.4426950408889634f));
    uint32_t e = pack2(e0, e1), t = pack2(t0, t1), r;
    asm("min.bf16x2 %0, %0, %1;" : "+r"(e) : "r"(0x3f803f80u));
    asm("max.bf16x2 %0, %0, %1;" : "+r"(t) : "r"(0x35863586u));
    asm("add.bf16x2 %0, %1, %2;" : "=r"(r) : "r"(e), "r"(t));
    return r;
}
__device__ __forceinline__ void stsm4(uint32_t a, uint32_t r0, uint32_t r1, uint32_t r2, uint32_t r3) {
    asm volatile("stmatrix.sync.aligned.m8n8.x4.shared.b16 [%0], {%1,%2,%3,%4};" :: "r"(a), "r"(r0), "r"(r1), "r"(r2), "r"(r3) : "memory");
}
__device__ __forceinline__ float bf_lo(uint32_t w) { return __uint_as_float(w << 16); }
__device__ __forceinline__ float bf_hi(uint32_t w) { return __uint_as_float(w & 0xffff0000u); }
__device__ __forceinline__ void st_pkt(uint4* p, uint32_t w0, uint32_t w1, uint32_t w2, uint32_t w3) {
    asm volatile("{\n.reg .b64 lo, hi;\n.reg .b128 v;\nmov.b64 lo, {%1, %2};\nmov.b64 hi, {%3, %4};\nmov.b128 v, {lo, hi};\nst.relaxed.gpu.global.b128 [%0], v;\n}"
        :: "l"(p), "r"(w0), "r"(w1), "r"(w2), "r"(w3) : "memory");
}
__device__ __forceinline__ void ld_pkt(const uint4* p, uint32_t& w0, uint32_t& w1, uint32_t& w2, uint32_t& w3) {
    asm volatile("{\n.reg .b64 lo, hi;\n.reg .b128 v;\nld.relaxed.gpu.global.b128 v, [%4];\nmov.b128 {lo, hi}, v;\nmov.b64 {%0, %1}, lo;\nmov.b64 {%2, %3}, hi;\n}"
        : "=r"(w0), "=r"(w1), "=r"(w2), "=r"(w3) : "l"(p) : "memory");
}

template <uint32_t AO, uint32_t BO, uint32_t BH> __device__ __forceinline__ void wg_ss128(float (&d)[64], uint32_t ab, uint32_t bb) {
    asm volatile("{\n.reg .b64 da, db;\n.reg .b32 ta, tb, th, ah;\nadd.u32 ta, %64, %66;\nadd.u32 tb, %65, %67;\nmov.b32 th, %68;\nmov.b32 ah, 0x40000040;\nmov.b64 da, {ta, ah};\nmov.b64 db, {tb, th};\n"
        "wgmma.mma_async.sync.aligned.m64n128k16.f32.bf16.bf16 {%0,%1,%2,%3,%4,%5,%6,%7,%8,%9,%10,%11,%12,%13,%14,%15,%16,%17,%18,%19,%20,%21,%22,%23,%24,%25,%26,%27,%28,%29,%30,%31,%32,%33,%34,%35,%36,%37,%38,%39,%40,%41,%42,%43,%44,%45,%46,%47,%48,%49,%50,%51,%52,%53,%54,%55,%56,%57,%58,%59,%60,%61,%62,%63}, da, db, 1, 1, 1, 0, 1;\n}\n"
        : "+f"(d[0]),"+f"(d[1]),"+f"(d[2]),"+f"(d[3]),"+f"(d[4]),"+f"(d[5]),"+f"(d[6]),"+f"(d[7]),"+f"(d[8]),"+f"(d[9]),"+f"(d[10]),"+f"(d[11]),"+f"(d[12]),"+f"(d[13]),"+f"(d[14]),"+f"(d[15]),"+f"(d[16]),"+f"(d[17]),"+f"(d[18]),"+f"(d[19]),"+f"(d[20]),"+f"(d[21]),"+f"(d[22]),"+f"(d[23]),"+f"(d[24]),"+f"(d[25]),"+f"(d[26]),"+f"(d[27]),"+f"(d[28]),"+f"(d[29]),"+f"(d[30]),"+f"(d[31]),"+f"(d[32]),"+f"(d[33]),"+f"(d[34]),"+f"(d[35]),"+f"(d[36]),"+f"(d[37]),"+f"(d[38]),"+f"(d[39]),"+f"(d[40]),"+f"(d[41]),"+f"(d[42]),"+f"(d[43]),"+f"(d[44]),"+f"(d[45]),"+f"(d[46]),"+f"(d[47]),"+f"(d[48]),"+f"(d[49]),"+f"(d[50]),"+f"(d[51]),"+f"(d[52]),"+f"(d[53]),"+f"(d[54]),"+f"(d[55]),"+f"(d[56]),"+f"(d[57]),"+f"(d[58]),"+f"(d[59]),"+f"(d[60]),"+f"(d[61]),"+f"(d[62]),"+f"(d[63])
        : "r"(ab), "r"(bb), "n"(AO), "n"(BO), "n"(BH));
}
template <uint32_t AO, uint32_t BO, uint32_t BH> __device__ __forceinline__ void wg_ss128_z(float (&d)[64], uint32_t ab, uint32_t bb) {
    asm volatile("{\n.reg .b64 da, db;\n.reg .b32 ta, tb, th, ah;\nadd.u32 ta, %64, %66;\nadd.u32 tb, %65, %67;\nmov.b32 th, %68;\nmov.b32 ah, 0x40000040;\nmov.b64 da, {ta, ah};\nmov.b64 db, {tb, th};\n"
        "wgmma.mma_async.sync.aligned.m64n128k16.f32.bf16.bf16 {%0,%1,%2,%3,%4,%5,%6,%7,%8,%9,%10,%11,%12,%13,%14,%15,%16,%17,%18,%19,%20,%21,%22,%23,%24,%25,%26,%27,%28,%29,%30,%31,%32,%33,%34,%35,%36,%37,%38,%39,%40,%41,%42,%43,%44,%45,%46,%47,%48,%49,%50,%51,%52,%53,%54,%55,%56,%57,%58,%59,%60,%61,%62,%63}, da, db, 0, 1, 1, 0, 1;\n}\n"
        : "=f"(d[0]),"=f"(d[1]),"=f"(d[2]),"=f"(d[3]),"=f"(d[4]),"=f"(d[5]),"=f"(d[6]),"=f"(d[7]),"=f"(d[8]),"=f"(d[9]),"=f"(d[10]),"=f"(d[11]),"=f"(d[12]),"=f"(d[13]),"=f"(d[14]),"=f"(d[15]),"=f"(d[16]),"=f"(d[17]),"=f"(d[18]),"=f"(d[19]),"=f"(d[20]),"=f"(d[21]),"=f"(d[22]),"=f"(d[23]),"=f"(d[24]),"=f"(d[25]),"=f"(d[26]),"=f"(d[27]),"=f"(d[28]),"=f"(d[29]),"=f"(d[30]),"=f"(d[31]),"=f"(d[32]),"=f"(d[33]),"=f"(d[34]),"=f"(d[35]),"=f"(d[36]),"=f"(d[37]),"=f"(d[38]),"=f"(d[39]),"=f"(d[40]),"=f"(d[41]),"=f"(d[42]),"=f"(d[43]),"=f"(d[44]),"=f"(d[45]),"=f"(d[46]),"=f"(d[47]),"=f"(d[48]),"=f"(d[49]),"=f"(d[50]),"=f"(d[51]),"=f"(d[52]),"=f"(d[53]),"=f"(d[54]),"=f"(d[55]),"=f"(d[56]),"=f"(d[57]),"=f"(d[58]),"=f"(d[59]),"=f"(d[60]),"=f"(d[61]),"=f"(d[62]),"=f"(d[63])
        : "r"(ab), "r"(bb), "n"(AO), "n"(BO), "n"(BH));
}
template <uint32_t BO, uint32_t BH> __device__ __forceinline__ void wg_rs128(float (&d)[64], uint32_t a0, uint32_t a1, uint32_t a2, uint32_t a3, uint32_t bb) {
    asm volatile("{\n.reg .b64 db;\n.reg .b32 tb, th;\nadd.u32 tb, %68, %69;\nmov.b32 th, %70;\nmov.b64 db, {tb, th};\n"
        "wgmma.mma_async.sync.aligned.m64n128k16.f32.bf16.bf16 {%0,%1,%2,%3,%4,%5,%6,%7,%8,%9,%10,%11,%12,%13,%14,%15,%16,%17,%18,%19,%20,%21,%22,%23,%24,%25,%26,%27,%28,%29,%30,%31,%32,%33,%34,%35,%36,%37,%38,%39,%40,%41,%42,%43,%44,%45,%46,%47,%48,%49,%50,%51,%52,%53,%54,%55,%56,%57,%58,%59,%60,%61,%62,%63}, {%64,%65,%66,%67}, db, 1, 1, 1, 1;\n}\n"
        : "+f"(d[0]),"+f"(d[1]),"+f"(d[2]),"+f"(d[3]),"+f"(d[4]),"+f"(d[5]),"+f"(d[6]),"+f"(d[7]),"+f"(d[8]),"+f"(d[9]),"+f"(d[10]),"+f"(d[11]),"+f"(d[12]),"+f"(d[13]),"+f"(d[14]),"+f"(d[15]),"+f"(d[16]),"+f"(d[17]),"+f"(d[18]),"+f"(d[19]),"+f"(d[20]),"+f"(d[21]),"+f"(d[22]),"+f"(d[23]),"+f"(d[24]),"+f"(d[25]),"+f"(d[26]),"+f"(d[27]),"+f"(d[28]),"+f"(d[29]),"+f"(d[30]),"+f"(d[31]),"+f"(d[32]),"+f"(d[33]),"+f"(d[34]),"+f"(d[35]),"+f"(d[36]),"+f"(d[37]),"+f"(d[38]),"+f"(d[39]),"+f"(d[40]),"+f"(d[41]),"+f"(d[42]),"+f"(d[43]),"+f"(d[44]),"+f"(d[45]),"+f"(d[46]),"+f"(d[47]),"+f"(d[48]),"+f"(d[49]),"+f"(d[50]),"+f"(d[51]),"+f"(d[52]),"+f"(d[53]),"+f"(d[54]),"+f"(d[55]),"+f"(d[56]),"+f"(d[57]),"+f"(d[58]),"+f"(d[59]),"+f"(d[60]),"+f"(d[61]),"+f"(d[62]),"+f"(d[63])
        : "r"(a0), "r"(a1), "r"(a2), "r"(a3), "r"(bb), "n"(BO), "n"(BH));
}
template <uint32_t BO, uint32_t BH> __device__ __forceinline__ void wg_rs128_z(float (&d)[64], uint32_t a0, uint32_t a1, uint32_t a2, uint32_t a3, uint32_t bb) {
    asm volatile("{\n.reg .b64 db;\n.reg .b32 tb, th;\nadd.u32 tb, %68, %69;\nmov.b32 th, %70;\nmov.b64 db, {tb, th};\n"
        "wgmma.mma_async.sync.aligned.m64n128k16.f32.bf16.bf16 {%0,%1,%2,%3,%4,%5,%6,%7,%8,%9,%10,%11,%12,%13,%14,%15,%16,%17,%18,%19,%20,%21,%22,%23,%24,%25,%26,%27,%28,%29,%30,%31,%32,%33,%34,%35,%36,%37,%38,%39,%40,%41,%42,%43,%44,%45,%46,%47,%48,%49,%50,%51,%52,%53,%54,%55,%56,%57,%58,%59,%60,%61,%62,%63}, {%64,%65,%66,%67}, db, 0, 1, 1, 1;\n}\n"
        : "=f"(d[0]),"=f"(d[1]),"=f"(d[2]),"=f"(d[3]),"=f"(d[4]),"=f"(d[5]),"=f"(d[6]),"=f"(d[7]),"=f"(d[8]),"=f"(d[9]),"=f"(d[10]),"=f"(d[11]),"=f"(d[12]),"=f"(d[13]),"=f"(d[14]),"=f"(d[15]),"=f"(d[16]),"=f"(d[17]),"=f"(d[18]),"=f"(d[19]),"=f"(d[20]),"=f"(d[21]),"=f"(d[22]),"=f"(d[23]),"=f"(d[24]),"=f"(d[25]),"=f"(d[26]),"=f"(d[27]),"=f"(d[28]),"=f"(d[29]),"=f"(d[30]),"=f"(d[31]),"=f"(d[32]),"=f"(d[33]),"=f"(d[34]),"=f"(d[35]),"=f"(d[36]),"=f"(d[37]),"=f"(d[38]),"=f"(d[39]),"=f"(d[40]),"=f"(d[41]),"=f"(d[42]),"=f"(d[43]),"=f"(d[44]),"=f"(d[45]),"=f"(d[46]),"=f"(d[47]),"=f"(d[48]),"=f"(d[49]),"=f"(d[50]),"=f"(d[51]),"=f"(d[52]),"=f"(d[53]),"=f"(d[54]),"=f"(d[55]),"=f"(d[56]),"=f"(d[57]),"=f"(d[58]),"=f"(d[59]),"=f"(d[60]),"=f"(d[61]),"=f"(d[62]),"=f"(d[63])
        : "r"(a0), "r"(a1), "r"(a2), "r"(a3), "r"(bb), "n"(BO), "n"(BH));
}
template <uint32_t AO, uint32_t BO, uint32_t BH> __device__ __forceinline__ void wg_ss64t(float (&d)[32], uint32_t ab, uint32_t bb) {
    asm volatile("{\n.reg .b64 da, db;\n.reg .b32 ta, tb, th, ah;\nadd.u32 ta, %32, %34;\nadd.u32 tb, %33, %35;\nmov.b32 th, %36;\nmov.b32 ah, 0x40000040;\nmov.b64 da, {ta, ah};\nmov.b64 db, {tb, th};\n"
        "wgmma.mma_async.sync.aligned.m64n64k16.f32.bf16.bf16 {%0,%1,%2,%3,%4,%5,%6,%7,%8,%9,%10,%11,%12,%13,%14,%15,%16,%17,%18,%19,%20,%21,%22,%23,%24,%25,%26,%27,%28,%29,%30,%31}, da, db, 1, 1, 1, 1, 1;\n}\n"
        : "+f"(d[0]),"+f"(d[1]),"+f"(d[2]),"+f"(d[3]),"+f"(d[4]),"+f"(d[5]),"+f"(d[6]),"+f"(d[7]),"+f"(d[8]),"+f"(d[9]),"+f"(d[10]),"+f"(d[11]),"+f"(d[12]),"+f"(d[13]),"+f"(d[14]),"+f"(d[15]),"+f"(d[16]),"+f"(d[17]),"+f"(d[18]),"+f"(d[19]),"+f"(d[20]),"+f"(d[21]),"+f"(d[22]),"+f"(d[23]),"+f"(d[24]),"+f"(d[25]),"+f"(d[26]),"+f"(d[27]),"+f"(d[28]),"+f"(d[29]),"+f"(d[30]),"+f"(d[31])
        : "r"(ab), "r"(bb), "n"(AO), "n"(BO), "n"(BH));
}
template <uint32_t AO, uint32_t BO, uint32_t BH> __device__ __forceinline__ void wg_ss64t_z(float (&d)[32], uint32_t ab, uint32_t bb) {
    asm volatile("{\n.reg .b64 da, db;\n.reg .b32 ta, tb, th, ah;\nadd.u32 ta, %32, %34;\nadd.u32 tb, %33, %35;\nmov.b32 th, %36;\nmov.b32 ah, 0x40000040;\nmov.b64 da, {ta, ah};\nmov.b64 db, {tb, th};\n"
        "wgmma.mma_async.sync.aligned.m64n64k16.f32.bf16.bf16 {%0,%1,%2,%3,%4,%5,%6,%7,%8,%9,%10,%11,%12,%13,%14,%15,%16,%17,%18,%19,%20,%21,%22,%23,%24,%25,%26,%27,%28,%29,%30,%31}, da, db, 0, 1, 1, 1, 1;\n}\n"
        : "=f"(d[0]),"=f"(d[1]),"=f"(d[2]),"=f"(d[3]),"=f"(d[4]),"=f"(d[5]),"=f"(d[6]),"=f"(d[7]),"=f"(d[8]),"=f"(d[9]),"=f"(d[10]),"=f"(d[11]),"=f"(d[12]),"=f"(d[13]),"=f"(d[14]),"=f"(d[15]),"=f"(d[16]),"=f"(d[17]),"=f"(d[18]),"=f"(d[19]),"=f"(d[20]),"=f"(d[21]),"=f"(d[22]),"=f"(d[23]),"=f"(d[24]),"=f"(d[25]),"=f"(d[26]),"=f"(d[27]),"=f"(d[28]),"=f"(d[29]),"=f"(d[30]),"=f"(d[31])
        : "r"(ab), "r"(bb), "n"(AO), "n"(BO), "n"(BH));
}
template <uint32_t AO, uint32_t BO, uint32_t BH> __device__ __forceinline__ void wg_ss8t(float (&d)[4], uint32_t ab, uint32_t bb) {
    asm volatile("{\n.reg .b64 da, db;\n.reg .b32 ta, tb, th, ah;\nadd.u32 ta, %4, %6;\nadd.u32 tb, %5, %7;\nmov.b32 th, %8;\nmov.b32 ah, 0x40000040;\nmov.b64 da, {ta, ah};\nmov.b64 db, {tb, th};\n"
        "wgmma.mma_async.sync.aligned.m64n8k16.f32.bf16.bf16 {%0,%1,%2,%3}, da, db, 1, 1, 1, 1, 0;\n}\n"
        : "+f"(d[0]),"+f"(d[1]),"+f"(d[2]),"+f"(d[3])
        : "r"(ab), "r"(bb), "n"(AO), "n"(BO), "n"(BH));
}
template <uint32_t AO, uint32_t BO, uint32_t BH> __device__ __forceinline__ void wg_ss8t_z(float (&d)[4], uint32_t ab, uint32_t bb) {
    asm volatile("{\n.reg .b64 da, db;\n.reg .b32 ta, tb, th, ah;\nadd.u32 ta, %4, %6;\nadd.u32 tb, %5, %7;\nmov.b32 th, %8;\nmov.b32 ah, 0x40000040;\nmov.b64 da, {ta, ah};\nmov.b64 db, {tb, th};\n"
        "wgmma.mma_async.sync.aligned.m64n8k16.f32.bf16.bf16 {%0,%1,%2,%3}, da, db, 0, 1, 1, 1, 0;\n}\n"
        : "=f"(d[0]),"=f"(d[1]),"=f"(d[2]),"=f"(d[3])
        : "r"(ab), "r"(bb), "n"(AO), "n"(BO), "n"(BH));
}
template <uint32_t BO, uint32_t BH> __device__ __forceinline__ void wg_rs24_z(float (&d)[12], uint32_t a0, uint32_t a1, uint32_t a2, uint32_t a3, uint32_t bb) {
    asm volatile("{\n.reg .b64 db;\n.reg .b32 tb, th;\nadd.u32 tb, %16, %17;\nmov.b32 th, %18;\nmov.b64 db, {tb, th};\n"
        "wgmma.mma_async.sync.aligned.m64n24k16.f32.bf16.bf16 {%0,%1,%2,%3,%4,%5,%6,%7,%8,%9,%10,%11}, {%12,%13,%14,%15}, db, 0, 1, 1, 0;\n}\n"
        : "=f"(d[0]),"=f"(d[1]),"=f"(d[2]),"=f"(d[3]),"=f"(d[4]),"=f"(d[5]),"=f"(d[6]),"=f"(d[7]),"=f"(d[8]),"=f"(d[9]),"=f"(d[10]),"=f"(d[11])
        : "r"(a0), "r"(a1), "r"(a2), "r"(a3), "r"(bb), "n"(BO), "n"(BH));
}

constexpr uint32_t DH128 = 64u | 0x40000000u;
constexpr uint32_t DH64 = 32u | 0x80000000u;
constexpr uint32_t LBO4K = (4096u >> 4) << 16, LBO8K = (8192u >> 4) << 16, LBO1 = 1u << 16;

template <uint32_t AO, uint32_t BO, bool SW64, bool FIRST> __device__ __forceinline__ void stage_ss(float (&acc)[64], uint32_t ab, uint32_t bb) {
    constexpr uint32_t KS = SW64 ? 64 : 128, BH = SW64 ? DH64 : DH128, B0 = BO + (SW64 ? LBO4K : LBO8K);
    wg_fence();
    if (FIRST) wg_ss128_z<AO, B0, BH>(acc, ab, bb); else wg_ss128<AO, B0, BH>(acc, ab, bb);
    wg_ss128<AO + 2, B0 + KS, BH>(acc, ab, bb);
    wg_ss128<AO + 4, B0 + 2 * KS, BH>(acc, ab, bb);
    wg_ss128<AO + 6, B0 + 3 * KS, BH>(acc, ab, bb);
    wg_commit();
}
template <uint32_t BO, bool FIRST> __device__ __forceinline__ void stage_rs(float (&acc)[64], const uint32_t (&f)[16], uint32_t bb) {
    wg_fence();
    if (FIRST) wg_rs128_z<BO + LBO8K, DH128>(acc, f[0], f[1], f[2], f[3], bb); else wg_rs128<BO + LBO8K, DH128>(acc, f[0], f[1], f[2], f[3], bb);
    wg_rs128<BO + LBO8K + 128, DH128>(acc, f[4], f[5], f[6], f[7], bb);
    wg_rs128<BO + LBO8K + 256, DH128>(acc, f[8], f[9], f[10], f[11], bb);
    wg_rs128<BO + LBO8K + 384, DH128>(acc, f[12], f[13], f[14], f[15], bb);
    wg_commit();
}

template <int N> __device__ __forceinline__ void stash(uint32_t base, uint32_t sw, const uint32_t (&f)[N]) {
#pragma unroll
    for (int t = 0; t < N / 4; t++) stsm4(base + ((sw ^ (2 * t)) << 4), f[4 * t], f[4 * t + 1], f[4 * t + 2], f[4 * t + 3]);
}

template <int V0, int V1, int N> __device__ __forceinline__ void send_frag(const uint32_t (&f)[N], uint4* p, uint32_t tag) {
#pragma unroll
    for (int v = V0; v < V1; v++) st_pkt(p + v * 32, (f[4 * v] & ~1u) | tag, f[4 * v + 1], f[4 * v + 2], f[4 * v + 3]);
}
template <int V0, int V1, int N> __device__ __forceinline__ void send_h(const uint32_t (&f)[N], uint4* p) {
#pragma unroll
    for (int v = V0; v < V1; v++) {
        const int h = v >> 1, hi = v & 1;
        asm volatile("st.global.v4.u32 [%0], {%1,%2,%3,%4};" :: "l"(p + 4 * h + 64 * hi),
                     "r"(f[8 * h + hi]), "r"(f[8 * h + 2 + hi]), "r"(f[8 * h + 4 + hi]), "r"(f[8 * h + 6 + hi]) : "memory");
    }
}
template <int O, int N, int M> __device__ __forceinline__ void pack_sub(uint32_t (&f)[N], const float (&acc)[M]) {
#pragma unroll
    for (int i = 0; i < N; i++) f[i] = keep(pack2(acc[O + 2 * i], acc[O + 2 * i + 1]));
}
template <int N> __device__ __forceinline__ void recv_issue(uint32_t (&q)[N], const uint4* p) {
#pragma unroll
    for (int v = 0; v < N / 4; v++) ld_pkt(p + v * 32, q[4 * v], q[4 * v + 1], q[4 * v + 2], q[4 * v + 3]);
}
template <int N> __device__ __forceinline__ void recv_check(uint32_t (&q)[N], const uint4* p, uint32_t tag) {
    uint32_t it = 0;
    while (true) {
        uint32_t bad = 0;
#pragma unroll
        for (int v = 0; v < N / 4; v++) bad |= q[4 * v] ^ tag;
        if (__all_sync(0xffffffffu, (bad & 1u) == 0) || ++it > SPIN_GLOBAL) break;
        recv_issue(q, p);
    }
}
__device__ __forceinline__ void accum(const uint32_t (&q)[32], float (&sum)[64]) {
#pragma unroll
    for (int i = 0; i < 32; i++) { sum[2 * i] += bf_lo(q[i]); sum[2 * i + 1] += bf_hi(q[i]); }
}

}

__global__ void __launch_bounds__(384, 1)
fused_kernel(const __grid_constant__ Maps maps, const __nv_bfloat16* __restrict__ xg, const __nv_bfloat16* __restrict__ gate_w,
             const char* __restrict__ pf_qkv, const char* __restrict__ pf_g, const char* __restrict__ pf_u,
             const char* __restrict__ pf_d, const char* __restrict__ pf_o, __nv_bfloat16* __restrict__ out) {
    extern __shared__ __align__(1024) uint8_t smem_raw[];
    const uint32_t sb = (uint32_t)__cvta_generic_to_shared(smem_raw);
    const int tid = threadIdx.x, lane = tid & 31;
    const int warp = __shfl_sync(0xffffffffu, tid >> 5, 0);
    const int j = (blockIdx.x >> 1) & 7;
    const int r = ((blockIdx.x >> 4) << 1) | (blockIdx.x & 1);
    const uint32_t rank = blockIdx.x & 1;

    if (warp == 0) { TSG(0, 30); TS(0, 0); }
    if (tid == 256) {
        for (int i = 0; i < 5; i++) { mbar_init(sb + B_FULL + 8 * i, 1); mbar_init(sb + B_EMPTY + 8 * i, MC ? 4 : 2); }
        for (int i = 0; i < 9; i++) mbar_init(sb + B_XFULL + 8 * i, 1);
        asm volatile("fence.mbarrier_init.release.cluster;" ::: "memory");
        mbar_expect(sb + B_XFULL, 16384);
        tma2(sb + OFF_X, &maps.x, 0, r * 128, sb + B_XFULL);
        TS2(0);
        mbar_expect(sb + B_FULL, 16384);
        tmaw3(sb + OFF_RING, &maps.kv, 64 * j, 0, 1, sb + B_FULL);
        TS2(1);
        mbar_expect(sb + B_FULL + 8, 16384);
        tmaw3(sb + OFF_RING + 16384, &maps.gu, 224 * j, 0, 0, sb + B_FULL + 8);
    } else if (tid == 288) {
        for (int i = 0; i < 3; i++) mbar_init(sb + B_HSENT + 8 * i, 8);
        for (int i = 0; i < 4; i++) { mbar_init(sb + B_EFULL + 8 * i, 1); mbar_init(sb + B_EEMPTY + 8 * i, MC ? 4 : 2); }
        mbar_init(sb + B_XFREE, 2); mbar_init(sb + B_XFREE + 8, 2); mbar_init(sb + B_XFREE + 16, 2);
        mbar_init(sb + B_AHEAD, 1); mbar_init(sb + B_PART, 1); mbar_init(sb + B_GRDY, 1); mbar_init(sb + B_KVDONE, 8); mbar_init(sb + B_KVRDY, 2);
        asm volatile("fence.mbarrier_init.release.cluster;" ::: "memory");
    } else if (warp == 10 && lane < 10) {
        asm volatile("prefetch.tensormap [%0];" :: "l"(&maps.gu + lane) : "memory");
    }
    __syncthreads();

    if (warp >= 8) {
        asm volatile("setmaxnreg.dec.sync.aligned.u32 56;");
        if (warp == 8) {
            if (lane == 0) {
                int slot = MC ? 0 : 2, ph = 1;
                uint32_t full, dst;
                if (!MC) { mbar_expect(sb + B_XFULL + 8, 16384); tma2(sb + OFF_X + 16384, &maps.x, 64, r * 128, sb + B_XFULL + 8); }
#define P_BEGIN(S, BYTES) full = sb + B_FULL + 8 * slot; dst = sb + OFF_RING + slot * 16384; \
                mbar_wait(sb + B_EMPTY + 8 * slot, ph); TS2(S); mbar_expect(full, BYTES); if (!MC || (((S) ^ rank) & 1) == 0)
#define P_END() if (++slot == 5) { slot = 0; ph ^= 1; }
                for (int s = MC ? 0 : 2; s < 16; s++) {
                    const int kb = (int)(0x7654763542312100ull >> (4 * s)) & 15;
                    P_BEGIN(s, 16384) {
                        if ((0x0DADu >> s) & 1) tmaw3(dst, &maps.kv, 64 * j, 64 * kb, 1, full);
                        else tmaw3(dst, &maps.gu, 224 * j, 64 * kb, 0, full);
                    }
                    const int xb = (int)(0x0000000765403210ull >> (4 * s)) & 15;
                    if (xb) { mbar_expect(sb + B_XFULL + 8 * xb, 16384); tma2(sb + OFF_X + xb * 16384, &maps.x, 64 * xb, r * 128, sb + B_XFULL + 8 * xb); }
                    P_END()
                }
                for (int s = 0; s < 24; s++) {
                    P_BEGIN(16 + s, 16384) {
                        if (s < 8) {
                            tmaw3(dst, &maps.q64, 0, 64 * s, 2 * j, full);
                            tmaw3(dst + 8192, &maps.gu64, 224 * j + 192, 64 * s, 0, full);
                        } else {
                            tmaw3(dst, &maps.gu, 224 * j + 64 * (s >> 3), 64 * (s & 7), 0, full);
                        }
                    }
                    P_END()
                }
                const int p = j >> 1;
#pragma unroll 1
                for (int t = 0; t < 18; t++) {
                    const int q = t >= 9, sl = (int)(0x846352107ull >> (4 * (t - 9 * q))) & 15;
                    const int u = (int)((q ? 0x432186758ull : 0x327064105ull) >> (4 * (t - 9 * q))) & 15;
                    const int cw = (j & 1) * 4 + ((p & 2) ^ ((t == 5 || t > 9) ? 0 : 2)), cc = 64 * cw;
                    if (sl < 5) {
                        full = sb + B_FULL + 8 * sl; dst = sb + OFF_RING + sl * 16384;
                        mbar_wait(sb + B_EMPTY + 8 * sl, q ^ 1);
                    } else {
                        full = sb + B_EFULL + 8 * (sl - 5); dst = sb + OFF_X + (sl == 7 ? 8 : sl == 8 ? 7 : sl) * 16384;
                        mbar_wait(sb + B_EEMPTY + 8 * (sl - 5), q);
                    }
                    TS2(40 + t);
                    mbar_expect(full, 16384);
                    if (!MC || ((t ^ rank) & 1) == 0) {
                        if (u == 4) {
                            tmaw5(dst, &maps.wdph, cc, 14 * p + 6, full); tmaw5(dst + 4096, &maps.wdph, cc, 14 * p + 13, full);
                            tmaw5(dst + 8192, &maps.wdph, cc + 64, 14 * p + 6, full); tmaw5(dst + 12288, &maps.wdph, cc + 64, 14 * p + 13, full);
                        } else if (u > 4) {
                            const int js = u > 6 ? j ^ 1 : j;
                            tmaw3(dst, (u & 1) ? &maps.wow : &maps.wdw, 0, (u & 1) ? 64 * js : 224 * js + 128, cw, full);
                        } else {
                            const int g = 14 * p + 7 * (u & 1) + (u & 2);
                            tmaw5(dst, &maps.wdp, cc, g, full); tmaw5(dst + 8192, &maps.wdp, cc + 64, g, full);
                        }
                    }
                }
            }
        } else if (warp < 11) {
            const int hx = warp - 9;
            uint32_t epoch;
            asm volatile("ld.relaxed.gpu.global.u32 %0, [%1];" : "=r"(epoch) : "l"(g_epoch + blockIdx.x) : "memory");
            {
                const uint4* xr = (const uint4*)(xg + (size_t)(r * 128 + j * 16 + hx * 8) * kD) + lane;
                const uint4 wa = __ldg((const uint4*)gate_w + lane), wb = __ldg((const uint4*)gate_w + 32 + lane);
                const uint32_t tag = (epoch + 1) & 1;
                uint4* gp = g_gx + r * 32;
                if (lane < 2) st_pkt(gp + j * 4 + hx * 2 + lane, tag ^ 1, 0, 0, 0);
                float s[8];
#pragma unroll
                for (int i0 = 0; i0 < 8; i0 += 4) {
                    uint4 va[4], vb[4];
#pragma unroll
                    for (int i = 0; i < 4; i++) { va[i] = __ldg(xr + (i0 + i) * 64); vb[i] = __ldg(xr + (i0 + i) * 64 + 32); }
#pragma unroll
                    for (int i = 0; i < 4; i++) {
                        float t0 = bf_lo(va[i].x) * bf_lo(wa.x), t1 = bf_hi(va[i].x) * bf_hi(wa.x);
                        t0 = fmaf(bf_lo(va[i].y), bf_lo(wa.y), t0); t1 = fmaf(bf_hi(va[i].y), bf_hi(wa.y), t1);
                        t0 = fmaf(bf_lo(va[i].z), bf_lo(wa.z), t0); t1 = fmaf(bf_hi(va[i].z), bf_hi(wa.z), t1);
                        t0 = fmaf(bf_lo(va[i].w), bf_lo(wa.w), t0); t1 = fmaf(bf_hi(va[i].w), bf_hi(wa.w), t1);
                        t0 = fmaf(bf_lo(vb[i].x), bf_lo(wb.x), t0); t1 = fmaf(bf_hi(vb[i].x), bf_hi(wb.x), t1);
                        t0 = fmaf(bf_lo(vb[i].y), bf_lo(wb.y), t0); t1 = fmaf(bf_hi(vb[i].y), bf_hi(wb.y), t1);
                        t0 = fmaf(bf_lo(vb[i].z), bf_lo(wb.z), t0); t1 = fmaf(bf_hi(vb[i].z), bf_hi(wb.z), t1);
                        t0 = fmaf(bf_lo(vb[i].w), bf_lo(wb.w), t0); t1 = fmaf(bf_hi(vb[i].w), bf_hi(wb.w), t1);
                        s[i0 + i] = t0 + t1;
                    }
                }
#pragma unroll
                for (int i = 0; i < 8; i++) {
#pragma unroll
                    for (int o = 16; o; o >>= 1) s[i] += __shfl_xor_sync(0xffffffffu, s[i], o);
                    s[i] = 1.f / (1.f + __expf(-s[i]));
                }
                if (lane < 2) {
                    const float v0 = lane ? s[4] : s[0], v1 = lane ? s[5] : s[1], v2 = lane ? s[6] : s[2], v3 = lane ? s[7] : s[3];
                    st_pkt(gp + j * 4 + hx * 2 + lane, (__float_as_uint(v0) & ~1u) | tag, __float_as_uint(v1), __float_as_uint(v2), __float_as_uint(v3));
                }
                if (hx == 1) {
                    asm volatile("st.shared.u32 [%0], %1;" :: "r"(sb + OFF_ONES + lane * 4), "r"(0x3f803f80u) : "memory");
                    asm volatile("fence.proxy.async.shared::cta;" ::: "memory");
                }
                asm volatile("bar.sync 3, 96;" ::: "memory");
                if (hx == 0) {
                    uint32_t q[4];
                    recv_issue(q, gp + lane);
                    recv_check(q, gp + lane, tag);
                    asm volatile("st.shared.v4.u32 [%0], {%1,%2,%3,%4};" :: "r"(sb + OFF_G + lane * 16), "r"(q[0]), "r"(q[1]), "r"(q[2]), "r"(q[3]) : "memory");
                    if (lane == 0) {
                        asm volatile("st.shared.u32 [%0], %1;" :: "r"(sb + OFF_EPOCH), "r"(epoch) : "memory");
                        g_epoch[blockIdx.x] = epoch + 1;
                    }
                    __syncwarp();
                    if (lane == 0) mbar_arrive(sb + B_GRDY);
                } else {
                    if (r == 0) {
                        float4* zp = (float4*)(g_kvacc + (((epoch & 1) ^ 1) * 8 + j) * 4 * 272);
                        for (int i = lane; i < 272; i += 32) zp[i] = make_float4(0.f, 0.f, 0.f, 0.f);
                    }
                }
            }
            TS(2 + hx, 1);
#define PUBLISH_H(B) do { mbar_wait(sb + B_HSENT + 8 * (B), 0); if (lane == 0) { \
                asm volatile("st.release.gpu.global.u32 [%0], %1;" :: "l"(g_hflag + (r * 8 + j) * 8 + (B)), "r"(epoch + 1) : "memory"); } __syncwarp(); } while (0)
            if (hx == 1) {
#pragma unroll 1
                for (int b = 0; b < 3; b++) { PUBLISH_H(b); TS(3, 5 + b); }
            } else {
                const float* accp = g_kvacc + ((epoch & 1) * 8 + j) * 4 * 272;
                unsigned* cnt = g_kvcnt + j * 32;
                mbar_wait(sb + B_KVDONE, 0);
                TS(2, 5);
                if (lane == 0) asm volatile("red.release.gpu.global.add.u32 [%0], 1;" :: "l"(cnt) : "memory");
                __syncwarp();
                TS(2, 2);
                {
                    const unsigned target = 16u * (epoch + 1);
                    uint32_t it = 0, v;
                    do {
                        asm volatile("ld.acquire.gpu.global.u32 %0, [%1];" : "=r"(v) : "l"(cnt) : "memory");
                    } while ((int)(v - target) < 0 && ++it < SPIN_GLOBAL);
                }
                TS(2, 3);
#pragma unroll
                for (int h = 0; h < 4; h++) {
                    const float4 d0 = __ldcg((const float4*)(accp + h * 272) + lane);
                    const float4 d1 = __ldcg((const float4*)(accp + h * 272 + 128) + lane);
                    const float2 z0 = __ldcg((const float2*)(accp + h * 272 + 256) + (lane & 3));
                    const float2 z1 = __ldcg((const float2*)(accp + h * 272 + 264) + (lane & 3));
                    const uint32_t ba = sb + OFF_STG + h * 768 + lane * 4;
                    asm volatile("st.shared.u32 [%0], %1;" :: "r"(ba), "r"(pack2(d0.x, d0.y)) : "memory");
                    asm volatile("st.shared.u32 [%0], %1;" :: "r"(ba + 128), "r"(pack2(d1.x, d1.y)) : "memory");
                    asm volatile("st.shared.u32 [%0], %1;" :: "r"(ba + 256), "r"(pack2(d0.z, d0.w)) : "memory");
                    asm volatile("st.shared.u32 [%0], %1;" :: "r"(ba + 384), "r"(pack2(d1.z, d1.w)) : "memory");
                    asm volatile("st.shared.u32 [%0], %1;" :: "r"(ba + 512), "r"(pack2(z0.x, z0.y)) : "memory");
                    asm volatile("st.shared.u32 [%0], %1;" :: "r"(ba + 640), "r"(pack2(z1.x, z1.y)) : "memory");
                }
                asm volatile("fence.proxy.async.shared::cta;" ::: "memory");
                __syncwarp();
                if (lane == 0) mbar_arrive(sb + B_KVRDY);
                TS(2, 4);
            }
        } else {
            uint32_t epoch;
            asm volatile("ld.relaxed.gpu.global.u32 %0, [%1];" : "=r"(epoch) : "l"(g_epoch + blockIdx.x) : "memory");
            asm volatile("bar.arrive 3, 96;" :: "r"(epoch) : "memory");
            const int b = blockIdx.x, p = j >> 1;
            mbar_wait(sb + B_XFULL, 0);
#pragma unroll 1
            for (int kb = 1; kb < 8; kb++) {
                mbar_wait(sb + B_XFULL + 8 * kb, 0);
                const char* base = kb < 3 ? pf_g : kb < 5 ? pf_u : kb == 5 ? pf_qkv : pf_d;
                const int off = kb == 5 ? b * 12288 : b * 14336 + ((kb < 5 ? kb - 1 : kb) & 1) * 7168;
                if (kb == 5) {
                    asm volatile("prefetch.global.L2 [%0];" :: "l"(base + off + (lane >> 3) * 3072 + (lane & 7) * 128));
                } else {
                    asm volatile("prefetch.global.L2 [%0];" :: "l"(base + off + lane * 128));
                    if (lane < 24) asm volatile("prefetch.global.L2 [%0];" :: "l"(base + off + 4096 + lane * 128));
                }
                if (kb == 7) asm volatile("prefetch.global.L2 [%0];" :: "l"(pf_o + b * 4096 + lane * 128));
            }
            {
                uint4* mb = g_part + (size_t)(r * 2 + (j & 1)) * 16384 + (((p ^ 1) * 4 + p) << 10) + lane;
#pragma unroll 1
                for (int i = 0; i < 32; i++) { st_pkt(mb + i * 32, epoch & 1, 0, 0, 0); __nanosleep(40); }
                __syncwarp();
                if (lane == 0) mbar_arrive(sb + B_KVRDY);
            }
            {
                const uint32_t want = epoch + 1;
                const int hrow = (r * 4 + p) * 5 * 128;
                const unsigned* fl = g_hflag + (r * 8 + (j & 6)) * 8 + (lane & 15);
                uint32_t it = 0;
                int i = 0;
                mbar_wait(sb + B_HSENT + 8, 0);
#pragma unroll 1
                while (i < 3 && ++it < SPIN_GLOBAL) {
                    uint32_t v;
                    asm volatile("ld.acquire.gpu.global.u32 %0, [%1];" : "=r"(v) : "l"(fl) : "memory");
                    const uint32_t rdy = __ballot_sync(0xffffffffu, v == want);
#pragma unroll 1
                    while (i < 3 && ((rdy >> i) & 0x101u) == 0x101u) {
                        if (i < 2) mbar_wait(sb + B_XFREE + 8 * i, 0);
                        if (lane == 0) {
                            const int pc = (6 - 2 * i) % 6;
                            asm volatile("fence.proxy.async.global;" ::: "memory");
                            TS2(140 + i);
                            mbar_expect(sb + B_XFULL + 8 * pc, i != 1 ? 32768 : 16384);
                            tma2(sb + OFF_X + pc * 16384, i != 1 ? &maps.hx2 : &maps.hx, 0, hrow + pc * 128, sb + B_XFULL + 8 * pc);
                        }
                        i++;
                    }
                }
            }
        }
    } else {
        asm volatile("setmaxnreg.inc.sync.aligned.u32 224;");
        const int wg = warp >> 2;
        const bool elect = (tid & 127) == 0;
        const uint32_t sbd = sb >> 4, xlo = (sbd + wg * 512) | LBO1;
        auto release = [&](uint32_t bar) {
            if (elect) {
                mbar_arrive(sb + bar);
            }
        };
#define S_SL(S) ((S) < 40 ? (S) % 5 : (int)((0x846352107ull >> (4 * (((S) - 40) % 9))) & 15))
#define S_WAIT(S) do { mbar_wait(sb + (S_SL(S) < 5 ? B_FULL + 8 * S_SL(S) : B_EFULL + 8 * (S_SL(S) - 5)), (S) < 40 ? ((S) / 5) & 1 : (S) >= 49); \
            if (PROF && tid == 0) TS2(64 + (S)); } while (0)
#define S_B(S) (S_SL(S) < 5 ? OFF_RING / 16 + S_SL(S) * 1024 : (S_SL(S) == 7 ? 8 : S_SL(S) == 8 ? 7 : S_SL(S)) * 1024)
#define S_REL(S) do { if ((S) < 49) release(S_SL(S) < 5 ? B_EMPTY + 8 * S_SL(S) : B_EEMPTY + 8 * (S_SL(S) - 5)); } while (0)
#define G1(S, acc, SW, KB) stage_ss<(KB) * 1024, S_B(S), SW, (KB) == 0>(acc, xlo, sbd)
#define RET(S) do { S_WAIT((S) + 1); wg_wait<1>(); S_REL((S) - 1); } while (0)
#define RET2(S) do { S_WAIT((S) + 1); wg_wait<2>(); S_REL((S) - 1); } while (0)
#define SCHED() mbar_wait(sb + B_XFULL + 8 * 7, 0)
#define A2_SYNC() do { asm volatile("fence.proxy.async.shared::cta;" ::: "memory"); asm volatile("bar.sync %0, 128;" :: "r"(wg + 1) : "memory"); } while (0)
#define H_EPI(acc, F, I0, I1, OG, OU) _Pragma("unroll") for (int i = (I0); i < (I1); i++) \
            F[i] = keep(hmul2(pack2(acc[(OG) + 2 * i] * acc[(OU) + 2 * i], acc[(OG) + 2 * i + 1] * acc[(OU) + 2 * i + 1]), (i & 1) ? m_hi : m_lo))
#define PHI(acc, F, I0, I1) _Pragma("unroll") for (int i = (I0); i < (I1); i++) F[i] = keep(phi2(acc[2 * i], acc[2 * i + 1]))

        float a0[64], b0[64], a1[64], a2_[64], a3[64];
        mbar_wait(sb + B_XFULL, 0);
#define X_WAIT(KB) do { mbar_wait(sb + B_XFULL + 8 * (KB), 0); if (PROF && tid == 0) TS2(128 + (KB)); } while (0)
        S_WAIT(0); G1(0, b0, false, 0);
        if ((warp & 3) == 0) TS(wg, 1);
        S_WAIT(1); G1(1, a0, false, 0); RET(1);
        X_WAIT(1); G1(2, b0, false, 1); RET(2);
        X_WAIT(2); G1(3, b0, false, 2); RET(3);
        G1(4, a0, false, 1); RET(4);
        X_WAIT(3); G1(5, b0, false, 3); RET(5);
        G1(6, a0, false, 2); RET(6);
        X_WAIT(4); G1(7, b0, false, 4); RET(7);
        X_WAIT(5); G1(8, b0, false, 5); RET(8);
        G1(9, a0, false, 3); RET(9);
        X_WAIT(6); G1(10, b0, false, 6); RET(10);
        X_WAIT(7); G1(11, b0, false, 7); RET(11);
        G1(12, a0, false, 4);
        const uint32_t lrow = ((lane & 7) + 8 * ((lane >> 3) & 1)) * 128;
        const uint32_t srow = (warp & 3) * 2048 + lrow;
        const uint32_t ssw = (lane >> 4) ^ (lane & 7);
        uint4* const hsend = g_hx + (size_t)((r * 4 + (j >> 1)) * 5 + (j & 1)) * 1024 + warp * 128 + (lane >> 2) * 8 + (lane & 3);
#define SENT_H(B) do { __syncwarp(); if (lane == 0) mbar_arrive(sb + B_HSENT + 8 * (B)); } while (0)
        RET(12);
        pin(b0);
        uint32_t fh0[16], fh1[16], fh2[16], fh3[8], fo[16], pk[16], pv[16];
        float kv[32], zs[4];
        const uint32_t stg = sb + OFF_STG + wg * 8192, stl = stg + (warp & 1) * 2048 + lrow;
#define KV_ROUND(Z) do { A2_SYNC(); wg_fence(); \
            wg_ss64t##Z<8192 + 256, 8192, DH128>(kv, xlo, xlo); wg_ss64t<8192 + 384, 8192 + 128, DH128>(kv, xlo, xlo); \
            wg_ss8t##Z<8192, OFF_ONES / 16, 0>(zs, xlo, sbd); wg_ss8t<8192 + 128, OFF_ONES / 16, 0>(zs, xlo, sbd); wg_commit(); } while (0)
        G1(13, a0, false, 5); SCHED(); pack_sub<32>(pv, b0); PHI(b0, pk, 0, 4); RET(13);
        G1(14, a0, false, 6); SCHED(); if (!(warp & 2)) stash<16>(stl + 4096, ssw, pv); PHI(b0, pk, 4, 10); RET(14);
        G1(15, a0, false, 7); SCHED(); PHI(b0, pk, 10, 16); RET(15);
        if ((warp & 3) == 0) TS(wg, 2);

        G1(16, a1, true, 0); SCHED(); if (!(warp & 2)) stash<16>(stl, ssw, pk);
        mbar_wait(sb + B_GRDY, 0);
        float g_lo, g_hi;
        uint32_t tag;
        {
            const uint32_t ga = sb + OFF_G + (warp * 16 + (lane >> 2)) * 4;
            asm volatile("ld.shared.f32 %0, [%1];" : "=f"(g_lo) : "r"(ga) : "memory");
            asm volatile("ld.shared.f32 %0, [%1];" : "=f"(g_hi) : "r"(ga + 32) : "memory");
            asm volatile("ld.shared.u32 %0, [%1];" : "=r"(tag) : "r"(sb + OFF_EPOCH) : "memory");
        }
        float* const kvp = g_kvacc + (((tag & 1) * 8 + j) * 4 + (warp & 3)) * 272;
        tag = (tag + 1) & 1;
        const uint32_t m_lo = pack2(1.f - g_lo, 1.f - g_lo), m_hi = pack2(1.f - g_hi, 1.f - g_hi);
        RET(16);
        pin(a0);
        G1(17, a1, true, 1); SCHED(); H_EPI(a0, fh0, 0, 16, 0, 32); RET(17);
        G1(18, a1, true, 2); KV_ROUND(_z); RET2(18);
        G1(19, a1, true, 3); SCHED(); send_h<0, 1>(fh0, hsend); RET(19);
        G1(20, a1, true, 4); SCHED(); if (warp & 2) { stash<16>(stl, ssw, pk); stash<16>(stl + 4096, ssw, pv); } RET(20);
        G1(21, a1, true, 5); KV_ROUND(); RET2(21);
        G1(22, a1, true, 6); RET(22);
        pin(kv); pin(zs);
        G1(23, a1, true, 7); SCHED();
#define KV_RED(W) do { asm volatile("red.global.add.v4.f32 [%0], {%1,%2,%3,%4};" :: "l"(kvp + lane * 4), "f"(kv[8 * W]), "f"(kv[8 * W + 1]), "f"(kv[8 * W + 2]), "f"(kv[8 * W + 3]) : "memory"); \
                       asm volatile("red.global.add.v4.f32 [%0], {%1,%2,%3,%4};" :: "l"(kvp + 128 + lane * 4), "f"(kv[8 * W + 4]), "f"(kv[8 * W + 5]), "f"(kv[8 * W + 6]), "f"(kv[8 * W + 7]) : "memory"); } while (0)
        if ((warp & 3) == 0) KV_RED(0); else if ((warp & 3) == 1) KV_RED(1); else if ((warp & 3) == 2) KV_RED(2); else KV_RED(3);
        if ((lane & 3) == 0) {
            asm volatile("red.global.add.f32 [%0], %1;" :: "l"(kvp + 256 + (lane >> 2)), "f"(zs[0]) : "memory");
            asm volatile("red.global.add.f32 [%0], %1;" :: "l"(kvp + 264 + (lane >> 2)), "f"(zs[2]) : "memory");
        }
        __syncwarp();
        if (lane == 0) mbar_arrive(sb + B_KVDONE);
        RET(23);
        if ((warp & 3) == 0) TS(wg, 3);

        G1(24, a2_, false, 0); SCHED(); send_h<1, 2>(fh0, hsend); RET(24);
        pin(a1);
        G1(25, a2_, false, 1); SCHED(); send_h<2, 3>(fh0, hsend); H_EPI(a1, fh3, 0, 8, 32, 48); RET(25);
        G1(26, a2_, false, 2); SCHED(); send_h<3, 4>(fh0, hsend); SENT_H(0); PHI(a1, fo, 0, 4); RET(26);
        G1(27, a2_, false, 3); SCHED(); send_h<0, 1>(fh3, hsend + 4 * 1024 - (j & 1) * 1020); PHI(a1, fo, 4, 8); RET(27);
        G1(28, a2_, false, 4); SCHED(); send_h<1, 2>(fh3, hsend + 4 * 1024 - (j & 1) * 1020); SENT_H(1); PHI(a1, fo, 8, 12); RET(28);
        G1(29, a2_, false, 5); SCHED(); PHI(a1, fo, 12, 16); RET(29);
        G1(30, a2_, false, 6); RET(30);
        G1(31, a2_, false, 7); RET(31);
        if ((warp & 3) == 0) TS(wg, 4);

        float on[4][12];
#define O_SCALE(h) do { const float s_lo = __fdividef(g_lo, on[h][8] + 1e-6f), s_hi = __fdividef(g_hi, on[h][10] + 1e-6f); \
            const uint32_t sl_ = pack2(s_lo, s_lo), sh_ = pack2(s_hi, s_hi); \
            fo[4 * h] = keep(hmul2(pack2(on[h][0], on[h][1]), sl_)); fo[4 * h + 1] = keep(hmul2(pack2(on[h][2], on[h][3]), sh_)); \
            fo[4 * h + 2] = keep(hmul2(pack2(on[h][4], on[h][5]), sl_)); fo[4 * h + 3] = keep(hmul2(pack2(on[h][6], on[h][7]), sh_)); } while (0)
        uint4* const lsend = g_lx + (size_t)(r * 8 + j) * 2048 + warp * 128 + lane;
        const uint4* const lrecv = g_lx + (size_t)(r * 8 + (j ^ 1)) * 2048 + warp * 128 + lane;
        G1(32, a3, false, 0); RET(32);
        pin(a2_);
        G1(33, a3, false, 1); SCHED(); H_EPI(a2_, fh1, 0, 16, 0, 32); send_h<0, 1>(fh1, hsend + 2 * 1024); RET(33);
        G1(34, a3, false, 2); SCHED(); send_h<1, 3>(fh1, hsend + 2 * 1024); RET(34);
        if (elect) mbar_arrive(sb + B_XFREE);
        G1(35, a3, false, 3); SCHED(); send_h<3, 4>(fh1, hsend + 2 * 1024); SENT_H(2);
        if ((warp & 3) == 0) TS(wg, 5);
        mbar_wait(sb + B_KVRDY, 0);
        if ((warp & 3) == 0) TS(wg, 6);
        wg_fence();
#define O_MMA(h) wg_rs24_z<OFF_STG / 16 + (h) * 48 + (8u << 16), 16>(on[h], fo[4 * (h)], fo[4 * (h) + 1], fo[4 * (h) + 2], fo[4 * (h) + 3], sbd)
        O_MMA(0); O_MMA(1); O_MMA(2); O_MMA(3);
        wg_commit();
        RET2(35);
        G1(36, a3, false, 4); RET(36);
        pin(on[0]); pin(on[1]); pin(on[2]); pin(on[3]);
        release(B_EEMPTY + 16);
        G1(37, a3, false, 5); SCHED(); O_SCALE(0); O_SCALE(1); O_SCALE(2); O_SCALE(3); RET(37);
        if (elect) mbar_arrive(sb + B_XFREE + 8);
        G1(38, a3, false, 6); SCHED(); send_frag<0, 2>(fo, lsend, tag); RET(38);
        release(B_EEMPTY);
        G1(39, a3, false, 7); SCHED(); send_frag<2, 4>(fo, lsend, tag); RET(39);
        release(B_EEMPTY + 8);
        if ((warp & 3) == 0) TS(wg, 7);

#define G2S(S, acc, U) stage_ss<(U) * 1024, S_B(S), false, (S) == 45>(acc, xlo, sbd)
#define G2R(S, acc, F) stage_rs<S_B(S), (S) == 40>(acc, F, sbd)
#define H_WAIT(P) do { mbar_wait(sb + B_XFULL + 8 * (P), 1); if (PROF && tid == 0) TS2(150 + (P)); } while (0)
        const int p = j >> 1, pw = (p & 2) ^ 2;
        const bool own = wg == (p & 1);
        uint4* const pbase = g_part + (size_t)(r * 2 + (j & 1)) * 16384 + (warp & 3) * 256 + lane;

        float p1[64], p2[64];
        uint32_t po[16], ph2[16];
        G2R(40, p1, fo); RET(40);
        release(B_EEMPTY + 24);
        pin(a3);
        H_WAIT(0); G2S(41, p1, 0); SCHED(); H_EPI(a3, fh2, 0, 16, 0, 32); send_frag<0, 2>(fh2, lsend + 1024, tag); RET(41);
        G2S(42, p1, 1); SCHED(); recv_issue(po, lrecv); send_frag<2, 4>(fh2, lsend + 1024, tag); RET(42);
        H_WAIT(4); G2S(43, p1, 4); RET(43);
        G2R(44, p1, fh2); RET(44);
        G2S(45, p2, 0); SCHED(); recv_check(po, lrecv, tag); recv_issue(ph2, lrecv + 1024); RET(45);
        G2R(46, p1, po); RET(46);
        H_WAIT(2); G2S(47, p1, 2); RET(47);
        G2S(48, p1, 3); SCHED(); recv_check(ph2, lrecv + 1024, tag); RET(48);
        G2R(49, p1, ph2); RET(49);
        if ((warp & 3) == 0) TS(wg, 8);
        uint32_t sp[32], qa[32], qb[32];
        uint4* const s1 = pbase + (((pw + wg) * 4 + p) << 10);
        G2R(50, p2, fo); RET(50);
        pin(p1);
        G2R(51, p2, po); SCHED(); pack_sub<0>(sp, p1); send_frag<0, 2>(sp, s1, tag); RET(51);
        G2R(52, p2, fh2); SCHED(); send_frag<2, 5>(sp, s1, tag); RET(52);
        if (elect) mbar_arrive(sb + B_XFREE + 16);
        G2R(53, p2, ph2); SCHED(); send_frag<5, 8>(sp, s1, tag); RET(53);
        const uint4* ra = pbase + ((p * 4 + pw) << 10);
        const uint4* rc = pbase + ((p * 4 + (p ^ 1)) << 10);
        if (own) mbar_wait(sb + B_AHEAD, 0);
        G2S(54, p2, 1); RET(54);
        G2S(55, p2, 2); RET(55);
        G2S(56, p2, 3); RET(56);
        G2S(57, p2, 4); SCHED();
        if ((warp & 3) == 0) TS(wg, 9);
        if (!own && elect) {
            mbar_arrive(sb + B_AHEAD);
            mbar_wait(sb + B_XFREE + 16, 0);
            mbar_expect(sb + B_PART, 32768);
            asm volatile("cp.async.bulk.shared::cluster.global.mbarrier::complete_tx::bytes [%0], [%1], %2, [%3];"
                         :: "r"(sb + OFF_RING), "l"(ra), "r"(32768), "r"(sb + B_PART) : "memory");
        }
        wg_wait<0>();
        pin(p2);
        if ((warp & 3) == 0) TS(wg, 11);
        if (!own) {
            pack_sub<0>(sp, p2); send_frag<0, 8>(sp, pbase + (((p ^ 1) * 4 + p) << 10), tag);
        } else {
            recv_issue(sp, rc);
            mbar_wait(sb + B_PART, 0);
            const uint32_t pa = sb + OFF_RING + (warp & 3) * 4096 + lane * 16;
#pragma unroll
            for (int v = 0; v < 8; v++) {
                asm volatile("ld.shared.v4.u32 {%0,%1,%2,%3}, [%4];" : "=r"(qa[4 * v]), "=r"(qa[4 * v + 1]), "=r"(qa[4 * v + 2]), "=r"(qa[4 * v + 3]) : "r"(pa + v * 512) : "memory");
                asm volatile("ld.shared.v4.u32 {%0,%1,%2,%3}, [%4];" : "=r"(qb[4 * v]), "=r"(qb[4 * v + 1]), "=r"(qb[4 * v + 2]), "=r"(qb[4 * v + 3]) : "r"(pa + 16384 + v * 512) : "memory");
            }
            recv_check(qa, ra, tag); recv_check(qb, ra + 1024, tag);
#pragma unroll
            for (int i = 0; i < 32; i++) qa[i] = hadd2(qa[i], qb[i]);
            accum(qa, p2);
            pack_sub<0>(qb, p2);
            if ((warp & 3) == 0) TS(wg, 12);
            recv_check(sp, rc, tag);
            if ((warp & 3) == 0) TS(wg, 13);
            uint32_t f0[16], f1[16];
#pragma unroll
            for (int i = 0; i < 16; i++) { f0[i] = hadd2(qb[i], sp[i]); f1[i] = hadd2(qb[16 + i], sp[16 + i]); }
            const uint32_t slab = sb + OFF_X + 2 * 16384 + wg * 8192;
            stash<16>(slab + srow, ssw, f0); stash<16>(slab + 16384 + srow, ssw, f1);
            __syncwarp();
            __nv_bfloat16* op = out + (size_t)(r * 128 + warp * 16 + (lane >> 4)) * kD + (j & 1) * 256 + (p & 2) * 64 + (lane & 15) * 8;
#pragma unroll
            for (int i = 0; i < 8; i++) {
                const int row = i * 2 + (lane >> 4);
                uint4 v;
                asm volatile("ld.shared.v4.u32 {%0,%1,%2,%3}, [%4];" : "=r"(v.x), "=r"(v.y), "=r"(v.z), "=r"(v.w)
                             : "r"(slab + (lane & 8) * 2048 + ((warp & 3) * 16 + row) * 128 + (((lane & 7) ^ (row & 7)) << 4)) : "memory");
                *(uint4*)(op + i * 2 * kD) = v;
            }
        }
        if ((warp & 3) == 0) { TS(wg, 14); TSG(wg, 31); }
    }
}

typedef CUresult (*EncodeFn)(CUtensorMap*, CUtensorMapDataType, cuuint32_t, void*, const cuuint64_t*, const cuuint64_t*, const cuuint32_t*,
                             const cuuint32_t*, CUtensorMapInterleave, CUtensorMapSwizzle, CUtensorMapL2promotion, CUtensorMapFloatOOBfill);

static void encode(EncodeFn fn, CUtensorMap* m, int rank, const void* base, const cuuint64_t (&gd)[5], const cuuint64_t (&gs)[4],
                   const cuuint32_t (&bd)[5], CUtensorMapSwizzle sw) {
    cuuint32_t es[5] = {1, 1, 1, 1, 1};
    fn(m, CU_TENSOR_MAP_DATA_TYPE_BFLOAT16, rank, const_cast<void*>(base), gd, gs, bd, es, CU_TENSOR_MAP_INTERLEAVE_NONE, sw,
       CU_TENSOR_MAP_L2_PROMOTION_L2_128B, CU_TENSOR_MAP_FLOAT_OOB_FILL_NONE);
}

extern "C" void kernel_launch(void* const* d_in, const int* in_sizes, int n_in, void* d_out, int out_size) {
    const char* x = (const char*)d_in[0];
    const char* wqkv = (const char*)d_in[1];
    const char* wo = (const char*)d_in[2];
    const char* wg = (const char*)d_in[4];
    const char* wu = (const char*)d_in[5];
    const char* wd = (const char*)d_in[6];
    void* fnp = nullptr;
    cudaDriverEntryPointQueryResult qr;
    cudaGetDriverEntryPoint("cuTensorMapEncodeTiled", &fnp, cudaEnableDefault, &qr);
    EncodeFn fn = (EncodeFn)fnp;
    Maps maps;
    const char* lo = wg < wu ? wg : wu;
    const uint64_t diff = wg < wu ? (uint64_t)(wu - wg) : (uint64_t)(wg - wu);
    const CUtensorMapSwizzle S128 = CU_TENSOR_MAP_SWIZZLE_128B, S64 = CU_TENSOR_MAP_SWIZZLE_64B;
    encode(fn, &maps.x, 2, x, {512, 2048, 1, 1}, {1024, 0, 0}, {64, 128, 1, 1}, S128);
    encode(fn, &maps.gu, 3, lo, {1792, 512, 2, 1}, {3584, diff, 0}, {64, 64, 2, 1}, S128);
    encode(fn, &maps.kv, 3, wqkv, {512, 512, 3, 1}, {3072, 1024, 0}, {64, 64, 2, 1}, S128);
    encode(fn, &maps.q64, 3, wqkv, {32, 512, 48, 1}, {3072, 64, 0}, {32, 64, 2, 1}, S64);
    encode(fn, &maps.gu64, 3, lo, {1792, 512, 2, 1}, {3584, diff, 0}, {32, 64, 2, 1}, S64);
    encode(fn, &maps.wdw, 3, wd, {64, 1792, 8, 1}, {1024, 128, 0}, {64, 64, 2, 1}, S128);
    encode(fn, &maps.wow, 3, wo, {64, 512, 8}, {1024, 128}, {64, 64, 2}, S128);
    encode(fn, &maps.wdp, 5, wd, {512, 2, 4, 4, 56}, {1024, 8192, 2048, 32768}, {64, 2, 4, 4, 2}, S128);
    encode(fn, &maps.wdph, 5, wd, {512, 2, 4, 4, 56}, {1024, 8192, 2048, 32768}, {64, 2, 4, 4, 1}, S128);
    void* hx = nullptr;
    cudaGetSymbolAddress(&hx, g_hx);
    encode(fn, &maps.hx, 2, hx, {64, 16 * 4 * 5 * 128}, {128}, {64, 128}, S128);
    encode(fn, &maps.hx2, 2, hx, {64, 16 * 4 * 5 * 128}, {128}, {64, 256}, S128);
    cudaFuncSetAttribute(fused_kernel, cudaFuncAttributeMaxDynamicSharedMemorySize, SMEM_BYTES);
    cudaLaunchConfig_t cfg = {};
    cfg.gridDim = dim3(128);
    cfg.blockDim = dim3(384);
    cfg.dynamicSmemBytes = SMEM_BYTES;
    cfg.stream = cudaStreamPerThread;
    cudaLaunchAttribute at[1];
    at[0].id = cudaLaunchAttributeClusterDimension;
    at[0].val.clusterDim.x = 2; at[0].val.clusterDim.y = 1; at[0].val.clusterDim.z = 1;
    cfg.attrs = at;
    cfg.numAttrs = MC ? 1 : 0;
    cudaLaunchKernelEx(&cfg, fused_kernel, maps, (const __nv_bfloat16*)d_in[0], (const __nv_bfloat16*)d_in[7], wqkv, wg, wu, wd, wo, (__nv_bfloat16*)d_out);
}
```

```cpp
#include <cuda_runtime.h>
#include <cuda.h>
#include <cuda_bf16.h>
#include <stdint.h>

#define PFMODE 1
#define PHI_SAT 0
#define EXPT 0
#define PROF 0

namespace {

constexpr int kD = 512;
constexpr uint32_t OFF_X = 0, OFF_STG = 131072, OFF_RING = 147456, OFF_MISC = 229376;
constexpr uint32_t B_FULL = OFF_MISC, B_EMPTY = OFF_MISC + 40, B_XFULL = OFF_MISC + 80;
constexpr uint32_t B_GRDY = OFF_MISC + 152, B_KVDONE = OFF_MISC + 160, B_KVRDY = OFF_MISC + 168;
constexpr uint32_t B_HSENT = OFF_MISC + 176, B_XFREE = OFF_MISC + 200;
constexpr uint32_t OFF_EPOCH = OFF_MISC + 240, OFF_G = OFF_MISC + 256;
constexpr uint32_t B_AHEAD = OFF_MISC + 248, B_PART = OFF_MISC + 232, B_LAST = OFF_MISC + 224, B_RFREE = OFF_MISC + 960;
constexpr uint32_t OFF_ONES = OFF_MISC + 768;
constexpr uint32_t B_EFULL = OFF_MISC + 896, B_EEMPTY = OFF_MISC + 928;
constexpr uint32_t SMEM_BYTES = OFF_MISC + 968;
constexpr uint32_t SPIN_GLOBAL = 1u << 14;

struct alignas(64) Maps { CUtensorMap x, gu, kv, q64, gu64, wdw, wow, wdp, wdph, hx, hx2; };

}

__device__ uint4 g_part[16 * 2 * 4 * 4 * 1024];
__device__ uint4 g_hx[16 * 4 * 5 * 1024];
__device__ uint4 g_lx[16 * 8 * 2 * 1024];
__device__ unsigned g_hflag[128 * 8];
__device__ uint4 g_gx[16 * 32];
__device__ float g_kvacc[2 * 8 * 4 * 272];
__device__ unsigned g_kvcnt[8 * 32];
__device__ unsigned g_epoch[128];
#define TS(role, idx)
#define TS2(idx)
#define TSG(role, idx)

namespace {

__device__ __forceinline__ void mbar_init(uint32_t bar, uint32_t cnt) { asm volatile("mbarrier.init.shared::cta.b64 [%0], %1;" :: "r"(bar), "r"(cnt) : "memory"); }
__device__ __forceinline__ void mbar_expect(uint32_t bar, uint32_t bytes) { asm volatile("mbarrier.arrive.expect_tx.shared::cta.b64 _, [%0], %1;" :: "r"(bar), "r"(bytes) : "memory"); }
__device__ __forceinline__ void mbar_arrive(uint32_t bar) { asm volatile("mbarrier.arrive.shared::cta.b64 _, [%0];" :: "r"(bar) : "memory"); }
__device__ __forceinline__ void mbar_arrive_cta(uint32_t bar, uint32_t cta) {
    asm volatile("{\n.reg .b32 ra;\nmapa.shared::cluster.u32 ra, %0, %1;\nmbarrier.arrive.shared::cluster.b64 _, [ra];\n}" :: "r"(bar), "r"(cta) : "memory");
}
__device__ __forceinline__ void mbar_wait(uint32_t bar, uint32_t parity) {
    asm volatile("{\n.reg .pred p;\n.reg .u32 c;\n"
                 "mbarrier.try_wait.parity.shared::cta.b64 p, [%0], %1;\n@p bra DONE;\n"
                 "mov.u32 c, 0;\nLAB_WAIT:\nmbarrier.try_wait.parity.shared::cta.b64 p, [%0], %1;\n@p bra DONE;\n"
                 "add.u32 c, c, 1;\nsetp.lt.u32 p, c, 65536;\n@p bra LAB_WAIT;\nDONE:\n}" :: "r"(bar), "r"(parity) : "memory");
}
__device__ __forceinline__ void tma2(uint32_t dst, const CUtensorMap* m, int c0, int c1, uint32_t bar) {
    asm volatile("cp.async.bulk.tensor.2d.shared::cluster.global.mbarrier::complete_tx::bytes [%0], [%1, {%3, %4}], [%2];"
        :: "r"(dst), "l"(m), "r"(bar), "r"(c0), "r"(c1) : "memory");
}
__device__ __forceinline__ void tmaw2(uint32_t dst, const CUtensorMap* m, int c0, int c1, uint32_t bar) {
    tma2(dst, m, c0, c1, bar);
}
__device__ __forceinline__ void tmaw3(uint32_t dst, const CUtensorMap* m, int c0, int c1, int c2, uint32_t bar) {
    asm volatile("cp.async.bulk.tensor.3d.shared::cluster.global.mbarrier::complete_tx::bytes [%0], [%1, {%3, %4, %5}], [%2];"
        :: "r"(dst), "l"(m), "r"(bar), "r"(c0), "r"(c1), "r"(c2) : "memory");
}
__device__ __forceinline__ void tmaw5(uint32_t dst, const CUtensorMap* m, int c0, int c4, uint32_t bar) {
    asm volatile("cp.async.bulk.tensor.5d.shared::cluster.global.mbarrier::complete_tx::bytes [%0], [%1, {%3, %5, %5, %5, %4}], [%2];"
        :: "r"(dst), "l"(m), "r"(bar), "r"(c0), "r"(c4), "r"(0) : "memory");
}
__device__ __forceinline__ void wg_fence() { asm volatile("wgmma.fence.sync.aligned;" ::: "memory"); }
__device__ __forceinline__ void wg_commit() { asm volatile("wgmma.commit_group.sync.aligned;" ::: "memory"); }
template <int N> __device__ __forceinline__ void wg_wait() { asm volatile("wgmma.wait_group.sync.aligned %0;" :: "n"(N) : "memory"); }
template <int N> __device__ __forceinline__ void pin(float (&d)[N]) {
#pragma unroll
    for (int i = 0; i < N; i++) asm volatile("" : "+f"(d[i]) :: "memory");
}
__device__ __forceinline__ uint32_t pack2(float lo, float hi) { uint32_t r; asm("cvt.rn.bf16x2.f32 %0, %1, %2;" : "=r"(r) : "f"(hi), "f"(lo)); return r; }
__device__ __forceinline__ uint32_t keep(uint32_t v) { asm volatile("" : "+r"(v)); return v; }
__device__ __forceinline__ uint32_t hadd2(uint32_t a, uint32_t b) { uint32_t r; asm("add.bf16x2 %0, %1, %2;" : "=r"(r) : "r"(a), "r"(b)); return r; }
__device__ __forceinline__ uint32_t hmul2(uint32_t a, uint32_t b) { uint32_t r; asm("mul.bf16x2 %0, %1, %2;" : "=r"(r) : "r"(a), "r"(b)); return r; }
__device__ __forceinline__ uint32_t phi2(float t0, float t1) {
    float e0, e1;
    asm("ex2.approx.ftz.f32 %0, %1;" : "=f"(e0) : "f"(t0 * 1.4426950408889634f));
    asm("ex2.approx.ftz.f32 %0, %1;" : "=f"(e1) : "f"(t1 * 1.4426950408889634f));
    uint32_t e = pack2(e0, e1), t = pack2(t0, t1), r;
    asm("min.bf16x2 %0, %0, %1;" : "+r"(e) : "r"(0x3f803f80u));
    asm("max.bf16x2 %0, %0, %1;" : "+r"(t) : "r"(0x35863586u));
    asm("add.bf16x2 %0, %1, %2;" : "=r"(r) : "r"(e), "r"(t));
    return r;
}
__device__ __forceinline__ void stsm4(uint32_t a, uint32_t r0, uint32_t r1, uint32_t r2, uint32_t r3) {
    asm volatile("stmatrix.sync.aligned.m8n8.x4.shared.b16 [%0], {%1,%2,%3,%4};" :: "r"(a), "r"(r0), "r"(r1), "r"(r2), "r"(r3) : "memory");
}
__device__ __forceinline__ float bf_lo(uint32_t w) { return __uint_as_float(w << 16); }
__device__ __forceinline__ float bf_hi(uint32_t w) { return __uint_as_float(w & 0xffff0000u); }
__device__ __forceinline__ void st_pkt(uint4* p, uint32_t w0, uint32_t w1, uint32_t w2, uint32_t w3) {
    asm volatile("{\n.reg .b64 lo, hi;\n.reg .b128 v;\nmov.b64 lo, {%1, %2};\nmov.b64 hi, {%3, %4};\nmov.b128 v, {lo, hi};\nst.relaxed.gpu.global.b128 [%0], v;\n}"
        :: "l"(p), "r"(w0), "r"(w1), "r"(w2), "r"(w3) : "memory");
}
__device__ __forceinline__ void ld_pkt(const uint4* p, uint32_t& w0, uint32_t& w1, uint32_t& w2, uint32_t& w3) {
    asm volatile("{\n.reg .b64 lo, hi;\n.reg .b128 v;\nld.relaxed.gpu.global.b128 v, [%4];\nmov.b128 {lo, hi}, v;\nmov.b64 {%0, %1}, lo;\nmov.b64 {%2, %3}, hi;\n}"
        : "=r"(w0), "=r"(w1), "=r"(w2), "=r"(w3) : "l"(p) : "memory");
}

template <uint32_t AO, uint32_t BO, uint32_t BH> __device__ __forceinline__ void wg_ss128(float (&d)[64], uint32_t ab, uint32_t bb) {
    asm volatile("{\n.reg .b64 da, db;\n.reg .b32 ta, tb, th, ah;\nadd.u32 ta, %64, %66;\nadd.u32 tb, %65, %67;\nmov.b32 th, %68;\nmov.b32 ah, 0x40000040;\nmov.b64 da, {ta, ah};\nmov.b64 db, {tb, th};\n"
        "wgmma.mma_async.sync.aligned.m64n128k16.f32.bf16.bf16 {%0,%1,%2,%3,%4,%5,%6,%7,%8,%9,%10,%11,%12,%13,%14,%15,%16,%17,%18,%19,%20,%21,%22,%23,%24,%25,%26,%27,%28,%29,%30,%31,%32,%33,%34,%35,%36,%37,%38,%39,%40,%41,%42,%43,%44,%45,%46,%47,%48,%49,%50,%51,%52,%53,%54,%55,%56,%57,%58,%59,%60,%61,%62,%63}, da, db, 1, 1, 1, 0, 1;\n}\n"
        : "+f"(d[0]),"+f"(d[1]),"+f"(d[2]),"+f"(d[3]),"+f"(d[4]),"+f"(d[5]),"+f"(d[6]),"+f"(d[7]),"+f"(d[8]),"+f"(d[9]),"+f"(d[10]),"+f"(d[11]),"+f"(d[12]),"+f"(d[13]),"+f"(d[14]),"+f"(d[15]),"+f"(d[16]),"+f"(d[17]),"+f"(d[18]),"+f"(d[19]),"+f"(d[20]),"+f"(d[21]),"+f"(d[22]),"+f"(d[23]),"+f"(d[24]),"+f"(d[25]),"+f"(d[26]),"+f"(d[27]),"+f"(d[28]),"+f"(d[29]),"+f"(d[30]),"+f"(d[31]),"+f"(d[32]),"+f"(d[33]),"+f"(d[34]),"+f"(d[35]),"+f"(d[36]),"+f"(d[37]),"+f"(d[38]),"+f"(d[39]),"+f"(d[40]),"+f"(d[41]),"+f"(d[42]),"+f"(d[43]),"+f"(d[44]),"+f"(d[45]),"+f"(d[46]),"+f"(d[47]),"+f"(d[48]),"+f"(d[49]),"+f"(d[50]),"+f"(d[51]),"+f"(d[52]),"+f"(d[53]),"+f"(d[54]),"+f"(d[55]),"+f"(d[56]),"+f"(d[57]),"+f"(d[58]),"+f"(d[59]),"+f"(d[60]),"+f"(d[61]),"+f"(d[62]),"+f"(d[63])
        : "r"(ab), "r"(bb), "n"(AO), "n"(BO), "n"(BH));
}
template <uint32_t AO, uint32_t BO, uint32_t BH> __device__ __forceinline__ void wg_ss128_z(float (&d)[64], uint32_t ab, uint32_t bb) {
    asm volatile("{\n.reg .b64 da, db;\n.reg .b32 ta, tb, th, ah;\nadd.u32 ta, %64, %66;\nadd.u32 tb, %65, %67;\nmov.b32 th, %68;\nmov.b32 ah, 0x40000040;\nmov.b64 da, {ta, ah};\nmov.b64 db, {tb, th};\n"
        "wgmma.mma_async.sync.aligned.m64n128k16.f32.bf16.bf16 {%0,%1,%2,%3,%4,%5,%6,%7,%8,%9,%10,%11,%12,%13,%14,%15,%16,%17,%18,%19,%20,%21,%22,%23,%24,%25,%26,%27,%28,%29,%30,%31,%32,%33,%34,%35,%36,%37,%38,%39,%40,%41,%42,%43,%44,%45,%46,%47,%48,%49,%50,%51,%52,%53,%54,%55,%56,%57,%58,%59,%60,%61,%62,%63}, da, db, 0, 1, 1, 0, 1;\n}\n"
        : "=f"(d[0]),"=f"(d[1]),"=f"(d[2]),"=f"(d[3]),"=f"(d[4]),"=f"(d[5]),"=f"(d[6]),"=f"(d[7]),"=f"(d[8]),"=f"(d[9]),"=f"(d[10]),"=f"(d[11]),"=f"(d[12]),"=f"(d[13]),"=f"(d[14]),"=f"(d[15]),"=f"(d[16]),"=f"(d[17]),"=f"(d[18]),"=f"(d[19]),"=f"(d[20]),"=f"(d[21]),"=f"(d[22]),"=f"(d[23]),"=f"(d[24]),"=f"(d[25]),"=f"(d[26]),"=f"(d[27]),"=f"(d[28]),"=f"(d[29]),"=f"(d[30]),"=f"(d[31]),"=f"(d[32]),"=f"(d[33]),"=f"(d[34]),"=f"(d[35]),"=f"(d[36]),"=f"(d[37]),"=f"(d[38]),"=f"(d[39]),"=f"(d[40]),"=f"(d[41]),"=f"(d[42]),"=f"(d[43]),"=f"(d[44]),"=f"(d[45]),"=f"(d[46]),"=f"(d[47]),"=f"(d[48]),"=f"(d[49]),"=f"(d[50]),"=f"(d[51]),"=f"(d[52]),"=f"(d[53]),"=f"(d[54]),"=f"(d[55]),"=f"(d[56]),"=f"(d[57]),"=f"(d[58]),"=f"(d[59]),"=f"(d[60]),"=f"(d[61]),"=f"(d[62]),"=f"(d[63])
        : "r"(ab), "r"(bb), "n"(AO), "n"(BO), "n"(BH));
}
template <uint32_t BO, uint32_t BH> __device__ __forceinline__ void wg_rs128(float (&d)[64], uint32_t a0, uint32_t a1, uint32_t a2, uint32_t a3, uint32_t bb) {
    asm volatile("{\n.reg .b64 db;\n.reg .b32 tb, th;\nadd.u32 tb, %68, %69;\nmov.b32 th, %70;\nmov.b64 db, {tb, th};\n"
        "wgmma.mma_async.sync.aligned.m64n128k16.f32.bf16.bf16 {%0,%1,%2,%3,%4,%5,%6,%7,%8,%9,%10,%11,%12,%13,%14,%15,%16,%17,%18,%19,%20,%21,%22,%23,%24,%25,%26,%27,%28,%29,%30,%31,%32,%33,%34,%35,%36,%37,%38,%39,%40,%41,%42,%43,%44,%45,%46,%47,%48,%49,%50,%51,%52,%53,%54,%55,%56,%57,%58,%59,%60,%61,%62,%63}, {%64,%65,%66,%67}, db, 1, 1, 1, 1;\n}\n"
        : "+f"(d[0]),"+f"(d[1]),"+f"(d[2]),"+f"(d[3]),"+f"(d[4]),"+f"(d[5]),"+f"(d[6]),"+f"(d[7]),"+f"(d[8]),"+f"(d[9]),"+f"(d[10]),"+f"(d[11]),"+f"(d[12]),"+f"(d[13]),"+f"(d[14]),"+f"(d[15]),"+f"(d[16]),"+f"(d[17]),"+f"(d[18]),"+f"(d[19]),"+f"(d[20]),"+f"(d[21]),"+f"(d[22]),"+f"(d[23]),"+f"(d[24]),"+f"(d[25]),"+f"(d[26]),"+f"(d[27]),"+f"(d[28]),"+f"(d[29]),"+f"(d[30]),"+f"(d[31]),"+f"(d[32]),"+f"(d[33]),"+f"(d[34]),"+f"(d[35]),"+f"(d[36]),"+f"(d[37]),"+f"(d[38]),"+f"(d[39]),"+f"(d[40]),"+f"(d[41]),"+f"(d[42]),"+f"(d[43]),"+f"(d[44]),"+f"(d[45]),"+f"(d[46]),"+f"(d[47]),"+f"(d[48]),"+f"(d[49]),"+f"(d[50]),"+f"(d[51]),"+f"(d[52]),"+f"(d[53]),"+f"(d[54]),"+f"(d[55]),"+f"(d[56]),"+f"(d[57]),"+f"(d[58]),"+f"(d[59]),"+f"(d[60]),"+f"(d[61]),"+f"(d[62]),"+f"(d[63])
        : "r"(a0), "r"(a1), "r"(a2), "r"(a3), "r"(bb), "n"(BO), "n"(BH));
}
template <uint32_t BO, uint32_t BH> __device__ __forceinline__ void wg_rs128_z(float (&d)[64], uint32_t a0, uint32_t a1, uint32_t a2, uint32_t a3, uint32_t bb) {
    asm volatile("{\n.reg .b64 db;\n.reg .b32 tb, th;\nadd.u32 tb, %68, %69;\nmov.b32 th, %70;\nmov.b64 db, {tb, th};\n"
        "wgmma.mma_async.sync.aligned.m64n128k16.f32.bf16.bf16 {%0,%1,%2,%3,%4,%5,%6,%7,%8,%9,%10,%11,%12,%13,%14,%15,%16,%17,%18,%19,%20,%21,%22,%23,%24,%25,%26,%27,%28,%29,%30,%31,%32,%33,%34,%35,%36,%37,%38,%39,%40,%41,%42,%43,%44,%45,%46,%47,%48,%49,%50,%51,%52,%53,%54,%55,%56,%57,%58,%59,%60,%61,%62,%63}, {%64,%65,%66,%67}, db, 0, 1, 1, 1;\n}\n"
        : "=f"(d[0]),"=f"(d[1]),"=f"(d[2]),"=f"(d[3]),"=f"(d[4]),"=f"(d[5]),"=f"(d[6]),"=f"(d[7]),"=f"(d[8]),"=f"(d[9]),"=f"(d[10]),"=f"(d[11]),"=f"(d[12]),"=f"(d[13]),"=f"(d[14]),"=f"(d[15]),"=f"(d[16]),"=f"(d[17]),"=f"(d[18]),"=f"(d[19]),"=f"(d[20]),"=f"(d[21]),"=f"(d[22]),"=f"(d[23]),"=f"(d[24]),"=f"(d[25]),"=f"(d[26]),"=f"(d[27]),"=f"(d[28]),"=f"(d[29]),"=f"(d[30]),"=f"(d[31]),"=f"(d[32]),"=f"(d[33]),"=f"(d[34]),"=f"(d[35]),"=f"(d[36]),"=f"(d[37]),"=f"(d[38]),"=f"(d[39]),"=f"(d[40]),"=f"(d[41]),"=f"(d[42]),"=f"(d[43]),"=f"(d[44]),"=f"(d[45]),"=f"(d[46]),"=f"(d[47]),"=f"(d[48]),"=f"(d[49]),"=f"(d[50]),"=f"(d[51]),"=f"(d[52]),"=f"(d[53]),"=f"(d[54]),"=f"(d[55]),"=f"(d[56]),"=f"(d[57]),"=f"(d[58]),"=f"(d[59]),"=f"(d[60]),"=f"(d[61]),"=f"(d[62]),"=f"(d[63])
        : "r"(a0), "r"(a1), "r"(a2), "r"(a3), "r"(bb), "n"(BO), "n"(BH));
}
template <uint32_t AO, uint32_t BO, uint32_t BH> __device__ __forceinline__ void wg_ss64t(float (&d)[32], uint32_t ab, uint32_t bb) {
    asm volatile("{\n.reg .b64 da, db;\n.reg .b32 ta, tb, th, ah;\nadd.u32 ta, %32, %34;\nadd.u32 tb, %33, %35;\nmov.b32 th, %36;\nmov.b32 ah, 0x40000040;\nmov.b64 da, {ta, ah};\nmov.b64 db, {tb, th};\n"
        "wgmma.mma_async.sync.aligned.m64n64k16.f32.bf16.bf16 {%0,%1,%2,%3,%4,%5,%6,%7,%8,%9,%10,%11,%12,%13,%14,%15,%16,%17,%18,%19,%20,%21,%22,%23,%24,%25,%26,%27,%28,%29,%30,%31}, da, db, 1, 1, 1, 1, 1;\n}\n"
        : "+f"(d[0]),"+f"(d[1]),"+f"(d[2]),"+f"(d[3]),"+f"(d[4]),"+f"(d[5]),"+f"(d[6]),"+f"(d[7]),"+f"(d[8]),"+f"(d[9]),"+f"(d[10]),"+f"(d[11]),"+f"(d[12]),"+f"(d[13]),"+f"(d[14]),"+f"(d[15]),"+f"(d[16]),"+f"(d[17]),"+f"(d[18]),"+f"(d[19]),"+f"(d[20]),"+f"(d[21]),"+f"(d[22]),"+f"(d[23]),"+f"(d[24]),"+f"(d[25]),"+f"(d[26]),"+f"(d[27]),"+f"(d[28]),"+f"(d[29]),"+f"(d[30]),"+f"(d[31])
        : "r"(ab), "r"(bb), "n"(AO), "n"(BO), "n"(BH));
}
template <uint32_t AO, uint32_t BO, uint32_t BH> __device__ __forceinline__ void wg_ss64t_z(float (&d)[32], uint32_t ab, uint32_t bb) {
    asm volatile("{\n.reg .b64 da, db;\n.reg .b32 ta, tb, th, ah;\nadd.u32 ta, %32, %34;\nadd.u32 tb, %33, %35;\nmov.b32 th, %36;\nmov.b32 ah, 0x40000040;\nmov.b64 da, {ta, ah};\nmov.b64 db, {tb, th};\n"
        "wgmma.mma_async.sync.aligned.m64n64k16.f32.bf16.bf16 {%0,%1,%2,%3,%4,%5,%6,%7,%8,%9,%10,%11,%12,%13,%14,%15,%16,%17,%18,%19,%20,%21,%22,%23,%24,%25,%26,%27,%28,%29,%30,%31}, da, db, 0, 1, 1, 1, 1;\n}\n"
        : "=f"(d[0]),"=f"(d[1]),"=f"(d[2]),"=f"(d[3]),"=f"(d[4]),"=f"(d[5]),"=f"(d[6]),"=f"(d[7]),"=f"(d[8]),"=f"(d[9]),"=f"(d[10]),"=f"(d[11]),"=f"(d[12]),"=f"(d[13]),"=f"(d[14]),"=f"(d[15]),"=f"(d[16]),"=f"(d[17]),"=f"(d[18]),"=f"(d[19]),"=f"(d[20]),"=f"(d[21]),"=f"(d[22]),"=f"(d[23]),"=f"(d[24]),"=f"(d[25]),"=f"(d[26]),"=f"(d[27]),"=f"(d[28]),"=f"(d[29]),"=f"(d[30]),"=f"(d[31])
        : "r"(ab), "r"(bb), "n"(AO), "n"(BO), "n"(BH));
}
template <uint32_t AO, uint32_t BO, uint32_t BH> __device__ __forceinline__ void wg_ss8t(float (&d)[4], uint32_t ab, uint32_t bb) {
    asm volatile("{\n.reg .b64 da, db;\n.reg .b32 ta, tb, th, ah;\nadd.u32 ta, %4, %6;\nadd.u32 tb, %5, %7;\nmov.b32 th, %8;\nmov.b32 ah, 0x40000040;\nmov.b64 da, {ta, ah};\nmov.b64 db, {tb, th};\n"
        "wgmma.mma_async.sync.aligned.m64n8k16.f32.bf16.bf16 {%0,%1,%2,%3}, da, db, 1, 1, 1, 1, 0;\n}\n"
        : "+f"(d[0]),"+f"(d[1]),"+f"(d[2]),"+f"(d[3])
        : "r"(ab), "r"(bb), "n"(AO), "n"(BO), "n"(BH));
}
template <uint32_t AO, uint32_t BO, uint32_t BH> __device__ __forceinline__ void wg_ss8t_z(float (&d)[4], uint32_t ab, uint32_t bb) {
    asm volatile("{\n.reg .b64 da, db;\n.reg .b32 ta, tb, th, ah;\nadd.u32 ta, %4, %6;\nadd.u32 tb, %5, %7;\nmov.b32 th, %8;\nmov.b32 ah, 0x40000040;\nmov.b64 da, {ta, ah};\nmov.b64 db, {tb, th};\n"
        "wgmma.mma_async.sync.aligned.m64n8k16.f32.bf16.bf16 {%0,%1,%2,%3}, da, db, 0, 1, 1, 1, 0;\n}\n"
        : "=f"(d[0]),"=f"(d[1]),"=f"(d[2]),"=f"(d[3])
        : "r"(ab), "r"(bb), "n"(AO), "n"(BO), "n"(BH));
}
template <uint32_t BO, uint32_t BH> __device__ __forceinline__ void wg_rs24_z(float (&d)[12], uint32_t a0, uint32_t a1, uint32_t a2, uint32_t a3, uint32_t bb) {
    asm volatile("{\n.reg .b64 db;\n.reg .b32 tb, th;\nadd.u32 tb, %16, %17;\nmov.b32 th, %18;\nmov.b64 db, {tb, th};\n"
        "wgmma.mma_async.sync.aligned.m64n24k16.f32.bf16.bf16 {%0,%1,%2,%3,%4,%5,%6,%7,%8,%9,%10,%11}, {%12,%13,%14,%15}, db, 0, 1, 1, 0;\n}\n"
        : "=f"(d[0]),"=f"(d[1]),"=f"(d[2]),"=f"(d[3]),"=f"(d[4]),"=f"(d[5]),"=f"(d[6]),"=f"(d[7]),"=f"(d[8]),"=f"(d[9]),"=f"(d[10]),"=f"(d[11])
        : "r"(a0), "r"(a1), "r"(a2), "r"(a3), "r"(bb), "n"(BO), "n"(BH));
}

constexpr uint32_t DH128 = 64u | 0x40000000u;
constexpr uint32_t DH64 = 32u | 0x80000000u;
constexpr uint32_t LBO4K = (4096u >> 4) << 16, LBO8K = (8192u >> 4) << 16, LBO1 = 1u << 16;

template <uint32_t AO, uint32_t BO, bool SW64, bool FIRST> __device__ __forceinline__ void stage_ss(float (&acc)[64], uint32_t ab, uint32_t bb) {
    constexpr uint32_t KS = SW64 ? 64 : 128, BH = SW64 ? DH64 : DH128, B0 = BO + (SW64 ? LBO4K : LBO8K);
    wg_fence();
    if (FIRST) wg_ss128_z<AO, B0, BH>(acc, ab, bb); else wg_ss128<AO, B0, BH>(acc, ab, bb);
    wg_ss128<AO + 2, B0 + KS, BH>(acc, ab, bb);
    wg_ss128<AO + 4, B0 + 2 * KS, BH>(acc, ab, bb);
    wg_ss128<AO + 6, B0 + 3 * KS, BH>(acc, ab, bb);
    wg_commit();
}
template <uint32_t BO, bool FIRST> __device__ __forceinline__ void stage_rs(float (&acc)[64], const uint32_t (&f)[16], uint32_t bb) {
    wg_fence();
    if (FIRST) wg_rs128_z<BO + LBO8K, DH128>(acc, f[0], f[1], f[2], f[3], bb); else wg_rs128<BO + LBO8K, DH128>(acc, f[0], f[1], f[2], f[3], bb);
    wg_rs128<BO + LBO8K + 128, DH128>(acc, f[4], f[5], f[6], f[7], bb);
    wg_rs128<BO + LBO8K + 256, DH128>(acc, f[8], f[9], f[10], f[11], bb);
    wg_rs128<BO + LBO8K + 384, DH128>(acc, f[12], f[13], f[14], f[15], bb);
    wg_commit();
}

template <int N> __device__ __forceinline__ void stash(uint32_t base, uint32_t sw, const uint32_t (&f)[N]) {
#pragma unroll
    for (int t = 0; t < N / 4; t++) stsm4(base + ((sw ^ (2 * t)) << 4), f[4 * t], f[4 * t + 1], f[4 * t + 2], f[4 * t + 3]);
}

template <int V0, int V1, int N> __device__ __forceinline__ void send_frag(const uint32_t (&f)[N], uint4* p, uint32_t tag) {
#pragma unroll
    for (int v = V0; v < V1; v++) st_pkt(p + v * 32, (f[4 * v] & ~1u) | tag, f[4 * v + 1], f[4 * v + 2], f[4 * v + 3]);
}
template <int V0, int V1, int N> __device__ __forceinline__ void send_h(const uint32_t (&f)[N], uint4* p) {
#pragma unroll
    for (int v = V0; v < V1; v++) {
        const int h = v >> 1, hi = v & 1;
        asm volatile("st.global.v4.u32 [%0], {%1,%2,%3,%4};" :: "l"(p + 4 * h + 64 * hi),
                     "r"(f[8 * h + hi]), "r"(f[8 * h + 2 + hi]), "r"(f[8 * h + 4 + hi]), "r"(f[8 * h + 6 + hi]) : "memory");
    }
}
template <int O, int N, int M> __device__ __forceinline__ void pack_sub(uint32_t (&f)[N], const float (&acc)[M]) {
#pragma unroll
    for (int i = 0; i < N; i++) f[i] = keep(pack2(acc[O + 2 * i], acc[O + 2 * i + 1]));
}
template <int N> __device__ __forceinline__ void recv_issue(uint32_t (&q)[N], const uint4* p) {
#pragma unroll
    for (int v = 0; v < N / 4; v++) ld_pkt(p + v * 32, q[4 * v], q[4 * v + 1], q[4 * v + 2], q[4 * v + 3]);
}
template <int N> __device__ __forceinline__ void recv_check(uint32_t (&q)[N], const uint4* p, uint32_t tag) {
    uint32_t it = 0;
    while (true) {
        uint32_t bad = 0;
#pragma unroll
        for (int v = 0; v < N / 4; v++) bad |= q[4 * v] ^ tag;
        if (__all_sync(0xffffffffu, (bad & 1u) == 0) || ++it > SPIN_GLOBAL) break;
        recv_issue(q, p);
    }
}
__device__ __forceinline__ void accum(const uint32_t (&q)[32], float (&sum)[64]) {
#pragma unroll
    for (int i = 0; i < 32; i++) { sum[2 * i] += bf_lo(q[i]); sum[2 * i + 1] += bf_hi(q[i]); }
}

}

__global__ void __launch_bounds__(384, 1)
fused_kernel(const __grid_constant__ Maps maps, const __nv_bfloat16* __restrict__ xg, const __nv_bfloat16* __restrict__ gate_w,
             const char* __restrict__ pf_qkv, const char* __restrict__ pf_g, const char* __restrict__ pf_u,
             const char* __restrict__ pf_d, const char* __restrict__ pf_o, __nv_bfloat16* __restrict__ out) {
    extern __shared__ __align__(1024) uint8_t smem_raw[];
    const uint32_t sb = (uint32_t)__cvta_generic_to_shared(smem_raw);
    const int tid = threadIdx.x, lane = tid & 31;
    const int warp = __shfl_sync(0xffffffffu, tid >> 5, 0);
    const int j = (blockIdx.x & 4) | ((blockIdx.x & 1) << 1) | ((blockIdx.x >> 1) & 1);
    const int r = blockIdx.x >> 3;

    if (warp == 0) { TSG(0, 30); TS(0, 0); }
    if (tid == 256) {
        for (int i = 0; i < 5; i++) { mbar_init(sb + B_FULL + 8 * i, 1); mbar_init(sb + B_EMPTY + 8 * i, 2); }
        for (int i = 0; i < 9; i++) mbar_init(sb + B_XFULL + 8 * i, 1);
        asm volatile("fence.mbarrier_init.release.cluster;" ::: "memory");
        mbar_expect(sb + B_XFULL, 16384);
        tma2(sb + OFF_X, &maps.x, 0, r * 128, sb + B_XFULL);
        TS2(0);
        mbar_expect(sb + B_FULL, 16384);
        tmaw3(sb + OFF_RING, &maps.kv, 64 * j, 0, 1, sb + B_FULL);
        TS2(1);
        mbar_expect(sb + B_FULL + 8, 16384);
        tmaw3(sb + OFF_RING + 16384, &maps.gu, 224 * j, 0, 0, sb + B_FULL + 8);
    } else if (tid == 288) {
        for (int i = 0; i < 3; i++) mbar_init(sb + B_HSENT + 8 * i, 8);
        for (int i = 0; i < 4; i++) { mbar_init(sb + B_EFULL + 8 * i, 1); mbar_init(sb + B_EEMPTY + 8 * i, 2); }
        mbar_init(sb + B_XFREE, 2); mbar_init(sb + B_XFREE + 8, 2); mbar_init(sb + B_XFREE + 16, 2);
        mbar_init(sb + B_AHEAD, 1); mbar_init(sb + B_PART, 1); mbar_init(sb + B_LAST, 1); mbar_init(sb + B_RFREE, 2);
        mbar_expect(sb + B_LAST, 16384); mbar_init(sb + B_GRDY, 1); mbar_init(sb + B_KVDONE, 8); mbar_init(sb + B_KVRDY, 1);
        asm volatile("fence.mbarrier_init.release.cluster;" ::: "memory");
    } else if (warp == 10 && lane < 10) {
        asm volatile("prefetch.tensormap [%0];" :: "l"(&maps.gu + lane) : "memory");
    }
    asm volatile("barrier.cluster.arrive.release.aligned;\nbarrier.cluster.wait.acquire.aligned;" ::: "memory");

    if (warp >= 8) {
        asm volatile("setmaxnreg.dec.sync.aligned.u32 56;");
        if (warp == 8) {
            if (lane == 0) {
                int slot = 2, ph = 1;
                uint32_t full, dst;
                { mbar_expect(sb + B_XFULL + 8, 16384); tma2(sb + OFF_X + 16384, &maps.x, 64, r * 128, sb + B_XFULL + 8); }
#define P_BEGIN(S, BYTES) full = sb + B_FULL + 8 * slot; dst = sb + OFF_RING + slot * 16384; \
                mbar_wait(sb + B_EMPTY + 8 * slot, ph); TS2(S); mbar_expect(full, BYTES);
#define P_END() if (++slot == 5) { slot = 0; ph ^= 1; }
                for (int s = 2; s < 16; s++) {
                    const int kb = (int)(0x7654763542312100ull >> (4 * s)) & 15;
                    P_BEGIN(s, 16384) {
                        if ((0x0DADu >> s) & 1) tmaw3(dst, &maps.kv, 64 * j, 64 * kb, 1, full);
                        else tmaw3(dst, &maps.gu, 224 * j, 64 * kb, 0, full);
                    }
                    const int xb = (int)(0x0000000765403210ull >> (4 * s)) & 15;
                    if (xb) { mbar_expect(sb + B_XFULL + 8 * xb, 16384); tma2(sb + OFF_X + xb * 16384, &maps.x, 64 * xb, r * 128, sb + B_XFULL + 8 * xb); }
                    P_END()
                }
                for (int s = 0; s < 24; s++) {
                    P_BEGIN(16 + s, 16384) {
                        if (s < 8) {
                            tmaw3(dst, &maps.q64, 0, 64 * s, 2 * j, full);
                            tmaw3(dst + 8192, &maps.gu64, 224 * j + 192, 64 * s, 0, full);
                        } else {
                            tmaw3(dst, &maps.gu, 224 * j + 64 * (s >> 3), 64 * (s & 7), 0, full);
                        }
                    }
                    P_END()
                }
                const int p = j >> 1;
#pragma unroll 1
                for (int t = 0; t < 18; t++) {
                    const int q = t >= 9, sl = (int)(0x846352107ull >> (4 * (t - 9 * q))) & 15;
                    const int u = (int)((q ? 0x432186758ull : 0x327064105ull) >> (4 * (t - 9 * q))) & 15;
                    const int cw = (j & 1) * 4 + ((p & 2) ^ ((t == 5 || t > 9) ? 0 : 2)), cc = 64 * cw;
                    if (sl < 5) {
                        full = sb + B_FULL + 8 * sl; dst = sb + OFF_RING + sl * 16384;
                        mbar_wait(sb + B_EMPTY + 8 * sl, q ^ 1);
                    } else {
                        full = sb + B_EFULL + 8 * (sl - 5); dst = sb + OFF_X + (sl == 7 ? 8 : sl == 8 ? 7 : sl) * 16384;
                        mbar_wait(sb + B_EEMPTY + 8 * (sl - 5), q);
                    }
                    TS2(40 + t);
                    mbar_expect(full, 16384);
                    {
                        if (u == 4) {
                            tmaw5(dst, &maps.wdph, cc, 14 * p + 6, full); tmaw5(dst + 4096, &maps.wdph, cc, 14 * p + 13, full);
                            tmaw5(dst + 8192, &maps.wdph, cc + 64, 14 * p + 6, full); tmaw5(dst + 12288, &maps.wdph, cc + 64, 14 * p + 13, full);
                        } else if (u > 4) {
                            const int js = u > 6 ? j ^ 1 : j;
                            tmaw3(dst, (u & 1) ? &maps.wow : &maps.wdw, 0, (u & 1) ? 64 * js : 224 * js + 128, cw, full);
                        } else {
                            const int g = 14 * p + 7 * (u & 1) + (u & 2);
                            tmaw5(dst, &maps.wdp, cc, g, full); tmaw5(dst + 8192, &maps.wdp, cc + 64, g, full);
                        }
                    }
                }
            }
        } else if (warp < 11) {
            const int hx = warp - 9;
            uint32_t epoch;
            asm volatile("ld.relaxed.gpu.global.u32 %0, [%1];" : "=r"(epoch) : "l"(g_epoch + blockIdx.x) : "memory");
            {
                const uint4* xr = (const uint4*)(xg + (size_t)(r * 128 + j * 16 + hx * 8) * kD) + lane;
                const uint4 wa = __ldg((const uint4*)gate_w + lane), wb = __ldg((const uint4*)gate_w + 32 + lane);
                const uint32_t tag = (epoch + 1) & 1;
                uint4* gp = g_gx + r * 32;
                if (lane < 2) st_pkt(gp + j * 4 + hx * 2 + lane, tag ^ 1, 0, 0, 0);
                float s[8];
#pragma unroll
                for (int i0 = 0; i0 < 8; i0 += 4) {
                    uint4 va[4], vb[4];
#pragma unroll
                    for (int i = 0; i < 4; i++) { va[i] = __ldg(xr + (i0 + i) * 64); vb[i] = __ldg(xr + (i0 + i) * 64 + 32); }
#pragma unroll
                    for (int i = 0; i < 4; i++) {
                        float t0 = bf_lo(va[i].x) * bf_lo(wa.x), t1 = bf_hi(va[i].x) * bf_hi(wa.x);
                        t0 = fmaf(bf_lo(va[i].y), bf_lo(wa.y), t0); t1 = fmaf(bf_hi(va[i].y), bf_hi(wa.y), t1);
                        t0 = fmaf(bf_lo(va[i].z), bf_lo(wa.z), t0); t1 = fmaf(bf_hi(va[i].z), bf_hi(wa.z), t1);
                        t0 = fmaf(bf_lo(va[i].w), bf_lo(wa.w), t0); t1 = fmaf(bf_hi(va[i].w), bf_hi(wa.w), t1);
                        t0 = fmaf(bf_lo(vb[i].x), bf_lo(wb.x), t0); t1 = fmaf(bf_hi(vb[i].x), bf_hi(wb.x), t1);
                        t0 = fmaf(bf_lo(vb[i].y), bf_lo(wb.y), t0); t1 = fmaf(bf_hi(vb[i].y), bf_hi(wb.y), t1);
                        t0 = fmaf(bf_lo(vb[i].z), bf_lo(wb.z), t0); t1 = fmaf(bf_hi(vb[i].z), bf_hi(wb.z), t1);
                        t0 = fmaf(bf_lo(vb[i].w), bf_lo(wb.w), t0); t1 = fmaf(bf_hi(vb[i].w), bf_hi(wb.w), t1);
                        s[i0 + i] = t0 + t1;
                    }
                }
#pragma unroll
                for (int i = 0; i < 8; i++) {
#pragma unroll
                    for (int o = 16; o; o >>= 1) s[i] += __shfl_xor_sync(0xffffffffu, s[i], o);
                    s[i] = 1.f / (1.f + __expf(-s[i]));
                }
                if (lane < 2) {
                    const float v0 = lane ? s[4] : s[0], v1 = lane ? s[5] : s[1], v2 = lane ? s[6] : s[2], v3 = lane ? s[7] : s[3];
                    st_pkt(gp + j * 4 + hx * 2 + lane, (__float_as_uint(v0) & ~1u) | tag, __float_as_uint(v1), __float_as_uint(v2), __float_as_uint(v3));
                }
                if (hx == 1) {
                    asm volatile("st.shared.u32 [%0], %1;" :: "r"(sb + OFF_ONES + lane * 4), "r"(0x3f803f80u) : "memory");
                    asm volatile("fence.proxy.async.shared::cta;" ::: "memory");
                }
                asm volatile("bar.sync 3, 96;" ::: "memory");
                if (hx == 0) {
                    uint32_t q[4];
                    recv_issue(q, gp + lane);
                    recv_check(q, gp + lane, tag);
                    asm volatile("st.shared.v4.u32 [%0], {%1,%2,%3,%4};" :: "r"(sb + OFF_G + lane * 16), "r"(q[0]), "r"(q[1]), "r"(q[2]), "r"(q[3]) : "memory");
                    if (lane == 0) {
                        asm volatile("st.shared.u32 [%0], %1;" :: "r"(sb + OFF_EPOCH), "r"(epoch) : "memory");
                        g_epoch[blockIdx.x] = epoch + 1;
                    }
                    __syncwarp();
                    if (lane == 0) mbar_arrive(sb + B_GRDY);
                } else {
                    if (r == 0) {
                        float4* zp = (float4*)(g_kvacc + (((epoch & 1) ^ 1) * 8 + j) * 4 * 272);
                        for (int i = lane; i < 272; i += 32) zp[i] = make_float4(0.f, 0.f, 0.f, 0.f);
                    }
                }
            }
            TS(2 + hx, 1);
#define PUBLISH_H(B) do { mbar_wait(sb + B_HSENT + 8 * (B), 0); if (lane == 0) { \
                asm volatile("st.release.gpu.global.u32 [%0], %1;" :: "l"(g_hflag + (r * 8 + j) * 8 + (B)), "r"(epoch + 1) : "memory"); } __syncwarp(); } while (0)
            if (hx == 1) {
#pragma unroll 1
                for (int b = 0; b < 3; b++) { PUBLISH_H(b); TS(3, 5 + b); }
            } else {
                const float* accp = g_kvacc + ((epoch & 1) * 8 + j) * 4 * 272;
                unsigned* cnt = g_kvcnt + j * 32;
                mbar_wait(sb + B_KVDONE, 0);
                TS(2, 5);
                if (lane == 0) asm volatile("red.release.gpu.global.add.u32 [%0], 1;" :: "l"(cnt) : "memory");
                __syncwarp();
                TS(2, 2);
                {
                    const unsigned target = 16u * (epoch + 1);
                    uint32_t it = 0, v;
                    do {
                        asm volatile("ld.acquire.gpu.global.u32 %0, [%1];" : "=r"(v) : "l"(cnt) : "memory");
                    } while ((int)(v - target) < 0 && ++it < SPIN_GLOBAL);
                }
                TS(2, 3);
#pragma unroll
                for (int h = 0; h < 4; h++) {
                    const float4 d0 = __ldcg((const float4*)(accp + h * 272) + lane);
                    const float4 d1 = __ldcg((const float4*)(accp + h * 272 + 128) + lane);
                    const float2 z0 = __ldcg((const float2*)(accp + h * 272 + 256) + (lane & 3));
                    const float2 z1 = __ldcg((const float2*)(accp + h * 272 + 264) + (lane & 3));
                    const uint32_t ba = sb + OFF_STG + h * 768 + lane * 4;
                    asm volatile("st.shared.u32 [%0], %1;" :: "r"(ba), "r"(pack2(d0.x, d0.y)) : "memory");
                    asm volatile("st.shared.u32 [%0], %1;" :: "r"(ba + 128), "r"(pack2(d1.x, d1.y)) : "memory");
                    asm volatile("st.shared.u32 [%0], %1;" :: "r"(ba + 256), "r"(pack2(d0.z, d0.w)) : "memory");
                    asm volatile("st.shared.u32 [%0], %1;" :: "r"(ba + 384), "r"(pack2(d1.z, d1.w)) : "memory");
                    asm volatile("st.shared.u32 [%0], %1;" :: "r"(ba + 512), "r"(pack2(z0.x, z0.y)) : "memory");
                    asm volatile("st.shared.u32 [%0], %1;" :: "r"(ba + 640), "r"(pack2(z1.x, z1.y)) : "memory");
                }
                asm volatile("fence.proxy.async.shared::cta;" ::: "memory");
                __syncwarp();
                if (lane == 0) mbar_arrive(sb + B_KVRDY);
                TS(2, 4);
            }
        } else {
            uint32_t epoch;
            asm volatile("ld.relaxed.gpu.global.u32 %0, [%1];" : "=r"(epoch) : "l"(g_epoch + blockIdx.x) : "memory");
            asm volatile("bar.arrive 3, 96;" :: "r"(epoch) : "memory");
            const int b = blockIdx.x, p = j >> 1;
            mbar_wait(sb + B_XFULL, 0);
#pragma unroll 1
            for (int kb = 1; kb < 8; kb++) {
                mbar_wait(sb + B_XFULL + 8 * kb, 0);
                const char* base = kb < 3 ? pf_g : kb < 5 ? pf_u : kb == 5 ? pf_qkv : pf_d;
                const int off = kb == 5 ? b * 12288 : b * 14336 + ((kb < 5 ? kb - 1 : kb) & 1) * 7168;
                if (kb == 5) {
                    asm volatile("prefetch.global.L2 [%0];" :: "l"(base + off + (lane >> 3) * 3072 + (lane & 7) * 128));
                } else {
                    asm volatile("prefetch.global.L2 [%0];" :: "l"(base + off + lane * 128));
                    if (lane < 24) asm volatile("prefetch.global.L2 [%0];" :: "l"(base + off + 4096 + lane * 128));
                }
                if (kb == 7) asm volatile("prefetch.global.L2 [%0];" :: "l"(pf_o + b * 4096 + lane * 128));
            }
            {
                const uint32_t want = epoch + 1;
                const int hrow = (r * 4 + p) * 5 * 128;
                const unsigned* fl = g_hflag + (r * 8 + (j & 6)) * 8 + (lane & 15);
                uint32_t it = 0;
                int i = 0;
                mbar_wait(sb + B_HSENT + 8, 0);
#pragma unroll 1
                while (i < 3 && ++it < SPIN_GLOBAL) {
                    uint32_t v;
                    asm volatile("ld.acquire.gpu.global.u32 %0, [%1];" : "=r"(v) : "l"(fl) : "memory");
                    const uint32_t rdy = __ballot_sync(0xffffffffu, v == want);
#pragma unroll 1
                    while (i < 3 && ((rdy >> i) & 0x101u) == 0x101u) {
                        if (i < 2) mbar_wait(sb + B_XFREE + 8 * i, 0);
                        if (lane == 0) {
                            const int pc = (6 - 2 * i) % 6;
                            asm volatile("fence.proxy.async.global;" ::: "memory");
                            TS2(140 + i);
                            mbar_expect(sb + B_XFULL + 8 * pc, i != 1 ? 32768 : 16384);
                            tma2(sb + OFF_X + pc * 16384, i != 1 ? &maps.hx2 : &maps.hx, 0, hrow + pc * 128, sb + B_XFULL + 8 * pc);
                        }
                        i++;
                    }
                }
            }
        }
    } else {
        asm volatile("setmaxnreg.inc.sync.aligned.u32 224;");
        const int wg = warp >> 2;
        const bool elect = (tid & 127) == 0;
        const uint32_t sbd = (sb & 0x3FFFFu) >> 4, xlo = (sbd + wg * 512) | LBO1;
        auto release = [&](uint32_t bar) {
            if (elect) {
                mbar_arrive(sb + bar);
            }
        };
#define S_SL(S) ((S) < 40 ? (S) % 5 : (int)((0x846352107ull >> (4 * (((S) - 40) % 9))) & 15))
#define S_WAIT(S) do { mbar_wait(sb + (S_SL(S) < 5 ? B_FULL + 8 * S_SL(S) : B_EFULL + 8 * (S_SL(S) - 5)), (S) < 40 ? ((S) / 5) & 1 : (S) >= 49); \
            if (PROF && tid == 0) TS2(64 + (S)); } while (0)
#define S_B(S) (S_SL(S) < 5 ? OFF_RING / 16 + S_SL(S) * 1024 : (S_SL(S) == 7 ? 8 : S_SL(S) == 8 ? 7 : S_SL(S)) * 1024)
#define S_REL(S) do { if ((S) < 49) release(S_SL(S) < 5 ? B_EMPTY + 8 * S_SL(S) : B_EEMPTY + 8 * (S_SL(S) - 5)); } while (0)
#define G1(S, acc, SW, KB) stage_ss<(KB) * 1024, S_B(S), SW, (KB) == 0>(acc, xlo, sbd)
#define RET(S) do { S_WAIT((S) + 1); wg_wait<1>(); S_REL((S) - 1); } while (0)
#define RET2(S) do { S_WAIT((S) + 1); wg_wait<2>(); S_REL((S) - 1); } while (0)
#define SCHED() mbar_wait(sb + B_XFULL + 8 * 7, 0)
#define A2_SYNC() do { asm volatile("fence.proxy.async.shared::cta;" ::: "memory"); asm volatile("bar.sync %0, 128;" :: "r"(wg + 1) : "memory"); } while (0)
#define H_EPI(acc, F, I0, I1, OG, OU) _Pragma("unroll") for (int i = (I0); i < (I1); i++) \
            F[i] = keep(hmul2(pack2(acc[(OG) + 2 * i] * acc[(OU) + 2 * i], acc[(OG) + 2 * i + 1] * acc[(OU) + 2 * i + 1]), (i & 1) ? m_hi : m_lo))
#define PHI(acc, F, I0, I1) _Pragma("unroll") for (int i = (I0); i < (I1); i++) F[i] = keep(phi2(acc[2 * i], acc[2 * i + 1]))

        float a0[64], b0[64], a1[64], a2_[64], a3[64];
        mbar_wait(sb + B_XFULL, 0);
#define X_WAIT(KB) do { mbar_wait(sb + B_XFULL + 8 * (KB), 0); if (PROF && tid == 0) TS2(128 + (KB)); } while (0)
        S_WAIT(0); G1(0, b0, false, 0);
        if ((warp & 3) == 0) TS(wg, 1);
        S_WAIT(1); G1(1, a0, false, 0); RET(1);
        X_WAIT(1); G1(2, b0, false, 1); RET(2);
        X_WAIT(2); G1(3, b0, false, 2); RET(3);
        G1(4, a0, false, 1); RET(4);
        X_WAIT(3); G1(5, b0, false, 3); RET(5);
        G1(6, a0, false, 2); RET(6);
        X_WAIT(4); G1(7, b0, false, 4); RET(7);
        X_WAIT(5); G1(8, b0, false, 5); RET(8);
        G1(9, a0, false, 3); RET(9);
        X_WAIT(6); G1(10, b0, false, 6); RET(10);
        X_WAIT(7); G1(11, b0, false, 7); RET(11);
        G1(12, a0, false, 4);
        const uint32_t lrow = ((lane & 7) + 8 * ((lane >> 3) & 1)) * 128;
        const uint32_t srow = (warp & 3) * 2048 + lrow;
        const uint32_t ssw = (lane >> 4) ^ (lane & 7);
        uint4* const hsend = g_hx + (size_t)((r * 4 + (j >> 1)) * 5 + (j & 1)) * 1024 + warp * 128 + (lane >> 2) * 8 + (lane & 3);
#define SENT_H(B) do { __syncwarp(); if (lane == 0) mbar_arrive(sb + B_HSENT + 8 * (B)); } while (0)
        RET(12);
        pin(b0);
        uint32_t fh0[16], fh1[16], fh2[16], fh3[8], fo[16], pk[16], pv[16];
        float kv[32], zs[4];
        const uint32_t stg = sb + OFF_STG + wg * 8192, stl = stg + (warp & 1) * 2048 + lrow;
#define KV_ROUND(Z) do { A2_SYNC(); wg_fence(); \
            wg_ss64t##Z<8192 + 256, 8192, DH128>(kv, xlo, xlo); wg_ss64t<8192 + 384, 8192 + 128, DH128>(kv, xlo, xlo); \
            wg_ss8t##Z<8192, OFF_ONES / 16, 0>(zs, xlo, sbd); wg_ss8t<8192 + 128, OFF_ONES / 16, 0>(zs, xlo, sbd); wg_commit(); } while (0)
        G1(13, a0, false, 5); SCHED(); pack_sub<32>(pv, b0); PHI(b0, pk, 0, 4); RET(13);
        G1(14, a0, false, 6); SCHED(); if (!(warp & 2)) stash<16>(stl + 4096, ssw, pv); PHI(b0, pk, 4, 10); RET(14);
        G1(15, a0, false, 7); SCHED(); PHI(b0, pk, 10, 16); RET(15);
        if ((warp & 3) == 0) TS(wg, 2);

        G1(16, a1, true, 0); SCHED(); if (!(warp & 2)) stash<16>(stl, ssw, pk);
        mbar_wait(sb + B_GRDY, 0);
        float g_lo, g_hi;
        uint32_t tag;
        {
            const uint32_t ga = sb + OFF_G + (warp * 16 + (lane >> 2)) * 4;
            asm volatile("ld.shared.f32 %0, [%1];" : "=f"(g_lo) : "r"(ga) : "memory");
            asm volatile("ld.shared.f32 %0, [%1];" : "=f"(g_hi) : "r"(ga + 32) : "memory");
            asm volatile("ld.shared.u32 %0, [%1];" : "=r"(tag) : "r"(sb + OFF_EPOCH) : "memory");
        }
        float* const kvp = g_kvacc + (((tag & 1) * 8 + j) * 4 + (warp & 3)) * 272;
        tag = (tag + 1) & 1;
        const uint32_t m_lo = pack2(1.f - g_lo, 1.f - g_lo), m_hi = pack2(1.f - g_hi, 1.f - g_hi);
        RET(16);
        pin(a0);
        G1(17, a1, true, 1); SCHED(); H_EPI(a0, fh0, 0, 16, 0, 32); RET(17);
        G1(18, a1, true, 2); KV_ROUND(_z); RET2(18);
        G1(19, a1, true, 3); SCHED(); send_h<0, 1>(fh0, hsend); RET(19);
        G1(20, a1, true, 4); SCHED(); if (warp & 2) { stash<16>(stl, ssw, pk); stash<16>(stl + 4096, ssw, pv); } RET(20);
        G1(21, a1, true, 5); KV_ROUND(); RET2(21);
        G1(22, a1, true, 6); RET(22);
        pin(kv); pin(zs);
        G1(23, a1, true, 7); SCHED();
#define KV_RED(W) do { asm volatile("red.global.add.v4.f32 [%0], {%1,%2,%3,%4};" :: "l"(kvp + lane * 4), "f"(kv[8 * W]), "f"(kv[8 * W + 1]), "f"(kv[8 * W + 2]), "f"(kv[8 * W + 3]) : "memory"); \
                       asm volatile("red.global.add.v4.f32 [%0], {%1,%2,%3,%4};" :: "l"(kvp + 128 + lane * 4), "f"(kv[8 * W + 4]), "f"(kv[8 * W + 5]), "f"(kv[8 * W + 6]), "f"(kv[8 * W + 7]) : "memory"); } while (0)
        if ((warp & 3) == 0) KV_RED(0); else if ((warp & 3) == 1) KV_RED(1); else if ((warp & 3) == 2) KV_RED(2); else KV_RED(3);
        if ((lane & 3) == 0) {
            asm volatile("red.global.add.f32 [%0], %1;" :: "l"(kvp + 256 + (lane >> 2)), "f"(zs[0]) : "memory");
            asm volatile("red.global.add.f32 [%0], %1;" :: "l"(kvp + 264 + (lane >> 2)), "f"(zs[2]) : "memory");
        }
        __syncwarp();
        if (lane == 0) mbar_arrive(sb + B_KVDONE);
        RET(23);
        if ((warp & 3) == 0) TS(wg, 3);

        G1(24, a2_, false, 0); SCHED(); send_h<1, 2>(fh0, hsend); RET(24);
        pin(a1);
        G1(25, a2_, false, 1); SCHED(); send_h<2, 3>(fh0, hsend); H_EPI(a1, fh3, 0, 8, 32, 48); RET(25);
        G1(26, a2_, false, 2); SCHED(); send_h<3, 4>(fh0, hsend); SENT_H(0); PHI(a1, fo, 0, 4); RET(26);
        G1(27, a2_, false, 3); SCHED(); send_h<0, 1>(fh3, hsend + 4 * 1024 - (j & 1) * 1020); PHI(a1, fo, 4, 8); RET(27);
        G1(28, a2_, false, 4); SCHED(); send_h<1, 2>(fh3, hsend + 4 * 1024 - (j & 1) * 1020); SENT_H(1); PHI(a1, fo, 8, 12); RET(28);
        G1(29, a2_, false, 5); SCHED(); PHI(a1, fo, 12, 16); RET(29);
        G1(30, a2_, false, 6); RET(30);
        G1(31, a2_, false, 7); RET(31);
        if ((warp & 3) == 0) TS(wg, 4);

        float on[4][12];
#define O_SCALE(h) do { const float s_lo = __fdividef(g_lo, on[h][8] + 1e-6f), s_hi = __fdividef(g_hi, on[h][10] + 1e-6f); \
            const uint32_t sl_ = pack2(s_lo, s_lo), sh_ = pack2(s_hi, s_hi); \
            fo[4 * h] = keep(hmul2(pack2(on[h][0], on[h][1]), sl_)); fo[4 * h + 1] = keep(hmul2(pack2(on[h][2], on[h][3]), sh_)); \
            fo[4 * h + 2] = keep(hmul2(pack2(on[h][4], on[h][5]), sl_)); fo[4 * h + 3] = keep(hmul2(pack2(on[h][6], on[h][7]), sh_)); } while (0)
        uint4* const lsend = g_lx + (size_t)(r * 8 + j) * 2048 + warp * 128 + lane;
        const uint4* const lrecv = g_lx + (size_t)(r * 8 + (j ^ 1)) * 2048 + warp * 128 + lane;
        G1(32, a3, false, 0); RET(32);
        pin(a2_);
        G1(33, a3, false, 1); SCHED(); H_EPI(a2_, fh1, 0, 16, 0, 32); send_h<0, 1>(fh1, hsend + 2 * 1024); RET(33);
        G1(34, a3, false, 2); SCHED(); send_h<1, 3>(fh1, hsend + 2 * 1024); RET(34);
        if (elect) mbar_arrive(sb + B_XFREE);
        G1(35, a3, false, 3); SCHED(); send_h<3, 4>(fh1, hsend + 2 * 1024); SENT_H(2);
        if ((warp & 3) == 0) TS(wg, 5);
        mbar_wait(sb + B_KVRDY, 0);
        if ((warp & 3) == 0) TS(wg, 6);
        wg_fence();
#define O_MMA(h) wg_rs24_z<OFF_STG / 16 + (h) * 48 + (8u << 16), 16>(on[h], fo[4 * (h)], fo[4 * (h) + 1], fo[4 * (h) + 2], fo[4 * (h) + 3], sbd)
        O_MMA(0); O_MMA(1); O_MMA(2); O_MMA(3);
        wg_commit();
        RET2(35);
        G1(36, a3, false, 4); RET(36);
        pin(on[0]); pin(on[1]); pin(on[2]); pin(on[3]);
        release(B_EEMPTY + 16);
        G1(37, a3, false, 5); SCHED(); O_SCALE(0); O_SCALE(1); O_SCALE(2); O_SCALE(3); RET(37);
        if (elect) mbar_arrive(sb + B_XFREE + 8);
        G1(38, a3, false, 6); SCHED(); send_frag<0, 2>(fo, lsend, tag); RET(38);
        release(B_EEMPTY);
        G1(39, a3, false, 7); SCHED(); send_frag<2, 4>(fo, lsend, tag); RET(39);
        release(B_EEMPTY + 8);
        if ((warp & 3) == 0) TS(wg, 7);

#define G2S(S, acc, U) stage_ss<(U) * 1024, S_B(S), false, (S) == 45>(acc, xlo, sbd)
#define G2R(S, acc, F) stage_rs<S_B(S), (S) == 40>(acc, F, sbd)
#define H_WAIT(P) do { mbar_wait(sb + B_XFULL + 8 * (P), 1); if (PROF && tid == 0) TS2(150 + (P)); } while (0)
        const int p = j >> 1, pw = (p & 2) ^ 2;
        const bool own = wg == (p & 1);
        uint4* const pbase = g_part + (size_t)(r * 2 + (j & 1)) * 16384 + (warp & 3) * 256 + lane;

        float p1[64], p2[64];
        uint32_t po[16], ph2[16];
        G2R(40, p1, fo); RET(40);
        release(B_EEMPTY + 24);
        pin(a3);
        H_WAIT(0); G2S(41, p1, 0); SCHED(); H_EPI(a3, fh2, 0, 16, 0, 32); send_frag<0, 2>(fh2, lsend + 1024, tag); RET(41);
        G2S(42, p1, 1); SCHED(); recv_issue(po, lrecv); send_frag<2, 4>(fh2, lsend + 1024, tag); RET(42);
        H_WAIT(4); G2S(43, p1, 4); RET(43);
        G2R(44, p1, fh2); RET(44);
        G2S(45, p2, 0); SCHED(); if (!(EXPT & 2)) recv_check(po, lrecv, tag); recv_issue(ph2, lrecv + 1024); RET(45);
        G2R(46, p1, po); RET(46);
        if (elect) mbar_arrive_cta(sb + B_RFREE, (blockIdx.x & 1) ^ 1);
        H_WAIT(2); G2S(47, p1, 2); RET(47);
        G2S(48, p1, 3); SCHED(); if (!(EXPT & 2)) recv_check(ph2, lrecv + 1024, tag); RET(48);
        G2R(49, p1, ph2); RET(49);
        if ((warp & 3) == 0) TS(wg, 8);
        uint32_t sp[32], qa[32], qb[32];
        uint4* const s1 = pbase + (((pw + wg) * 4 + p) << 10);
        G2R(50, p2, fo); RET(50);
        pin(p1);
        G2R(51, p2, po); SCHED(); pack_sub<0>(sp, p1); send_frag<0, 2>(sp, s1, tag); RET(51);
        G2R(52, p2, fh2); SCHED(); send_frag<2, 5>(sp, s1, tag); RET(52);
        if (elect) mbar_arrive(sb + B_XFREE + 16);
        G2R(53, p2, ph2); SCHED(); send_frag<5, 8>(sp, s1, tag); RET(53);
        const uint4* ra = pbase + ((p * 4 + pw) << 10);
        if (own) mbar_wait(sb + B_AHEAD, 0);
        G2S(54, p2, 1); RET(54);
        G2S(55, p2, 2); RET(55);
        G2S(56, p2, 3); RET(56);
        G2S(57, p2, 4); SCHED();
        if ((warp & 3) == 0) TS(wg, 9);
        if (!own && elect) {
            mbar_arrive(sb + B_AHEAD);
            mbar_wait(sb + B_XFREE + 16, 0);
            mbar_expect(sb + B_PART, 32768);
            asm volatile("cp.async.bulk.shared::cluster.global.mbarrier::complete_tx::bytes [%0], [%1], %2, [%3];"
                         :: "r"(sb + OFF_RING), "l"(ra), "r"(32768), "r"(sb + B_PART) : "memory");
        }
        wg_wait<0>();
        pin(p2);
        if ((warp & 3) == 0) TS(wg, 11);
        if (!own) {
            pack_sub<0>(sp, p2);
            mbar_wait(sb + B_RFREE, 0);
            uint32_t rd, rb;
            asm volatile("mapa.shared::cluster.u32 %0, %1, %2;" : "=r"(rd) : "r"(sb + OFF_X + (warp & 3) * 4096 + lane * 16), "r"((blockIdx.x & 1) ^ 1));
            asm volatile("mapa.shared::cluster.u32 %0, %1, %2;" : "=r"(rb) : "r"(sb + B_LAST), "r"((blockIdx.x & 1) ^ 1));
#pragma unroll
            for (int v = 0; v < 8; v++)
                asm volatile("st.async.shared::cluster.mbarrier::complete_tx::bytes.v4.b32 [%0], {%1,%2,%3,%4}, [%5];"
                             :: "r"(rd + v * 512), "r"(sp[4 * v]), "r"(sp[4 * v + 1]), "r"(sp[4 * v + 2]), "r"(sp[4 * v + 3]), "r"(rb) : "memory");
        } else {
            mbar_wait(sb + B_PART, 0);
            if ((warp & 3) == 0) TS(wg, 10);
            const uint32_t pa = sb + OFF_RING + (warp & 3) * 4096 + lane * 16;
#pragma unroll
            for (int v = 0; v < 8; v++) {
                asm volatile("ld.shared.v4.u32 {%0,%1,%2,%3}, [%4];" : "=r"(qa[4 * v]), "=r"(qa[4 * v + 1]), "=r"(qa[4 * v + 2]), "=r"(qa[4 * v + 3]) : "r"(pa + v * 512) : "memory");
                asm volatile("ld.shared.v4.u32 {%0,%1,%2,%3}, [%4];" : "=r"(qb[4 * v]), "=r"(qb[4 * v + 1]), "=r"(qb[4 * v + 2]), "=r"(qb[4 * v + 3]) : "r"(pa + 16384 + v * 512) : "memory");
            }
#if !(EXPT & 1)
            recv_check(qa, ra, tag); recv_check(qb, ra + 1024, tag);
#endif
#pragma unroll
            for (int i = 0; i < 32; i++) qa[i] = hadd2(qa[i], qb[i]);
            accum(qa, p2);
            pack_sub<0>(qb, p2);
            if ((warp & 3) == 0) TS(wg, 12);
            mbar_wait(sb + B_LAST, 0);
#pragma unroll
            for (int v = 0; v < 8; v++)
                asm volatile("ld.shared.v4.u32 {%0,%1,%2,%3}, [%4];" : "=r"(sp[4 * v]), "=r"(sp[4 * v + 1]), "=r"(sp[4 * v + 2]), "=r"(sp[4 * v + 3])
                             : "r"(sb + OFF_X + (warp & 3) * 4096 + lane * 16 + v * 512) : "memory");
            if ((warp & 3) == 0) TS(wg, 13);
            uint32_t f0[16], f1[16];
#pragma unroll
            for (int i = 0; i < 16; i++) { f0[i] = hadd2(qb[i], sp[i]); f1[i] = hadd2(qb[16 + i], sp[16 + i]); }
            const uint32_t slab = sb + OFF_X + 2 * 16384 + wg * 8192;
            stash<16>(slab + srow, ssw, f0); stash<16>(slab + 16384 + srow, ssw, f1);
            __syncwarp();
            __nv_bfloat16* op = out + (size_t)(r * 128 + warp * 16 + (lane >> 4)) * kD + (j & 1) * 256 + (p & 2) * 64 + (lane & 15) * 8;
#pragma unroll
            for (int i = 0; i < 8; i++) {
                const int row = i * 2 + (lane >> 4);
                uint4 v;
                asm volatile("ld.shared.v4.u32 {%0,%1,%2,%3}, [%4];" : "=r"(v.x), "=r"(v.y), "=r"(v.z), "=r"(v.w)
                             : "r"(slab + (lane & 8) * 2048 + ((warp & 3) * 16 + row) * 128 + (((lane & 7) ^ (row & 7)) << 4)) : "memory");
                *(uint4*)(op + i * 2 * kD) = v;
            }
        }
        if ((warp & 3) == 0) { TS(wg, 14); TSG(wg, 31); }
    }
}

typedef CUresult (*EncodeFn)(CUtensorMap*, CUtensorMapDataType, cuuint32_t, void*, const cuuint64_t*, const cuuint64_t*, const cuuint32_t*,
                             const cuuint32_t*, CUtensorMapInterleave, CUtensorMapSwizzle, CUtensorMapL2promotion, CUtensorMapFloatOOBfill);

static void encode(EncodeFn fn, CUtensorMap* m, int rank, const void* base, const cuuint64_t (&gd)[5], const cuuint64_t (&gs)[4],
                   const cuuint32_t (&bd)[5], CUtensorMapSwizzle sw) {
    cuuint32_t es[5] = {1, 1, 1, 1, 1};
    fn(m, CU_TENSOR_MAP_DATA_TYPE_BFLOAT16, rank, const_cast<void*>(base), gd, gs, bd, es, CU_TENSOR_MAP_INTERLEAVE_NONE, sw,
       CU_TENSOR_MAP_L2_PROMOTION_L2_128B, CU_TENSOR_MAP_FLOAT_OOB_FILL_NONE);
}

extern "C" void kernel_launch(void* const* d_in, const int* in_sizes, int n_in, void* d_out, int out_size) {
    const char* x = (const char*)d_in[0];
    const char* wqkv = (const char*)d_in[1];
    const char* wo = (const char*)d_in[2];
    const char* wg = (const char*)d_in[4];
    const char* wu = (const char*)d_in[5];
    const char* wd = (const char*)d_in[6];
    void* fnp = nullptr;
    cudaDriverEntryPointQueryResult qr;
    cudaGetDriverEntryPoint("cuTensorMapEncodeTiled", &fnp, cudaEnableDefault, &qr);
    EncodeFn fn = (EncodeFn)fnp;
    Maps maps;
    const char* lo = wg < wu ? wg : wu;
    const uint64_t diff = wg < wu ? (uint64_t)(wu - wg) : (uint64_t)(wg - wu);
    const CUtensorMapSwizzle S128 = CU_TENSOR_MAP_SWIZZLE_128B, S64 = CU_TENSOR_MAP_SWIZZLE_64B;
    encode(fn, &maps.x, 2, x, {512, 2048, 1, 1}, {1024, 0, 0}, {64, 128, 1, 1}, S128);
    encode(fn, &maps.gu, 3, lo, {1792, 512, 2, 1}, {3584, diff, 0}, {64, 64, 2, 1}, S128);
    encode(fn, &maps.kv, 3, wqkv, {512, 512, 3, 1}, {3072, 1024, 0}, {64, 64, 2, 1}, S128);
    encode(fn, &maps.q64, 3, wqkv, {32, 512, 48, 1}, {3072, 64, 0}, {32, 64, 2, 1}, S64);
    encode(fn, &maps.gu64, 3, lo, {1792, 512, 2, 1}, {3584, diff, 0}, {32, 64, 2, 1}, S64);
    encode(fn, &maps.wdw, 3, wd, {64, 1792, 8, 1}, {1024, 128, 0}, {64, 64, 2, 1}, S128);
    encode(fn, &maps.wow, 3, wo, {64, 512, 8}, {1024, 128}, {64, 64, 2}, S128);
    encode(fn, &maps.wdp, 5, wd, {512, 2, 4, 4, 56}, {1024, 8192, 2048, 32768}, {64, 2, 4, 4, 2}, S128);
    encode(fn, &maps.wdph, 5, wd, {512, 2, 4, 4, 56}, {1024, 8192, 2048, 32768}, {64, 2, 4, 4, 1}, S128);
    void* hx = nullptr;
    cudaGetSymbolAddress(&hx, g_hx);
    encode(fn, &maps.hx, 2, hx, {64, 16 * 4 * 5 * 128}, {128}, {64, 128}, S128);
    encode(fn, &maps.hx2, 2, hx, {64, 16 * 4 * 5 * 128}, {128}, {64, 256}, S128);
    cudaFuncSetAttribute(fused_kernel, cudaFuncAttributeMaxDynamicSharedMemorySize, SMEM_BYTES);
    cudaLaunchConfig_t cfg = {};
    cfg.gridDim = dim3(128);
    cfg.blockDim = dim3(384);
    cfg.dynamicSmemBytes = SMEM_BYTES;
    cfg.stream = cudaStreamPerThread;
    cudaLaunchAttribute at[1];
    at[0].id = cudaLaunchAttributeClusterDimension;
    at[0].val.clusterDim.x = 2; at[0].val.clusterDim.y = 1; at[0].val.clusterDim.z = 1;
    cfg.attrs = at;
    cfg.numAttrs = 1;
    cudaLaunchKernelEx(&cfg, fused_kernel, maps, (const __nv_bfloat16*)d_in[0], (const __nv_bfloat16*)d_in[7], wqkv, wg, wu, wd, wo, (__nv_bfloat16*)d_out);
}
```

```cpp
#include <cuda_runtime.h>
#include <cuda.h>
#include <cuda_bf16.h>
#include <stdint.h>

#define PFMODE 1
#define PHI_SAT 0
#define EXPT 0
#define MAPV 1
#define PROF 0

namespace {

constexpr int kD = 512;
constexpr uint32_t OFF_X = 0, OFF_STG = 131072, OFF_RING = 147456, OFF_MISC = 229376;
constexpr uint32_t B_FULL = OFF_MISC, B_EMPTY = OFF_MISC + 40, B_XFULL = OFF_MISC + 80;
constexpr uint32_t B_GRDY = OFF_MISC + 152, B_KVDONE = OFF_MISC + 160, B_KVRDY = OFF_MISC + 168;
constexpr uint32_t B_HSENT = OFF_MISC + 176, B_XFREE = OFF_MISC + 200;
constexpr uint32_t OFF_EPOCH = OFF_MISC + 240, OFF_G = OFF_MISC + 256;
constexpr uint32_t B_AHEAD = OFF_MISC + 248, B_PART = OFF_MISC + 232, B_LAST = OFF_MISC + 224, B_RFREE = OFF_MISC + 960;
constexpr uint32_t OFF_ONES = OFF_MISC + 768;
constexpr uint32_t B_EFULL = OFF_MISC + 896, B_EEMPTY = OFF_MISC + 928;
constexpr uint32_t SMEM_BYTES = OFF_MISC + 968;
constexpr uint32_t SPIN_GLOBAL = 1u << 14;

struct alignas(64) Maps { CUtensorMap x, gu, kv, q64, gu64, wdw, wow, wdp, wdph, hx, hx2; };

}

__device__ uint4 g_part[16 * 2 * 4 * 4 * 1024];
__device__ uint4 g_hx[16 * 4 * 5 * 1024];
__device__ uint4 g_lx[16 * 8 * 2 * 1024];
__device__ unsigned g_hflag[128 * 8];
__device__ uint4 g_gx[16 * 32];
__device__ float g_kvacc[2 * 8 * 4 * 272];
__device__ unsigned g_kvcnt[8 * 32];
__device__ unsigned g_epoch[128];
#define TS(role, idx)
#define TS2(idx)
#define TSG(role, idx)

namespace {

__device__ __forceinline__ void mbar_init(uint32_t bar, uint32_t cnt) { asm volatile("mbarrier.init.shared::cta.b64 [%0], %1;" :: "r"(bar), "r"(cnt) : "memory"); }
__device__ __forceinline__ void mbar_expect(uint32_t bar, uint32_t bytes) { asm volatile("mbarrier.arrive.expect_tx.shared::cta.b64 _, [%0], %1;" :: "r"(bar), "r"(bytes) : "memory"); }
__device__ __forceinline__ void mbar_arrive(uint32_t bar) { asm volatile("mbarrier.arrive.shared::cta.b64 _, [%0];" :: "r"(bar) : "memory"); }
__device__ __forceinline__ void mbar_arrive_cta(uint32_t bar, uint32_t cta) {
    asm volatile("{\n.reg .b32 ra;\nmapa.shared::cluster.u32 ra, %0, %1;\nmbarrier.arrive.shared::cluster.b64 _, [ra];\n}" :: "r"(bar), "r"(cta) : "memory");
}
__device__ __forceinline__ void mbar_wait(uint32_t bar, uint32_t parity) {
    asm volatile("{\n.reg .pred p;\n.reg .u32 c;\n"
                 "mbarrier.try_wait.parity.shared::cta.b64 p, [%0], %1;\n@p bra DONE;\n"
                 "mov.u32 c, 0;\nLAB_WAIT:\nmbarrier.try_wait.parity.shared::cta.b64 p, [%0], %1;\n@p bra DONE;\n"
                 "add.u32 c, c, 1;\nsetp.lt.u32 p, c, 65536;\n@p bra LAB_WAIT;\nDONE:\n}" :: "r"(bar), "r"(parity) : "memory");
}
__device__ __forceinline__ void tma2(uint32_t dst, const CUtensorMap* m, int c0, int c1, uint32_t bar) {
    asm volatile("cp.async.bulk.tensor.2d.shared::cluster.global.mbarrier::complete_tx::bytes [%0], [%1, {%3, %4}], [%2];"
        :: "r"(dst), "l"(m), "r"(bar), "r"(c0), "r"(c1) : "memory");
}
__device__ __forceinline__ void tmaw2(uint32_t dst, const CUtensorMap* m, int c0, int c1, uint32_t bar) {
    tma2(dst, m, c0, c1, bar);
}
__device__ __forceinline__ void tmaw3(uint32_t dst, const CUtensorMap* m, int c0, int c1, int c2, uint32_t bar) {
    asm volatile("cp.async.bulk.tensor.3d.shared::cluster.global.mbarrier::complete_tx::bytes [%0], [%1, {%3, %4, %5}], [%2];"
        :: "r"(dst), "l"(m), "r"(bar), "r"(c0), "r"(c1), "r"(c2) : "memory");
}
__device__ __forceinline__ void tmaw5(uint32_t dst, const CUtensorMap* m, int c0, int c4, uint32_t bar) {
    asm volatile("cp.async.bulk.tensor.5d.shared::cluster.global.mbarrier::complete_tx::bytes [%0], [%1, {%3, %5, %5, %5, %4}], [%2];"
        :: "r"(dst), "l"(m), "r"(bar), "r"(c0), "r"(c4), "r"(0) : "memory");
}
__device__ __forceinline__ void wg_fence() { asm volatile("wgmma.fence.sync.aligned;" ::: "memory"); }
__device__ __forceinline__ void wg_commit() { asm volatile("wgmma.commit_group.sync.aligned;" ::: "memory"); }
template <int N> __device__ __forceinline__ void wg_wait() { asm volatile("wgmma.wait_group.sync.aligned %0;" :: "n"(N) : "memory"); }
template <int N> __device__ __forceinline__ void pin(float (&d)[N]) {
#pragma unroll
    for (int i = 0; i < N; i++) asm volatile("" : "+f"(d[i]) :: "memory");
}
__device__ __forceinline__ uint32_t pack2(float lo, float hi) { uint32_t r; asm("cvt.rn.bf16x2.f32 %0, %1, %2;" : "=r"(r) : "f"(hi), "f"(lo)); return r; }
__device__ __forceinline__ uint32_t keep(uint32_t v) { asm volatile("" : "+r"(v)); return v; }
__device__ __forceinline__ uint32_t hadd2(uint32_t a, uint32_t b) { uint32_t r; asm("add.bf16x2 %0, %1, %2;" : "=r"(r) : "r"(a), "r"(b)); return r; }
__device__ __forceinline__ uint32_t hmul2(uint32_t a, uint32_t b) { uint32_t r; asm("mul.bf16x2 %0, %1, %2;" : "=r"(r) : "r"(a), "r"(b)); return r; }
__device__ __forceinline__ uint32_t phi2(float t0, float t1) {
    float e0, e1;
    asm("ex2.approx.ftz.f32 %0, %1;" : "=f"(e0) : "f"(t0 * 1.4426950408889634f));
    asm("ex2.approx.ftz.f32 %0, %1;" : "=f"(e1) : "f"(t1 * 1.4426950408889634f));
    uint32_t e = pack2(e0, e1), t = pack2(t0, t1), r;
    asm("min.bf16x2 %0, %0, %1;" : "+r"(e) : "r"(0x3f803f80u));
    asm("max.bf16x2 %0, %0, %1;" : "+r"(t) : "r"(0x35863586u));
    asm("add.bf16x2 %0, %1, %2;" : "=r"(r) : "r"(e), "r"(t));
    return r;
}
__device__ __forceinline__ void stsm4(uint32_t a, uint32_t r0, uint32_t r1, uint32_t r2, uint32_t r3) {
    asm volatile("stmatrix.sync.aligned.m8n8.x4.shared.b16 [%0], {%1,%2,%3,%4};" :: "r"(a), "r"(r0), "r"(r1), "r"(r2), "r"(r3) : "memory");
}
__device__ __forceinline__ float bf_lo(uint32_t w) { return __uint_as_float(w << 16); }
__device__ __forceinline__ float bf_hi(uint32_t w) { return __uint_as_float(w & 0xffff0000u); }
__device__ __forceinline__ void st_pkt(uint4* p, uint32_t w0, uint32_t w1, uint32_t w2, uint32_t w3) {
    asm volatile("{\n.reg .b64 lo, hi;\n.reg .b128 v;\nmov.b64 lo, {%1, %2};\nmov.b64 hi, {%3, %4};\nmov.b128 v, {lo, hi};\nst.relaxed.gpu.global.b128 [%0], v;\n}"
        :: "l"(p), "r"(w0), "r"(w1), "r"(w2), "r"(w3) : "memory");
}
__device__ __forceinline__ void ld_pkt(const uint4* p, uint32_t& w0, uint32_t& w1, uint32_t& w2, uint32_t& w3) {
    asm volatile("{\n.reg .b64 lo, hi;\n.reg .b128 v;\nld.relaxed.gpu.global.b128 v, [%4];\nmov.b128 {lo, hi}, v;\nmov.b64 {%0, %1}, lo;\nmov.b64 {%2, %3}, hi;\n}"
        : "=r"(w0), "=r"(w1), "=r"(w2), "=r"(w3) : "l"(p) : "memory");
}

template <uint32_t AO, uint32_t BO, uint32_t BH> __device__ __forceinline__ void wg_ss128(float (&d)[64], uint32_t ab, uint32_t bb) {
    asm volatile("{\n.reg .b64 da, db;\n.reg .b32 ta, tb, th, ah;\nadd.u32 ta, %64, %66;\nadd.u32 tb, %65, %67;\nmov.b32 th, %68;\nmov.b32 ah, 0x40000040;\nmov.b64 da, {ta, ah};\nmov.b64 db, {tb, th};\n"
        "wgmma.mma_async.sync.aligned.m64n128k16.f32.bf16.bf16 {%0,%1,%2,%3,%4,%5,%6,%7,%8,%9,%10,%11,%12,%13,%14,%15,%16,%17,%18,%19,%20,%21,%22,%23,%24,%25,%26,%27,%28,%29,%30,%31,%32,%33,%34,%35,%36,%37,%38,%39,%40,%41,%42,%43,%44,%45,%46,%47,%48,%49,%50,%51,%52,%53,%54,%55,%56,%57,%58,%59,%60,%61,%62,%63}, da, db, 1, 1, 1, 0, 1;\n}\n"
        : "+f"(d[0]),"+f"(d[1]),"+f"(d[2]),"+f"(d[3]),"+f"(d[4]),"+f"(d[5]),"+f"(d[6]),"+f"(d[7]),"+f"(d[8]),"+f"(d[9]),"+f"(d[10]),"+f"(d[11]),"+f"(d[12]),"+f"(d[13]),"+f"(d[14]),"+f"(d[15]),"+f"(d[16]),"+f"(d[17]),"+f"(d[18]),"+f"(d[19]),"+f"(d[20]),"+f"(d[21]),"+f"(d[22]),"+f"(d[23]),"+f"(d[24]),"+f"(d[25]),"+f"(d[26]),"+f"(d[27]),"+f"(d[28]),"+f"(d[29]),"+f"(d[30]),"+f"(d[31]),"+f"(d[32]),"+f"(d[33]),"+f"(d[34]),"+f"(d[35]),"+f"(d[36]),"+f"(d[37]),"+f"(d[38]),"+f"(d[39]),"+f"(d[40]),"+f"(d[41]),"+f"(d[42]),"+f"(d[43]),"+f"(d[44]),"+f"(d[45]),"+f"(d[46]),"+f"(d[47]),"+f"(d[48]),"+f"(d[49]),"+f"(d[50]),"+f"(d[51]),"+f"(d[52]),"+f"(d[53]),"+f"(d[54]),"+f"(d[55]),"+f"(d[56]),"+f"(d[57]),"+f"(d[58]),"+f"(d[59]),"+f"(d[60]),"+f"(d[61]),"+f"(d[62]),"+f"(d[63])
        : "r"(ab), "r"(bb), "n"(AO), "n"(BO), "n"(BH));
}
template <uint32_t AO, uint32_t BO, uint32_t BH> __device__ __forceinline__ void wg_ss128_z(float (&d)[64], uint32_t ab, uint32_t bb) {
    asm volatile("{\n.reg .b64 da, db;\n.reg .b32 ta, tb, th, ah;\nadd.u32 ta, %64, %66;\nadd.u32 tb, %65, %67;\nmov.b32 th, %68;\nmov.b32 ah, 0x40000040;\nmov.b64 da, {ta, ah};\nmov.b64 db, {tb, th};\n"
        "wgmma.mma_async.sync.aligned.m64n128k16.f32.bf16.bf16 {%0,%1,%2,%3,%4,%5,%6,%7,%8,%9,%10,%11,%12,%13,%14,%15,%16,%17,%18,%19,%20,%21,%22,%23,%24,%25,%26,%27,%28,%29,%30,%31,%32,%33,%34,%35,%36,%37,%38,%39,%40,%41,%42,%43,%44,%45,%46,%47,%48,%49,%50,%51,%52,%53,%54,%55,%56,%57,%58,%59,%60,%61,%62,%63}, da, db, 0, 1, 1, 0, 1;\n}\n"
        : "=f"(d[0]),"=f"(d[1]),"=f"(d[2]),"=f"(d[3]),"=f"(d[4]),"=f"(d[5]),"=f"(d[6]),"=f"(d[7]),"=f"(d[8]),"=f"(d[9]),"=f"(d[10]),"=f"(d[11]),"=f"(d[12]),"=f"(d[13]),"=f"(d[14]),"=f"(d[15]),"=f"(d[16]),"=f"(d[17]),"=f"(d[18]),"=f"(d[19]),"=f"(d[20]),"=f"(d[21]),"=f"(d[22]),"=f"(d[23]),"=f"(d[24]),"=f"(d[25]),"=f"(d[26]),"=f"(d[27]),"=f"(d[28]),"=f"(d[29]),"=f"(d[30]),"=f"(d[31]),"=f"(d[32]),"=f"(d[33]),"=f"(d[34]),"=f"(d[35]),"=f"(d[36]),"=f"(d[37]),"=f"(d[38]),"=f"(d[39]),"=f"(d[40]),"=f"(d[41]),"=f"(d[42]),"=f"(d[43]),"=f"(d[44]),"=f"(d[45]),"=f"(d[46]),"=f"(d[47]),"=f"(d[48]),"=f"(d[49]),"=f"(d[50]),"=f"(d[51]),"=f"(d[52]),"=f"(d[53]),"=f"(d[54]),"=f"(d[55]),"=f"(d[56]),"=f"(d[57]),"=f"(d[58]),"=f"(d[59]),"=f"(d[60]),"=f"(d[61]),"=f"(d[62]),"=f"(d[63])
        : "r"(ab), "r"(bb), "n"(AO), "n"(BO), "n"(BH));
}
template <uint32_t BO, uint32_t BH> __device__ __forceinline__ void wg_rs128(float (&d)[64], uint32_t a0, uint32_t a1, uint32_t a2, uint32_t a3, uint32_t bb) {
    asm volatile("{\n.reg .b64 db;\n.reg .b32 tb, th;\nadd.u32 tb, %68, %69;\nmov.b32 th, %70;\nmov.b64 db, {tb, th};\n"
        "wgmma.mma_async.sync.aligned.m64n128k16.f32.bf16.bf16 {%0,%1,%2,%3,%4,%5,%6,%7,%8,%9,%10,%11,%12,%13,%14,%15,%16,%17,%18,%19,%20,%21,%22,%23,%24,%25,%26,%27,%28,%29,%30,%31,%32,%33,%34,%35,%36,%37,%38,%39,%40,%41,%42,%43,%44,%45,%46,%47,%48,%49,%50,%51,%52,%53,%54,%55,%56,%57,%58,%59,%60,%61,%62,%63}, {%64,%65,%66,%67}, db, 1, 1, 1, 1;\n}\n"
        : "+f"(d[0]),"+f"(d[1]),"+f"(d[2]),"+f"(d[3]),"+f"(d[4]),"+f"(d[5]),"+f"(d[6]),"+f"(d[7]),"+f"(d[8]),"+f"(d[9]),"+f"(d[10]),"+f"(d[11]),"+f"(d[12]),"+f"(d[13]),"+f"(d[14]),"+f"(d[15]),"+f"(d[16]),"+f"(d[17]),"+f"(d[18]),"+f"(d[19]),"+f"(d[20]),"+f"(d[21]),"+f"(d[22]),"+f"(d[23]),"+f"(d[24]),"+f"(d[25]),"+f"(d[26]),"+f"(d[27]),"+f"(d[28]),"+f"(d[29]),"+f"(d[30]),"+f"(d[31]),"+f"(d[32]),"+f"(d[33]),"+f"(d[34]),"+f"(d[35]),"+f"(d[36]),"+f"(d[37]),"+f"(d[38]),"+f"(d[39]),"+f"(d[40]),"+f"(d[41]),"+f"(d[42]),"+f"(d[43]),"+f"(d[44]),"+f"(d[45]),"+f"(d[46]),"+f"(d[47]),"+f"(d[48]),"+f"(d[49]),"+f"(d[50]),"+f"(d[51]),"+f"(d[52]),"+f"(d[53]),"+f"(d[54]),"+f"(d[55]),"+f"(d[56]),"+f"(d[57]),"+f"(d[58]),"+f"(d[59]),"+f"(d[60]),"+f"(d[61]),"+f"(d[62]),"+f"(d[63])
        : "r"(a0), "r"(a1), "r"(a2), "r"(a3), "r"(bb), "n"(BO), "n"(BH));
}
template <uint32_t BO, uint32_t BH> __device__ __forceinline__ void wg_rs128_z(float (&d)[64], uint32_t a0, uint32_t a1, uint32_t a2, uint32_t a3, uint32_t bb) {
    asm volatile("{\n.reg .b64 db;\n.reg .b32 tb, th;\nadd.u32 tb, %68, %69;\nmov.b32 th, %70;\nmov.b64 db, {tb, th};\n"
        "wgmma.mma_async.sync.aligned.m64n128k16.f32.bf16.bf16 {%0,%1,%2,%3,%4,%5,%6,%7,%8,%9,%10,%11,%12,%13,%14,%15,%16,%17,%18,%19,%20,%21,%22,%23,%24,%25,%26,%27,%28,%29,%30,%31,%32,%33,%34,%35,%36,%37,%38,%39,%40,%41,%42,%43,%44,%45,%46,%47,%48,%49,%50,%51,%52,%53,%54,%55,%56,%57,%58,%59,%60,%61,%62,%63}, {%64,%65,%66,%67}, db, 0, 1, 1, 1;\n}\n"
        : "=f"(d[0]),"=f"(d[1]),"=f"(d[2]),"=f"(d[3]),"=f"(d[4]),"=f"(d[5]),"=f"(d[6]),"=f"(d[7]),"=f"(d[8]),"=f"(d[9]),"=f"(d[10]),"=f"(d[11]),"=f"(d[12]),"=f"(d[13]),"=f"(d[14]),"=f"(d[15]),"=f"(d[16]),"=f"(d[17]),"=f"(d[18]),"=f"(d[19]),"=f"(d[20]),"=f"(d[21]),"=f"(d[22]),"=f"(d[23]),"=f"(d[24]),"=f"(d[25]),"=f"(d[26]),"=f"(d[27]),"=f"(d[28]),"=f"(d[29]),"=f"(d[30]),"=f"(d[31]),"=f"(d[32]),"=f"(d[33]),"=f"(d[34]),"=f"(d[35]),"=f"(d[36]),"=f"(d[37]),"=f"(d[38]),"=f"(d[39]),"=f"(d[40]),"=f"(d[41]),"=f"(d[42]),"=f"(d[43]),"=f"(d[44]),"=f"(d[45]),"=f"(d[46]),"=f"(d[47]),"=f"(d[48]),"=f"(d[49]),"=f"(d[50]),"=f"(d[51]),"=f"(d[52]),"=f"(d[53]),"=f"(d[54]),"=f"(d[55]),"=f"(d[56]),"=f"(d[57]),"=f"(d[58]),"=f"(d[59]),"=f"(d[60]),"=f"(d[61]),"=f"(d[62]),"=f"(d[63])
        : "r"(a0), "r"(a1), "r"(a2), "r"(a3), "r"(bb), "n"(BO), "n"(BH));
}
template <uint32_t AO, uint32_t BO, uint32_t BH> __device__ __forceinline__ void wg_ss64t(float (&d)[32], uint32_t ab, uint32_t bb) {
    asm volatile("{\n.reg .b64 da, db;\n.reg .b32 ta, tb, th, ah;\nadd.u32 ta, %32, %34;\nadd.u32 tb, %33, %35;\nmov.b32 th, %36;\nmov.b32 ah, 0x40000040;\nmov.b64 da, {ta, ah};\nmov.b64 db, {tb, th};\n"
        "wgmma.mma_async.sync.aligned.m64n64k16.f32.bf16.bf16 {%0,%1,%2,%3,%4,%5,%6,%7,%8,%9,%10,%11,%12,%13,%14,%15,%16,%17,%18,%19,%20,%21,%22,%23,%24,%25,%26,%27,%28,%29,%30,%31}, da, db, 1, 1, 1, 1, 1;\n}\n"
        : "+f"(d[0]),"+f"(d[1]),"+f"(d[2]),"+f"(d[3]),"+f"(d[4]),"+f"(d[5]),"+f"(d[6]),"+f"(d[7]),"+f"(d[8]),"+f"(d[9]),"+f"(d[10]),"+f"(d[11]),"+f"(d[12]),"+f"(d[13]),"+f"(d[14]),"+f"(d[15]),"+f"(d[16]),"+f"(d[17]),"+f"(d[18]),"+f"(d[19]),"+f"(d[20]),"+f"(d[21]),"+f"(d[22]),"+f"(d[23]),"+f"(d[24]),"+f"(d[25]),"+f"(d[26]),"+f"(d[27]),"+f"(d[28]),"+f"(d[29]),"+f"(d[30]),"+f"(d[31])
        : "r"(ab), "r"(bb), "n"(AO), "n"(BO), "n"(BH));
}
template <uint32_t AO, uint32_t BO, uint32_t BH> __device__ __forceinline__ void wg_ss64t_z(float (&d)[32], uint32_t ab, uint32_t bb) {
    asm volatile("{\n.reg .b64 da, db;\n.reg .b32 ta, tb, th, ah;\nadd.u32 ta, %32, %34;\nadd.u32 tb, %33, %35;\nmov.b32 th, %36;\nmov.b32 ah, 0x40000040;\nmov.b64 da, {ta, ah};\nmov.b64 db, {tb, th};\n"
        "wgmma.mma_async.sync.aligned.m64n64k16.f32.bf16.bf16 {%0,%1,%2,%3,%4,%5,%6,%7,%8,%9,%10,%11,%12,%13,%14,%15,%16,%17,%18,%19,%20,%21,%22,%23,%24,%25,%26,%27,%28,%29,%30,%31}, da, db, 0, 1, 1, 1, 1;\n}\n"
        : "=f"(d[0]),"=f"(d[1]),"=f"(d[2]),"=f"(d[3]),"=f"(d[4]),"=f"(d[5]),"=f"(d[6]),"=f"(d[7]),"=f"(d[8]),"=f"(d[9]),"=f"(d[10]),"=f"(d[11]),"=f"(d[12]),"=f"(d[13]),"=f"(d[14]),"=f"(d[15]),"=f"(d[16]),"=f"(d[17]),"=f"(d[18]),"=f"(d[19]),"=f"(d[20]),"=f"(d[21]),"=f"(d[22]),"=f"(d[23]),"=f"(d[24]),"=f"(d[25]),"=f"(d[26]),"=f"(d[27]),"=f"(d[28]),"=f"(d[29]),"=f"(d[30]),"=f"(d[31])
        : "r"(ab), "r"(bb), "n"(AO), "n"(BO), "n"(BH));
}
template <uint32_t AO, uint32_t BO, uint32_t BH> __device__ __forceinline__ void wg_ss8t(float (&d)[4], uint32_t ab, uint32_t bb) {
    asm volatile("{\n.reg .b64 da, db;\n.reg .b32 ta, tb, th, ah;\nadd.u32 ta, %4, %6;\nadd.u32 tb, %5, %7;\nmov.b32 th, %8;\nmov.b32 ah, 0x40000040;\nmov.b64 da, {ta, ah};\nmov.b64 db, {tb, th};\n"
        "wgmma.mma_async.sync.aligned.m64n8k16.f32.bf16.bf16 {%0,%1,%2,%3}, da, db, 1, 1, 1, 1, 0;\n}\n"
        : "+f"(d[0]),"+f"(d[1]),"+f"(d[2]),"+f"(d[3])
        : "r"(ab), "r"(bb), "n"(AO), "n"(BO), "n"(BH));
}
template <uint32_t AO, uint32_t BO, uint32_t BH> __device__ __forceinline__ void wg_ss8t_z(float (&d)[4], uint32_t ab, uint32_t bb) {
    asm volatile("{\n.reg .b64 da, db;\n.reg .b32 ta, tb, th, ah;\nadd.u32 ta, %4, %6;\nadd.u32 tb, %5, %7;\nmov.b32 th, %8;\nmov.b32 ah, 0x40000040;\nmov.b64 da, {ta, ah};\nmov.b64 db, {tb, th};\n"
        "wgmma.mma_async.sync.aligned.m64n8k16.f32.bf16.bf16 {%0,%1,%2,%3}, da, db, 0, 1, 1, 1, 0;\n}\n"
        : "=f"(d[0]),"=f"(d[1]),"=f"(d[2]),"=f"(d[3])
        : "r"(ab), "r"(bb), "n"(AO), "n"(BO), "n"(BH));
}
template <uint32_t BO, uint32_t BH> __device__ __forceinline__ void wg_rs24_z(float (&d)[12], uint32_t a0, uint32_t a1, uint32_t a2, uint32_t a3, uint32_t bb) {
    asm volatile("{\n.reg .b64 db;\n.reg .b32 tb, th;\nadd.u32 tb, %16, %17;\nmov.b32 th, %18;\nmov.b64 db, {tb, th};\n"
        "wgmma.mma_async.sync.aligned.m64n24k16.f32.bf16.bf16 {%0,%1,%2,%3,%4,%5,%6,%7,%8,%9,%10,%11}, {%12,%13,%14,%15}, db, 0, 1, 1, 0;\n}\n"
        : "=f"(d[0]),"=f"(d[1]),"=f"(d[2]),"=f"(d[3]),"=f"(d[4]),"=f"(d[5]),"=f"(d[6]),"=f"(d[7]),"=f"(d[8]),"=f"(d[9]),"=f"(d[10]),"=f"(d[11])
        : "r"(a0), "r"(a1), "r"(a2), "r"(a3), "r"(bb), "n"(BO), "n"(BH));
}

constexpr uint32_t DH128 = 64u | 0x40000000u;
constexpr uint32_t DH64 = 32u | 0x80000000u;
constexpr uint32_t LBO4K = (4096u >> 4) << 16, LBO8K = (8192u >> 4) << 16, LBO1 = 1u << 16;

template <uint32_t AO, uint32_t BO, bool SW64, bool FIRST> __device__ __forceinline__ void stage_ss(float (&acc)[64], uint32_t ab, uint32_t bb) {
    constexpr uint32_t KS = SW64 ? 64 : 128, BH = SW64 ? DH64 : DH128, B0 = BO + (SW64 ? LBO4K : LBO8K);
    wg_fence();
    if (FIRST) wg_ss128_z<AO, B0, BH>(acc, ab, bb); else wg_ss128<AO, B0, BH>(acc, ab, bb);
    wg_ss128<AO + 2, B0 + KS, BH>(acc, ab, bb);
    wg_ss128<AO + 4, B0 + 2 * KS, BH>(acc, ab, bb);
    wg_ss128<AO + 6, B0 + 3 * KS, BH>(acc, ab, bb);
    wg_commit();
}
template <uint32_t BO, bool FIRST> __device__ __forceinline__ void stage_rs(float (&acc)[64], const uint32_t (&f)[16], uint32_t bb) {
    wg_fence();
    if (FIRST) wg_rs128_z<BO + LBO8K, DH128>(acc, f[0], f[1], f[2], f[3], bb); else wg_rs128<BO + LBO8K, DH128>(acc, f[0], f[1], f[2], f[3], bb);
    wg_rs128<BO + LBO8K + 128, DH128>(acc, f[4], f[5], f[6], f[7], bb);
    wg_rs128<BO + LBO8K + 256, DH128>(acc, f[8], f[9], f[10], f[11], bb);
    wg_rs128<BO + LBO8K + 384, DH128>(acc, f[12], f[13], f[14], f[15], bb);
    wg_commit();
}

template <int N> __device__ __forceinline__ void stash(uint32_t base, uint32_t sw, const uint32_t (&f)[N]) {
#pragma unroll
    for (int t = 0; t < N / 4; t++) stsm4(base + ((sw ^ (2 * t)) << 4), f[4 * t], f[4 * t + 1], f[4 * t + 2], f[4 * t + 3]);
}

template <int V0, int V1, int N> __device__ __forceinline__ void send_frag(const uint32_t (&f)[N], uint4* p, uint32_t tag) {
#pragma unroll
    for (int v = V0; v < V1; v++) st_pkt(p + v * 32, (f[4 * v] & ~1u) | tag, f[4 * v + 1], f[4 * v + 2], f[4 * v + 3]);
}
template <int V0, int V1, int N> __device__ __forceinline__ void send_h(const uint32_t (&f)[N], uint4* p) {
#pragma unroll
    for (int v = V0; v < V1; v++) {
        const int h = v >> 1, hi = v & 1;
        asm volatile("st.global.v4.u32 [%0], {%1,%2,%3,%4};" :: "l"(p + 4 * h + 64 * hi),
                     "r"(f[8 * h + hi]), "r"(f[8 * h + 2 + hi]), "r"(f[8 * h + 4 + hi]), "r"(f[8 * h + 6 + hi]) : "memory");
    }
}
template <int O, int N, int M> __device__ __forceinline__ void pack_sub(uint32_t (&f)[N], const float (&acc)[M]) {
#pragma unroll
    for (int i = 0; i < N; i++) f[i] = keep(pack2(acc[O + 2 * i], acc[O + 2 * i + 1]));
}
template <int N> __device__ __forceinline__ void recv_issue(uint32_t (&q)[N], const uint4* p) {
#pragma unroll
    for (int v = 0; v < N / 4; v++) ld_pkt(p + v * 32, q[4 * v], q[4 * v + 1], q[4 * v + 2], q[4 * v + 3]);
}
template <int N> __device__ __forceinline__ void recv_check(uint32_t (&q)[N], const uint4* p, uint32_t tag) {
    uint32_t it = 0;
    while (true) {
        uint32_t bad = 0;
#pragma unroll
        for (int v = 0; v < N / 4; v++) bad |= q[4 * v] ^ tag;
        if (__all_sync(0xffffffffu, (bad & 1u) == 0) || ++it > SPIN_GLOBAL) break;
        recv_issue(q, p);
    }
}
__device__ __forceinline__ void accum(const uint32_t (&q)[32], float (&sum)[64]) {
#pragma unroll
    for (int i = 0; i < 32; i++) { sum[2 * i] += bf_lo(q[i]); sum[2 * i + 1] += bf_hi(q[i]); }
}

}

__global__ void __launch_bounds__(384, 1)
fused_kernel(const __grid_constant__ Maps maps, const __nv_bfloat16* __restrict__ xg, const __nv_bfloat16* __restrict__ gate_w,
             const char* __restrict__ pf_qkv, const char* __restrict__ pf_g, const char* __restrict__ pf_u,
             const char* __restrict__ pf_d, const char* __restrict__ pf_o, __nv_bfloat16* __restrict__ out) {
    extern __shared__ __align__(1024) uint8_t smem_raw[];
    const uint32_t sb = (uint32_t)__cvta_generic_to_shared(smem_raw);
    const int tid = threadIdx.x, lane = tid & 31;
    const int warp = __shfl_sync(0xffffffffu, tid >> 5, 0);
    const int j = ((blockIdx.x >> 4) & 4) | ((blockIdx.x & 1) << 1) | ((blockIdx.x >> 5) & 1);
    const int r = (blockIdx.x >> 1) & 15;

    if (warp == 0) { TSG(0, 30); TS(0, 0); }
    if (tid == 256) {
        for (int i = 0; i < 5; i++) { mbar_init(sb + B_FULL + 8 * i, 1); mbar_init(sb + B_EMPTY + 8 * i, 2); }
        for (int i = 0; i < 9; i++) mbar_init(sb + B_XFULL + 8 * i, 1);
        asm volatile("fence.mbarrier_init.release.cluster;" ::: "memory");
        mbar_expect(sb + B_XFULL, 16384);
        tma2(sb + OFF_X, &maps.x, 0, r * 128, sb + B_XFULL);
        TS2(0);
        mbar_expect(sb + B_FULL, 16384);
        tmaw3(sb + OFF_RING, &maps.kv, 64 * j, 0, 1, sb + B_FULL);
        TS2(1);
        mbar_expect(sb + B_FULL + 8, 16384);
        tmaw3(sb + OFF_RING + 16384, &maps.gu, 224 * j, 0, 0, sb + B_FULL + 8);
    } else if (tid == 288) {
        for (int i = 0; i < 3; i++) mbar_init(sb + B_HSENT + 8 * i, 8);
        for (int i = 0; i < 4; i++) { mbar_init(sb + B_EFULL + 8 * i, 1); mbar_init(sb + B_EEMPTY + 8 * i, 2); }
        mbar_init(sb + B_XFREE, 2); mbar_init(sb + B_XFREE + 8, 2); mbar_init(sb + B_XFREE + 16, 2);
        mbar_init(sb + B_AHEAD, 1); mbar_init(sb + B_PART, 1); mbar_init(sb + B_LAST, 1); mbar_init(sb + B_RFREE, 2);
        mbar_expect(sb + B_LAST, 16384); mbar_init(sb + B_GRDY, 1); mbar_init(sb + B_KVDONE, 8); mbar_init(sb + B_KVRDY, 1);
        asm volatile("fence.mbarrier_init.release.cluster;" ::: "memory");
    } else if (warp == 10 && lane < 10) {
        asm volatile("prefetch.tensormap [%0];" :: "l"(&maps.gu + lane) : "memory");
    }
    __syncthreads();
    asm volatile("barrier.cluster.arrive.relaxed.aligned;" ::: "memory");

    if (warp >= 8) {
        asm volatile("setmaxnreg.dec.sync.aligned.u32 56;");
        if (warp == 8) {
            if (lane == 0) {
                int slot = 2, ph = 1;
                uint32_t full, dst;
                { mbar_expect(sb + B_XFULL + 8, 16384); tma2(sb + OFF_X + 16384, &maps.x, 64, r * 128, sb + B_XFULL + 8); }
#define P_BEGIN(S, BYTES) full = sb + B_FULL + 8 * slot; dst = sb + OFF_RING + slot * 16384; \
                mbar_wait(sb + B_EMPTY + 8 * slot, ph); TS2(S); mbar_expect(full, BYTES);
#define P_END() if (++slot == 5) { slot = 0; ph ^= 1; }
                for (int s = 2; s < 16; s++) {
                    const int kb = (int)(0x7654763542312100ull >> (4 * s)) & 15;
                    P_BEGIN(s, 16384) {
                        if ((0x0DADu >> s) & 1) tmaw3(dst, &maps.kv, 64 * j, 64 * kb, 1, full);
                        else tmaw3(dst, &maps.gu, 224 * j, 64 * kb, 0, full);
                    }
                    const int xb = (int)(0x0000000765403210ull >> (4 * s)) & 15;
                    if (xb) { mbar_expect(sb + B_XFULL + 8 * xb, 16384); tma2(sb + OFF_X + xb * 16384, &maps.x, 64 * xb, r * 128, sb + B_XFULL + 8 * xb); }
                    P_END()
                }
                for (int s = 0; s < 24; s++) {
                    P_BEGIN(16 + s, 16384) {
                        if (s < 8) {
                            tmaw3(dst, &maps.q64, 0, 64 * s, 2 * j, full);
                            tmaw3(dst + 8192, &maps.gu64, 224 * j + 192, 64 * s, 0, full);
                        } else {
                            tmaw3(dst, &maps.gu, 224 * j + 64 * (s >> 3), 64 * (s & 7), 0, full);
                        }
                    }
                    P_END()
                }
                const int p = j >> 1;
#pragma unroll 1
                for (int t = 0; t < 18; t++) {
                    const int q = t >= 9, sl = (int)(0x846352107ull >> (4 * (t - 9 * q))) & 15;
                    const int u = (int)((q ? 0x432186758ull : 0x327064105ull) >> (4 * (t - 9 * q))) & 15;
                    const int cw = (j & 1) * 4 + ((p & 2) ^ ((t == 5 || t > 9) ? 0 : 2)), cc = 64 * cw;
                    if (sl < 5) {
                        full = sb + B_FULL + 8 * sl; dst = sb + OFF_RING + sl * 16384;
                        mbar_wait(sb + B_EMPTY + 8 * sl, q ^ 1);
                    } else {
                        full = sb + B_EFULL + 8 * (sl - 5); dst = sb + OFF_X + (sl == 7 ? 8 : sl == 8 ? 7 : sl) * 16384;
                        mbar_wait(sb + B_EEMPTY + 8 * (sl - 5), q);
                    }
                    TS2(40 + t);
                    mbar_expect(full, 16384);
                    {
                        if (u == 4) {
                            tmaw5(dst, &maps.wdph, cc, 14 * p + 6, full); tmaw5(dst + 4096, &maps.wdph, cc, 14 * p + 13, full);
                            tmaw5(dst + 8192, &maps.wdph, cc + 64, 14 * p + 6, full); tmaw5(dst + 12288, &maps.wdph, cc + 64, 14 * p + 13, full);
                        } else if (u > 4) {
                            const int js = u > 6 ? j ^ 1 : j;
                            tmaw3(dst, (u & 1) ? &maps.wow : &maps.wdw, 0, (u & 1) ? 64 * js : 224 * js + 128, cw, full);
                        } else {
                            const int g = 14 * p + 7 * (u & 1) + (u & 2);
                            tmaw5(dst, &maps.wdp, cc, g, full); tmaw5(dst + 8192, &maps.wdp, cc + 64, g, full);
                        }
                    }
                }
            }
        } else if (warp < 11) {
            const int hx = warp - 9;
            uint32_t epoch;
            asm volatile("ld.relaxed.gpu.global.u32 %0, [%1];" : "=r"(epoch) : "l"(g_epoch + blockIdx.x) : "memory");
            {
                const uint4* xr = (const uint4*)(xg + (size_t)(r * 128 + j * 16 + hx * 8) * kD) + lane;
                const uint4 wa = __ldg((const uint4*)gate_w + lane), wb = __ldg((const uint4*)gate_w + 32 + lane);
                const uint32_t tag = (epoch + 1) & 1;
                uint4* gp = g_gx + r * 32;
                if (lane < 2) st_pkt(gp + j * 4 + hx * 2 + lane, tag ^ 1, 0, 0, 0);
                float s[8];
#pragma unroll
                for (int i0 = 0; i0 < 8; i0 += 4) {
                    uint4 va[4], vb[4];
#pragma unroll
                    for (int i = 0; i < 4; i++) { va[i] = __ldg(xr + (i0 + i) * 64); vb[i] = __ldg(xr + (i0 + i) * 64 + 32); }
#pragma unroll
                    for (int i = 0; i < 4; i++) {
                        float t0 = bf_lo(va[i].x) * bf_lo(wa.x), t1 = bf_hi(va[i].x) * bf_hi(wa.x);
                        t0 = fmaf(bf_lo(va[i].y), bf_lo(wa.y), t0); t1 = fmaf(bf_hi(va[i].y), bf_hi(wa.y), t1);
                        t0 = fmaf(bf_lo(va[i].z), bf_lo(wa.z), t0); t1 = fmaf(bf_hi(va[i].z), bf_hi(wa.z), t1);
                        t0 = fmaf(bf_lo(va[i].w), bf_lo(wa.w), t0); t1 = fmaf(bf_hi(va[i].w), bf_hi(wa.w), t1);
                        t0 = fmaf(bf_lo(vb[i].x), bf_lo(wb.x), t0); t1 = fmaf(bf_hi(vb[i].x), bf_hi(wb.x), t1);
                        t0 = fmaf(bf_lo(vb[i].y), bf_lo(wb.y), t0); t1 = fmaf(bf_hi(vb[i].y), bf_hi(wb.y), t1);
                        t0 = fmaf(bf_lo(vb[i].z), bf_lo(wb.z), t0); t1 = fmaf(bf_hi(vb[i].z), bf_hi(wb.z), t1);
                        t0 = fmaf(bf_lo(vb[i].w), bf_lo(wb.w), t0); t1 = fmaf(bf_hi(vb[i].w), bf_hi(wb.w), t1);
                        s[i0 + i] = t0 + t1;
                    }
                }
#pragma unroll
                for (int i = 0; i < 8; i++) {
#pragma unroll
                    for (int o = 16; o; o >>= 1) s[i] += __shfl_xor_sync(0xffffffffu, s[i], o);
                    s[i] = 1.f / (1.f + __expf(-s[i]));
                }
                if (lane < 2) {
                    const float v0 = lane ? s[4] : s[0], v1 = lane ? s[5] : s[1], v2 = lane ? s[6] : s[2], v3 = lane ? s[7] : s[3];
                    st_pkt(gp + j * 4 + hx * 2 + lane, (__float_as_uint(v0) & ~1u) | tag, __float_as_uint(v1), __float_as_uint(v2), __float_as_uint(v3));
                }
                if (hx == 1) {
                    asm volatile("st.shared.u32 [%0], %1;" :: "r"(sb + OFF_ONES + lane * 4), "r"(0x3f803f80u) : "memory");
                    asm volatile("fence.proxy.async.shared::cta;" ::: "memory");
                }
                asm volatile("bar.sync 3, 96;" ::: "memory");
                if (hx == 0) {
                    uint32_t q[4];
                    recv_issue(q, gp + lane);
                    recv_check(q, gp + lane, tag);
                    asm volatile("st.shared.v4.u32 [%0], {%1,%2,%3,%4};" :: "r"(sb + OFF_G + lane * 16), "r"(q[0]), "r"(q[1]), "r"(q[2]), "r"(q[3]) : "memory");
                    if (lane == 0) {
                        asm volatile("st.shared.u32 [%0], %1;" :: "r"(sb + OFF_EPOCH), "r"(epoch) : "memory");
                        g_epoch[blockIdx.x] = epoch + 1;
                    }
                    __syncwarp();
                    if (lane == 0) mbar_arrive(sb + B_GRDY);
                } else {
                    if (r == 0) {
                        float4* zp = (float4*)(g_kvacc + (((epoch & 1) ^ 1) * 8 + j) * 4 * 272);
                        for (int i = lane; i < 272; i += 32) zp[i] = make_float4(0.f, 0.f, 0.f, 0.f);
                    }
                }
            }
            TS(2 + hx, 1);
#define PUBLISH_H(B) do { mbar_wait(sb + B_HSENT + 8 * (B), 0); if (lane == 0) { \
                asm volatile("st.release.gpu.global.u32 [%0], %1;" :: "l"(g_hflag + (r * 8 + j) * 8 + (B)), "r"(epoch + 1) : "memory"); } __syncwarp(); } while (0)
            if (hx == 1) {
#pragma unroll 1
                for (int b = 0; b < 3; b++) { PUBLISH_H(b); TS(3, 5 + b); }
            } else {
                const float* accp = g_kvacc + ((epoch & 1) * 8 + j) * 4 * 272;
                unsigned* cnt = g_kvcnt + j * 32;
                mbar_wait(sb + B_KVDONE, 0);
                TS(2, 5);
                if (lane == 0) asm volatile("red.release.gpu.global.add.u32 [%0], 1;" :: "l"(cnt) : "memory");
                __syncwarp();
                TS(2, 2);
                {
                    const unsigned target = 16u * (epoch + 1);
                    uint32_t it = 0, v;
                    do {
                        asm volatile("ld.acquire.gpu.global.u32 %0, [%1];" : "=r"(v) : "l"(cnt) : "memory");
                    } while ((int)(v - target) < 0 && ++it < SPIN_GLOBAL);
                }
                TS(2, 3);
#pragma unroll
                for (int h = 0; h < 4; h++) {
                    const float4 d0 = __ldcg((const float4*)(accp + h * 272) + lane);
                    const float4 d1 = __ldcg((const float4*)(accp + h * 272 + 128) + lane);
                    const float2 z0 = __ldcg((const float2*)(accp + h * 272 + 256) + (lane & 3));
                    const float2 z1 = __ldcg((const float2*)(accp + h * 272 + 264) + (lane & 3));
                    const uint32_t ba = sb + OFF_STG + h * 768 + lane * 4;
                    asm volatile("st.shared.u32 [%0], %1;" :: "r"(ba), "r"(pack2(d0.x, d0.y)) : "memory");
                    asm volatile("st.shared.u32 [%0], %1;" :: "r"(ba + 128), "r"(pack2(d1.x, d1.y)) : "memory");
                    asm volatile("st.shared.u32 [%0], %1;" :: "r"(ba + 256), "r"(pack2(d0.z, d0.w)) : "memory");
                    asm volatile("st.shared.u32 [%0], %1;" :: "r"(ba + 384), "r"(pack2(d1.z, d1.w)) : "memory");
                    asm volatile("st.shared.u32 [%0], %1;" :: "r"(ba + 512), "r"(pack2(z0.x, z0.y)) : "memory");
                    asm volatile("st.shared.u32 [%0], %1;" :: "r"(ba + 640), "r"(pack2(z1.x, z1.y)) : "memory");
                }
                asm volatile("fence.proxy.async.shared::cta;" ::: "memory");
                __syncwarp();
                if (lane == 0) mbar_arrive(sb + B_KVRDY);
                TS(2, 4);
            }
        } else {
            uint32_t epoch;
            asm volatile("ld.relaxed.gpu.global.u32 %0, [%1];" : "=r"(epoch) : "l"(g_epoch + blockIdx.x) : "memory");
            asm volatile("bar.arrive 3, 96;" :: "r"(epoch) : "memory");
            const int b = blockIdx.x, p = j >> 1;
            mbar_wait(sb + B_XFULL, 0);
#pragma unroll 1
            for (int kb = 1; kb < 8; kb++) {
                mbar_wait(sb + B_XFULL + 8 * kb, 0);
                const char* base = kb < 3 ? pf_g : kb < 5 ? pf_u : kb == 5 ? pf_qkv : pf_d;
                const int off = kb == 5 ? b * 12288 : b * 14336 + ((kb < 5 ? kb - 1 : kb) & 1) * 7168;
                if (kb == 5) {
                    asm volatile("prefetch.global.L2 [%0];" :: "l"(base + off + (lane >> 3) * 3072 + (lane & 7) * 128));
                } else {
                    asm volatile("prefetch.global.L2 [%0];" :: "l"(base + off + lane * 128));
                    if (lane < 24) asm volatile("prefetch.global.L2 [%0];" :: "l"(base + off + 4096 + lane * 128));
                }
                if (kb == 7) asm volatile("prefetch.global.L2 [%0];" :: "l"(pf_o + b * 4096 + lane * 128));
            }
            {
                const uint32_t want = epoch + 1;
                const int hrow = (r * 4 + p) * 5 * 128;
                const unsigned* fl = g_hflag + (r * 8 + (j & 6)) * 8 + (lane & 15);
                uint32_t it = 0;
                int i = 0;
                mbar_wait(sb + B_HSENT + 8, 0);
#pragma unroll 1
                while (i < 3 && ++it < SPIN_GLOBAL) {
                    uint32_t v;
                    asm volatile("ld.acquire.gpu.global.u32 %0, [%1];" : "=r"(v) : "l"(fl) : "memory");
                    const uint32_t rdy = __ballot_sync(0xffffffffu, v == want);
#pragma unroll 1
                    while (i < 3 && ((rdy >> i) & 0x101u) == 0x101u) {
                        if (i < 2) mbar_wait(sb + B_XFREE + 8 * i, 0);
                        if (lane == 0) {
                            const int pc = (6 - 2 * i) % 6;
                            asm volatile("fence.proxy.async.global;" ::: "memory");
                            TS2(140 + i);
                            mbar_expect(sb + B_XFULL + 8 * pc, i != 1 ? 32768 : 16384);
                            tma2(sb + OFF_X + pc * 16384, i != 1 ? &maps.hx2 : &maps.hx, 0, hrow + pc * 128, sb + B_XFULL + 8 * pc);
                        }
                        i++;
                    }
                }
            }
        }
        asm volatile("barrier.cluster.wait;" ::: "memory");
    } else {
        asm volatile("setmaxnreg.inc.sync.aligned.u32 224;");
        const int wg = warp >> 2;
        const bool elect = (tid & 127) == 0;
        const uint32_t sbd = (sb & 0x3FFFFu) >> 4, xlo = (sbd + wg * 512) | LBO1;
        auto release = [&](uint32_t bar) {
            if (elect) {
                mbar_arrive(sb + bar);
            }
        };
#define S_SL(S) ((S) < 40 ? (S) % 5 : (int)((0x846352107ull >> (4 * (((S) - 40) % 9))) & 15))
#define S_WAIT(S) do { mbar_wait(sb + (S_SL(S) < 5 ? B_FULL + 8 * S_SL(S) : B_EFULL + 8 * (S_SL(S) - 5)), (S) < 40 ? ((S) / 5) & 1 : (S) >= 49); \
            if (PROF && tid == 0) TS2(64 + (S)); } while (0)
#define S_B(S) (S_SL(S) < 5 ? OFF_RING / 16 + S_SL(S) * 1024 : (S_SL(S) == 7 ? 8 : S_SL(S) == 8 ? 7 : S_SL(S)) * 1024)
#define S_REL(S) do { if ((S) < 49) release(S_SL(S) < 5 ? B_EMPTY + 8 * S_SL(S) : B_EEMPTY + 8 * (S_SL(S) - 5)); } while (0)
#define G1(S, acc, SW, KB) stage_ss<(KB) * 1024, S_B(S), SW, (KB) == 0>(acc, xlo, sbd)
#define RET(S) do { S_WAIT((S) + 1); wg_wait<1>(); S_REL((S) - 1); } while (0)
#define RET2(S) do { S_WAIT((S) + 1); wg_wait<2>(); S_REL((S) - 1); } while (0)
#define SCHED() mbar_wait(sb + B_XFULL + 8 * 7, 0)
#define A2_SYNC() do { asm volatile("fence.proxy.async.shared::cta;" ::: "memory"); asm volatile("bar.sync %0, 128;" :: "r"(wg + 1) : "memory"); } while (0)
#define H_EPI(acc, F, I0, I1, OG, OU) _Pragma("unroll") for (int i = (I0); i < (I1); i++) \
            F[i] = keep(hmul2(pack2(acc[(OG) + 2 * i] * acc[(OU) + 2 * i], acc[(OG) + 2 * i + 1] * acc[(OU) + 2 * i + 1]), (i & 1) ? m_hi : m_lo))
#define PHI(acc, F, I0, I1) _Pragma("unroll") for (int i = (I0); i < (I1); i++) F[i] = keep(phi2(acc[2 * i], acc[2 * i + 1]))

        float a0[64], b0[64], a1[64], a2_[64], a3[64];
        mbar_wait(sb + B_XFULL, 0);
#define X_WAIT(KB) do { mbar_wait(sb + B_XFULL + 8 * (KB), 0); if (PROF && tid == 0) TS2(128 + (KB)); } while (0)
        S_WAIT(0); G1(0, b0, false, 0);
        if ((warp & 3) == 0) TS(wg, 1);
        S_WAIT(1); G1(1, a0, false, 0); RET(1);
        X_WAIT(1); G1(2, b0, false, 1); RET(2);
        X_WAIT(2); G1(3, b0, false, 2); RET(3);
        G1(4, a0, false, 1); RET(4);
        X_WAIT(3); G1(5, b0, false, 3); RET(5);
        G1(6, a0, false, 2); RET(6);
        X_WAIT(4); G1(7, b0, false, 4); RET(7);
        X_WAIT(5); G1(8, b0, false, 5); RET(8);
        G1(9, a0, false, 3); RET(9);
        X_WAIT(6); G1(10, b0, false, 6); RET(10);
        X_WAIT(7); G1(11, b0, false, 7); RET(11);
        G1(12, a0, false, 4);
        const uint32_t lrow = ((lane & 7) + 8 * ((lane >> 3) & 1)) * 128;
        const uint32_t srow = (warp & 3) * 2048 + lrow;
        const uint32_t ssw = (lane >> 4) ^ (lane & 7);
        uint4* const hsend = g_hx + (size_t)((r * 4 + (j >> 1)) * 5 + (j & 1)) * 1024 + warp * 128 + (lane >> 2) * 8 + (lane & 3);
#define SENT_H(B) do { __syncwarp(); if (lane == 0) mbar_arrive(sb + B_HSENT + 8 * (B)); } while (0)
        RET(12);
        pin(b0);
        uint32_t fh0[16], fh1[16], fh2[16], fh3[8], fo[16], pk[16], pv[16];
        float kv[32], zs[4];
        const uint32_t stg = sb + OFF_STG + wg * 8192, stl = stg + (warp & 1) * 2048 + lrow;
#define KV_ROUND(Z) do { A2_SYNC(); wg_fence(); \
            wg_ss64t##Z<8192 + 256, 8192, DH128>(kv, xlo, xlo); wg_ss64t<8192 + 384, 8192 + 128, DH128>(kv, xlo, xlo); \
            wg_ss8t##Z<8192, OFF_ONES / 16, 0>(zs, xlo, sbd); wg_ss8t<8192 + 128, OFF_ONES / 16, 0>(zs, xlo, sbd); wg_commit(); } while (0)
        G1(13, a0, false, 5); SCHED(); pack_sub<32>(pv, b0); PHI(b0, pk, 0, 4); RET(13);
        G1(14, a0, false, 6); SCHED(); if (!(warp & 2)) stash<16>(stl + 4096, ssw, pv); PHI(b0, pk, 4, 10); RET(14);
        G1(15, a0, false, 7); SCHED(); PHI(b0, pk, 10, 16); RET(15);
        if ((warp & 3) == 0) TS(wg, 2);

        G1(16, a1, true, 0); SCHED(); if (!(warp & 2)) stash<16>(stl, ssw, pk);
        mbar_wait(sb + B_GRDY, 0);
        float g_lo, g_hi;
        uint32_t tag;
        {
            const uint32_t ga = sb + OFF_G + (warp * 16 + (lane >> 2)) * 4;
            asm volatile("ld.shared.f32 %0, [%1];" : "=f"(g_lo) : "r"(ga) : "memory");
            asm volatile("ld.shared.f32 %0, [%1];" : "=f"(g_hi) : "r"(ga + 32) : "memory");
            asm volatile("ld.shared.u32 %0, [%1];" : "=r"(tag) : "r"(sb + OFF_EPOCH) : "memory");
        }
        float* const kvp = g_kvacc + (((tag & 1) * 8 + j) * 4 + (warp & 3)) * 272;
        tag = (tag + 1) & 1;
        const uint32_t m_lo = pack2(1.f - g_lo, 1.f - g_lo), m_hi = pack2(1.f - g_hi, 1.f - g_hi);
        RET(16);
        pin(a0);
        G1(17, a1, true, 1); SCHED(); H_EPI(a0, fh0, 0, 16, 0, 32); RET(17);
        G1(18, a1, true, 2); KV_ROUND(_z); RET2(18);
        G1(19, a1, true, 3); SCHED(); send_h<0, 1>(fh0, hsend); RET(19);
        G1(20, a1, true, 4); SCHED(); if (warp & 2) { stash<16>(stl, ssw, pk); stash<16>(stl + 4096, ssw, pv); } RET(20);
        G1(21, a1, true, 5); KV_ROUND(); RET2(21);
        G1(22, a1, true, 6); RET(22);
        pin(kv); pin(zs);
        G1(23, a1, true, 7); SCHED();
#define KV_RED(W) do { asm volatile("red.global.add.v4.f32 [%0], {%1,%2,%3,%4};" :: "l"(kvp + lane * 4), "f"(kv[8 * W]), "f"(kv[8 * W + 1]), "f"(kv[8 * W + 2]), "f"(kv[8 * W + 3]) : "memory"); \
                       asm volatile("red.global.add.v4.f32 [%0], {%1,%2,%3,%4};" :: "l"(kvp + 128 + lane * 4), "f"(kv[8 * W + 4]), "f"(kv[8 * W + 5]), "f"(kv[8 * W + 6]), "f"(kv[8 * W + 7]) : "memory"); } while (0)
        if ((warp & 3) == 0) KV_RED(0); else if ((warp & 3) == 1) KV_RED(1); else if ((warp & 3) == 2) KV_RED(2); else KV_RED(3);
        if ((lane & 3) == 0) {
            asm volatile("red.global.add.f32 [%0], %1;" :: "l"(kvp + 256 + (lane >> 2)), "f"(zs[0]) : "memory");
            asm volatile("red.global.add.f32 [%0], %1;" :: "l"(kvp + 264 + (lane >> 2)), "f"(zs[2]) : "memory");
        }
        __syncwarp();
        if (lane == 0) mbar_arrive(sb + B_KVDONE);
        RET(23);
        if ((warp & 3) == 0) TS(wg, 3);

        G1(24, a2_, false, 0); SCHED(); send_h<1, 2>(fh0, hsend); RET(24);
        pin(a1);
        G1(25, a2_, false, 1); SCHED(); send_h<2, 3>(fh0, hsend); H_EPI(a1, fh3, 0, 8, 32, 48); RET(25);
        G1(26, a2_, false, 2); SCHED(); send_h<3, 4>(fh0, hsend); SENT_H(0); PHI(a1, fo, 0, 4); RET(26);
        G1(27, a2_, false, 3); SCHED(); send_h<0, 1>(fh3, hsend + 4 * 1024 - (j & 1) * 1020); PHI(a1, fo, 4, 8); RET(27);
        G1(28, a2_, false, 4); SCHED(); send_h<1, 2>(fh3, hsend + 4 * 1024 - (j & 1) * 1020); SENT_H(1); PHI(a1, fo, 8, 12); RET(28);
        G1(29, a2_, false, 5); SCHED(); PHI(a1, fo, 12, 16); RET(29);
        G1(30, a2_, false, 6); RET(30);
        G1(31, a2_, false, 7); RET(31);
        if ((warp & 3) == 0) TS(wg, 4);

        float on[4][12];
#define O_SCALE(h) do { const float s_lo = __fdividef(g_lo, on[h][8] + 1e-6f), s_hi = __fdividef(g_hi, on[h][10] + 1e-6f); \
            const uint32_t sl_ = pack2(s_lo, s_lo), sh_ = pack2(s_hi, s_hi); \
            fo[4 * h] = keep(hmul2(pack2(on[h][0], on[h][1]), sl_)); fo[4 * h + 1] = keep(hmul2(pack2(on[h][2], on[h][3]), sh_)); \
            fo[4 * h + 2] = keep(hmul2(pack2(on[h][4], on[h][5]), sl_)); fo[4 * h + 3] = keep(hmul2(pack2(on[h][6], on[h][7]), sh_)); } while (0)
        uint4* const lsend = g_lx + (size_t)(r * 8 + j) * 2048 + warp * 128 + lane;
        const uint4* const lrecv = g_lx + (size_t)(r * 8 + (j ^ 1)) * 2048 + warp * 128 + lane;
        G1(32, a3, false, 0); RET(32);
        pin(a2_);
        G1(33, a3, false, 1); SCHED(); H_EPI(a2_, fh1, 0, 16, 0, 32); send_h<0, 1>(fh1, hsend + 2 * 1024); RET(33);
        G1(34, a3, false, 2); SCHED(); send_h<1, 3>(fh1, hsend + 2 * 1024); RET(34);
        if (elect) mbar_arrive(sb + B_XFREE);
        G1(35, a3, false, 3); SCHED(); send_h<3, 4>(fh1, hsend + 2 * 1024); SENT_H(2);
        if ((warp & 3) == 0) TS(wg, 5);
        mbar_wait(sb + B_KVRDY, 0);
        if ((warp & 3) == 0) TS(wg, 6);
        wg_fence();
#define O_MMA(h) wg_rs24_z<OFF_STG / 16 + (h) * 48 + (8u << 16), 16>(on[h], fo[4 * (h)], fo[4 * (h) + 1], fo[4 * (h) + 2], fo[4 * (h) + 3], sbd)
        O_MMA(0); O_MMA(1); O_MMA(2); O_MMA(3);
        wg_commit();
        RET2(35);
        G1(36, a3, false, 4); RET(36);
        pin(on[0]); pin(on[1]); pin(on[2]); pin(on[3]);
        release(B_EEMPTY + 16);
        G1(37, a3, false, 5); SCHED(); O_SCALE(0); O_SCALE(1); O_SCALE(2); O_SCALE(3); RET(37);
        if (elect) mbar_arrive(sb + B_XFREE + 8);
        G1(38, a3, false, 6); SCHED(); send_frag<0, 2>(fo, lsend, tag); RET(38);
        release(B_EEMPTY);
        G1(39, a3, false, 7); SCHED(); send_frag<2, 4>(fo, lsend, tag); RET(39);
        release(B_EEMPTY + 8);
        if ((warp & 3) == 0) TS(wg, 7);

#define G2S(S, acc, U) stage_ss<(U) * 1024, S_B(S), false, (S) == 45>(acc, xlo, sbd)
#define G2R(S, acc, F) stage_rs<S_B(S), (S) == 40>(acc, F, sbd)
#define H_WAIT(P) do { mbar_wait(sb + B_XFULL + 8 * (P), 1); if (PROF && tid == 0) TS2(150 + (P)); } while (0)
        const int p = j >> 1, pw = (p & 2) ^ 2;
        const bool own = wg == (p & 1);
        uint4* const pbase = g_part + (size_t)(r * 2 + (j & 1)) * 16384 + (warp & 3) * 256 + lane;

        float p1[64], p2[64];
        uint32_t po[16], ph2[16];
        G2R(40, p1, fo); RET(40);
        release(B_EEMPTY + 24);
        pin(a3);
        H_WAIT(0); G2S(41, p1, 0); SCHED(); H_EPI(a3, fh2, 0, 16, 0, 32); send_frag<0, 2>(fh2, lsend + 1024, tag); RET(41);
        G2S(42, p1, 1); SCHED(); recv_issue(po, lrecv); send_frag<2, 4>(fh2, lsend + 1024, tag); RET(42);
        H_WAIT(4); G2S(43, p1, 4); RET(43);
        G2R(44, p1, fh2); RET(44);
        G2S(45, p2, 0); SCHED(); if (!(EXPT & 2)) recv_check(po, lrecv, tag); recv_issue(ph2, lrecv + 1024); RET(45);
        G2R(46, p1, po); RET(46);
        asm volatile("barrier.cluster.wait.aligned;" ::: "memory");
        if (elect) mbar_arrive_cta(sb + B_RFREE, (blockIdx.x & 1) ^ 1);
        H_WAIT(2); G2S(47, p1, 2); RET(47);
        G2S(48, p1, 3); SCHED(); if (!(EXPT & 2)) recv_check(ph2, lrecv + 1024, tag); RET(48);
        G2R(49, p1, ph2); RET(49);
        if ((warp & 3) == 0) TS(wg, 8);
        uint32_t sp[32], qa[32], qb[32];
        uint4* const s1 = pbase + (((pw + wg) * 4 + p) << 10);
        G2R(50, p2, fo); RET(50);
        pin(p1);
        G2R(51, p2, po); SCHED(); pack_sub<0>(sp, p1); send_frag<0, 2>(sp, s1, tag); RET(51);
        G2R(52, p2, fh2); SCHED(); send_frag<2, 5>(sp, s1, tag); RET(52);
        if (elect) mbar_arrive(sb + B_XFREE + 16);
        G2R(53, p2, ph2); SCHED(); send_frag<5, 8>(sp, s1, tag); RET(53);
        const uint4* ra = pbase + ((p * 4 + pw) << 10);
        if (own) mbar_wait(sb + B_AHEAD, 0);
        G2S(54, p2, 1); RET(54);
        G2S(55, p2, 2); RET(55);
        G2S(56, p2, 3); RET(56);
        G2S(57, p2, 4); SCHED();
        if ((warp & 3) == 0) TS(wg, 9);
        if (!own && elect) {
            mbar_arrive(sb + B_AHEAD);
            mbar_wait(sb + B_XFREE + 16, 0);
            mbar_expect(sb + B_PART, 32768);
            asm volatile("cp.async.bulk.shared::cluster.global.mbarrier::complete_tx::bytes [%0], [%1], %2, [%3];"
                         :: "r"(sb + OFF_RING), "l"(ra), "r"(32768), "r"(sb + B_PART) : "memory");
        }
        wg_wait<0>();
        pin(p2);
        if ((warp & 3) == 0) TS(wg, 11);
        if (!own) {
            pack_sub<0>(sp, p2);
            mbar_wait(sb + B_RFREE, 0);
            uint32_t rd, rb;
            asm volatile("mapa.shared::cluster.u32 %0, %1, %2;" : "=r"(rd) : "r"(sb + OFF_X + (warp & 3) * 4096 + lane * 16), "r"((blockIdx.x & 1) ^ 1));
            asm volatile("mapa.shared::cluster.u32 %0, %1, %2;" : "=r"(rb) : "r"(sb + B_LAST), "r"((blockIdx.x & 1) ^ 1));
#pragma unroll
            for (int v = 0; v < 8; v++)
                asm volatile("st.async.shared::cluster.mbarrier::complete_tx::bytes.v4.b32 [%0], {%1,%2,%3,%4}, [%5];"
                             :: "r"(rd + v * 512), "r"(sp[4 * v]), "r"(sp[4 * v + 1]), "r"(sp[4 * v + 2]), "r"(sp[4 * v + 3]), "r"(rb) : "memory");
        } else {
            mbar_wait(sb + B_PART, 0);
            if ((warp & 3) == 0) TS(wg, 10);
            const uint32_t pa = sb + OFF_RING + (warp & 3) * 4096 + lane * 16;
#pragma unroll
            for (int v = 0; v < 8; v++) {
                asm volatile("ld.shared.v4.u32 {%0,%1,%2,%3}, [%4];" : "=r"(qa[4 * v]), "=r"(qa[4 * v + 1]), "=r"(qa[4 * v + 2]), "=r"(qa[4 * v + 3]) : "r"(pa + v * 512) : "memory");
                asm volatile("ld.shared.v4.u32 {%0,%1,%2,%3}, [%4];" : "=r"(qb[4 * v]), "=r"(qb[4 * v + 1]), "=r"(qb[4 * v + 2]), "=r"(qb[4 * v + 3]) : "r"(pa + 16384 + v * 512) : "memory");
            }
#if !(EXPT & 1)
            recv_check(qa, ra, tag); recv_check(qb, ra + 1024, tag);
#endif
#pragma unroll
            for (int i = 0; i < 32; i++) qa[i] = hadd2(qa[i], qb[i]);
            accum(qa, p2);
            pack_sub<0>(qb, p2);
            if ((warp & 3) == 0) TS(wg, 12);
            mbar_wait(sb + B_LAST, 0);
#pragma unroll
            for (int v = 0; v < 8; v++)
                asm volatile("ld.shared.v4.u32 {%0,%1,%2,%3}, [%4];" : "=r"(sp[4 * v]), "=r"(sp[4 * v + 1]), "=r"(sp[4 * v + 2]), "=r"(sp[4 * v + 3])
                             : "r"(sb + OFF_X + (warp & 3) * 4096 + lane * 16 + v * 512) : "memory");
            if ((warp & 3) == 0) TS(wg, 13);
            uint32_t f0[16], f1[16];
#pragma unroll
            for (int i = 0; i < 16; i++) { f0[i] = hadd2(qb[i], sp[i]); f1[i] = hadd2(qb[16 + i], sp[16 + i]); }
            const uint32_t slab = sb + OFF_X + 2 * 16384 + wg * 8192;
            stash<16>(slab + srow, ssw, f0); stash<16>(slab + 16384 + srow, ssw, f1);
            __syncwarp();
            __nv_bfloat16* op = out + (size_t)(r * 128 + warp * 16 + (lane >> 4)) * kD + (j & 1) * 256 + (p & 2) * 64 + (lane & 15) * 8;
#pragma unroll
            for (int i = 0; i < 8; i++) {
                const int row = i * 2 + (lane >> 4);
                uint4 v;
                asm volatile("ld.shared.v4.u32 {%0,%1,%2,%3}, [%4];" : "=r"(v.x), "=r"(v.y), "=r"(v.z), "=r"(v.w)
                             : "r"(slab + (lane & 8) * 2048 + ((warp & 3) * 16 + row) * 128 + (((lane & 7) ^ (row & 7)) << 4)) : "memory");
                *(uint4*)(op + i * 2 * kD) = v;
            }
        }
        if ((warp & 3) == 0) { TS(wg, 14); TSG(wg, 31); }
    }
}

typedef CUresult (*EncodeFn)(CUtensorMap*, CUtensorMapDataType, cuuint32_t, void*, const cuuint64_t*, const cuuint64_t*, const cuuint32_t*,
                             const cuuint32_t*, CUtensorMapInterleave, CUtensorMapSwizzle, CUtensorMapL2promotion, CUtensorMapFloatOOBfill);

static void encode(EncodeFn fn, CUtensorMap* m, int rank, const void* base, const cuuint64_t (&gd)[5], const cuuint64_t (&gs)[4],
                   const cuuint32_t (&bd)[5], CUtensorMapSwizzle sw) {
    cuuint32_t es[5] = {1, 1, 1, 1, 1};
    fn(m, CU_TENSOR_MAP_DATA_TYPE_BFLOAT16, rank, const_cast<void*>(base), gd, gs, bd, es, CU_TENSOR_MAP_INTERLEAVE_NONE, sw,
       CU_TENSOR_MAP_L2_PROMOTION_L2_128B, CU_TENSOR_MAP_FLOAT_OOB_FILL_NONE);
}

extern "C" void kernel_launch(void* const* d_in, const int* in_sizes, int n_in, void* d_out, int out_size) {
    const char* x = (const char*)d_in[0];
    const char* wqkv = (const char*)d_in[1];
    const char* wo = (const char*)d_in[2];
    const char* wg = (const char*)d_in[4];
    const char* wu = (const char*)d_in[5];
    const char* wd = (const char*)d_in[6];
    void* fnp = nullptr;
    cudaDriverEntryPointQueryResult qr;
    cudaGetDriverEntryPoint("cuTensorMapEncodeTiled", &fnp, cudaEnableDefault, &qr);
    EncodeFn fn = (EncodeFn)fnp;
    Maps maps;
    const char* lo = wg < wu ? wg : wu;
    const uint64_t diff = wg < wu ? (uint64_t)(wu - wg) : (uint64_t)(wg - wu);
    const CUtensorMapSwizzle S128 = CU_TENSOR_MAP_SWIZZLE_128B, S64 = CU_TENSOR_MAP_SWIZZLE_64B;
    encode(fn, &maps.x, 2, x, {512, 2048, 1, 1}, {1024, 0, 0}, {64, 128, 1, 1}, S128);
    encode(fn, &maps.gu, 3, lo, {1792, 512, 2, 1}, {3584, diff, 0}, {64, 64, 2, 1}, S128);
    encode(fn, &maps.kv, 3, wqkv, {512, 512, 3, 1}, {3072, 1024, 0}, {64, 64, 2, 1}, S128);
    encode(fn, &maps.q64, 3, wqkv, {32, 512, 48, 1}, {3072, 64, 0}, {32, 64, 2, 1}, S64);
    encode(fn, &maps.gu64, 3, lo, {1792, 512, 2, 1}, {3584, diff, 0}, {32, 64, 2, 1}, S64);
    encode(fn, &maps.wdw, 3, wd, {64, 1792, 8, 1}, {1024, 128, 0}, {64, 64, 2, 1}, S128);
    encode(fn, &maps.wow, 3, wo, {64, 512, 8}, {1024, 128}, {64, 64, 2}, S128);
    encode(fn, &maps.wdp, 5, wd, {512, 2, 4, 4, 56}, {1024, 8192, 2048, 32768}, {64, 2, 4, 4, 2}, S128);
    encode(fn, &maps.wdph, 5, wd, {512, 2, 4, 4, 56}, {1024, 8192, 2048, 32768}, {64, 2, 4, 4, 1}, S128);
    void* hx = nullptr;
    cudaGetSymbolAddress(&hx, g_hx);
    encode(fn, &maps.hx, 2, hx, {64, 16 * 4 * 5 * 128}, {128}, {64, 128}, S128);
    encode(fn, &maps.hx2, 2, hx, {64, 16 * 4 * 5 * 128}, {128}, {64, 256}, S128);
    cudaFuncSetAttribute(fused_kernel, cudaFuncAttributeMaxDynamicSharedMemorySize, SMEM_BYTES);
    cudaLaunchConfig_t cfg = {};
    cfg.gridDim = dim3(128);
    cfg.blockDim = dim3(384);
    cfg.dynamicSmemBytes = SMEM_BYTES;
    cfg.stream = cudaStreamPerThread;
    cudaLaunchAttribute at[1];
    at[0].id = cudaLaunchAttributeClusterDimension;
    at[0].val.clusterDim.x = 2; at[0].val.clusterDim.y = 1; at[0].val.clusterDim.z = 1;
    cfg.attrs = at;
    cfg.numAttrs = 1;
    cudaLaunchKernelEx(&cfg, fused_kernel, maps, (const __nv_bfloat16*)d_in[0], (const __nv_bfloat16*)d_in[7], wqkv, wg, wu, wd, wo, (__nv_bfloat16*)d_out);
}
```

```cpp
#include <cuda_runtime.h>
#include <cuda.h>
#include <cuda_bf16.h>
#include <stdint.h>

#define MC 0
#define PFMODE 1
#define PHI_SAT 0
#define EXPT 0
#define COPY_AT 0
#define PROF 0

namespace {

constexpr int kD = 512;
constexpr uint32_t OFF_X = 0, OFF_STG = 131072, OFF_RING = 147456, OFF_MISC = 229376;
constexpr uint32_t B_FULL = OFF_MISC, B_EMPTY = OFF_MISC + 40, B_XFULL = OFF_MISC + 80;
constexpr uint32_t B_GRDY = OFF_MISC + 152, B_KVDONE = OFF_MISC + 160, B_KVRDY = OFF_MISC + 168;
constexpr uint32_t B_HSENT = OFF_MISC + 176, B_XFREE = OFF_MISC + 200;
constexpr uint32_t OFF_EPOCH = OFF_MISC + 240, OFF_G = OFF_MISC + 256;
constexpr uint32_t B_AHEAD = OFF_MISC + 248, B_PART = OFF_MISC + 232;
constexpr uint32_t OFF_ONES = OFF_MISC + 768;
constexpr uint32_t B_EFULL = OFF_MISC + 896, B_EEMPTY = OFF_MISC + 928;
constexpr uint32_t SMEM_BYTES = OFF_MISC + 960;
constexpr uint32_t SPIN_GLOBAL = 1u << 14;

struct alignas(64) Maps { CUtensorMap x, gu, kv, q64, gu64, wdw, wow, wdp, wdph, hx, hx2; };

}

__device__ uint4 g_part[16 * 2 * 4 * 4 * 1024];
__device__ uint4 g_hx[16 * 4 * 5 * 1024];
__device__ uint4 g_lx[16 * 8 * 2 * 1024];
__device__ unsigned g_hflag[128 * 8];
__device__ uint4 g_gx[16 * 32];
__device__ float g_kvacc[2 * 8 * 4 * 272];
__device__ unsigned g_kvcnt[8 * 32];
__device__ unsigned g_epoch[128];
#define TS(role, idx)
#define TS2(idx)
#define TSG(role, idx)

namespace {

__device__ __forceinline__ void mbar_init(uint32_t bar, uint32_t cnt) { asm volatile("mbarrier.init.shared::cta.b64 [%0], %1;" :: "r"(bar), "r"(cnt) : "memory"); }
__device__ __forceinline__ void mbar_expect(uint32_t bar, uint32_t bytes) { asm volatile("mbarrier.arrive.expect_tx.shared::cta.b64 _, [%0], %1;" :: "r"(bar), "r"(bytes) : "memory"); }
__device__ __forceinline__ void mbar_arrive(uint32_t bar) { asm volatile("mbarrier.arrive.shared::cta.b64 _, [%0];" :: "r"(bar) : "memory"); }
__device__ __forceinline__ void mbar_arrive_cta(uint32_t bar, uint32_t cta) {
    asm volatile("{\n.reg .b32 ra;\nmapa.shared::cluster.u32 ra, %0, %1;\nmbarrier.arrive.shared::cluster.b64 _, [ra];\n}" :: "r"(bar), "r"(cta) : "memory");
}
__device__ __forceinline__ void mbar_wait(uint32_t bar, uint32_t parity) {
    asm volatile("{\n.reg .pred p;\n.reg .u32 c;\n"
                 "mbarrier.try_wait.parity.shared::cta.b64 p, [%0], %1;\n@p bra DONE;\n"
                 "mov.u32 c, 0;\nLAB_WAIT:\nmbarrier.try_wait.parity.shared::cta.b64 p, [%0], %1;\n@p bra DONE;\n"
                 "add.u32 c, c, 1;\nsetp.lt.u32 p, c, 65536;\n@p bra LAB_WAIT;\nDONE:\n}" :: "r"(bar), "r"(parity) : "memory");
}
__device__ __forceinline__ void tma2(uint32_t dst, const CUtensorMap* m, int c0, int c1, uint32_t bar) {
    asm volatile("cp.async.bulk.tensor.2d.shared::cluster.global.mbarrier::complete_tx::bytes [%0], [%1, {%3, %4}], [%2];"
        :: "r"(dst), "l"(m), "r"(bar), "r"(c0), "r"(c1) : "memory");
}
__device__ __forceinline__ void tmaw2(uint32_t dst, const CUtensorMap* m, int c0, int c1, uint32_t bar) {
    tma2(dst, m, c0, c1, bar);
}
__device__ __forceinline__ void tmaw3(uint32_t dst, const CUtensorMap* m, int c0, int c1, int c2, uint32_t bar) {
    asm volatile("cp.async.bulk.tensor.3d.shared::cluster.global.mbarrier::complete_tx::bytes [%0], [%1, {%3, %4, %5}], [%2];"
        :: "r"(dst), "l"(m), "r"(bar), "r"(c0), "r"(c1), "r"(c2) : "memory");
}
__device__ __forceinline__ void tmaw5(uint32_t dst, const CUtensorMap* m, int c0, int c4, uint32_t bar) {
    asm volatile("cp.async.bulk.tensor.5d.shared::cluster.global.mbarrier::complete_tx::bytes [%0], [%1, {%3, %5, %5, %5, %4}], [%2];"
        :: "r"(dst), "l"(m), "r"(bar), "r"(c0), "r"(c4), "r"(0) : "memory");
}
__device__ __forceinline__ void wg_fence() { asm volatile("wgmma.fence.sync.aligned;" ::: "memory"); }
__device__ __forceinline__ void wg_commit() { asm volatile("wgmma.commit_group.sync.aligned;" ::: "memory"); }
template <int N> __device__ __forceinline__ void wg_wait() { asm volatile("wgmma.wait_group.sync.aligned %0;" :: "n"(N) : "memory"); }
template <int N> __device__ __forceinline__ void pin(float (&d)[N]) {
#pragma unroll
    for (int i = 0; i < N; i++) asm volatile("" : "+f"(d[i]) :: "memory");
}
__device__ __forceinline__ uint32_t pack2(float lo, float hi) { uint32_t r; asm("cvt.rn.bf16x2.f32 %0, %1, %2;" : "=r"(r) : "f"(hi), "f"(lo)); return r; }
__device__ __forceinline__ uint32_t keep(uint32_t v) { asm volatile("" : "+r"(v)); return v; }
__device__ __forceinline__ uint32_t hadd2(uint32_t a, uint32_t b) { uint32_t r; asm("add.bf16x2 %0, %1, %2;" : "=r"(r) : "r"(a), "r"(b)); return r; }
__device__ __forceinline__ uint32_t hmul2(uint32_t a, uint32_t b) { uint32_t r; asm("mul.bf16x2 %0, %1, %2;" : "=r"(r) : "r"(a), "r"(b)); return r; }
__device__ __forceinline__ uint32_t phi2(float t0, float t1) {
    float e0, e1;
    asm("ex2.approx.ftz.f32 %0, %1;" : "=f"(e0) : "f"(t0 * 1.4426950408889634f));
    asm("ex2.approx.ftz.f32 %0, %1;" : "=f"(e1) : "f"(t1 * 1.4426950408889634f));
    uint32_t e = pack2(e0, e1), t = pack2(t0, t1), r;
    asm("min.bf16x2 %0, %0, %1;" : "+r"(e) : "r"(0x3f803f80u));
    asm("max.bf16x2 %0, %0, %1;" : "+r"(t) : "r"(0x35863586u));
    asm("add.bf16x2 %0, %1, %2;" : "=r"(r) : "r"(e), "r"(t));
    return r;
}
__device__ __forceinline__ void stsm4(uint32_t a, uint32_t r0, uint32_t r1, uint32_t r2, uint32_t r3) {
    asm volatile("stmatrix.sync.aligned.m8n8.x4.shared.b16 [%0], {%1,%2,%3,%4};" :: "r"(a), "r"(r0), "r"(r1), "r"(r2), "r"(r3) : "memory");
}
__device__ __forceinline__ float bf_lo(uint32_t w) { return __uint_as_float(w << 16); }
__device__ __forceinline__ float bf_hi(uint32_t w) { return __uint_as_float(w & 0xffff0000u); }
__device__ __forceinline__ void st_pkt(uint4* p, uint32_t w0, uint32_t w1, uint32_t w2, uint32_t w3) {
    asm volatile("{\n.reg .b64 lo, hi;\n.reg .b128 v;\nmov.b64 lo, {%1, %2};\nmov.b64 hi, {%3, %4};\nmov.b128 v, {lo, hi};\nst.relaxed.gpu.global.b128 [%0], v;\n}"
        :: "l"(p), "r"(w0), "r"(w1), "r"(w2), "r"(w3) : "memory");
}
__device__ __forceinline__ void ld_pkt(const uint4* p, uint32_t& w0, uint32_t& w1, uint32_t& w2, uint32_t& w3) {
    asm volatile("{\n.reg .b64 lo, hi;\n.reg .b128 v;\nld.relaxed.gpu.global.b128 v, [%4];\nmov.b128 {lo, hi}, v;\nmov.b64 {%0, %1}, lo;\nmov.b64 {%2, %3}, hi;\n}"
        : "=r"(w0), "=r"(w1), "=r"(w2), "=r"(w3) : "l"(p) : "memory");
}

template <uint32_t AO, uint32_t BO, uint32_t BH> __device__ __forceinline__ void wg_ss128(float (&d)[64], uint32_t ab, uint32_t bb) {
    asm volatile("{\n.reg .b64 da, db;\n.reg .b32 ta, tb, th, ah;\nadd.u32 ta, %64, %66;\nadd.u32 tb, %65, %67;\nmov.b32 th, %68;\nmov.b32 ah, 0x40000040;\nmov.b64 da, {ta, ah};\nmov.b64 db, {tb, th};\n"
        "wgmma.mma_async.sync.aligned.m64n128k16.f32.bf16.bf16 {%0,%1,%2,%3,%4,%5,%6,%7,%8,%9,%10,%11,%12,%13,%14,%15,%16,%17,%18,%19,%20,%21,%22,%23,%24,%25,%26,%27,%28,%29,%30,%31,%32,%33,%34,%35,%36,%37,%38,%39,%40,%41,%42,%43,%44,%45,%46,%47,%48,%49,%50,%51,%52,%53,%54,%55,%56,%57,%58,%59,%60,%61,%62,%63}, da, db, 1, 1, 1, 0, 1;\n}\n"
        : "+f"(d[0]),"+f"(d[1]),"+f"(d[2]),"+f"(d[3]),"+f"(d[4]),"+f"(d[5]),"+f"(d[6]),"+f"(d[7]),"+f"(d[8]),"+f"(d[9]),"+f"(d[10]),"+f"(d[11]),"+f"(d[12]),"+f"(d[13]),"+f"(d[14]),"+f"(d[15]),"+f"(d[16]),"+f"(d[17]),"+f"(d[18]),"+f"(d[19]),"+f"(d[20]),"+f"(d[21]),"+f"(d[22]),"+f"(d[23]),"+f"(d[24]),"+f"(d[25]),"+f"(d[26]),"+f"(d[27]),"+f"(d[28]),"+f"(d[29]),"+f"(d[30]),"+f"(d[31]),"+f"(d[32]),"+f"(d[33]),"+f"(d[34]),"+f"(d[35]),"+f"(d[36]),"+f"(d[37]),"+f"(d[38]),"+f"(d[39]),"+f"(d[40]),"+f"(d[41]),"+f"(d[42]),"+f"(d[43]),"+f"(d[44]),"+f"(d[45]),"+f"(d[46]),"+f"(d[47]),"+f"(d[48]),"+f"(d[49]),"+f"(d[50]),"+f"(d[51]),"+f"(d[52]),"+f"(d[53]),"+f"(d[54]),"+f"(d[55]),"+f"(d[56]),"+f"(d[57]),"+f"(d[58]),"+f"(d[59]),"+f"(d[60]),"+f"(d[61]),"+f"(d[62]),"+f"(d[63])
        : "r"(ab), "r"(bb), "n"(AO), "n"(BO), "n"(BH));
}
template <uint32_t AO, uint32_t BO, uint32_t BH> __device__ __forceinline__ void wg_ss128_z(float (&d)[64], uint32_t ab, uint32_t bb) {
    asm volatile("{\n.reg .b64 da, db;\n.reg .b32 ta, tb, th, ah;\nadd.u32 ta, %64, %66;\nadd.u32 tb, %65, %67;\nmov.b32 th, %68;\nmov.b32 ah, 0x40000040;\nmov.b64 da, {ta, ah};\nmov.b64 db, {tb, th};\n"
        "wgmma.mma_async.sync.aligned.m64n128k16.f32.bf16.bf16 {%0,%1,%2,%3,%4,%5,%6,%7,%8,%9,%10,%11,%12,%13,%14,%15,%16,%17,%18,%19,%20,%21,%22,%23,%24,%25,%26,%27,%28,%29,%30,%31,%32,%33,%34,%35,%36,%37,%38,%39,%40,%41,%42,%43,%44,%45,%46,%47,%48,%49,%50,%51,%52,%53,%54,%55,%56,%57,%58,%59,%60,%61,%62,%63}, da, db, 0, 1, 1, 0, 1;\n}\n"
        : "=f"(d[0]),"=f"(d[1]),"=f"(d[2]),"=f"(d[3]),"=f"(d[4]),"=f"(d[5]),"=f"(d[6]),"=f"(d[7]),"=f"(d[8]),"=f"(d[9]),"=f"(d[10]),"=f"(d[11]),"=f"(d[12]),"=f"(d[13]),"=f"(d[14]),"=f"(d[15]),"=f"(d[16]),"=f"(d[17]),"=f"(d[18]),"=f"(d[19]),"=f"(d[20]),"=f"(d[21]),"=f"(d[22]),"=f"(d[23]),"=f"(d[24]),"=f"(d[25]),"=f"(d[26]),"=f"(d[27]),"=f"(d[28]),"=f"(d[29]),"=f"(d[30]),"=f"(d[31]),"=f"(d[32]),"=f"(d[33]),"=f"(d[34]),"=f"(d[35]),"=f"(d[36]),"=f"(d[37]),"=f"(d[38]),"=f"(d[39]),"=f"(d[40]),"=f"(d[41]),"=f"(d[42]),"=f"(d[43]),"=f"(d[44]),"=f"(d[45]),"=f"(d[46]),"=f"(d[47]),"=f"(d[48]),"=f"(d[49]),"=f"(d[50]),"=f"(d[51]),"=f"(d[52]),"=f"(d[53]),"=f"(d[54]),"=f"(d[55]),"=f"(d[56]),"=f"(d[57]),"=f"(d[58]),"=f"(d[59]),"=f"(d[60]),"=f"(d[61]),"=f"(d[62]),"=f"(d[63])
        : "r"(ab), "r"(bb), "n"(AO), "n"(BO), "n"(BH));
}
template <uint32_t BO, uint32_t BH> __device__ __forceinline__ void wg_rs128(float (&d)[64], uint32_t a0, uint32_t a1, uint32_t a2, uint32_t a3, uint32_t bb) {
    asm volatile("{\n.reg .b64 db;\n.reg .b32 tb, th;\nadd.u32 tb, %68, %69;\nmov.b32 th, %70;\nmov.b64 db, {tb, th};\n"
        "wgmma.mma_async.sync.aligned.m64n128k16.f32.bf16.bf16 {%0,%1,%2,%3,%4,%5,%6,%7,%8,%9,%10,%11,%12,%13,%14,%15,%16,%17,%18,%19,%20,%21,%22,%23,%24,%25,%26,%27,%28,%29,%30,%31,%32,%33,%34,%35,%36,%37,%38,%39,%40,%41,%42,%43,%44,%45,%46,%47,%48,%49,%50,%51,%52,%53,%54,%55,%56,%57,%58,%59,%60,%61,%62,%63}, {%64,%65,%66,%67}, db, 1, 1, 1, 1;\n}\n"
        : "+f"(d[0]),"+f"(d[1]),"+f"(d[2]),"+f"(d[3]),"+f"(d[4]),"+f"(d[5]),"+f"(d[6]),"+f"(d[7]),"+f"(d[8]),"+f"(d[9]),"+f"(d[10]),"+f"(d[11]),"+f"(d[12]),"+f"(d[13]),"+f"(d[14]),"+f"(d[15]),"+f"(d[16]),"+f"(d[17]),"+f"(d[18]),"+f"(d[19]),"+f"(d[20]),"+f"(d[21]),"+f"(d[22]),"+f"(d[23]),"+f"(d[24]),"+f"(d[25]),"+f"(d[26]),"+f"(d[27]),"+f"(d[28]),"+f"(d[29]),"+f"(d[30]),"+f"(d[31]),"+f"(d[32]),"+f"(d[33]),"+f"(d[34]),"+f"(d[35]),"+f"(d[36]),"+f"(d[37]),"+f"(d[38]),"+f"(d[39]),"+f"(d[40]),"+f"(d[41]),"+f"(d[42]),"+f"(d[43]),"+f"(d[44]),"+f"(d[45]),"+f"(d[46]),"+f"(d[47]),"+f"(d[48]),"+f"(d[49]),"+f"(d[50]),"+f"(d[51]),"+f"(d[52]),"+f"(d[53]),"+f"(d[54]),"+f"(d[55]),"+f"(d[56]),"+f"(d[57]),"+f"(d[58]),"+f"(d[59]),"+f"(d[60]),"+f"(d[61]),"+f"(d[62]),"+f"(d[63])
        : "r"(a0), "r"(a1), "r"(a2), "r"(a3), "r"(bb), "n"(BO), "n"(BH));
}
template <uint32_t BO, uint32_t BH> __device__ __forceinline__ void wg_rs128_z(float (&d)[64], uint32_t a0, uint32_t a1, uint32_t a2, uint32_t a3, uint32_t bb) {
    asm volatile("{\n.reg .b64 db;\n.reg .b32 tb, th;\nadd.u32 tb, %68, %69;\nmov.b32 th, %70;\nmov.b64 db, {tb, th};\n"
        "wgmma.mma_async.sync.aligned.m64n128k16.f32.bf16.bf16 {%0,%1,%2,%3,%4,%5,%6,%7,%8,%9,%10,%11,%12,%13,%14,%15,%16,%17,%18,%19,%20,%21,%22,%23,%24,%25,%26,%27,%28,%29,%30,%31,%32,%33,%34,%35,%36,%37,%38,%39,%40,%41,%42,%43,%44,%45,%46,%47,%48,%49,%50,%51,%52,%53,%54,%55,%56,%57,%58,%59,%60,%61,%62,%63}, {%64,%65,%66,%67}, db, 0, 1, 1, 1;\n}\n"
        : "=f"(d[0]),"=f"(d[1]),"=f"(d[2]),"=f"(d[3]),"=f"(d[4]),"=f"(d[5]),"=f"(d[6]),"=f"(d[7]),"=f"(d[8]),"=f"(d[9]),"=f"(d[10]),"=f"(d[11]),"=f"(d[12]),"=f"(d[13]),"=f"(d[14]),"=f"(d[15]),"=f"(d[16]),"=f"(d[17]),"=f"(d[18]),"=f"(d[19]),"=f"(d[20]),"=f"(d[21]),"=f"(d[22]),"=f"(d[23]),"=f"(d[24]),"=f"(d[25]),"=f"(d[26]),"=f"(d[27]),"=f"(d[28]),"=f"(d[29]),"=f"(d[30]),"=f"(d[31]),"=f"(d[32]),"=f"(d[33]),"=f"(d[34]),"=f"(d[35]),"=f"(d[36]),"=f"(d[37]),"=f"(d[38]),"=f"(d[39]),"=f"(d[40]),"=f"(d[41]),"=f"(d[42]),"=f"(d[43]),"=f"(d[44]),"=f"(d[45]),"=f"(d[46]),"=f"(d[47]),"=f"(d[48]),"=f"(d[49]),"=f"(d[50]),"=f"(d[51]),"=f"(d[52]),"=f"(d[53]),"=f"(d[54]),"=f"(d[55]),"=f"(d[56]),"=f"(d[57]),"=f"(d[58]),"=f"(d[59]),"=f"(d[60]),"=f"(d[61]),"=f"(d[62]),"=f"(d[63])
        : "r"(a0), "r"(a1), "r"(a2), "r"(a3), "r"(bb), "n"(BO), "n"(BH));
}
template <uint32_t AO, uint32_t BO, uint32_t BH> __device__ __forceinline__ void wg_ss64t(float (&d)[32], uint32_t ab, uint32_t bb) {
    asm volatile("{\n.reg .b64 da, db;\n.reg .b32 ta, tb, th, ah;\nadd.u32 ta, %32, %34;\nadd.u32 tb, %33, %35;\nmov.b32 th, %36;\nmov.b32 ah, 0x40000040;\nmov.b64 da, {ta, ah};\nmov.b64 db, {tb, th};\n"
        "wgmma.mma_async.sync.aligned.m64n64k16.f32.bf16.bf16 {%0,%1,%2,%3,%4,%5,%6,%7,%8,%9,%10,%11,%12,%13,%14,%15,%16,%17,%18,%19,%20,%21,%22,%23,%24,%25,%26,%27,%28,%29,%30,%31}, da, db, 1, 1, 1, 1, 1;\n}\n"
        : "+f"(d[0]),"+f"(d[1]),"+f"(d[2]),"+f"(d[3]),"+f"(d[4]),"+f"(d[5]),"+f"(d[6]),"+f"(d[7]),"+f"(d[8]),"+f"(d[9]),"+f"(d[10]),"+f"(d[11]),"+f"(d[12]),"+f"(d[13]),"+f"(d[14]),"+f"(d[15]),"+f"(d[16]),"+f"(d[17]),"+f"(d[18]),"+f"(d[19]),"+f"(d[20]),"+f"(d[21]),"+f"(d[22]),"+f"(d[23]),"+f"(d[24]),"+f"(d[25]),"+f"(d[26]),"+f"(d[27]),"+f"(d[28]),"+f"(d[29]),"+f"(d[30]),"+f"(d[31])
        : "r"(ab), "r"(bb), "n"(AO), "n"(BO), "n"(BH));
}
template <uint32_t AO, uint32_t BO, uint32_t BH> __device__ __forceinline__ void wg_ss64t_z(float (&d)[32], uint32_t ab, uint32_t bb) {
    asm volatile("{\n.reg .b64 da, db;\n.reg .b32 ta, tb, th, ah;\nadd.u32 ta, %32, %34;\nadd.u32 tb, %33, %35;\nmov.b32 th, %36;\nmov.b32 ah, 0x40000040;\nmov.b64 da, {ta, ah};\nmov.b64 db, {tb, th};\n"
        "wgmma.mma_async.sync.aligned.m64n64k16.f32.bf16.bf16 {%0,%1,%2,%3,%4,%5,%6,%7,%8,%9,%10,%11,%12,%13,%14,%15,%16,%17,%18,%19,%20,%21,%22,%23,%24,%25,%26,%27,%28,%29,%30,%31}, da, db, 0, 1, 1, 1, 1;\n}\n"
        : "=f"(d[0]),"=f"(d[1]),"=f"(d[2]),"=f"(d[3]),"=f"(d[4]),"=f"(d[5]),"=f"(d[6]),"=f"(d[7]),"=f"(d[8]),"=f"(d[9]),"=f"(d[10]),"=f"(d[11]),"=f"(d[12]),"=f"(d[13]),"=f"(d[14]),"=f"(d[15]),"=f"(d[16]),"=f"(d[17]),"=f"(d[18]),"=f"(d[19]),"=f"(d[20]),"=f"(d[21]),"=f"(d[22]),"=f"(d[23]),"=f"(d[24]),"=f"(d[25]),"=f"(d[26]),"=f"(d[27]),"=f"(d[28]),"=f"(d[29]),"=f"(d[30]),"=f"(d[31])
        : "r"(ab), "r"(bb), "n"(AO), "n"(BO), "n"(BH));
}
template <uint32_t AO, uint32_t BO, uint32_t BH> __device__ __forceinline__ void wg_ss8t(float (&d)[4], uint32_t ab, uint32_t bb) {
    asm volatile("{\n.reg .b64 da, db;\n.reg .b32 ta, tb, th, ah;\nadd.u32 ta, %4, %6;\nadd.u32 tb, %5, %7;\nmov.b32 th, %8;\nmov.b32 ah, 0x40000040;\nmov.b64 da, {ta, ah};\nmov.b64 db, {tb, th};\n"
        "wgmma.mma_async.sync.aligned.m64n8k16.f32.bf16.bf16 {%0,%1,%2,%3}, da, db, 1, 1, 1, 1, 0;\n}\n"
        : "+f"(d[0]),"+f"(d[1]),"+f"(d[2]),"+f"(d[3])
        : "r"(ab), "r"(bb), "n"(AO), "n"(BO), "n"(BH));
}
template <uint32_t AO, uint32_t BO, uint32_t BH> __device__ __forceinline__ void wg_ss8t_z(float (&d)[4], uint32_t ab, uint32_t bb) {
    asm volatile("{\n.reg .b64 da, db;\n.reg .b32 ta, tb, th, ah;\nadd.u32 ta, %4, %6;\nadd.u32 tb, %5, %7;\nmov.b32 th, %8;\nmov.b32 ah, 0x40000040;\nmov.b64 da, {ta, ah};\nmov.b64 db, {tb, th};\n"
        "wgmma.mma_async.sync.aligned.m64n8k16.f32.bf16.bf16 {%0,%1,%2,%3}, da, db, 0, 1, 1, 1, 0;\n}\n"
        : "=f"(d[0]),"=f"(d[1]),"=f"(d[2]),"=f"(d[3])
        : "r"(ab), "r"(bb), "n"(AO), "n"(BO), "n"(BH));
}
template <uint32_t BO, uint32_t BH> __device__ __forceinline__ void wg_rs24_z(float (&d)[12], uint32_t a0, uint32_t a1, uint32_t a2, uint32_t a3, uint32_t bb) {
    asm volatile("{\n.reg .b64 db;\n.reg .b32 tb, th;\nadd.u32 tb, %16, %17;\nmov.b32 th, %18;\nmov.b64 db, {tb, th};\n"
        "wgmma.mma_async.sync.aligned.m64n24k16.f32.bf16.bf16 {%0,%1,%2,%3,%4,%5,%6,%7,%8,%9,%10,%11}, {%12,%13,%14,%15}, db, 0, 1, 1, 0;\n}\n"
        : "=f"(d[0]),"=f"(d[1]),"=f"(d[2]),"=f"(d[3]),"=f"(d[4]),"=f"(d[5]),"=f"(d[6]),"=f"(d[7]),"=f"(d[8]),"=f"(d[9]),"=f"(d[10]),"=f"(d[11])
        : "r"(a0), "r"(a1), "r"(a2), "r"(a3), "r"(bb), "n"(BO), "n"(BH));
}

constexpr uint32_t DH128 = 64u | 0x40000000u;
constexpr uint32_t DH64 = 32u | 0x80000000u;
constexpr uint32_t LBO4K = (4096u >> 4) << 16, LBO8K = (8192u >> 4) << 16, LBO1 = 1u << 16;

template <uint32_t AO, uint32_t BO, bool SW64, bool FIRST> __device__ __forceinline__ void stage_ss(float (&acc)[64], uint32_t ab, uint32_t bb) {
    constexpr uint32_t KS = SW64 ? 64 : 128, BH = SW64 ? DH64 : DH128, B0 = BO + (SW64 ? LBO4K : LBO8K);
    wg_fence();
    if (FIRST) wg_ss128_z<AO, B0, BH>(acc, ab, bb); else wg_ss128<AO, B0, BH>(acc, ab, bb);
    wg_ss128<AO + 2, B0 + KS, BH>(acc, ab, bb);
    wg_ss128<AO + 4, B0 + 2 * KS, BH>(acc, ab, bb);
    wg_ss128<AO + 6, B0 + 3 * KS, BH>(acc, ab, bb);
    wg_commit();
}
template <uint32_t BO, bool FIRST> __device__ __forceinline__ void stage_rs(float (&acc)[64], const uint32_t (&f)[16], uint32_t bb) {
    wg_fence();
    if (FIRST) wg_rs128_z<BO + LBO8K, DH128>(acc, f[0], f[1], f[2], f[3], bb); else wg_rs128<BO + LBO8K, DH128>(acc, f[0], f[1], f[2], f[3], bb);
    wg_rs128<BO + LBO8K + 128, DH128>(acc, f[4], f[5], f[6], f[7], bb);
    wg_rs128<BO + LBO8K + 256, DH128>(acc, f[8], f[9], f[10], f[11], bb);
    wg_rs128<BO + LBO8K + 384, DH128>(acc, f[12], f[13], f[14], f[15], bb);
    wg_commit();
}

template <int N> __device__ __forceinline__ void stash(uint32_t base, uint32_t sw, const uint32_t (&f)[N]) {
#pragma unroll
    for (int t = 0; t < N / 4; t++) stsm4(base + ((sw ^ (2 * t)) << 4), f[4 * t], f[4 * t + 1], f[4 * t + 2], f[4 * t + 3]);
}

template <int V0, int V1, int N> __device__ __forceinline__ void send_frag(const uint32_t (&f)[N], uint4* p, uint32_t tag) {
#pragma unroll
    for (int v = V0; v < V1; v++) st_pkt(p + v * 32, (f[4 * v] & ~1u) | tag, f[4 * v + 1], f[4 * v + 2], f[4 * v + 3]);
}
template <int V0, int V1, int N> __device__ __forceinline__ void send_h(const uint32_t (&f)[N], uint4* p) {
#pragma unroll
    for (int v = V0; v < V1; v++) {
        const int h = v >> 1, hi = v & 1;
        asm volatile("st.global.v4.u32 [%0], {%1,%2,%3,%4};" :: "l"(p + 4 * h + 64 * hi),
                     "r"(f[8 * h + hi]), "r"(f[8 * h + 2 + hi]), "r"(f[8 * h + 4 + hi]), "r"(f[8 * h + 6 + hi]) : "memory");
    }
}
template <int O, int N, int M> __device__ __forceinline__ void pack_sub(uint32_t (&f)[N], const float (&acc)[M]) {
#pragma unroll
    for (int i = 0; i < N; i++) f[i] = keep(pack2(acc[O + 2 * i], acc[O + 2 * i + 1]));
}
template <int N> __device__ __forceinline__ void recv_issue(uint32_t (&q)[N], const uint4* p) {
#pragma unroll
    for (int v = 0; v < N / 4; v++) ld_pkt(p + v * 32, q[4 * v], q[4 * v + 1], q[4 * v + 2], q[4 * v + 3]);
}
template <int N> __device__ __forceinline__ void recv_check(uint32_t (&q)[N], const uint4* p, uint32_t tag) {
    uint32_t it = 0;
    while (true) {
        uint32_t bad = 0;
#pragma unroll
        for (int v = 0; v < N / 4; v++) bad |= q[4 * v] ^ tag;
        if (__all_sync(0xffffffffu, (bad & 1u) == 0) || ++it > SPIN_GLOBAL) break;
        recv_issue(q, p);
    }
}
__device__ __forceinline__ void accum(const uint32_t (&q)[32], float (&sum)[64]) {
#pragma unroll
    for (int i = 0; i < 32; i++) { sum[2 * i] += bf_lo(q[i]); sum[2 * i + 1] += bf_hi(q[i]); }
}

}

__global__ void __launch_bounds__(384, 1)
fused_kernel(const __grid_constant__ Maps maps, const __nv_bfloat16* __restrict__ xg, const __nv_bfloat16* __restrict__ gate_w,
             const char* __restrict__ pf_qkv, const char* __restrict__ pf_g, const char* __restrict__ pf_u,
             const char* __restrict__ pf_d, const char* __restrict__ pf_o, __nv_bfloat16* __restrict__ out) {
    extern __shared__ __align__(1024) uint8_t smem_raw[];
    const uint32_t sb = (uint32_t)__cvta_generic_to_shared(smem_raw);
    const int tid = threadIdx.x, lane = tid & 31;
    const int warp = __shfl_sync(0xffffffffu, tid >> 5, 0);
    const int j = (blockIdx.x >> 1) & 7;
    const int r = ((blockIdx.x >> 4) << 1) | (blockIdx.x & 1);
    const uint32_t rank = blockIdx.x & 1;

    if (warp == 0) { TSG(0, 30); TS(0, 0); }
    if (tid == 256) {
        for (int i = 0; i < 5; i++) { mbar_init(sb + B_FULL + 8 * i, 1); mbar_init(sb + B_EMPTY + 8 * i, MC ? 4 : 2); }
        for (int i = 0; i < 9; i++) mbar_init(sb + B_XFULL + 8 * i, 1);
        asm volatile("fence.mbarrier_init.release.cluster;" ::: "memory");
        mbar_expect(sb + B_XFULL, 16384);
        tma2(sb + OFF_X, &maps.x, 0, r * 128, sb + B_XFULL);
        TS2(0);
        mbar_expect(sb + B_FULL, 16384);
        tmaw3(sb + OFF_RING, &maps.kv, 64 * j, 0, 1, sb + B_FULL);
        TS2(1);
        mbar_expect(sb + B_FULL + 8, 16384);
        tmaw3(sb + OFF_RING + 16384, &maps.gu, 224 * j, 0, 0, sb + B_FULL + 8);
    } else if (tid == 288) {
        for (int i = 0; i < 3; i++) mbar_init(sb + B_HSENT + 8 * i, 8);
        for (int i = 0; i < 4; i++) { mbar_init(sb + B_EFULL + 8 * i, 1); mbar_init(sb + B_EEMPTY + 8 * i, MC ? 4 : 2); }
        mbar_init(sb + B_XFREE, 2); mbar_init(sb + B_XFREE + 8, 2); mbar_init(sb + B_XFREE + 16, 2);
        mbar_init(sb + B_AHEAD, 1); mbar_init(sb + B_PART, 1); mbar_init(sb + B_GRDY, 1); mbar_init(sb + B_KVDONE, 8); mbar_init(sb + B_KVRDY, 2);
        asm volatile("fence.mbarrier_init.release.cluster;" ::: "memory");
    } else if (warp == 10 && lane < 10) {
        asm volatile("prefetch.tensormap [%0];" :: "l"(&maps.gu + lane) : "memory");
    }
    __syncthreads();

    if (warp >= 8) {
        asm volatile("setmaxnreg.dec.sync.aligned.u32 56;");
        if (warp == 8) {
            if (lane == 0) {
                int slot = MC ? 0 : 2, ph = 1;
                uint32_t full, dst;
                if (!MC) { mbar_expect(sb + B_XFULL + 8, 16384); tma2(sb + OFF_X + 16384, &maps.x, 64, r * 128, sb + B_XFULL + 8); }
#define P_BEGIN(S, BYTES) full = sb + B_FULL + 8 * slot; dst = sb + OFF_RING + slot * 16384; \
                mbar_wait(sb + B_EMPTY + 8 * slot, ph); TS2(S); mbar_expect(full, BYTES); if (!MC || (((S) ^ rank) & 1) == 0)
#define P_END() if (++slot == 5) { slot = 0; ph ^= 1; }
                for (int s = MC ? 0 : 2; s < 16; s++) {
                    const int kb = (int)(0x7654763542312100ull >> (4 * s)) & 15;
                    P_BEGIN(s, 16384) {
                        if ((0x0DADu >> s) & 1) tmaw3(dst, &maps.kv, 64 * j, 64 * kb, 1, full);
                        else tmaw3(dst, &maps.gu, 224 * j, 64 * kb, 0, full);
                    }
                    const int xb = (int)(0x0000000765403210ull >> (4 * s)) & 15;
                    if (xb) { mbar_expect(sb + B_XFULL + 8 * xb, 16384); tma2(sb + OFF_X + xb * 16384, &maps.x, 64 * xb, r * 128, sb + B_XFULL + 8 * xb); }
                    P_END()
                }
                for (int s = 0; s < 24; s++) {
                    P_BEGIN(16 + s, 16384) {
                        if (s < 8) {
                            tmaw3(dst, &maps.q64, 0, 64 * s, 2 * j, full);
                            tmaw3(dst + 8192, &maps.gu64, 224 * j + 192, 64 * s, 0, full);
                        } else {
                            tmaw3(dst, &maps.gu, 224 * j + 64 * (s >> 3), 64 * (s & 7), 0, full);
                        }
                    }
                    P_END()
                }
                const int p = j >> 1;
#pragma unroll 1
                for (int t = 0; t < 18; t++) {
                    const int q = t >= 9, sl = (int)(0x846352107ull >> (4 * (t - 9 * q))) & 15;
                    const int u = (int)((q ? 0x432186758ull : 0x327064105ull) >> (4 * (t - 9 * q))) & 15;
                    const int cw = (j & 1) * 4 + ((p & 2) ^ ((t == 5 || t > 9) ? 0 : 2)), cc = 64 * cw;
                    if (sl < 5) {
                        full = sb + B_FULL + 8 * sl; dst = sb + OFF_RING + sl * 16384;
                        mbar_wait(sb + B_EMPTY + 8 * sl, q ^ 1);
                    } else {
                        full = sb + B_EFULL + 8 * (sl - 5); dst = sb + OFF_X + (sl == 7 ? 8 : sl == 8 ? 7 : sl) * 16384;
                        mbar_wait(sb + B_EEMPTY + 8 * (sl - 5), q);
                    }
                    TS2(40 + t);
                    mbar_expect(full, 16384);
                    if (!MC || ((t ^ rank) & 1) == 0) {
                        if (u == 4) {
                            tmaw5(dst, &maps.wdph, cc, 14 * p + 6, full); tmaw5(dst + 4096, &maps.wdph, cc, 14 * p + 13, full);
                            tmaw5(dst + 8192, &maps.wdph, cc + 64, 14 * p + 6, full); tmaw5(dst + 12288, &maps.wdph, cc + 64, 14 * p + 13, full);
                        } else if (u > 4) {
                            const int js = u > 6 ? j ^ 1 : j;
                            tmaw3(dst, (u & 1) ? &maps.wow : &maps.wdw, 0, (u & 1) ? 64 * js : 224 * js + 128, cw, full);
                        } else {
                            const int g = 14 * p + 7 * (u & 1) + (u & 2);
                            tmaw5(dst, &maps.wdp, cc, g, full); tmaw5(dst + 8192, &maps.wdp, cc + 64, g, full);
                        }
                    }
                }
            }
        } else if (warp < 11) {
            const int hx = warp - 9;
            uint32_t epoch;
            asm volatile("ld.relaxed.gpu.global.u32 %0, [%1];" : "=r"(epoch) : "l"(g_epoch + blockIdx.x) : "memory");
            {
                const uint4* xr = (const uint4*)(xg + (size_t)(r * 128 + j * 16 + hx * 8) * kD) + lane;
                const uint4 wa = __ldg((const uint4*)gate_w + lane), wb = __ldg((const uint4*)gate_w + 32 + lane);
                const uint32_t tag = (epoch + 1) & 1;
                uint4* gp = g_gx + r * 32;
                if (lane < 2) st_pkt(gp + j * 4 + hx * 2 + lane, tag ^ 1, 0, 0, 0);
                float s[8];
#pragma unroll
                for (int i0 = 0; i0 < 8; i0 += 4) {
                    uint4 va[4], vb[4];
#pragma unroll
                    for (int i = 0; i < 4; i++) { va[i] = __ldg(xr + (i0 + i) * 64); vb[i] = __ldg(xr + (i0 + i) * 64 + 32); }
#pragma unroll
                    for (int i = 0; i < 4; i++) {
                        float t0 = bf_lo(va[i].x) * bf_lo(wa.x), t1 = bf_hi(va[i].x) * bf_hi(wa.x);
                        t0 = fmaf(bf_lo(va[i].y), bf_lo(wa.y), t0); t1 = fmaf(bf_hi(va[i].y), bf_hi(wa.y), t1);
                        t0 = fmaf(bf_lo(va[i].z), bf_lo(wa.z), t0); t1 = fmaf(bf_hi(va[i].z), bf_hi(wa.z), t1);
                        t0 = fmaf(bf_lo(va[i].w), bf_lo(wa.w), t0); t1 = fmaf(bf_hi(va[i].w), bf_hi(wa.w), t1);
                        t0 = fmaf(bf_lo(vb[i].x), bf_lo(wb.x), t0); t1 = fmaf(bf_hi(vb[i].x), bf_hi(wb.x), t1);
                        t0 = fmaf(bf_lo(vb[i].y), bf_lo(wb.y), t0); t1 = fmaf(bf_hi(vb[i].y), bf_hi(wb.y), t1);
                        t0 = fmaf(bf_lo(vb[i].z), bf_lo(wb.z), t0); t1 = fmaf(bf_hi(vb[i].z), bf_hi(wb.z), t1);
                        t0 = fmaf(bf_lo(vb[i].w), bf_lo(wb.w), t0); t1 = fmaf(bf_hi(vb[i].w), bf_hi(wb.w), t1);
                        s[i0 + i] = t0 + t1;
                    }
                }
#pragma unroll
                for (int i = 0; i < 8; i++) {
#pragma unroll
                    for (int o = 16; o; o >>= 1) s[i] += __shfl_xor_sync(0xffffffffu, s[i], o);
                    s[i] = 1.f / (1.f + __expf(-s[i]));
                }
                if (lane < 2) {
                    const float v0 = lane ? s[4] : s[0], v1 = lane ? s[5] : s[1], v2 = lane ? s[6] : s[2], v3 = lane ? s[7] : s[3];
                    st_pkt(gp + j * 4 + hx * 2 + lane, (__float_as_uint(v0) & ~1u) | tag, __float_as_uint(v1), __float_as_uint(v2), __float_as_uint(v3));
                }
                if (hx == 1) {
                    asm volatile("st.shared.u32 [%0], %1;" :: "r"(sb + OFF_ONES + lane * 4), "r"(0x3f803f80u) : "memory");
                    asm volatile("fence.proxy.async.shared::cta;" ::: "memory");
                }
                asm volatile("bar.sync 3, 96;" ::: "memory");
                if (hx == 0) {
                    uint32_t q[4];
                    recv_issue(q, gp + lane);
                    recv_check(q, gp + lane, tag);
                    asm volatile("st.shared.v4.u32 [%0], {%1,%2,%3,%4};" :: "r"(sb + OFF_G + lane * 16), "r"(q[0]), "r"(q[1]), "r"(q[2]), "r"(q[3]) : "memory");
                    if (lane == 0) {
                        asm volatile("st.shared.u32 [%0], %1;" :: "r"(sb + OFF_EPOCH), "r"(epoch) : "memory");
                        g_epoch[blockIdx.x] = epoch + 1;
                    }
                    __syncwarp();
                    if (lane == 0) mbar_arrive(sb + B_GRDY);
                } else {
                    if (r == 0) {
                        float4* zp = (float4*)(g_kvacc + (((epoch & 1) ^ 1) * 8 + j) * 4 * 272);
                        for (int i = lane; i < 272; i += 32) zp[i] = make_float4(0.f, 0.f, 0.f, 0.f);
                    }
                }
            }
            TS(2 + hx, 1);
#define PUBLISH_H(B) do { mbar_wait(sb + B_HSENT + 8 * (B), 0); if (lane == 0) { \
                asm volatile("st.release.gpu.global.u32 [%0], %1;" :: "l"(g_hflag + (r * 8 + j) * 8 + (B)), "r"(epoch + 1) : "memory"); } __syncwarp(); } while (0)
            if (hx == 1) {
#pragma unroll 1
                for (int b = 0; b < 3; b++) { PUBLISH_H(b); TS(3, 5 + b); }
            } else {
                const float* accp = g_kvacc + ((epoch & 1) * 8 + j) * 4 * 272;
                unsigned* cnt = g_kvcnt + j * 32;
                mbar_wait(sb + B_KVDONE, 0);
                TS(2, 5);
                if (lane == 0) asm volatile("red.release.gpu.global.add.u32 [%0], 1;" :: "l"(cnt) : "memory");
                __syncwarp();
                TS(2, 2);
                {
                    const unsigned target = 16u * (epoch + 1);
                    uint32_t it = 0, v;
                    do {
                        asm volatile("ld.acquire.gpu.global.u32 %0, [%1];" : "=r"(v) : "l"(cnt) : "memory");
                    } while ((int)(v - target) < 0 && ++it < SPIN_GLOBAL);
                }
                TS(2, 3);
#pragma unroll
                for (int h = 0; h < 4; h++) {
                    const float4 d0 = __ldcg((const float4*)(accp + h * 272) + lane);
                    const float4 d1 = __ldcg((const float4*)(accp + h * 272 + 128) + lane);
                    const float2 z0 = __ldcg((const float2*)(accp + h * 272 + 256) + (lane & 3));
                    const float2 z1 = __ldcg((const float2*)(accp + h * 272 + 264) + (lane & 3));
                    const uint32_t ba = sb + OFF_STG + h * 768 + lane * 4;
                    asm volatile("st.shared.u32 [%0], %1;" :: "r"(ba), "r"(pack2(d0.x, d0.y)) : "memory");
                    asm volatile("st.shared.u32 [%0], %1;" :: "r"(ba + 128), "r"(pack2(d1.x, d1.y)) : "memory");
                    asm volatile("st.shared.u32 [%0], %1;" :: "r"(ba + 256), "r"(pack2(d0.z, d0.w)) : "memory");
                    asm volatile("st.shared.u32 [%0], %1;" :: "r"(ba + 384), "r"(pack2(d1.z, d1.w)) : "memory");
                    asm volatile("st.shared.u32 [%0], %1;" :: "r"(ba + 512), "r"(pack2(z0.x, z0.y)) : "memory");
                    asm volatile("st.shared.u32 [%0], %1;" :: "r"(ba + 640), "r"(pack2(z1.x, z1.y)) : "memory");
                }
                asm volatile("fence.proxy.async.shared::cta;" ::: "memory");
                __syncwarp();
                if (lane == 0) mbar_arrive(sb + B_KVRDY);
                TS(2, 4);
            }
        } else {
            uint32_t epoch;
            asm volatile("ld.relaxed.gpu.global.u32 %0, [%1];" : "=r"(epoch) : "l"(g_epoch + blockIdx.x) : "memory");
            asm volatile("bar.arrive 3, 96;" :: "r"(epoch) : "memory");
            const int b = blockIdx.x, p = j >> 1;
            mbar_wait(sb + B_XFULL, 0);
#pragma unroll 1
            for (int kb = 1; kb < 8; kb++) {
                mbar_wait(sb + B_XFULL + 8 * kb, 0);
                const char* base = kb < 3 ? pf_g : kb < 5 ? pf_u : kb == 5 ? pf_qkv : pf_d;
                const int off = kb == 5 ? b * 12288 : b * 14336 + ((kb < 5 ? kb - 1 : kb) & 1) * 7168;
                if (kb == 5) {
                    asm volatile("prefetch.global.L2 [%0];" :: "l"(base + off + (lane >> 3) * 3072 + (lane & 7) * 128));
                } else {
                    asm volatile("prefetch.global.L2 [%0];" :: "l"(base + off + lane * 128));
                    if (lane < 24) asm volatile("prefetch.global.L2 [%0];" :: "l"(base + off + 4096 + lane * 128));
                }
                if (kb == 7) asm volatile("prefetch.global.L2 [%0];" :: "l"(pf_o + b * 4096 + lane * 128));
            }
            {
                uint4* mb = g_part + (size_t)(r * 2 + (j & 1)) * 16384 + (((p ^ 1) * 4 + p) << 10) + lane;
#pragma unroll 1
                for (int i = 0; i < 32; i++) { st_pkt(mb + i * 32, epoch & 1, 0, 0, 0); __nanosleep(40); }
                __syncwarp();
                if (lane == 0) mbar_arrive(sb + B_KVRDY);
            }
            {
                const uint32_t want = epoch + 1;
                const int hrow = (r * 4 + p) * 5 * 128;
                const unsigned* fl = g_hflag + (r * 8 + (j & 6)) * 8 + (lane & 15);
                uint32_t it = 0;
                int i = 0;
                mbar_wait(sb + B_HSENT + 8, 0);
#pragma unroll 1
                while (i < 3 && ++it < SPIN_GLOBAL) {
                    uint32_t v;
                    asm volatile("ld.acquire.gpu.global.u32 %0, [%1];" : "=r"(v) : "l"(fl) : "memory");
                    const uint32_t rdy = __ballot_sync(0xffffffffu, v == want);
#pragma unroll 1
                    while (i < 3 && ((rdy >> i) & 0x101u) == 0x101u) {
                        if (i < 2) mbar_wait(sb + B_XFREE + 8 * i, 0);
                        if (lane == 0) {
                            const int pc = (6 - 2 * i) % 6;
                            asm volatile("fence.proxy.async.global;" ::: "memory");
                            TS2(140 + i);
                            mbar_expect(sb + B_XFULL + 8 * pc, i != 1 ? 32768 : 16384);
                            tma2(sb + OFF_X + pc * 16384, i != 1 ? &maps.hx2 : &maps.hx, 0, hrow + pc * 128, sb + B_XFULL + 8 * pc);
                        }
                        i++;
                    }
                }
            }
        }
    } else {
        asm volatile("setmaxnreg.inc.sync.aligned.u32 224;");
        const int wg = warp >> 2;
        const bool elect = (tid & 127) == 0;
        const uint32_t sbd = (sb & 0x3FFFFu) >> 4, xlo = (sbd + wg * 512) | LBO1;
        auto release = [&](uint32_t bar) {
            if (elect) {
                mbar_arrive(sb + bar);
            }
        };
#define S_SL(S) ((S) < 40 ? (S) % 5 : (int)((0x846352107ull >> (4 * (((S) - 40) % 9))) & 15))
#define S_WAIT(S) do { mbar_wait(sb + (S_SL(S) < 5 ? B_FULL + 8 * S_SL(S) : B_EFULL + 8 * (S_SL(S) - 5)), (S) < 40 ? ((S) / 5) & 1 : (S) >= 49); \
            if (PROF && tid == 0) TS2(64 + (S)); } while (0)
#define S_B(S) (S_SL(S) < 5 ? OFF_RING / 16 + S_SL(S) * 1024 : (S_SL(S) == 7 ? 8 : S_SL(S) == 8 ? 7 : S_SL(S)) * 1024)
#define S_REL(S) do { if ((S) < 49) release(S_SL(S) < 5 ? B_EMPTY + 8 * S_SL(S) : B_EEMPTY + 8 * (S_SL(S) - 5)); } while (0)
#define G1(S, acc, SW, KB) stage_ss<(KB) * 1024, S_B(S), SW, (KB) == 0>(acc, xlo, sbd)
#define RET(S) do { S_WAIT((S) + 1); wg_wait<1>(); S_REL((S) - 1); } while (0)
#define RET2(S) do { S_WAIT((S) + 1); wg_wait<2>(); S_REL((S) - 1); } while (0)
#define SCHED() mbar_wait(sb + B_XFULL + 8 * 7, 0)
#define A2_SYNC() do { asm volatile("fence.proxy.async.shared::cta;" ::: "memory"); asm volatile("bar.sync %0, 128;" :: "r"(wg + 1) : "memory"); } while (0)
#define H_EPI(acc, F, I0, I1, OG, OU) _Pragma("unroll") for (int i = (I0); i < (I1); i++) \
            F[i] = keep(hmul2(pack2(acc[(OG) + 2 * i] * acc[(OU) + 2 * i], acc[(OG) + 2 * i + 1] * acc[(OU) + 2 * i + 1]), (i & 1) ? m_hi : m_lo))
#define PHI(acc, F, I0, I1) _Pragma("unroll") for (int i = (I0); i < (I1); i++) F[i] = keep(phi2(acc[2 * i], acc[2 * i + 1]))

        float a0[64], b0[64], a1[64], a2_[64], a3[64];
        mbar_wait(sb + B_XFULL, 0);
#define X_WAIT(KB) do { mbar_wait(sb + B_XFULL + 8 * (KB), 0); if (PROF && tid == 0) TS2(128 + (KB)); } while (0)
        S_WAIT(0); G1(0, b0, false, 0);
        if ((warp & 3) == 0) TS(wg, 1);
        S_WAIT(1); G1(1, a0, false, 0); RET(1);
        X_WAIT(1); G1(2, b0, false, 1); RET(2);
        X_WAIT(2); G1(3, b0, false, 2); RET(3);
        G1(4, a0, false, 1); RET(4);
        X_WAIT(3); G1(5, b0, false, 3); RET(5);
        G1(6, a0, false, 2); RET(6);
        X_WAIT(4); G1(7, b0, false, 4); RET(7);
        X_WAIT(5); G1(8, b0, false, 5); RET(8);
        G1(9, a0, false, 3); RET(9);
        X_WAIT(6); G1(10, b0, false, 6); RET(10);
        X_WAIT(7); G1(11, b0, false, 7); RET(11);
        G1(12, a0, false, 4);
        const uint32_t lrow = ((lane & 7) + 8 * ((lane >> 3) & 1)) * 128;
        const uint32_t srow = (warp & 3) * 2048 + lrow;
        const uint32_t ssw = (lane >> 4) ^ (lane & 7);
        uint4* const hsend = g_hx + (size_t)((r * 4 + (j >> 1)) * 5 + (j & 1)) * 1024 + warp * 128 + (lane >> 2) * 8 + (lane & 3);
#define SENT_H(B) do { __syncwarp(); if (lane == 0) mbar_arrive(sb + B_HSENT + 8 * (B)); } while (0)
        RET(12);
        pin(b0);
        uint32_t fh0[16], fh1[16], fh2[16], fh3[8], fo[16], pk[16], pv[16];
        float kv[32], zs[4];
        const uint32_t stg = sb + OFF_STG + wg * 8192, stl = stg + (warp & 1) * 2048 + lrow;
#define KV_ROUND(Z) do { A2_SYNC(); wg_fence(); \
            wg_ss64t##Z<8192 + 256, 8192, DH128>(kv, xlo, xlo); wg_ss64t<8192 + 384, 8192 + 128, DH128>(kv, xlo, xlo); \
            wg_ss8t##Z<8192, OFF_ONES / 16, 0>(zs, xlo, sbd); wg_ss8t<8192 + 128, OFF_ONES / 16, 0>(zs, xlo, sbd); wg_commit(); } while (0)
        G1(13, a0, false, 5); SCHED(); pack_sub<32>(pv, b0); PHI(b0, pk, 0, 4); RET(13);
        G1(14, a0, false, 6); SCHED(); if (!(warp & 2)) stash<16>(stl + 4096, ssw, pv); PHI(b0, pk, 4, 10); RET(14);
        G1(15, a0, false, 7); SCHED(); PHI(b0, pk, 10, 16); RET(15);
        if ((warp & 3) == 0) TS(wg, 2);

        G1(16, a1, true, 0); SCHED(); if (!(warp & 2)) stash<16>(stl, ssw, pk);
        mbar_wait(sb + B_GRDY, 0);
        float g_lo, g_hi;
        uint32_t tag;
        {
            const uint32_t ga = sb + OFF_G + (warp * 16 + (lane >> 2)) * 4;
            asm volatile("ld.shared.f32 %0, [%1];" : "=f"(g_lo) : "r"(ga) : "memory");
            asm volatile("ld.shared.f32 %0, [%1];" : "=f"(g_hi) : "r"(ga + 32) : "memory");
            asm volatile("ld.shared.u32 %0, [%1];" : "=r"(tag) : "r"(sb + OFF_EPOCH) : "memory");
        }
        float* const kvp = g_kvacc + (((tag & 1) * 8 + j) * 4 + (warp & 3)) * 272;
        tag = (tag + 1) & 1;
        const uint32_t m_lo = pack2(1.f - g_lo, 1.f - g_lo), m_hi = pack2(1.f - g_hi, 1.f - g_hi);
        RET(16);
        pin(a0);
        G1(17, a1, true, 1); SCHED(); H_EPI(a0, fh0, 0, 16, 0, 32); RET(17);
        G1(18, a1, true, 2); KV_ROUND(_z); RET2(18);
        G1(19, a1, true, 3); SCHED(); send_h<0, 1>(fh0, hsend); RET(19);
        G1(20, a1, true, 4); SCHED(); if (warp & 2) { stash<16>(stl, ssw, pk); stash<16>(stl + 4096, ssw, pv); } RET(20);
        G1(21, a1, true, 5); KV_ROUND(); RET2(21);
        G1(22, a1, true, 6); RET(22);
        pin(kv); pin(zs);
        G1(23, a1, true, 7); SCHED();
#define KV_RED(W) do { asm volatile("red.global.add.v4.f32 [%0], {%1,%2,%3,%4};" :: "l"(kvp + lane * 4), "f"(kv[8 * W]), "f"(kv[8 * W + 1]), "f"(kv[8 * W + 2]), "f"(kv[8 * W + 3]) : "memory"); \
                       asm volatile("red.global.add.v4.f32 [%0], {%1,%2,%3,%4};" :: "l"(kvp + 128 + lane * 4), "f"(kv[8 * W + 4]), "f"(kv[8 * W + 5]), "f"(kv[8 * W + 6]), "f"(kv[8 * W + 7]) : "memory"); } while (0)
        if ((warp & 3) == 0) KV_RED(0); else if ((warp & 3) == 1) KV_RED(1); else if ((warp & 3) == 2) KV_RED(2); else KV_RED(3);
        if ((lane & 3) == 0) {
            asm volatile("red.global.add.f32 [%0], %1;" :: "l"(kvp + 256 + (lane >> 2)), "f"(zs[0]) : "memory");
            asm volatile("red.global.add.f32 [%0], %1;" :: "l"(kvp + 264 + (lane >> 2)), "f"(zs[2]) : "memory");
        }
        __syncwarp();
        if (lane == 0) mbar_arrive(sb + B_KVDONE);
        RET(23);
        if ((warp & 3) == 0) TS(wg, 3);

        G1(24, a2_, false, 0); SCHED(); send_h<1, 2>(fh0, hsend); RET(24);
        pin(a1);
        G1(25, a2_, false, 1); SCHED(); send_h<2, 3>(fh0, hsend); H_EPI(a1, fh3, 0, 8, 32, 48); RET(25);
        G1(26, a2_, false, 2); SCHED(); send_h<3, 4>(fh0, hsend); SENT_H(0); PHI(a1, fo, 0, 4); RET(26);
        G1(27, a2_, false, 3); SCHED(); send_h<0, 1>(fh3, hsend + 4 * 1024 - (j & 1) * 1020); PHI(a1, fo, 4, 8); RET(27);
        G1(28, a2_, false, 4); SCHED(); send_h<1, 2>(fh3, hsend + 4 * 1024 - (j & 1) * 1020); SENT_H(1); PHI(a1, fo, 8, 12); RET(28);
        G1(29, a2_, false, 5); SCHED(); PHI(a1, fo, 12, 16); RET(29);
        G1(30, a2_, false, 6); RET(30);
        G1(31, a2_, false, 7); RET(31);
        if ((warp & 3) == 0) TS(wg, 4);

        float on[4][12];
#define O_SCALE(h) do { const float s_lo = __fdividef(g_lo, on[h][8] + 1e-6f), s_hi = __fdividef(g_hi, on[h][10] + 1e-6f); \
            const uint32_t sl_ = pack2(s_lo, s_lo), sh_ = pack2(s_hi, s_hi); \
            fo[4 * h] = keep(hmul2(pack2(on[h][0], on[h][1]), sl_)); fo[4 * h + 1] = keep(hmul2(pack2(on[h][2], on[h][3]), sh_)); \
            fo[4 * h + 2] = keep(hmul2(pack2(on[h][4], on[h][5]), sl_)); fo[4 * h + 3] = keep(hmul2(pack2(on[h][6], on[h][7]), sh_)); } while (0)
        uint4* const lsend = g_lx + (size_t)(r * 8 + j) * 2048 + warp * 128 + lane;
        const uint4* const lrecv = g_lx + (size_t)(r * 8 + (j ^ 1)) * 2048 + warp * 128 + lane;
        G1(32, a3, false, 0); RET(32);
        pin(a2_);
        G1(33, a3, false, 1); SCHED(); H_EPI(a2_, fh1, 0, 16, 0, 32); send_h<0, 1>(fh1, hsend + 2 * 1024); RET(33);
        G1(34, a3, false, 2); SCHED(); send_h<1, 3>(fh1, hsend + 2 * 1024); RET(34);
        if (elect) mbar_arrive(sb + B_XFREE);
        G1(35, a3, false, 3); SCHED(); send_h<3, 4>(fh1, hsend + 2 * 1024); SENT_H(2);
        if ((warp & 3) == 0) TS(wg, 5);
        mbar_wait(sb + B_KVRDY, 0);
        if ((warp & 3) == 0) TS(wg, 6);
        wg_fence();
#define O_MMA(h) wg_rs24_z<OFF_STG / 16 + (h) * 48 + (8u << 16), 16>(on[h], fo[4 * (h)], fo[4 * (h) + 1], fo[4 * (h) + 2], fo[4 * (h) + 3], sbd)
        O_MMA(0); O_MMA(1); O_MMA(2); O_MMA(3);
        wg_commit();
        RET2(35);
        G1(36, a3, false, 4); RET(36);
        pin(on[0]); pin(on[1]); pin(on[2]); pin(on[3]);
        release(B_EEMPTY + 16);
        G1(37, a3, false, 5); SCHED(); O_SCALE(0); O_SCALE(1); O_SCALE(2); O_SCALE(3); RET(37);
        if (elect) mbar_arrive(sb + B_XFREE + 8);
        G1(38, a3, false, 6); SCHED(); send_frag<0, 2>(fo, lsend, tag); RET(38);
        release(B_EEMPTY);
        G1(39, a3, false, 7); SCHED(); send_frag<2, 4>(fo, lsend, tag); RET(39);
        release(B_EEMPTY + 8);
        if ((warp & 3) == 0) TS(wg, 7);

#define G2S(S, acc, U) stage_ss<(U) * 1024, S_B(S), false, (S) == 45>(acc, xlo, sbd)
#define G2R(S, acc, F) stage_rs<S_B(S), (S) == 40>(acc, F, sbd)
#define H_WAIT(P) do { mbar_wait(sb + B_XFULL + 8 * (P), 1); if (PROF && tid == 0) TS2(150 + (P)); } while (0)
        const int p = j >> 1, pw = (p & 2) ^ 2;
        const bool own = wg == (p & 1);
        uint4* const pbase = g_part + (size_t)(r * 2 + (j & 1)) * 16384 + (warp & 3) * 256 + lane;

        float p1[64], p2[64];
        uint32_t po[16], ph2[16];
        G2R(40, p1, fo); RET(40);
        release(B_EEMPTY + 24);
        pin(a3);
        H_WAIT(0); G2S(41, p1, 0); SCHED(); H_EPI(a3, fh2, 0, 16, 0, 32); send_frag<0, 2>(fh2, lsend + 1024, tag); RET(41);
        G2S(42, p1, 1); SCHED(); recv_issue(po, lrecv); send_frag<2, 4>(fh2, lsend + 1024, tag); RET(42);
        H_WAIT(4); G2S(43, p1, 4); RET(43);
        G2R(44, p1, fh2); RET(44);
        G2S(45, p2, 0); SCHED(); if (!(EXPT & 2)) recv_check(po, lrecv, tag); recv_issue(ph2, lrecv + 1024); RET(45);
        G2R(46, p1, po); RET(46);
        H_WAIT(2); G2S(47, p1, 2); RET(47);
        G2S(48, p1, 3); SCHED(); if (!(EXPT & 2)) recv_check(ph2, lrecv + 1024, tag); RET(48);
        G2R(49, p1, ph2); RET(49);
        if ((warp & 3) == 0) TS(wg, 8);
        uint32_t sp[32], qa[32], qb[32];
        uint4* const s1 = pbase + (((pw + wg) * 4 + p) << 10);
        G2R(50, p2, fo); RET(50);
        pin(p1);
        G2R(51, p2, po); SCHED(); pack_sub<0>(sp, p1); send_frag<0, 2>(sp, s1, tag); RET(51);
        G2R(52, p2, fh2); SCHED(); send_frag<2, 5>(sp, s1, tag); RET(52);
        if (elect) mbar_arrive(sb + B_XFREE + 16);
        G2R(53, p2, ph2); SCHED(); send_frag<5, 8>(sp, s1, tag); RET(53);
        const uint4* ra = pbase + ((p * 4 + pw) << 10);
        const uint4* rc = pbase + ((p * 4 + (p ^ 1)) << 10);
        if (own) mbar_wait(sb + B_AHEAD, 0);
        G2S(54, p2, 1); RET(54);
        G2S(55, p2, 2); RET(55);
        G2S(56, p2, 3); RET(56);
        G2S(57, p2, 4); SCHED();
        if ((warp & 3) == 0) TS(wg, 9);
#define PART_COPY() do { mbar_wait(sb + B_XFREE + 16, 0); mbar_expect(sb + B_PART, 32768); \
            asm volatile("cp.async.bulk.shared::cluster.global.mbarrier::complete_tx::bytes [%0], [%1], %2, [%3];" \
                         :: "r"(sb + OFF_RING), "l"(ra), "r"(32768), "r"(sb + B_PART) : "memory"); } while (0)
        if (!own && elect) mbar_arrive(sb + B_AHEAD);
        wg_wait<0>();
        pin(p2);
        if ((warp & 3) == 0) TS(wg, 11);
        if (!own) {
            if (COPY_AT == 0 && elect) PART_COPY();
            pack_sub<0>(sp, p2);
            if (COPY_AT == 1 && elect) PART_COPY();
            send_frag<0, 4>(sp, pbase + (((p ^ 1) * 4 + p) << 10), tag);
            if (COPY_AT == 2 && elect) PART_COPY();
            send_frag<4, 8>(sp, pbase + (((p ^ 1) * 4 + p) << 10), tag);
            if (COPY_AT == 3 && elect) PART_COPY();
        } else {
            recv_issue(sp, rc);
            mbar_wait(sb + B_PART, 0);
            if ((warp & 3) == 0) TS(wg, 10);
            const uint32_t pa = sb + OFF_RING + (warp & 3) * 4096 + lane * 16;
#pragma unroll
            for (int v = 0; v < 8; v++) {
                asm volatile("ld.shared.v4.u32 {%0,%1,%2,%3}, [%4];" : "=r"(qa[4 * v]), "=r"(qa[4 * v + 1]), "=r"(qa[4 * v + 2]), "=r"(qa[4 * v + 3]) : "r"(pa + v * 512) : "memory");
                asm volatile("ld.shared.v4.u32 {%0,%1,%2,%3}, [%4];" : "=r"(qb[4 * v]), "=r"(qb[4 * v + 1]), "=r"(qb[4 * v + 2]), "=r"(qb[4 * v + 3]) : "r"(pa + 16384 + v * 512) : "memory");
            }
#if !(EXPT & 1)
            recv_check(qa, ra, tag); recv_check(qb, ra + 1024, tag);
#endif
#pragma unroll
            for (int i = 0; i < 32; i++) qa[i] = hadd2(qa[i], qb[i]);
            accum(qa, p2);
            pack_sub<0>(qb, p2);
            if ((warp & 3) == 0) TS(wg, 12);
            if (!(EXPT & 4)) recv_check(sp, rc, tag);
            if ((warp & 3) == 0) TS(wg, 13);
            uint32_t f0[16], f1[16];
#pragma unroll
            for (int i = 0; i < 16; i++) { f0[i] = hadd2(qb[i], sp[i]); f1[i] = hadd2(qb[16 + i], sp[16 + i]); }
            const uint32_t slab = sb + OFF_X + 2 * 16384 + wg * 8192;
            stash<16>(slab + srow, ssw, f0); stash<16>(slab + 16384 + srow, ssw, f1);
            __syncwarp();
            __nv_bfloat16* op = out + (size_t)(r * 128 + warp * 16 + (lane >> 4)) * kD + (j & 1) * 256 + (p & 2) * 64 + (lane & 15) * 8;
#pragma unroll
            for (int i = 0; i < 8; i++) {
                const int row = i * 2 + (lane >> 4);
                uint4 v;
                asm volatile("ld.shared.v4.u32 {%0,%1,%2,%3}, [%4];" : "=r"(v.x), "=r"(v.y), "=r"(v.z), "=r"(v.w)
                             : "r"(slab + (lane & 8) * 2048 + ((warp & 3) * 16 + row) * 128 + (((lane & 7) ^ (row & 7)) << 4)) : "memory");
                *(uint4*)(op + i * 2 * kD) = v;
            }
        }
        if ((warp & 3) == 0) { TS(wg, 14); TSG(wg, 31); }
    }
}

typedef CUresult (*EncodeFn)(CUtensorMap*, CUtensorMapDataType, cuuint32_t, void*, const cuuint64_t*, const cuuint64_t*, const cuuint32_t*,
                             const cuuint32_t*, CUtensorMapInterleave, CUtensorMapSwizzle, CUtensorMapL2promotion, CUtensorMapFloatOOBfill);

static void encode(EncodeFn fn, CUtensorMap* m, int rank, const void* base, const cuuint64_t (&gd)[5], const cuuint64_t (&gs)[4],
                   const cuuint32_t (&bd)[5], CUtensorMapSwizzle sw) {
    cuuint32_t es[5] = {1, 1, 1, 1, 1};
    fn(m, CU_TENSOR_MAP_DATA_TYPE_BFLOAT16, rank, const_cast<void*>(base), gd, gs, bd, es, CU_TENSOR_MAP_INTERLEAVE_NONE, sw,
       CU_TENSOR_MAP_L2_PROMOTION_L2_128B, CU_TENSOR_MAP_FLOAT_OOB_FILL_NONE);
}

extern "C" void kernel_launch(void* const* d_in, const int* in_sizes, int n_in, void* d_out, int out_size) {
    const char* x = (const char*)d_in[0];
    const char* wqkv = (const char*)d_in[1];
    const char* wo = (const char*)d_in[2];
    const char* wg = (const char*)d_in[4];
    const char* wu = (const char*)d_in[5];
    const char* wd = (const char*)d_in[6];
    void* fnp = nullptr;
    cudaDriverEntryPointQueryResult qr;
    cudaGetDriverEntryPoint("cuTensorMapEncodeTiled", &fnp, cudaEnableDefault, &qr);
    EncodeFn fn = (EncodeFn)fnp;
    Maps maps;
    const char* lo = wg < wu ? wg : wu;
    const uint64_t diff = wg < wu ? (uint64_t)(wu - wg) : (uint64_t)(wg - wu);
    const CUtensorMapSwizzle S128 = CU_TENSOR_MAP_SWIZZLE_128B, S64 = CU_TENSOR_MAP_SWIZZLE_64B;
    encode(fn, &maps.x, 2, x, {512, 2048, 1, 1}, {1024, 0, 0}, {64, 128, 1, 1}, S128);
    encode(fn, &maps.gu, 3, lo, {1792, 512, 2, 1}, {3584, diff, 0}, {64, 64, 2, 1}, S128);
    encode(fn, &maps.kv, 3, wqkv, {512, 512, 3, 1}, {3072, 1024, 0}, {64, 64, 2, 1}, S128);
    encode(fn, &maps.q64, 3, wqkv, {32, 512, 48, 1}, {3072, 64, 0}, {32, 64, 2, 1}, S64);
    encode(fn, &maps.gu64, 3, lo, {1792, 512, 2, 1}, {3584, diff, 0}, {32, 64, 2, 1}, S64);
    encode(fn, &maps.wdw, 3, wd, {64, 1792, 8, 1}, {1024, 128, 0}, {64, 64, 2, 1}, S128);
    encode(fn, &maps.wow, 3, wo, {64, 512, 8}, {1024, 128}, {64, 64, 2}, S128);
    encode(fn, &maps.wdp, 5, wd, {512, 2, 4, 4, 56}, {1024, 8192, 2048, 32768}, {64, 2, 4, 4, 2}, S128);
    encode(fn, &maps.wdph, 5, wd, {512, 2, 4, 4, 56}, {1024, 8192, 2048, 32768}, {64, 2, 4, 4, 1}, S128);
    void* hx = nullptr;
    cudaGetSymbolAddress(&hx, g_hx);
    encode(fn, &maps.hx, 2, hx, {64, 16 * 4 * 5 * 128}, {128}, {64, 128}, S128);
    encode(fn, &maps.hx2, 2, hx, {64, 16 * 4 * 5 * 128}, {128}, {64, 256}, S128);
    cudaFuncSetAttribute(fused_kernel, cudaFuncAttributeMaxDynamicSharedMemorySize, SMEM_BYTES);
    cudaLaunchConfig_t cfg = {};
    cfg.gridDim = dim3(128);
    cfg.blockDim = dim3(384);
    cfg.dynamicSmemBytes = SMEM_BYTES;
    cfg.stream = cudaStreamPerThread;
    cudaLaunchAttribute at[1];
    at[0].id = cudaLaunchAttributeClusterDimension;
    at[0].val.clusterDim.x = 2; at[0].val.clusterDim.y = 1; at[0].val.clusterDim.z = 1;
    cfg.attrs = at;
    cfg.numAttrs = MC ? 1 : 0;
    cudaLaunchKernelEx(&cfg, fused_kernel, maps, (const __nv_bfloat16*)d_in[0], (const __nv_bfloat16*)d_in[7], wqkv, wg, wu, wd, wo, (__nv_bfloat16*)d_out);
}
```

```cpp
#include <cuda_runtime.h>
#include <cuda.h>
#include <cuda_bf16.h>
#include <stdint.h>

#define MC 0
#define PFMODE 1
#define PHI_SAT 0
#define EXPT 0
#define COPY_AT 0
#define RX 0
#define PROF 0

namespace {

constexpr int kD = 512;
constexpr uint32_t OFF_X = 0, OFF_STG = 131072, OFF_RING = 147456, OFF_MISC = 229376;
constexpr uint32_t B_FULL = OFF_MISC, B_EMPTY = OFF_MISC + 40, B_XFULL = OFF_MISC + 80;
constexpr uint32_t B_GRDY = OFF_MISC + 152, B_KVDONE = OFF_MISC + 160, B_KVRDY = OFF_MISC + 168;
constexpr uint32_t B_HSENT = OFF_MISC + 176, B_XFREE = OFF_MISC + 200;
constexpr uint32_t OFF_EPOCH = OFF_MISC + 240, OFF_G = OFF_MISC + 256;
constexpr uint32_t B_AHEAD = OFF_MISC + 248, B_PART = OFF_MISC + 232;
constexpr uint32_t OFF_ONES = OFF_MISC + 768;
constexpr uint32_t B_EFULL = OFF_MISC + 896, B_EEMPTY = OFF_MISC + 928;
constexpr uint32_t SMEM_BYTES = OFF_MISC + 960;
constexpr uint32_t SPIN_GLOBAL = 1u << 14;

struct alignas(64) Maps { CUtensorMap x, gu, kv, q64, gu64, wdw, wow, wdp, wdph, hx, hx2; };

}

__device__ uint4 g_part[16 * 2 * 4 * 4 * 1024];
__device__ uint4 g_hx[16 * 4 * 5 * 1024];
__device__ uint4 g_lx[16 * 8 * 2 * 1024];
__device__ unsigned g_hflag[128 * 8];
__device__ uint4 g_gx[16 * 32];
__device__ float g_kvacc[2 * 8 * 4 * 272];
__device__ unsigned g_kvcnt[8 * 32];
__device__ unsigned g_epoch[128];
#define TS(role, idx)
#define TS2(idx)
#define TSG(role, idx)

namespace {

__device__ __forceinline__ void mbar_init(uint32_t bar, uint32_t cnt) { asm volatile("mbarrier.init.shared::cta.b64 [%0], %1;" :: "r"(bar), "r"(cnt) : "memory"); }
__device__ __forceinline__ void mbar_expect(uint32_t bar, uint32_t bytes) { asm volatile("mbarrier.arrive.expect_tx.shared::cta.b64 _, [%0], %1;" :: "r"(bar), "r"(bytes) : "memory"); }
__device__ __forceinline__ void mbar_arrive(uint32_t bar) { asm volatile("mbarrier.arrive.shared::cta.b64 _, [%0];" :: "r"(bar) : "memory"); }
__device__ __forceinline__ void mbar_arrive_cta(uint32_t bar, uint32_t cta) {
    asm volatile("{\n.reg .b32 ra;\nmapa.shared::cluster.u32 ra, %0, %1;\nmbarrier.arrive.shared::cluster.b64 _, [ra];\n}" :: "r"(bar), "r"(cta) : "memory");
}
__device__ __forceinline__ void mbar_wait(uint32_t bar, uint32_t parity) {
    asm volatile("{\n.reg .pred p;\n.reg .u32 c;\n"
                 "mbarrier.try_wait.parity.shared::cta.b64 p, [%0], %1;\n@p bra DONE;\n"
                 "mov.u32 c, 0;\nLAB_WAIT:\nmbarrier.try_wait.parity.shared::cta.b64 p, [%0], %1;\n@p bra DONE;\n"
                 "add.u32 c, c, 1;\nsetp.lt.u32 p, c, 65536;\n@p bra LAB_WAIT;\nDONE:\n}" :: "r"(bar), "r"(parity) : "memory");
}
__device__ __forceinline__ void tma2(uint32_t dst, const CUtensorMap* m, int c0, int c1, uint32_t bar) {
    asm volatile("cp.async.bulk.tensor.2d.shared::cluster.global.mbarrier::complete_tx::bytes [%0], [%1, {%3, %4}], [%2];"
        :: "r"(dst), "l"(m), "r"(bar), "r"(c0), "r"(c1) : "memory");
}
__device__ __forceinline__ void tmaw2(uint32_t dst, const CUtensorMap* m, int c0, int c1, uint32_t bar) {
    tma2(dst, m, c0, c1, bar);
}
__device__ __forceinline__ void tmaw3(uint32_t dst, const CUtensorMap* m, int c0, int c1, int c2, uint32_t bar) {
    asm volatile("cp.async.bulk.tensor.3d.shared::cluster.global.mbarrier::complete_tx::bytes [%0], [%1, {%3, %4, %5}], [%2];"
        :: "r"(dst), "l"(m), "r"(bar), "r"(c0), "r"(c1), "r"(c2) : "memory");
}
__device__ __forceinline__ void tmaw5(uint32_t dst, const CUtensorMap* m, int c0, int c4, uint32_t bar) {
    asm volatile("cp.async.bulk.tensor.5d.shared::cluster.global.mbarrier::complete_tx::bytes [%0], [%1, {%3, %5, %5, %5, %4}], [%2];"
        :: "r"(dst), "l"(m), "r"(bar), "r"(c0), "r"(c4), "r"(0) : "memory");
}
__device__ __forceinline__ void wg_fence() { asm volatile("wgmma.fence.sync.aligned;" ::: "memory"); }
__device__ __forceinline__ void wg_commit() { asm volatile("wgmma.commit_group.sync.aligned;" ::: "memory"); }
template <int N> __device__ __forceinline__ void wg_wait() { asm volatile("wgmma.wait_group.sync.aligned %0;" :: "n"(N) : "memory"); }
template <int N> __device__ __forceinline__ void pin(float (&d)[N]) {
#pragma unroll
    for (int i = 0; i < N; i++) asm volatile("" : "+f"(d[i]) :: "memory");
}
__device__ __forceinline__ uint32_t pack2(float lo, float hi) { uint32_t r; asm("cvt.rn.bf16x2.f32 %0, %1, %2;" : "=r"(r) : "f"(hi), "f"(lo)); return r; }
__device__ __forceinline__ uint32_t keep(uint32_t v) { asm volatile("" : "+r"(v)); return v; }
__device__ __forceinline__ uint32_t hadd2(uint32_t a, uint32_t b) { uint32_t r; asm("add.bf16x2 %0, %1, %2;" : "=r"(r) : "r"(a), "r"(b)); return r; }
__device__ __forceinline__ uint32_t hmul2(uint32_t a, uint32_t b) { uint32_t r; asm("mul.bf16x2 %0, %1, %2;" : "=r"(r) : "r"(a), "r"(b)); return r; }
__device__ __forceinline__ uint32_t phi2(float t0, float t1) {
    float e0, e1;
    asm("ex2.approx.ftz.f32 %0, %1;" : "=f"(e0) : "f"(t0 * 1.4426950408889634f));
    asm("ex2.approx.ftz.f32 %0, %1;" : "=f"(e1) : "f"(t1 * 1.4426950408889634f));
    uint32_t e = pack2(e0, e1), t = pack2(t0, t1), r;
    asm("min.bf16x2 %0, %0, %1;" : "+r"(e) : "r"(0x3f803f80u));
    asm("max.bf16x2 %0, %0, %1;" : "+r"(t) : "r"(0x35863586u));
    asm("add.bf16x2 %0, %1, %2;" : "=r"(r) : "r"(e), "r"(t));
    return r;
}
__device__ __forceinline__ void stsm4(uint32_t a, uint32_t r0, uint32_t r1, uint32_t r2, uint32_t r3) {
    asm volatile("stmatrix.sync.aligned.m8n8.x4.shared.b16 [%0], {%1,%2,%3,%4};" :: "r"(a), "r"(r0), "r"(r1), "r"(r2), "r"(r3) : "memory");
}
__device__ __forceinline__ float bf_lo(uint32_t w) { return __uint_as_float(w << 16); }
__device__ __forceinline__ float bf_hi(uint32_t w) { return __uint_as_float(w & 0xffff0000u); }
__device__ __forceinline__ void st_pkt(uint4* p, uint32_t w0, uint32_t w1, uint32_t w2, uint32_t w3) {
    asm volatile("{\n.reg .b64 lo, hi;\n.reg .b128 v;\nmov.b64 lo, {%1, %2};\nmov.b64 hi, {%3, %4};\nmov.b128 v, {lo, hi};\nst.relaxed.gpu.global.b128 [%0], v;\n}"
        :: "l"(p), "r"(w0), "r"(w1), "r"(w2), "r"(w3) : "memory");
}
__device__ __forceinline__ void ld_pkt(const uint4* p, uint32_t& w0, uint32_t& w1, uint32_t& w2, uint32_t& w3) {
    asm volatile("{\n.reg .b64 lo, hi;\n.reg .b128 v;\nld.relaxed.gpu.global.b128 v, [%4];\nmov.b128 {lo, hi}, v;\nmov.b64 {%0, %1}, lo;\nmov.b64 {%2, %3}, hi;\n}"
        : "=r"(w0), "=r"(w1), "=r"(w2), "=r"(w3) : "l"(p) : "memory");
}

template <uint32_t AO, uint32_t BO, uint32_t BH> __device__ __forceinline__ void wg_ss128(float (&d)[64], uint32_t ab, uint32_t bb) {
    asm volatile("{\n.reg .b64 da, db;\n.reg .b32 ta, tb, th, ah;\nadd.u32 ta, %64, %66;\nadd.u32 tb, %65, %67;\nmov.b32 th, %68;\nmov.b32 ah, 0x40000040;\nmov.b64 da, {ta, ah};\nmov.b64 db, {tb, th};\n"
        "wgmma.mma_async.sync.aligned.m64n128k16.f32.bf16.bf16 {%0,%1,%2,%3,%4,%5,%6,%7,%8,%9,%10,%11,%12,%13,%14,%15,%16,%17,%18,%19,%20,%21,%22,%23,%24,%25,%26,%27,%28,%29,%30,%31,%32,%33,%34,%35,%36,%37,%38,%39,%40,%41,%42,%43,%44,%45,%46,%47,%48,%49,%50,%51,%52,%53,%54,%55,%56,%57,%58,%59,%60,%61,%62,%63}, da, db, 1, 1, 1, 0, 1;\n}\n"
        : "+f"(d[0]),"+f"(d[1]),"+f"(d[2]),"+f"(d[3]),"+f"(d[4]),"+f"(d[5]),"+f"(d[6]),"+f"(d[7]),"+f"(d[8]),"+f"(d[9]),"+f"(d[10]),"+f"(d[11]),"+f"(d[12]),"+f"(d[13]),"+f"(d[14]),"+f"(d[15]),"+f"(d[16]),"+f"(d[17]),"+f"(d[18]),"+f"(d[19]),"+f"(d[20]),"+f"(d[21]),"+f"(d[22]),"+f"(d[23]),"+f"(d[24]),"+f"(d[25]),"+f"(d[26]),"+f"(d[27]),"+f"(d[28]),"+f"(d[29]),"+f"(d[30]),"+f"(d[31]),"+f"(d[32]),"+f"(d[33]),"+f"(d[34]),"+f"(d[35]),"+f"(d[36]),"+f"(d[37]),"+f"(d[38]),"+f"(d[39]),"+f"(d[40]),"+f"(d[41]),"+f"(d[42]),"+f"(d[43]),"+f"(d[44]),"+f"(d[45]),"+f"(d[46]),"+f"(d[47]),"+f"(d[48]),"+f"(d[49]),"+f"(d[50]),"+f"(d[51]),"+f"(d[52]),"+f"(d[53]),"+f"(d[54]),"+f"(d[55]),"+f"(d[56]),"+f"(d[57]),"+f"(d[58]),"+f"(d[59]),"+f"(d[60]),"+f"(d[61]),"+f"(d[62]),"+f"(d[63])
        : "r"(ab), "r"(bb), "n"(AO), "n"(BO), "n"(BH));
}
template <uint32_t AO, uint32_t BO, uint32_t BH> __device__ __forceinline__ void wg_ss128_z(float (&d)[64], uint32_t ab, uint32_t bb) {
    asm volatile("{\n.reg .b64 da, db;\n.reg .b32 ta, tb, th, ah;\nadd.u32 ta, %64, %66;\nadd.u32 tb, %65, %67;\nmov.b32 th, %68;\nmov.b32 ah, 0x40000040;\nmov.b64 da, {ta, ah};\nmov.b64 db, {tb, th};\n"
        "wgmma.mma_async.sync.aligned.m64n128k16.f32.bf16.bf16 {%0,%1,%2,%3,%4,%5,%6,%7,%8,%9,%10,%11,%12,%13,%14,%15,%16,%17,%18,%19,%20,%21,%22,%23,%24,%25,%26,%27,%28,%29,%30,%31,%32,%33,%34,%35,%36,%37,%38,%39,%40,%41,%42,%43,%44,%45,%46,%47,%48,%49,%50,%51,%52,%53,%54,%55,%56,%57,%58,%59,%60,%61,%62,%63}, da, db, 0, 1, 1, 0, 1;\n}\n"
        : "=f"(d[0]),"=f"(d[1]),"=f"(d[2]),"=f"(d[3]),"=f"(d[4]),"=f"(d[5]),"=f"(d[6]),"=f"(d[7]),"=f"(d[8]),"=f"(d[9]),"=f"(d[10]),"=f"(d[11]),"=f"(d[12]),"=f"(d[13]),"=f"(d[14]),"=f"(d[15]),"=f"(d[16]),"=f"(d[17]),"=f"(d[18]),"=f"(d[19]),"=f"(d[20]),"=f"(d[21]),"=f"(d[22]),"=f"(d[23]),"=f"(d[24]),"=f"(d[25]),"=f"(d[26]),"=f"(d[27]),"=f"(d[28]),"=f"(d[29]),"=f"(d[30]),"=f"(d[31]),"=f"(d[32]),"=f"(d[33]),"=f"(d[34]),"=f"(d[35]),"=f"(d[36]),"=f"(d[37]),"=f"(d[38]),"=f"(d[39]),"=f"(d[40]),"=f"(d[41]),"=f"(d[42]),"=f"(d[43]),"=f"(d[44]),"=f"(d[45]),"=f"(d[46]),"=f"(d[47]),"=f"(d[48]),"=f"(d[49]),"=f"(d[50]),"=f"(d[51]),"=f"(d[52]),"=f"(d[53]),"=f"(d[54]),"=f"(d[55]),"=f"(d[56]),"=f"(d[57]),"=f"(d[58]),"=f"(d[59]),"=f"(d[60]),"=f"(d[61]),"=f"(d[62]),"=f"(d[63])
        : "r"(ab), "r"(bb), "n"(AO), "n"(BO), "n"(BH));
}
template <uint32_t BO, uint32_t BH> __device__ __forceinline__ void wg_rs128(float (&d)[64], uint32_t a0, uint32_t a1, uint32_t a2, uint32_t a3, uint32_t bb) {
    asm volatile("{\n.reg .b64 db;\n.reg .b32 tb, th;\nadd.u32 tb, %68, %69;\nmov.b32 th, %70;\nmov.b64 db, {tb, th};\n"
        "wgmma.mma_async.sync.aligned.m64n128k16.f32.bf16.bf16 {%0,%1,%2,%3,%4,%5,%6,%7,%8,%9,%10,%11,%12,%13,%14,%15,%16,%17,%18,%19,%20,%21,%22,%23,%24,%25,%26,%27,%28,%29,%30,%31,%32,%33,%34,%35,%36,%37,%38,%39,%40,%41,%42,%43,%44,%45,%46,%47,%48,%49,%50,%51,%52,%53,%54,%55,%56,%57,%58,%59,%60,%61,%62,%63}, {%64,%65,%66,%67}, db, 1, 1, 1, 1;\n}\n"
        : "+f"(d[0]),"+f"(d[1]),"+f"(d[2]),"+f"(d[3]),"+f"(d[4]),"+f"(d[5]),"+f"(d[6]),"+f"(d[7]),"+f"(d[8]),"+f"(d[9]),"+f"(d[10]),"+f"(d[11]),"+f"(d[12]),"+f"(d[13]),"+f"(d[14]),"+f"(d[15]),"+f"(d[16]),"+f"(d[17]),"+f"(d[18]),"+f"(d[19]),"+f"(d[20]),"+f"(d[21]),"+f"(d[22]),"+f"(d[23]),"+f"(d[24]),"+f"(d[25]),"+f"(d[26]),"+f"(d[27]),"+f"(d[28]),"+f"(d[29]),"+f"(d[30]),"+f"(d[31]),"+f"(d[32]),"+f"(d[33]),"+f"(d[34]),"+f"(d[35]),"+f"(d[36]),"+f"(d[37]),"+f"(d[38]),"+f"(d[39]),"+f"(d[40]),"+f"(d[41]),"+f"(d[42]),"+f"(d[43]),"+f"(d[44]),"+f"(d[45]),"+f"(d[46]),"+f"(d[47]),"+f"(d[48]),"+f"(d[49]),"+f"(d[50]),"+f"(d[51]),"+f"(d[52]),"+f"(d[53]),"+f"(d[54]),"+f"(d[55]),"+f"(d[56]),"+f"(d[57]),"+f"(d[58]),"+f"(d[59]),"+f"(d[60]),"+f"(d[61]),"+f"(d[62]),"+f"(d[63])
        : "r"(a0), "r"(a1), "r"(a2), "r"(a3), "r"(bb), "n"(BO), "n"(BH));
}
template <uint32_t BO, uint32_t BH> __device__ __forceinline__ void wg_rs128_z(float (&d)[64], uint32_t a0, uint32_t a1, uint32_t a2, uint32_t a3, uint32_t bb) {
    asm volatile("{\n.reg .b64 db;\n.reg .b32 tb, th;\nadd.u32 tb, %68, %69;\nmov.b32 th, %70;\nmov.b64 db, {tb, th};\n"
        "wgmma.mma_async.sync.aligned.m64n128k16.f32.bf16.bf16 {%0,%1,%2,%3,%4,%5,%6,%7,%8,%9,%10,%11,%12,%13,%14,%15,%16,%17,%18,%19,%20,%21,%22,%23,%24,%25,%26,%27,%28,%29,%30,%31,%32,%33,%34,%35,%36,%37,%38,%39,%40,%41,%42,%43,%44,%45,%46,%47,%48,%49,%50,%51,%52,%53,%54,%55,%56,%57,%58,%59,%60,%61,%62,%63}, {%64,%65,%66,%67}, db, 0, 1, 1, 1;\n}\n"
        : "=f"(d[0]),"=f"(d[1]),"=f"(d[2]),"=f"(d[3]),"=f"(d[4]),"=f"(d[5]),"=f"(d[6]),"=f"(d[7]),"=f"(d[8]),"=f"(d[9]),"=f"(d[10]),"=f"(d[11]),"=f"(d[12]),"=f"(d[13]),"=f"(d[14]),"=f"(d[15]),"=f"(d[16]),"=f"(d[17]),"=f"(d[18]),"=f"(d[19]),"=f"(d[20]),"=f"(d[21]),"=f"(d[22]),"=f"(d[23]),"=f"(d[24]),"=f"(d[25]),"=f"(d[26]),"=f"(d[27]),"=f"(d[28]),"=f"(d[29]),"=f"(d[30]),"=f"(d[31]),"=f"(d[32]),"=f"(d[33]),"=f"(d[34]),"=f"(d[35]),"=f"(d[36]),"=f"(d[37]),"=f"(d[38]),"=f"(d[39]),"=f"(d[40]),"=f"(d[41]),"=f"(d[42]),"=f"(d[43]),"=f"(d[44]),"=f"(d[45]),"=f"(d[46]),"=f"(d[47]),"=f"(d[48]),"=f"(d[49]),"=f"(d[50]),"=f"(d[51]),"=f"(d[52]),"=f"(d[53]),"=f"(d[54]),"=f"(d[55]),"=f"(d[56]),"=f"(d[57]),"=f"(d[58]),"=f"(d[59]),"=f"(d[60]),"=f"(d[61]),"=f"(d[62]),"=f"(d[63])
        : "r"(a0), "r"(a1), "r"(a2), "r"(a3), "r"(bb), "n"(BO), "n"(BH));
}
template <uint32_t AO, uint32_t BO, uint32_t BH> __device__ __forceinline__ void wg_ss64t(float (&d)[32], uint32_t ab, uint32_t bb) {
    asm volatile("{\n.reg .b64 da, db;\n.reg .b32 ta, tb, th, ah;\nadd.u32 ta, %32, %34;\nadd.u32 tb, %33, %35;\nmov.b32 th, %36;\nmov.b32 ah, 0x40000040;\nmov.b64 da, {ta, ah};\nmov.b64 db, {tb, th};\n"
        "wgmma.mma_async.sync.aligned.m64n64k16.f32.bf16.bf16 {%0,%1,%2,%3,%4,%5,%6,%7,%8,%9,%10,%11,%12,%13,%14,%15,%16,%17,%18,%19,%20,%21,%22,%23,%24,%25,%26,%27,%28,%29,%30,%31}, da, db, 1, 1, 1, 1, 1;\n}\n"
        : "+f"(d[0]),"+f"(d[1]),"+f"(d[2]),"+f"(d[3]),"+f"(d[4]),"+f"(d[5]),"+f"(d[6]),"+f"(d[7]),"+f"(d[8]),"+f"(d[9]),"+f"(d[10]),"+f"(d[11]),"+f"(d[12]),"+f"(d[13]),"+f"(d[14]),"+f"(d[15]),"+f"(d[16]),"+f"(d[17]),"+f"(d[18]),"+f"(d[19]),"+f"(d[20]),"+f"(d[21]),"+f"(d[22]),"+f"(d[23]),"+f"(d[24]),"+f"(d[25]),"+f"(d[26]),"+f"(d[27]),"+f"(d[28]),"+f"(d[29]),"+f"(d[30]),"+f"(d[31])
        : "r"(ab), "r"(bb), "n"(AO), "n"(BO), "n"(BH));
}
template <uint32_t AO, uint32_t BO, uint32_t BH> __device__ __forceinline__ void wg_ss64t_z(float (&d)[32], uint32_t ab, uint32_t bb) {
    asm volatile("{\n.reg .b64 da, db;\n.reg .b32 ta, tb, th, ah;\nadd.u32 ta, %32, %34;\nadd.u32 tb, %33, %35;\nmov.b32 th, %36;\nmov.b32 ah, 0x40000040;\nmov.b64 da, {ta, ah};\nmov.b64 db, {tb, th};\n"
        "wgmma.mma_async.sync.aligned.m64n64k16.f32.bf16.bf16 {%0,%1,%2,%3,%4,%5,%6,%7,%8,%9,%10,%11,%12,%13,%14,%15,%16,%17,%18,%19,%20,%21,%22,%23,%24,%25,%26,%27,%28,%29,%30,%31}, da, db, 0, 1, 1, 1, 1;\n}\n"
        : "=f"(d[0]),"=f"(d[1]),"=f"(d[2]),"=f"(d[3]),"=f"(d[4]),"=f"(d[5]),"=f"(d[6]),"=f"(d[7]),"=f"(d[8]),"=f"(d[9]),"=f"(d[10]),"=f"(d[11]),"=f"(d[12]),"=f"(d[13]),"=f"(d[14]),"=f"(d[15]),"=f"(d[16]),"=f"(d[17]),"=f"(d[18]),"=f"(d[19]),"=f"(d[20]),"=f"(d[21]),"=f"(d[22]),"=f"(d[23]),"=f"(d[24]),"=f"(d[25]),"=f"(d[26]),"=f"(d[27]),"=f"(d[28]),"=f"(d[29]),"=f"(d[30]),"=f"(d[31])
        : "r"(ab), "r"(bb), "n"(AO), "n"(BO), "n"(BH));
}
template <uint32_t AO, uint32_t BO, uint32_t BH> __device__ __forceinline__ void wg_ss8t(float (&d)[4], uint32_t ab, uint32_t bb) {
    asm volatile("{\n.reg .b64 da, db;\n.reg .b32 ta, tb, th, ah;\nadd.u32 ta, %4, %6;\nadd.u32 tb, %5, %7;\nmov.b32 th, %8;\nmov.b32 ah, 0x40000040;\nmov.b64 da, {ta, ah};\nmov.b64 db, {tb, th};\n"
        "wgmma.mma_async.sync.aligned.m64n8k16.f32.bf16.bf16 {%0,%1,%2,%3}, da, db, 1, 1, 1, 1, 0;\n}\n"
        : "+f"(d[0]),"+f"(d[1]),"+f"(d[2]),"+f"(d[3])
        : "r"(ab), "r"(bb), "n"(AO), "n"(BO), "n"(BH));
}
template <uint32_t AO, uint32_t BO, uint32_t BH> __device__ __forceinline__ void wg_ss8t_z(float (&d)[4], uint32_t ab, uint32_t bb) {
    asm volatile("{\n.reg .b64 da, db;\n.reg .b32 ta, tb, th, ah;\nadd.u32 ta, %4, %6;\nadd.u32 tb, %5, %7;\nmov.b32 th, %8;\nmov.b32 ah, 0x40000040;\nmov.b64 da, {ta, ah};\nmov.b64 db, {tb, th};\n"
        "wgmma.mma_async.sync.aligned.m64n8k16.f32.bf16.bf16 {%0,%1,%2,%3}, da, db, 0, 1, 1, 1, 0;\n}\n"
        : "=f"(d[0]),"=f"(d[1]),"=f"(d[2]),"=f"(d[3])
        : "r"(ab), "r"(bb), "n"(AO), "n"(BO), "n"(BH));
}
template <uint32_t BO, uint32_t BH> __device__ __forceinline__ void wg_rs24_z(float (&d)[12], uint32_t a0, uint32_t a1, uint32_t a2, uint32_t a3, uint32_t bb) {
    asm volatile("{\n.reg .b64 db;\n.reg .b32 tb, th;\nadd.u32 tb, %16, %17;\nmov.b32 th, %18;\nmov.b64 db, {tb, th};\n"
        "wgmma.mma_async.sync.aligned.m64n24k16.f32.bf16.bf16 {%0,%1,%2,%3,%4,%5,%6,%7,%8,%9,%10,%11}, {%12,%13,%14,%15}, db, 0, 1, 1, 0;\n}\n"
        : "=f"(d[0]),"=f"(d[1]),"=f"(d[2]),"=f"(d[3]),"=f"(d[4]),"=f"(d[5]),"=f"(d[6]),"=f"(d[7]),"=f"(d[8]),"=f"(d[9]),"=f"(d[10]),"=f"(d[11])
        : "r"(a0), "r"(a1), "r"(a2), "r"(a3), "r"(bb), "n"(BO), "n"(BH));
}

constexpr uint32_t DH128 = 64u | 0x40000000u;
constexpr uint32_t DH64 = 32u | 0x80000000u;
constexpr uint32_t LBO4K = (4096u >> 4) << 16, LBO8K = (8192u >> 4) << 16, LBO1 = 1u << 16;

template <uint32_t AO, uint32_t BO, bool SW64, bool FIRST> __device__ __forceinline__ void stage_ss(float (&acc)[64], uint32_t ab, uint32_t bb) {
    constexpr uint32_t KS = SW64 ? 64 : 128, BH = SW64 ? DH64 : DH128, B0 = BO + (SW64 ? LBO4K : LBO8K);
    wg_fence();
    if (FIRST) wg_ss128_z<AO, B0, BH>(acc, ab, bb); else wg_ss128<AO, B0, BH>(acc, ab, bb);
    wg_ss128<AO + 2, B0 + KS, BH>(acc, ab, bb);
    wg_ss128<AO + 4, B0 + 2 * KS, BH>(acc, ab, bb);
    wg_ss128<AO + 6, B0 + 3 * KS, BH>(acc, ab, bb);
    wg_commit();
}
template <uint32_t BO, bool FIRST> __device__ __forceinline__ void stage_rs(float (&acc)[64], const uint32_t (&f)[16], uint32_t bb) {
    wg_fence();
    if (FIRST) wg_rs128_z<BO + LBO8K, DH128>(acc, f[0], f[1], f[2], f[3], bb); else wg_rs128<BO + LBO8K, DH128>(acc, f[0], f[1], f[2], f[3], bb);
    wg_rs128<BO + LBO8K + 128, DH128>(acc, f[4], f[5], f[6], f[7], bb);
    wg_rs128<BO + LBO8K + 256, DH128>(acc, f[8], f[9], f[10], f[11], bb);
    wg_rs128<BO + LBO8K + 384, DH128>(acc, f[12], f[13], f[14], f[15], bb);
    wg_commit();
}

template <int N> __device__ __forceinline__ void stash(uint32_t base, uint32_t sw, const uint32_t (&f)[N]) {
#pragma unroll
    for (int t = 0; t < N / 4; t++) stsm4(base + ((sw ^ (2 * t)) << 4), f[4 * t], f[4 * t + 1], f[4 * t + 2], f[4 * t + 3]);
}

template <int V0, int V1, int N> __device__ __forceinline__ void send_frag(const uint32_t (&f)[N], uint4* p, uint32_t tag) {
#pragma unroll
    for (int v = V0; v < V1; v++) st_pkt(p + v * 32, (f[4 * v] & ~1u) | tag, f[4 * v + 1], f[4 * v + 2], f[4 * v + 3]);
}
template <int V0, int V1, int N> __device__ __forceinline__ void send_h(const uint32_t (&f)[N], uint4* p) {
#pragma unroll
    for (int v = V0; v < V1; v++) {
        const int h = v >> 1, hi = v & 1;
        asm volatile("st.global.v4.u32 [%0], {%1,%2,%3,%4};" :: "l"(p + 4 * h + 64 * hi),
                     "r"(f[8 * h + hi]), "r"(f[8 * h + 2 + hi]), "r"(f[8 * h + 4 + hi]), "r"(f[8 * h + 6 + hi]) : "memory");
    }
}
template <int O, int N, int M> __device__ __forceinline__ void pack_sub(uint32_t (&f)[N], const float (&acc)[M]) {
#pragma unroll
    for (int i = 0; i < N; i++) f[i] = keep(pack2(acc[O + 2 * i], acc[O + 2 * i + 1]));
}
template <int N> __device__ __forceinline__ void recv_issue(uint32_t (&q)[N], const uint4* p) {
#pragma unroll
    for (int v = 0; v < N / 4; v++) ld_pkt(p + v * 32, q[4 * v], q[4 * v + 1], q[4 * v + 2], q[4 * v + 3]);
}
template <int N> __device__ __forceinline__ void recv_check(uint32_t (&q)[N], const uint4* p, uint32_t tag) {
    uint32_t it = 0;
    while (true) {
        uint32_t bad = 0;
#pragma unroll
        for (int v = 0; v < N / 4; v++) bad |= q[4 * v] ^ tag;
        if (__all_sync(0xffffffffu, (bad & 1u) == 0) || ++it > SPIN_GLOBAL) break;
        recv_issue(q, p);
    }
}
}

__global__ void __launch_bounds__(384, 1)
fused_kernel(const __grid_constant__ Maps maps, const __nv_bfloat16* __restrict__ xg, const __nv_bfloat16* __restrict__ gate_w,
             const char* __restrict__ pf_qkv, const char* __restrict__ pf_g, const char* __restrict__ pf_u,
             const char* __restrict__ pf_d, const char* __restrict__ pf_o, __nv_bfloat16* __restrict__ out) {
    extern __shared__ __align__(1024) uint8_t smem_raw[];
    const uint32_t sb = (uint32_t)__cvta_generic_to_shared(smem_raw);
    const int tid = threadIdx.x, lane = tid & 31;
    const int warp = __shfl_sync(0xffffffffu, tid >> 5, 0);
    const int j = (blockIdx.x >> 1) & 7;
    const int r = (((blockIdx.x >> 4) << 1) | (blockIdx.x & 1)) ^ RX;
    const uint32_t rank = blockIdx.x & 1;

    if (warp == 0) { TSG(0, 30); TS(0, 0); }
    if (tid == 256) {
        for (int i = 0; i < 5; i++) { mbar_init(sb + B_FULL + 8 * i, 1); mbar_init(sb + B_EMPTY + 8 * i, MC ? 4 : 2); }
        for (int i = 0; i < 9; i++) mbar_init(sb + B_XFULL + 8 * i, 1);
        asm volatile("fence.mbarrier_init.release.cluster;" ::: "memory");
        mbar_expect(sb + B_XFULL, 16384);
        tma2(sb + OFF_X, &maps.x, 0, r * 128, sb + B_XFULL);
        TS2(0);
        mbar_expect(sb + B_FULL, 16384);
        tmaw3(sb + OFF_RING, &maps.kv, 64 * j, 0, 1, sb + B_FULL);
        TS2(1);
        mbar_expect(sb + B_FULL + 8, 16384);
        tmaw3(sb + OFF_RING + 16384, &maps.gu, 224 * j, 0, 0, sb + B_FULL + 8);
    } else if (tid == 288) {
        for (int i = 0; i < 3; i++) mbar_init(sb + B_HSENT + 8 * i, 8);
        for (int i = 0; i < 4; i++) { mbar_init(sb + B_EFULL + 8 * i, 1); mbar_init(sb + B_EEMPTY + 8 * i, MC ? 4 : 2); }
        mbar_init(sb + B_XFREE, 2); mbar_init(sb + B_XFREE + 8, 2); mbar_init(sb + B_XFREE + 16, 2);
        mbar_init(sb + B_AHEAD, 1); mbar_init(sb + B_PART, 1); mbar_init(sb + B_GRDY, 1); mbar_init(sb + B_KVDONE, 8); mbar_init(sb + B_KVRDY, 2);
        asm volatile("fence.mbarrier_init.release.cluster;" ::: "memory");
    } else if (warp == 10 && lane < 10) {
        asm volatile("prefetch.tensormap [%0];" :: "l"(&maps.gu + lane) : "memory");
    }
    __syncthreads();

    if (warp >= 8) {
        asm volatile("setmaxnreg.dec.sync.aligned.u32 56;");
        if (warp == 8) {
            if (lane == 0) {
                int slot = MC ? 0 : 2, ph = 1;
                uint32_t full, dst;
                if (!MC) { mbar_expect(sb + B_XFULL + 8, 16384); tma2(sb + OFF_X + 16384, &maps.x, 64, r * 128, sb + B_XFULL + 8); }
#define P_BEGIN(S, BYTES) full = sb + B_FULL + 8 * slot; dst = sb + OFF_RING + slot * 16384; \
                mbar_wait(sb + B_EMPTY + 8 * slot, ph); TS2(S); mbar_expect(full, BYTES); if (!MC || (((S) ^ rank) & 1) == 0)
#define P_END() if (++slot == 5) { slot = 0; ph ^= 1; }
                for (int s = MC ? 0 : 2; s < 16; s++) {
                    const int kb = (int)(0x7654763542312100ull >> (4 * s)) & 15;
                    P_BEGIN(s, 16384) {
                        if ((0x0DADu >> s) & 1) tmaw3(dst, &maps.kv, 64 * j, 64 * kb, 1, full);
                        else tmaw3(dst, &maps.gu, 224 * j, 64 * kb, 0, full);
                    }
                    const int xb = (int)(0x0000000765403210ull >> (4 * s)) & 15;
                    if (xb) { mbar_expect(sb + B_XFULL + 8 * xb, 16384); tma2(sb + OFF_X + xb * 16384, &maps.x, 64 * xb, r * 128, sb + B_XFULL + 8 * xb); }
                    P_END()
                }
                for (int s = 0; s < 24; s++) {
                    P_BEGIN(16 + s, 16384) {
                        if (s < 8) {
                            tmaw3(dst, &maps.q64, 0, 64 * s, 2 * j, full);
                            tmaw3(dst + 8192, &maps.gu64, 224 * j + 192, 64 * s, 0, full);
                        } else {
                            tmaw3(dst, &maps.gu, 224 * j + 64 * (s >> 3), 64 * (s & 7), 0, full);
                        }
                    }
                    P_END()
                }
                const int p = j >> 1;
#pragma unroll 1
                for (int t = 0; t < 18; t++) {
                    const int q = t >= 9, sl = (int)(0x846352107ull >> (4 * (t - 9 * q))) & 15;
                    const int u = (int)((q ? 0x432186758ull : 0x327064105ull) >> (4 * (t - 9 * q))) & 15;
                    const int cw = (j & 1) * 4 + ((p & 2) ^ ((t == 5 || t > 9) ? 0 : 2)), cc = 64 * cw;
                    if (sl < 5) {
                        full = sb + B_FULL + 8 * sl; dst = sb + OFF_RING + sl * 16384;
                        mbar_wait(sb + B_EMPTY + 8 * sl, q ^ 1);
                    } else {
                        full = sb + B_EFULL + 8 * (sl - 5); dst = sb + OFF_X + (sl == 7 ? 8 : sl == 8 ? 7 : sl) * 16384;
                        mbar_wait(sb + B_EEMPTY + 8 * (sl - 5), q);
                    }
                    TS2(40 + t);
                    mbar_expect(full, 16384);
                    if (!MC || ((t ^ rank) & 1) == 0) {
                        if (u == 4) {
                            tmaw5(dst, &maps.wdph, cc, 14 * p + 6, full); tmaw5(dst + 4096, &maps.wdph, cc, 14 * p + 13, full);
                            tmaw5(dst + 8192, &maps.wdph, cc + 64, 14 * p + 6, full); tmaw5(dst + 12288, &maps.wdph, cc + 64, 14 * p + 13, full);
                        } else if (u > 4) {
                            const int js = u > 6 ? j ^ 1 : j;
                            tmaw3(dst, (u & 1) ? &maps.wow : &maps.wdw, 0, (u & 1) ? 64 * js : 224 * js + 128, cw, full);
                        } else {
                            const int g = 14 * p + 7 * (u & 1) + (u & 2);
                            tmaw5(dst, &maps.wdp, cc, g, full); tmaw5(dst + 8192, &maps.wdp, cc + 64, g, full);
                        }
                    }
                }
            }
        } else if (warp < 11) {
            const int hx = warp - 9;
            uint32_t epoch;
            asm volatile("ld.relaxed.gpu.global.u32 %0, [%1];" : "=r"(epoch) : "l"(g_epoch + blockIdx.x) : "memory");
            {
                const uint4* xr = (const uint4*)(xg + (size_t)(r * 128 + j * 16 + hx * 8) * kD) + lane;
                const uint4 wa = __ldg((const uint4*)gate_w + lane), wb = __ldg((const uint4*)gate_w + 32 + lane);
                const uint32_t tag = (epoch + 1) & 1;
                uint4* gp = g_gx + r * 32;
                if (lane < 2) st_pkt(gp + j * 4 + hx * 2 + lane, tag ^ 1, 0, 0, 0);
                float s[8];
#pragma unroll
                for (int i0 = 0; i0 < 8; i0 += 4) {
                    uint4 va[4], vb[4];
#pragma unroll
                    for (int i = 0; i < 4; i++) { va[i] = __ldg(xr + (i0 + i) * 64); vb[i] = __ldg(xr + (i0 + i) * 64 + 32); }
#pragma unroll
                    for (int i = 0; i < 4; i++) {
                        float t0 = bf_lo(va[i].x) * bf_lo(wa.x), t1 = bf_hi(va[i].x) * bf_hi(wa.x);
                        t0 = fmaf(bf_lo(va[i].y), bf_lo(wa.y), t0); t1 = fmaf(bf_hi(va[i].y), bf_hi(wa.y), t1);
                        t0 = fmaf(bf_lo(va[i].z), bf_lo(wa.z), t0); t1 = fmaf(bf_hi(va[i].z), bf_hi(wa.z), t1);
                        t0 = fmaf(bf_lo(va[i].w), bf_lo(wa.w), t0); t1 = fmaf(bf_hi(va[i].w), bf_hi(wa.w), t1);
                        t0 = fmaf(bf_lo(vb[i].x), bf_lo(wb.x), t0); t1 = fmaf(bf_hi(vb[i].x), bf_hi(wb.x), t1);
                        t0 = fmaf(bf_lo(vb[i].y), bf_lo(wb.y), t0); t1 = fmaf(bf_hi(vb[i].y), bf_hi(wb.y), t1);
                        t0 = fmaf(bf_lo(vb[i].z), bf_lo(wb.z), t0); t1 = fmaf(bf_hi(vb[i].z), bf_hi(wb.z), t1);
                        t0 = fmaf(bf_lo(vb[i].w), bf_lo(wb.w), t0); t1 = fmaf(bf_hi(vb[i].w), bf_hi(wb.w), t1);
                        s[i0 + i] = t0 + t1;
                    }
                }
#pragma unroll
                for (int i = 0; i < 8; i++) {
#pragma unroll
                    for (int o = 16; o; o >>= 1) s[i] += __shfl_xor_sync(0xffffffffu, s[i], o);
                    s[i] = 1.f / (1.f + __expf(-s[i]));
                }
                if (lane < 2) {
                    const float v0 = lane ? s[4] : s[0], v1 = lane ? s[5] : s[1], v2 = lane ? s[6] : s[2], v3 = lane ? s[7] : s[3];
                    st_pkt(gp + j * 4 + hx * 2 + lane, (__float_as_uint(v0) & ~1u) | tag, __float_as_uint(v1), __float_as_uint(v2), __float_as_uint(v3));
                }
                if (hx == 1) {
                    asm volatile("st.shared.u32 [%0], %1;" :: "r"(sb + OFF_ONES + lane * 4), "r"(0x3f803f80u) : "memory");
                    asm volatile("fence.proxy.async.shared::cta;" ::: "memory");
                }
                asm volatile("bar.sync 3, 96;" ::: "memory");
                if (hx == 0) {
                    uint32_t q[4];
                    recv_issue(q, gp + lane);
                    recv_check(q, gp + lane, tag);
                    asm volatile("st.shared.v4.u32 [%0], {%1,%2,%3,%4};" :: "r"(sb + OFF_G + lane * 16), "r"(q[0]), "r"(q[1]), "r"(q[2]), "r"(q[3]) : "memory");
                    if (lane == 0) {
                        asm volatile("st.shared.u32 [%0], %1;" :: "r"(sb + OFF_EPOCH), "r"(epoch) : "memory");
                        g_epoch[blockIdx.x] = epoch + 1;
                    }
                    __syncwarp();
                    if (lane == 0) mbar_arrive(sb + B_GRDY);
                } else {
                    if (r == 0) {
                        float4* zp = (float4*)(g_kvacc + (((epoch & 1) ^ 1) * 8 + j) * 4 * 272);
                        for (int i = lane; i < 272; i += 32) zp[i] = make_float4(0.f, 0.f, 0.f, 0.f);
                    }
                }
            }
            TS(2 + hx, 1);
#define PUBLISH_H(B) do { mbar_wait(sb + B_HSENT + 8 * (B), 0); if (lane == 0) { \
                asm volatile("st.release.gpu.global.u32 [%0], %1;" :: "l"(g_hflag + (r * 8 + j) * 8 + (B)), "r"(epoch + 1) : "memory"); } __syncwarp(); } while (0)
            if (hx == 1) {
#pragma unroll 1
                for (int b = 0; b < 3; b++) { PUBLISH_H(b); TS(3, 5 + b); }
            } else {
                const float* accp = g_kvacc + ((epoch & 1) * 8 + j) * 4 * 272;
                unsigned* cnt = g_kvcnt + j * 32;
                mbar_wait(sb + B_KVDONE, 0);
                TS(2, 5);
                if (lane == 0) asm volatile("red.release.gpu.global.add.u32 [%0], 1;" :: "l"(cnt) : "memory");
                __syncwarp();
                TS(2, 2);
                {
                    const unsigned target = 16u * (epoch + 1);
                    uint32_t it = 0, v;
                    do {
                        asm volatile("ld.acquire.gpu.global.u32 %0, [%1];" : "=r"(v) : "l"(cnt) : "memory");
                    } while ((int)(v - target) < 0 && ++it < SPIN_GLOBAL);
                }
                TS(2, 3);
#pragma unroll
                for (int h = 0; h < 4; h++) {
                    const float4 d0 = __ldcg((const float4*)(accp + h * 272) + lane);
                    const float4 d1 = __ldcg((const float4*)(accp + h * 272 + 128) + lane);
                    const float2 z0 = __ldcg((const float2*)(accp + h * 272 + 256) + (lane & 3));
                    const float2 z1 = __ldcg((const float2*)(accp + h * 272 + 264) + (lane & 3));
                    const uint32_t ba = sb + OFF_STG + h * 768 + lane * 4;
                    asm volatile("st.shared.u32 [%0], %1;" :: "r"(ba), "r"(pack2(d0.x, d0.y)) : "memory");
                    asm volatile("st.shared.u32 [%0], %1;" :: "r"(ba + 128), "r"(pack2(d1.x, d1.y)) : "memory");
                    asm volatile("st.shared.u32 [%0], %1;" :: "r"(ba + 256), "r"(pack2(d0.z, d0.w)) : "memory");
                    asm volatile("st.shared.u32 [%0], %1;" :: "r"(ba + 384), "r"(pack2(d1.z, d1.w)) : "memory");
                    asm volatile("st.shared.u32 [%0], %1;" :: "r"(ba + 512), "r"(pack2(z0.x, z0.y)) : "memory");
                    asm volatile("st.shared.u32 [%0], %1;" :: "r"(ba + 640), "r"(pack2(z1.x, z1.y)) : "memory");
                }
                asm volatile("fence.proxy.async.shared::cta;" ::: "memory");
                __syncwarp();
                if (lane == 0) mbar_arrive(sb + B_KVRDY);
                TS(2, 4);
            }
        } else {
            uint32_t epoch;
            asm volatile("ld.relaxed.gpu.global.u32 %0, [%1];" : "=r"(epoch) : "l"(g_epoch + blockIdx.x) : "memory");
            asm volatile("bar.arrive 3, 96;" :: "r"(epoch) : "memory");
            const int b = blockIdx.x, p = j >> 1;
            mbar_wait(sb + B_XFULL, 0);
#pragma unroll 1
            for (int kb = 1; kb < 8; kb++) {
                mbar_wait(sb + B_XFULL + 8 * kb, 0);
                const char* base = kb < 3 ? pf_g : kb < 5 ? pf_u : kb == 5 ? pf_qkv : pf_d;
                const int off = kb == 5 ? b * 12288 : b * 14336 + ((kb < 5 ? kb - 1 : kb) & 1) * 7168;
                if (kb == 5) {
                    asm volatile("prefetch.global.L2 [%0];" :: "l"(base + off + (lane >> 3) * 3072 + (lane & 7) * 128));
                } else {
                    asm volatile("prefetch.global.L2 [%0];" :: "l"(base + off + lane * 128));
                    if (lane < 24) asm volatile("prefetch.global.L2 [%0];" :: "l"(base + off + 4096 + lane * 128));
                }
                if (kb == 7) asm volatile("prefetch.global.L2 [%0];" :: "l"(pf_o + b * 4096 + lane * 128));
            }
            {
                uint4* mb = g_part + (size_t)(r * 2 + (j & 1)) * 16384 + (((p ^ 1) * 4 + p) << 10) + lane;
#pragma unroll 1
                for (int i = 0; i < 32; i++) { st_pkt(mb + i * 32, epoch & 1, 0, 0, 0); __nanosleep(40); }
                __syncwarp();
                if (lane == 0) mbar_arrive(sb + B_KVRDY);
            }
            {
                const uint32_t want = epoch + 1;
                const int hrow = (r * 4 + p) * 5 * 128;
                const unsigned* fl = g_hflag + (r * 8 + (j & 6)) * 8 + (lane & 15);
                uint32_t it = 0;
                int i = 0;
                mbar_wait(sb + B_HSENT + 8, 0);
#pragma unroll 1
                while (i < 3 && ++it < SPIN_GLOBAL) {
                    uint32_t v;
                    asm volatile("ld.acquire.gpu.global.u32 %0, [%1];" : "=r"(v) : "l"(fl) : "memory");
                    const uint32_t rdy = __ballot_sync(0xffffffffu, v == want);
#pragma unroll 1
                    while (i < 3 && ((rdy >> i) & 0x101u) == 0x101u) {
                        if (i < 2) mbar_wait(sb + B_XFREE + 8 * i, 0);
                        if (lane == 0) {
                            const int pc = (6 - 2 * i) % 6;
                            asm volatile("fence.proxy.async.global;" ::: "memory");
                            TS2(140 + i);
                            mbar_expect(sb + B_XFULL + 8 * pc, i != 1 ? 32768 : 16384);
                            tma2(sb + OFF_X + pc * 16384, i != 1 ? &maps.hx2 : &maps.hx, 0, hrow + pc * 128, sb + B_XFULL + 8 * pc);
                        }
                        i++;
                    }
                }
            }
        }
    } else {
        asm volatile("setmaxnreg.inc.sync.aligned.u32 224;");
        const int wg = warp >> 2;
        const bool elect = (tid & 127) == 0;
        const uint32_t sbd = (sb & 0x3FFFFu) >> 4, xlo = (sbd + wg * 512) | LBO1;
        auto release = [&](uint32_t bar) {
            if (elect) {
                mbar_arrive(sb + bar);
            }
        };
#define S_SL(S) ((S) < 40 ? (S) % 5 : (int)((0x846352107ull >> (4 * (((S) - 40) % 9))) & 15))
#define S_WAIT(S) do { mbar_wait(sb + (S_SL(S) < 5 ? B_FULL + 8 * S_SL(S) : B_EFULL + 8 * (S_SL(S) - 5)), (S) < 40 ? ((S) / 5) & 1 : (S) >= 49); \
            if (PROF && tid == 0) TS2(64 + (S)); } while (0)
#define S_B(S) (S_SL(S) < 5 ? OFF_RING / 16 + S_SL(S) * 1024 : (S_SL(S) == 7 ? 8 : S_SL(S) == 8 ? 7 : S_SL(S)) * 1024)
#define S_REL(S) do { if ((S) < 49) release(S_SL(S) < 5 ? B_EMPTY + 8 * S_SL(S) : B_EEMPTY + 8 * (S_SL(S) - 5)); } while (0)
#define G1(S, acc, SW, KB) stage_ss<(KB) * 1024, S_B(S), SW, (KB) == 0>(acc, xlo, sbd)
#define RET(S) do { S_WAIT((S) + 1); wg_wait<1>(); S_REL((S) - 1); } while (0)
#define RET2(S) do { S_WAIT((S) + 1); wg_wait<2>(); S_REL((S) - 1); } while (0)
#define SCHED() mbar_wait(sb + B_XFULL + 8 * 7, 0)
#define A2_SYNC() do { asm volatile("fence.proxy.async.shared::cta;" ::: "memory"); asm volatile("bar.sync %0, 128;" :: "r"(wg + 1) : "memory"); } while (0)
#define H_EPI(acc, F, I0, I1, OG, OU) _Pragma("unroll") for (int i = (I0); i < (I1); i++) \
            F[i] = keep(hmul2(pack2(acc[(OG) + 2 * i] * acc[(OU) + 2 * i], acc[(OG) + 2 * i + 1] * acc[(OU) + 2 * i + 1]), (i & 1) ? m_hi : m_lo))
#define PHI(acc, F, I0, I1) _Pragma("unroll") for (int i = (I0); i < (I1); i++) F[i] = keep(phi2(acc[2 * i], acc[2 * i + 1]))

        float a0[64], b0[64], a1[64], a2_[64], a3[64];
        mbar_wait(sb + B_XFULL, 0);
#define X_WAIT(KB) do { mbar_wait(sb + B_XFULL + 8 * (KB), 0); if (PROF && tid == 0) TS2(128 + (KB)); } while (0)
        S_WAIT(0); G1(0, b0, false, 0);
        if ((warp & 3) == 0) TS(wg, 1);
        S_WAIT(1); G1(1, a0, false, 0); RET(1);
        X_WAIT(1); G1(2, b0, false, 1); RET(2);
        X_WAIT(2); G1(3, b0, false, 2); RET(3);
        G1(4, a0, false, 1); RET(4);
        X_WAIT(3); G1(5, b0, false, 3); RET(5);
        G1(6, a0, false, 2); RET(6);
        X_WAIT(4); G1(7, b0, false, 4); RET(7);
        X_WAIT(5); G1(8, b0, false, 5); RET(8);
        G1(9, a0, false, 3); RET(9);
        X_WAIT(6); G1(10, b0, false, 6); RET(10);
        X_WAIT(7); G1(11, b0, false, 7); RET(11);
        G1(12, a0, false, 4);
        const uint32_t lrow = ((lane & 7) + 8 * ((lane >> 3) & 1)) * 128;
        const uint32_t srow = (warp & 3) * 2048 + lrow;
        const uint32_t ssw = (lane >> 4) ^ (lane & 7);
        uint4* const hsend = g_hx + (size_t)((r * 4 + (j >> 1)) * 5 + (j & 1)) * 1024 + warp * 128 + (lane >> 2) * 8 + (lane & 3);
#define SENT_H(B) do { __syncwarp(); if (lane == 0) mbar_arrive(sb + B_HSENT + 8 * (B)); } while (0)
        RET(12);
        pin(b0);
        uint32_t fh0[16], fh1[16], fh2[16], fh3[8], fo[16], pk[16], pv[16];
        float kv[32], zs[4];
        const uint32_t stg = sb + OFF_STG + wg * 8192, stl = stg + (warp & 1) * 2048 + lrow;
#define KV_ROUND(Z) do { A2_SYNC(); wg_fence(); \
            wg_ss64t##Z<8192 + 256, 8192, DH128>(kv, xlo, xlo); wg_ss64t<8192 + 384, 8192 + 128, DH128>(kv, xlo, xlo); \
            wg_ss8t##Z<8192, OFF_ONES / 16, 0>(zs, xlo, sbd); wg_ss8t<8192 + 128, OFF_ONES / 16, 0>(zs, xlo, sbd); wg_commit(); } while (0)
        G1(13, a0, false, 5); SCHED(); pack_sub<32>(pv, b0); PHI(b0, pk, 0, 4); RET(13);
        G1(14, a0, false, 6); SCHED(); if (!(warp & 2)) stash<16>(stl + 4096, ssw, pv); PHI(b0, pk, 4, 10); RET(14);
        G1(15, a0, false, 7); SCHED(); PHI(b0, pk, 10, 16); RET(15);
        if ((warp & 3) == 0) TS(wg, 2);

        G1(16, a1, true, 0); SCHED(); if (!(warp & 2)) stash<16>(stl, ssw, pk);
        mbar_wait(sb + B_GRDY, 0);
        float g_lo, g_hi;
        uint32_t tag;
        {
            const uint32_t ga = sb + OFF_G + (warp * 16 + (lane >> 2)) * 4;
            asm volatile("ld.shared.f32 %0, [%1];" : "=f"(g_lo) : "r"(ga) : "memory");
            asm volatile("ld.shared.f32 %0, [%1];" : "=f"(g_hi) : "r"(ga + 32) : "memory");
            asm volatile("ld.shared.u32 %0, [%1];" : "=r"(tag) : "r"(sb + OFF_EPOCH) : "memory");
        }
        float* const kvp = g_kvacc + (((tag & 1) * 8 + j) * 4 + (warp & 3)) * 272;
        tag = (tag + 1) & 1;
        const uint32_t m_lo = pack2(1.f - g_lo, 1.f - g_lo), m_hi = pack2(1.f - g_hi, 1.f - g_hi);
        RET(16);
        pin(a0);
        G1(17, a1, true, 1); SCHED(); H_EPI(a0, fh0, 0, 16, 0, 32); RET(17);
        G1(18, a1, true, 2); KV_ROUND(_z); RET2(18);
        G1(19, a1, true, 3); SCHED(); send_h<0, 1>(fh0, hsend); RET(19);
        G1(20, a1, true, 4); SCHED(); if (warp & 2) { stash<16>(stl, ssw, pk); stash<16>(stl + 4096, ssw, pv); } RET(20);
        G1(21, a1, true, 5); KV_ROUND(); RET2(21);
        G1(22, a1, true, 6); RET(22);
        pin(kv); pin(zs);
        G1(23, a1, true, 7); SCHED();
#define KV_RED(W) do { asm volatile("red.global.add.v4.f32 [%0], {%1,%2,%3,%4};" :: "l"(kvp + lane * 4), "f"(kv[8 * W]), "f"(kv[8 * W + 1]), "f"(kv[8 * W + 2]), "f"(kv[8 * W + 3]) : "memory"); \
                       asm volatile("red.global.add.v4.f32 [%0], {%1,%2,%3,%4};" :: "l"(kvp + 128 + lane * 4), "f"(kv[8 * W + 4]), "f"(kv[8 * W + 5]), "f"(kv[8 * W + 6]), "f"(kv[8 * W + 7]) : "memory"); } while (0)
        if ((warp & 3) == 0) KV_RED(0); else if ((warp & 3) == 1) KV_RED(1); else if ((warp & 3) == 2) KV_RED(2); else KV_RED(3);
        if ((lane & 3) == 0) {
            asm volatile("red.global.add.f32 [%0], %1;" :: "l"(kvp + 256 + (lane >> 2)), "f"(zs[0]) : "memory");
            asm volatile("red.global.add.f32 [%0], %1;" :: "l"(kvp + 264 + (lane >> 2)), "f"(zs[2]) : "memory");
        }
        __syncwarp();
        if (lane == 0) mbar_arrive(sb + B_KVDONE);
        RET(23);
        if ((warp & 3) == 0) TS(wg, 3);

        G1(24, a2_, false, 0); SCHED(); send_h<1, 2>(fh0, hsend); RET(24);
        pin(a1);
        G1(25, a2_, false, 1); SCHED(); send_h<2, 3>(fh0, hsend); H_EPI(a1, fh3, 0, 8, 32, 48); RET(25);
        G1(26, a2_, false, 2); SCHED(); send_h<3, 4>(fh0, hsend); SENT_H(0); PHI(a1, fo, 0, 4); RET(26);
        G1(27, a2_, false, 3); SCHED(); send_h<0, 1>(fh3, hsend + 4 * 1024 - (j & 1) * 1020); PHI(a1, fo, 4, 8); RET(27);
        G1(28, a2_, false, 4); SCHED(); send_h<1, 2>(fh3, hsend + 4 * 1024 - (j & 1) * 1020); SENT_H(1); PHI(a1, fo, 8, 12); RET(28);
        G1(29, a2_, false, 5); SCHED(); PHI(a1, fo, 12, 16); RET(29);
        G1(30, a2_, false, 6); RET(30);
        G1(31, a2_, false, 7); RET(31);
        if ((warp & 3) == 0) TS(wg, 4);

        float on[4][12];
#define O_SCALE(h) do { const float s_lo = __fdividef(g_lo, on[h][8] + 1e-6f), s_hi = __fdividef(g_hi, on[h][10] + 1e-6f); \
            const uint32_t sl_ = pack2(s_lo, s_lo), sh_ = pack2(s_hi, s_hi); \
            fo[4 * h] = keep(hmul2(pack2(on[h][0], on[h][1]), sl_)); fo[4 * h + 1] = keep(hmul2(pack2(on[h][2], on[h][3]), sh_)); \
            fo[4 * h + 2] = keep(hmul2(pack2(on[h][4], on[h][5]), sl_)); fo[4 * h + 3] = keep(hmul2(pack2(on[h][6], on[h][7]), sh_)); } while (0)
        uint4* const lsend = g_lx + (size_t)(r * 8 + j) * 2048 + warp * 128 + lane;
        const uint4* const lrecv = g_lx + (size_t)(r * 8 + (j ^ 1)) * 2048 + warp * 128 + lane;
        G1(32, a3, false, 0); RET(32);
        pin(a2_);
        G1(33, a3, false, 1); SCHED(); H_EPI(a2_, fh1, 0, 16, 0, 32); send_h<0, 1>(fh1, hsend + 2 * 1024); RET(33);
        G1(34, a3, false, 2); SCHED(); send_h<1, 3>(fh1, hsend + 2 * 1024); RET(34);
        if (elect) mbar_arrive(sb + B_XFREE);
        G1(35, a3, false, 3); SCHED(); send_h<3, 4>(fh1, hsend + 2 * 1024); SENT_H(2);
        if ((warp & 3) == 0) TS(wg, 5);
        mbar_wait(sb + B_KVRDY, 0);
        if ((warp & 3) == 0) TS(wg, 6);
        wg_fence();
#define O_MMA(h) wg_rs24_z<OFF_STG / 16 + (h) * 48 + (8u << 16), 16>(on[h], fo[4 * (h)], fo[4 * (h) + 1], fo[4 * (h) + 2], fo[4 * (h) + 3], sbd)
        O_MMA(0); O_MMA(1); O_MMA(2); O_MMA(3);
        wg_commit();
        RET2(35);
        G1(36, a3, false, 4); RET(36);
        pin(on[0]); pin(on[1]); pin(on[2]); pin(on[3]);
        release(B_EEMPTY + 16);
        G1(37, a3, false, 5); SCHED(); O_SCALE(0); O_SCALE(1); O_SCALE(2); O_SCALE(3); RET(37);
        if (elect) mbar_arrive(sb + B_XFREE + 8);
        G1(38, a3, false, 6); SCHED(); send_frag<0, 2>(fo, lsend, tag); RET(38);
        release(B_EEMPTY);
        G1(39, a3, false, 7); SCHED(); send_frag<2, 4>(fo, lsend, tag); RET(39);
        release(B_EEMPTY + 8);
        if ((warp & 3) == 0) TS(wg, 7);

#define G2S(S, acc, U) stage_ss<(U) * 1024, S_B(S), false, (S) == 45>(acc, xlo, sbd)
#define G2R(S, acc, F) stage_rs<S_B(S), (S) == 40>(acc, F, sbd)
#define H_WAIT(P) do { mbar_wait(sb + B_XFULL + 8 * (P), 1); if (PROF && tid == 0) TS2(150 + (P)); } while (0)
        const int p = j >> 1, pw = (p & 2) ^ 2;
        const bool own = wg == (p & 1);
        uint4* const pbase = g_part + (size_t)(r * 2 + (j & 1)) * 16384 + (warp & 3) * 256 + lane;

        float p1[64], p2[64];
        uint32_t po[16], ph2[16];
        G2R(40, p1, fo); RET(40);
        release(B_EEMPTY + 24);
        pin(a3);
        H_WAIT(0); G2S(41, p1, 0); SCHED(); H_EPI(a3, fh2, 0, 16, 0, 32); send_frag<0, 2>(fh2, lsend + 1024, tag); RET(41);
        G2S(42, p1, 1); SCHED(); recv_issue(po, lrecv); send_frag<2, 4>(fh2, lsend + 1024, tag); RET(42);
        H_WAIT(4); G2S(43, p1, 4); RET(43);
        G2R(44, p1, fh2); RET(44);
        G2S(45, p2, 0); SCHED(); if (!(EXPT & 2)) recv_check(po, lrecv, tag); recv_issue(ph2, lrecv + 1024); RET(45);
        G2R(46, p1, po); RET(46);
        H_WAIT(2); G2S(47, p1, 2); RET(47);
        G2S(48, p1, 3); SCHED(); if (!(EXPT & 2)) recv_check(ph2, lrecv + 1024, tag); RET(48);
        G2R(49, p1, ph2); RET(49);
        if ((warp & 3) == 0) TS(wg, 8);
        uint32_t sp[32], qa[32], qb[32];
        uint4* const s1 = pbase + (((pw + wg) * 4 + p) << 10);
        G2R(50, p2, fo); RET(50);
        pin(p1);
        G2R(51, p2, po); SCHED(); pack_sub<0>(sp, p1); send_frag<0, 2>(sp, s1, tag); RET(51);
        G2R(52, p2, fh2); SCHED(); send_frag<2, 5>(sp, s1, tag); RET(52);
        if (elect) mbar_arrive(sb + B_XFREE + 16);
        G2R(53, p2, ph2); SCHED(); send_frag<5, 8>(sp, s1, tag); RET(53);
        const uint4* ra = pbase + ((p * 4 + pw) << 10);
        const uint4* rc = pbase + ((p * 4 + (p ^ 1)) << 10);
        if (own) mbar_wait(sb + B_AHEAD, 0);
        G2S(54, p2, 1); RET(54);
        G2S(55, p2, 2); RET(55);
        G2S(56, p2, 3); RET(56);
        G2S(57, p2, 4); SCHED();
        if ((warp & 3) == 0) TS(wg, 9);
#define PART_COPY() do { mbar_wait(sb + B_XFREE + 16, 0); mbar_expect(sb + B_PART, 32768); \
            asm volatile("cp.async.bulk.shared::cluster.global.mbarrier::complete_tx::bytes [%0], [%1], %2, [%3];" \
                         :: "r"(sb + OFF_RING), "l"(ra), "r"(32768), "r"(sb + B_PART) : "memory"); } while (0)
        if (!own && elect) mbar_arrive(sb + B_AHEAD);
        wg_wait<0>();
        pin(p2);
        if ((warp & 3) == 0) TS(wg, 11);
        if (!own) {
            if (COPY_AT == 0 && elect) PART_COPY();
            pack_sub<0>(sp, p2);
            if (COPY_AT == 1 && elect) PART_COPY();
            send_frag<0, 4>(sp, pbase + (((p ^ 1) * 4 + p) << 10), tag);
            if (COPY_AT == 2 && elect) PART_COPY();
            send_frag<4, 8>(sp, pbase + (((p ^ 1) * 4 + p) << 10), tag);
            if (COPY_AT == 3 && elect) PART_COPY();
        } else {
            recv_issue(sp, rc);
            uint32_t f0[16], f1[16];
            pack_sub<0>(f0, p2); pack_sub<32>(f1, p2);
            mbar_wait(sb + B_PART, 0);
            if ((warp & 3) == 0) TS(wg, 10);
            const uint32_t pa = sb + OFF_RING + (warp & 3) * 4096 + lane * 16;
#pragma unroll
            for (int v = 0; v < 8; v++) {
                asm volatile("ld.shared.v4.u32 {%0,%1,%2,%3}, [%4];" : "=r"(qa[4 * v]), "=r"(qa[4 * v + 1]), "=r"(qa[4 * v + 2]), "=r"(qa[4 * v + 3]) : "r"(pa + v * 512) : "memory");
                asm volatile("ld.shared.v4.u32 {%0,%1,%2,%3}, [%4];" : "=r"(qb[4 * v]), "=r"(qb[4 * v + 1]), "=r"(qb[4 * v + 2]), "=r"(qb[4 * v + 3]) : "r"(pa + 16384 + v * 512) : "memory");
            }
            recv_check(qa, ra, tag); recv_check(qb, ra + 1024, tag);
#pragma unroll
            for (int i = 0; i < 32; i++) qa[i] = keep(hadd2(qa[i], qb[i]));
            if ((warp & 3) == 0) TS(wg, 12);
            recv_check(sp, rc, tag);
            if ((warp & 3) == 0) TS(wg, 13);
#pragma unroll
            for (int i = 0; i < 16; i++) { f0[i] = hadd2(hadd2(f0[i], sp[i]), qa[i]); f1[i] = hadd2(hadd2(f1[i], sp[16 + i]), qa[16 + i]); }
            const uint32_t slab = sb + OFF_X + 2 * 16384 + wg * 8192;
            stash<16>(slab + srow, ssw, f0); stash<16>(slab + 16384 + srow, ssw, f1);
            __syncwarp();
            __nv_bfloat16* op = out + (size_t)(r * 128 + warp * 16 + (lane >> 4)) * kD + (j & 1) * 256 + (p & 2) * 64 + (lane & 15) * 8;
#pragma unroll
            for (int i = 0; i < 8; i++) {
                const int row = i * 2 + (lane >> 4);
                uint4 v;
                asm volatile("ld.shared.v4.u32 {%0,%1,%2,%3}, [%4];" : "=r"(v.x), "=r"(v.y), "=r"(v.z), "=r"(v.w)
                             : "r"(slab + (lane & 8) * 2048 + ((warp & 3) * 16 + row) * 128 + (((lane & 7) ^ (row & 7)) << 4)) : "memory");
                *(uint4*)(op + i * 2 * kD) = v;
            }
        }
        if ((warp & 3) == 0) { TS(wg, 14); TSG(wg, 31); }
    }
}

typedef CUresult (*EncodeFn)(CUtensorMap*, CUtensorMapDataType, cuuint32_t, void*, const cuuint64_t*, const cuuint64_t*, const cuuint32_t*,
                             const cuuint32_t*, CUtensorMapInterleave, CUtensorMapSwizzle, CUtensorMapL2promotion, CUtensorMapFloatOOBfill);

static void encode(EncodeFn fn, CUtensorMap* m, int rank, const void* base, const cuuint64_t (&gd)[5], const cuuint64_t (&gs)[4],
                   const cuuint32_t (&bd)[5], CUtensorMapSwizzle sw) {
    cuuint32_t es[5] = {1, 1, 1, 1, 1};
    fn(m, CU_TENSOR_MAP_DATA_TYPE_BFLOAT16, rank, const_cast<void*>(base), gd, gs, bd, es, CU_TENSOR_MAP_INTERLEAVE_NONE, sw,
       CU_TENSOR_MAP_L2_PROMOTION_L2_128B, CU_TENSOR_MAP_FLOAT_OOB_FILL_NONE);
}

extern "C" void kernel_launch(void* const* d_in, const int* in_sizes, int n_in, void* d_out, int out_size) {
    const char* x = (const char*)d_in[0];
    const char* wqkv = (const char*)d_in[1];
    const char* wo = (const char*)d_in[2];
    const char* wg = (const char*)d_in[4];
    const char* wu = (const char*)d_in[5];
    const char* wd = (const char*)d_in[6];
    void* fnp = nullptr;
    cudaDriverEntryPointQueryResult qr;
    cudaGetDriverEntryPoint("cuTensorMapEncodeTiled", &fnp, cudaEnableDefault, &qr);
    EncodeFn fn = (EncodeFn)fnp;
    Maps maps;
    const char* lo = wg < wu ? wg : wu;
    const uint64_t diff = wg < wu ? (uint64_t)(wu - wg) : (uint64_t)(wg - wu);
    const CUtensorMapSwizzle S128 = CU_TENSOR_MAP_SWIZZLE_128B, S64 = CU_TENSOR_MAP_SWIZZLE_64B;
    encode(fn, &maps.x, 2, x, {512, 2048, 1, 1}, {1024, 0, 0}, {64, 128, 1, 1}, S128);
    encode(fn, &maps.gu, 3, lo, {1792, 512, 2, 1}, {3584, diff, 0}, {64, 64, 2, 1}, S128);
    encode(fn, &maps.kv, 3, wqkv, {512, 512, 3, 1}, {3072, 1024, 0}, {64, 64, 2, 1}, S128);
    encode(fn, &maps.q64, 3, wqkv, {32, 512, 48, 1}, {3072, 64, 0}, {32, 64, 2, 1}, S64);
    encode(fn, &maps.gu64, 3, lo, {1792, 512, 2, 1}, {3584, diff, 0}, {32, 64, 2, 1}, S64);
    encode(fn, &maps.wdw, 3, wd, {64, 1792, 8, 1}, {1024, 128, 0}, {64, 64, 2, 1}, S128);
    encode(fn, &maps.wow, 3, wo, {64, 512, 8}, {1024, 128}, {64, 64, 2}, S128);
    encode(fn, &maps.wdp, 5, wd, {512, 2, 4, 4, 56}, {1024, 8192, 2048, 32768}, {64, 2, 4, 4, 2}, S128);
    encode(fn, &maps.wdph, 5, wd, {512, 2, 4, 4, 56}, {1024, 8192, 2048, 32768}, {64, 2, 4, 4, 1}, S128);
    void* hx = nullptr;
    cudaGetSymbolAddress(&hx, g_hx);
    encode(fn, &maps.hx, 2, hx, {64, 16 * 4 * 5 * 128}, {128}, {64, 128}, S128);
    encode(fn, &maps.hx2, 2, hx, {64, 16 * 4 * 5 * 128}, {128}, {64, 256}, S128);
    cudaFuncSetAttribute(fused_kernel, cudaFuncAttributeMaxDynamicSharedMemorySize, SMEM_BYTES);
    cudaLaunchConfig_t cfg = {};
    cfg.gridDim = dim3(128);
    cfg.blockDim = dim3(384);
    cfg.dynamicSmemBytes = SMEM_BYTES;
    cfg.stream = cudaStreamPerThread;
    cudaLaunchAttribute at[1];
    at[0].id = cudaLaunchAttributeClusterDimension;
    at[0].val.clusterDim.x = 2; at[0].val.clusterDim.y = 1; at[0].val.clusterDim.z = 1;
    cfg.attrs = at;
    cfg.numAttrs = MC ? 1 : 0;
    cudaLaunchKernelEx(&cfg, fused_kernel, maps, (const __nv_bfloat16*)d_in[0], (const __nv_bfloat16*)d_in[7], wqkv, wg, wu, wd, wo, (__nv_bfloat16*)d_out);
}
```

```cpp
#include <cuda_runtime.h>
#include <cuda.h>
#include <cuda_bf16.h>
#include <stdint.h>

#define MC 0
#define PFMODE 1
#define PHI_SAT 0
#define EXPT 0
#define COPY_AT 0
#define RX 0
#define PROF 0

namespace {

constexpr int kD = 512;
constexpr uint32_t OFF_X = 0, OFF_STG = 131072, OFF_RING = 147456, OFF_MISC = 229376;
constexpr uint32_t B_FULL = OFF_MISC, B_EMPTY = OFF_MISC + 40, B_XFULL = OFF_MISC + 80;
constexpr uint32_t B_GRDY = OFF_MISC + 152, B_KVDONE = OFF_MISC + 160, B_KVRDY = OFF_MISC + 168;
constexpr uint32_t B_HSENT = OFF_MISC + 176, B_XFREE = OFF_MISC + 200;
constexpr uint32_t OFF_EPOCH = OFF_MISC + 240, OFF_G = OFF_MISC + 256;
constexpr uint32_t B_AHEAD = OFF_MISC + 248, B_PART = OFF_MISC + 232;
constexpr uint32_t OFF_ONES = OFF_MISC + 768;
constexpr uint32_t B_EFULL = OFF_MISC + 896, B_EEMPTY = OFF_MISC + 928;
constexpr uint32_t SMEM_BYTES = OFF_MISC + 960;
constexpr uint32_t SPIN_GLOBAL = 1u << 14;

struct alignas(64) Maps { CUtensorMap x, gu, kv, q64, gu64, wdw, wow, wdp, wdph, hx, hx2; };

}

__device__ uint4 g_part[16 * 2 * 4 * 4 * 1024];
__device__ uint4 g_hx[16 * 4 * 5 * 1024];
__device__ uint4 g_lx[16 * 8 * 2 * 1024];
__device__ unsigned g_hflag[128 * 8];
__device__ uint4 g_gx[16 * 32];
__device__ float g_kvacc[2 * 8 * 4 * 272];
__device__ unsigned g_kvcnt[8 * 32];
__device__ unsigned g_epoch[128];
#define TS(role, idx)
#define TS2(idx)
#define TSG(role, idx)

namespace {

__device__ __forceinline__ void mbar_init(uint32_t bar, uint32_t cnt) { asm volatile("mbarrier.init.shared::cta.b64 [%0], %1;" :: "r"(bar), "r"(cnt) : "memory"); }
__device__ __forceinline__ void mbar_expect(uint32_t bar, uint32_t bytes) { asm volatile("mbarrier.arrive.expect_tx.shared::cta.b64 _, [%0], %1;" :: "r"(bar), "r"(bytes) : "memory"); }
__device__ __forceinline__ void mbar_arrive(uint32_t bar) { asm volatile("mbarrier.arrive.shared::cta.b64 _, [%0];" :: "r"(bar) : "memory"); }
__device__ __forceinline__ void mbar_arrive_cta(uint32_t bar, uint32_t cta) {
    asm volatile("{\n.reg .b32 ra;\nmapa.shared::cluster.u32 ra, %0, %1;\nmbarrier.arrive.shared::cluster.b64 _, [ra];\n}" :: "r"(bar), "r"(cta) : "memory");
}
__device__ __forceinline__ void mbar_wait(uint32_t bar, uint32_t parity) {
    asm volatile("{\n.reg .pred p;\n.reg .u32 c;\n"
                 "mbarrier.try_wait.parity.shared::cta.b64 p, [%0], %1;\n@p bra DONE;\n"
                 "mov.u32 c, 0;\nLAB_WAIT:\nmbarrier.try_wait.parity.shared::cta.b64 p, [%0], %1;\n@p bra DONE;\n"
                 "add.u32 c, c, 1;\nsetp.lt.u32 p, c, 65536;\n@p bra LAB_WAIT;\nDONE:\n}" :: "r"(bar), "r"(parity) : "memory");
}
__device__ __forceinline__ void tma2(uint32_t dst, const CUtensorMap* m, int c0, int c1, uint32_t bar) {
    asm volatile("cp.async.bulk.tensor.2d.shared::cluster.global.mbarrier::complete_tx::bytes [%0], [%1, {%3, %4}], [%2];"
        :: "r"(dst), "l"(m), "r"(bar), "r"(c0), "r"(c1) : "memory");
}
__device__ __forceinline__ void tmaw2(uint32_t dst, const CUtensorMap* m, int c0, int c1, uint32_t bar) {
    tma2(dst, m, c0, c1, bar);
}
__device__ __forceinline__ void tmaw3(uint32_t dst, const CUtensorMap* m, int c0, int c1, int c2, uint32_t bar) {
    asm volatile("cp.async.bulk.tensor.3d.shared::cluster.global.mbarrier::complete_tx::bytes [%0], [%1, {%3, %4, %5}], [%2];"
        :: "r"(dst), "l"(m), "r"(bar), "r"(c0), "r"(c1), "r"(c2) : "memory");
}
__device__ __forceinline__ void tmaw5(uint32_t dst, const CUtensorMap* m, int c0, int c4, uint32_t bar) {
    asm volatile("cp.async.bulk.tensor.5d.shared::cluster.global.mbarrier::complete_tx::bytes [%0], [%1, {%3, %5, %5, %5, %4}], [%2];"
        :: "r"(dst), "l"(m), "r"(bar), "r"(c0), "r"(c4), "r"(0) : "memory");
}
__device__ __forceinline__ void wg_fence() { asm volatile("wgmma.fence.sync.aligned;" ::: "memory"); }
__device__ __forceinline__ void wg_commit() { asm volatile("wgmma.commit_group.sync.aligned;" ::: "memory"); }
template <int N> __device__ __forceinline__ void wg_wait() { asm volatile("wgmma.wait_group.sync.aligned %0;" :: "n"(N) : "memory"); }
template <int N> __device__ __forceinline__ void pin(float (&d)[N]) {
#pragma unroll
    for (int i = 0; i < N; i++) asm volatile("" : "+f"(d[i]) :: "memory");
}
__device__ __forceinline__ uint32_t pack2(float lo, float hi) { uint32_t r; asm("cvt.rn.bf16x2.f32 %0, %1, %2;" : "=r"(r) : "f"(hi), "f"(lo)); return r; }
__device__ __forceinline__ uint32_t keep(uint32_t v) { asm volatile("" : "+r"(v)); return v; }
__device__ __forceinline__ uint32_t hadd2(uint32_t a, uint32_t b) { uint32_t r; asm("add.bf16x2 %0, %1, %2;" : "=r"(r) : "r"(a), "r"(b)); return r; }
__device__ __forceinline__ uint32_t hmul2(uint32_t a, uint32_t b) { uint32_t r; asm("mul.bf16x2 %0, %1, %2;" : "=r"(r) : "r"(a), "r"(b)); return r; }
__device__ __forceinline__ uint32_t phi2(float t0, float t1) {
    float e0, e1;
    asm("ex2.approx.ftz.f32 %0, %1;" : "=f"(e0) : "f"(t0 * 1.4426950408889634f));
    asm("ex2.approx.ftz.f32 %0, %1;" : "=f"(e1) : "f"(t1 * 1.4426950408889634f));
    uint32_t e = pack2(e0, e1), t = pack2(t0, t1), r;
    asm("min.bf16x2 %0, %0, %1;" : "+r"(e) : "r"(0x3f803f80u));
    asm("max.bf16x2 %0, %0, %1;" : "+r"(t) : "r"(0x35863586u));
    asm("add.bf16x2 %0, %1, %2;" : "=r"(r) : "r"(e), "r"(t));
    return r;
}
__device__ __forceinline__ void stsm4(uint32_t a, uint32_t r0, uint32_t r1, uint32_t r2, uint32_t r3) {
    asm volatile("stmatrix.sync.aligned.m8n8.x4.shared.b16 [%0], {%1,%2,%3,%4};" :: "r"(a), "r"(r0), "r"(r1), "r"(r2), "r"(r3) : "memory");
}
__device__ __forceinline__ float bf_lo(uint32_t w) { return __uint_as_float(w << 16); }
__device__ __forceinline__ float bf_hi(uint32_t w) { return __uint_as_float(w & 0xffff0000u); }
__device__ __forceinline__ void st_pkt(uint4* p, uint32_t w0, uint32_t w1, uint32_t w2, uint32_t w3) {
    asm volatile("{\n.reg .b64 lo, hi;\n.reg .b128 v;\nmov.b64 lo, {%1, %2};\nmov.b64 hi, {%3, %4};\nmov.b128 v, {lo, hi};\nst.relaxed.gpu.global.b128 [%0], v;\n}"
        :: "l"(p), "r"(w0), "r"(w1), "r"(w2), "r"(w3) : "memory");
}
__device__ __forceinline__ void ld_pkt(const uint4* p, uint32_t& w0, uint32_t& w1, uint32_t& w2, uint32_t& w3) {
    asm volatile("{\n.reg .b64 lo, hi;\n.reg .b128 v;\nld.relaxed.gpu.global.b128 v, [%4];\nmov.b128 {lo, hi}, v;\nmov.b64 {%0, %1}, lo;\nmov.b64 {%2, %3}, hi;\n}"
        : "=r"(w0), "=r"(w1), "=r"(w2), "=r"(w3) : "l"(p) : "memory");
}

template <uint32_t AO, uint32_t BO, uint32_t BH> __device__ __forceinline__ void wg_ss128(float (&d)[64], uint32_t ab, uint32_t bb) {
    asm volatile("{\n.reg .b64 da, db;\n.reg .b32 ta, tb, th, ah;\nadd.u32 ta, %64, %66;\nadd.u32 tb, %65, %67;\nmov.b32 th, %68;\nmov.b32 ah, 0x40000040;\nmov.b64 da, {ta, ah};\nmov.b64 db, {tb, th};\n"
        "wgmma.mma_async.sync.aligned.m64n128k16.f32.bf16.bf16 {%0,%1,%2,%3,%4,%5,%6,%7,%8,%9,%10,%11,%12,%13,%14,%15,%16,%17,%18,%19,%20,%21,%22,%23,%24,%25,%26,%27,%28,%29,%30,%31,%32,%33,%34,%35,%36,%37,%38,%39,%40,%41,%42,%43,%44,%45,%46,%47,%48,%49,%50,%51,%52,%53,%54,%55,%56,%57,%58,%59,%60,%61,%62,%63}, da, db, 1, 1, 1, 0, 1;\n}\n"
        : "+f"(d[0]),"+f"(d[1]),"+f"(d[2]),"+f"(d[3]),"+f"(d[4]),"+f"(d[5]),"+f"(d[6]),"+f"(d[7]),"+f"(d[8]),"+f"(d[9]),"+f"(d[10]),"+f"(d[11]),"+f"(d[12]),"+f"(d[13]),"+f"(d[14]),"+f"(d[15]),"+f"(d[16]),"+f"(d[17]),"+f"(d[18]),"+f"(d[19]),"+f"(d[20]),"+f"(d[21]),"+f"(d[22]),"+f"(d[23]),"+f"(d[24]),"+f"(d[25]),"+f"(d[26]),"+f"(d[27]),"+f"(d[28]),"+f"(d[29]),"+f"(d[30]),"+f"(d[31]),"+f"(d[32]),"+f"(d[33]),"+f"(d[34]),"+f"(d[35]),"+f"(d[36]),"+f"(d[37]),"+f"(d[38]),"+f"(d[39]),"+f"(d[40]),"+f"(d[41]),"+f"(d[42]),"+f"(d[43]),"+f"(d[44]),"+f"(d[45]),"+f"(d[46]),"+f"(d[47]),"+f"(d[48]),"+f"(d[49]),"+f"(d[50]),"+f"(d[51]),"+f"(d[52]),"+f"(d[53]),"+f"(d[54]),"+f"(d[55]),"+f"(d[56]),"+f"(d[57]),"+f"(d[58]),"+f"(d[59]),"+f"(d[60]),"+f"(d[61]),"+f"(d[62]),"+f"(d[63])
        : "r"(ab), "r"(bb), "n"(AO), "n"(BO), "n"(BH));
}
template <uint32_t AO, uint32_t BO, uint32_t BH> __device__ __forceinline__ void wg_ss128_z(float (&d)[64], uint32_t ab, uint32_t bb) {
    asm volatile("{\n.reg .b64 da, db;\n.reg .b32 ta, tb, th, ah;\nadd.u32 ta, %64, %66;\nadd.u32 tb, %65, %67;\nmov.b32 th, %68;\nmov.b32 ah, 0x40000040;\nmov.b64 da, {ta, ah};\nmov.b64 db, {tb, th};\n"
        "wgmma.mma_async.sync.aligned.m64n128k16.f32.bf16.bf16 {%0,%1,%2,%3,%4,%5,%6,%7,%8,%9,%10,%11,%12,%13,%14,%15,%16,%17,%18,%19,%20,%21,%22,%23,%24,%25,%26,%27,%28,%29,%30,%31,%32,%33,%34,%35,%36,%37,%38,%39,%40,%41,%42,%43,%44,%45,%46,%47,%48,%49,%50,%51,%52,%53,%54,%55,%56,%57,%58,%59,%60,%61,%62,%63}, da, db, 0, 1, 1, 0, 1;\n}\n"
        : "=f"(d[0]),"=f"(d[1]),"=f"(d[2]),"=f"(d[3]),"=f"(d[4]),"=f"(d[5]),"=f"(d[6]),"=f"(d[7]),"=f"(d[8]),"=f"(d[9]),"=f"(d[10]),"=f"(d[11]),"=f"(d[12]),"=f"(d[13]),"=f"(d[14]),"=f"(d[15]),"=f"(d[16]),"=f"(d[17]),"=f"(d[18]),"=f"(d[19]),"=f"(d[20]),"=f"(d[21]),"=f"(d[22]),"=f"(d[23]),"=f"(d[24]),"=f"(d[25]),"=f"(d[26]),"=f"(d[27]),"=f"(d[28]),"=f"(d[29]),"=f"(d[30]),"=f"(d[31]),"=f"(d[32]),"=f"(d[33]),"=f"(d[34]),"=f"(d[35]),"=f"(d[36]),"=f"(d[37]),"=f"(d[38]),"=f"(d[39]),"=f"(d[40]),"=f"(d[41]),"=f"(d[42]),"=f"(d[43]),"=f"(d[44]),"=f"(d[45]),"=f"(d[46]),"=f"(d[47]),"=f"(d[48]),"=f"(d[49]),"=f"(d[50]),"=f"(d[51]),"=f"(d[52]),"=f"(d[53]),"=f"(d[54]),"=f"(d[55]),"=f"(d[56]),"=f"(d[57]),"=f"(d[58]),"=f"(d[59]),"=f"(d[60]),"=f"(d[61]),"=f"(d[62]),"=f"(d[63])
        : "r"(ab), "r"(bb), "n"(AO), "n"(BO), "n"(BH));
}
template <uint32_t BO, uint32_t BH> __device__ __forceinline__ void wg_rs128(float (&d)[64], uint32_t a0, uint32_t a1, uint32_t a2, uint32_t a3, uint32_t bb) {
    asm volatile("{\n.reg .b64 db;\n.reg .b32 tb, th;\nadd.u32 tb, %68, %69;\nmov.b32 th, %70;\nmov.b64 db, {tb, th};\n"
        "wgmma.mma_async.sync.aligned.m64n128k16.f32.bf16.bf16 {%0,%1,%2,%3,%4,%5,%6,%7,%8,%9,%10,%11,%12,%13,%14,%15,%16,%17,%18,%19,%20,%21,%22,%23,%24,%25,%26,%27,%28,%29,%30,%31,%32,%33,%34,%35,%36,%37,%38,%39,%40,%41,%42,%43,%44,%45,%46,%47,%48,%49,%50,%51,%52,%53,%54,%55,%56,%57,%58,%59,%60,%61,%62,%63}, {%64,%65,%66,%67}, db, 1, 1, 1, 1;\n}\n"
        : "+f"(d[0]),"+f"(d[1]),"+f"(d[2]),"+f"(d[3]),"+f"(d[4]),"+f"(d[5]),"+f"(d[6]),"+f"(d[7]),"+f"(d[8]),"+f"(d[9]),"+f"(d[10]),"+f"(d[11]),"+f"(d[12]),"+f"(d[13]),"+f"(d[14]),"+f"(d[15]),"+f"(d[16]),"+f"(d[17]),"+f"(d[18]),"+f"(d[19]),"+f"(d[20]),"+f"(d[21]),"+f"(d[22]),"+f"(d[23]),"+f"(d[24]),"+f"(d[25]),"+f"(d[26]),"+f"(d[27]),"+f"(d[28]),"+f"(d[29]),"+f"(d[30]),"+f"(d[31]),"+f"(d[32]),"+f"(d[33]),"+f"(d[34]),"+f"(d[35]),"+f"(d[36]),"+f"(d[37]),"+f"(d[38]),"+f"(d[39]),"+f"(d[40]),"+f"(d[41]),"+f"(d[42]),"+f"(d[43]),"+f"(d[44]),"+f"(d[45]),"+f"(d[46]),"+f"(d[47]),"+f"(d[48]),"+f"(d[49]),"+f"(d[50]),"+f"(d[51]),"+f"(d[52]),"+f"(d[53]),"+f"(d[54]),"+f"(d[55]),"+f"(d[56]),"+f"(d[57]),"+f"(d[58]),"+f"(d[59]),"+f"(d[60]),"+f"(d[61]),"+f"(d[62]),"+f"(d[63])
        : "r"(a0), "r"(a1), "r"(a2), "r"(a3), "r"(bb), "n"(BO), "n"(BH));
}
template <uint32_t BO, uint32_t BH> __device__ __forceinline__ void wg_rs128_z(float (&d)[64], uint32_t a0, uint32_t a1, uint32_t a2, uint32_t a3, uint32_t bb) {
    asm volatile("{\n.reg .b64 db;\n.reg .b32 tb, th;\nadd.u32 tb, %68, %69;\nmov.b32 th, %70;\nmov.b64 db, {tb, th};\n"
        "wgmma.mma_async.sync.aligned.m64n128k16.f32.bf16.bf16 {%0,%1,%2,%3,%4,%5,%6,%7,%8,%9,%10,%11,%12,%13,%14,%15,%16,%17,%18,%19,%20,%21,%22,%23,%24,%25,%26,%27,%28,%29,%30,%31,%32,%33,%34,%35,%36,%37,%38,%39,%40,%41,%42,%43,%44,%45,%46,%47,%48,%49,%50,%51,%52,%53,%54,%55,%56,%57,%58,%59,%60,%61,%62,%63}, {%64,%65,%66,%67}, db, 0, 1, 1, 1;\n}\n"
        : "=f"(d[0]),"=f"(d[1]),"=f"(d[2]),"=f"(d[3]),"=f"(d[4]),"=f"(d[5]),"=f"(d[6]),"=f"(d[7]),"=f"(d[8]),"=f"(d[9]),"=f"(d[10]),"=f"(d[11]),"=f"(d[12]),"=f"(d[13]),"=f"(d[14]),"=f"(d[15]),"=f"(d[16]),"=f"(d[17]),"=f"(d[18]),"=f"(d[19]),"=f"(d[20]),"=f"(d[21]),"=f"(d[22]),"=f"(d[23]),"=f"(d[24]),"=f"(d[25]),"=f"(d[26]),"=f"(d[27]),"=f"(d[28]),"=f"(d[29]),"=f"(d[30]),"=f"(d[31]),"=f"(d[32]),"=f"(d[33]),"=f"(d[34]),"=f"(d[35]),"=f"(d[36]),"=f"(d[37]),"=f"(d[38]),"=f"(d[39]),"=f"(d[40]),"=f"(d[41]),"=f"(d[42]),"=f"(d[43]),"=f"(d[44]),"=f"(d[45]),"=f"(d[46]),"=f"(d[47]),"=f"(d[48]),"=f"(d[49]),"=f"(d[50]),"=f"(d[51]),"=f"(d[52]),"=f"(d[53]),"=f"(d[54]),"=f"(d[55]),"=f"(d[56]),"=f"(d[57]),"=f"(d[58]),"=f"(d[59]),"=f"(d[60]),"=f"(d[61]),"=f"(d[62]),"=f"(d[63])
        : "r"(a0), "r"(a1), "r"(a2), "r"(a3), "r"(bb), "n"(BO), "n"(BH));
}
template <uint32_t AO, uint32_t BO, uint32_t BH> __device__ __forceinline__ void wg_ss64t(float (&d)[32], uint32_t ab, uint32_t bb) {
    asm volatile("{\n.reg .b64 da, db;\n.reg .b32 ta, tb, th, ah;\nadd.u32 ta, %32, %34;\nadd.u32 tb, %33, %35;\nmov.b32 th, %36;\nmov.b32 ah, 0x40000040;\nmov.b64 da, {ta, ah};\nmov.b64 db, {tb, th};\n"
        "wgmma.mma_async.sync.aligned.m64n64k16.f32.bf16.bf16 {%0,%1,%2,%3,%4,%5,%6,%7,%8,%9,%10,%11,%12,%13,%14,%15,%16,%17,%18,%19,%20,%21,%22,%23,%24,%25,%26,%27,%28,%29,%30,%31}, da, db, 1, 1, 1, 1, 1;\n}\n"
        : "+f"(d[0]),"+f"(d[1]),"+f"(d[2]),"+f"(d[3]),"+f"(d[4]),"+f"(d[5]),"+f"(d[6]),"+f"(d[7]),"+f"(d[8]),"+f"(d[9]),"+f"(d[10]),"+f"(d[11]),"+f"(d[12]),"+f"(d[13]),"+f"(d[14]),"+f"(d[15]),"+f"(d[16]),"+f"(d[17]),"+f"(d[18]),"+f"(d[19]),"+f"(d[20]),"+f"(d[21]),"+f"(d[22]),"+f"(d[23]),"+f"(d[24]),"+f"(d[25]),"+f"(d[26]),"+f"(d[27]),"+f"(d[28]),"+f"(d[29]),"+f"(d[30]),"+f"(d[31])
        : "r"(ab), "r"(bb), "n"(AO), "n"(BO), "n"(BH));
}
template <uint32_t AO, uint32_t BO, uint32_t BH> __device__ __forceinline__ void wg_ss64t_z(float (&d)[32], uint32_t ab, uint32_t bb) {
    asm volatile("{\n.reg .b64 da, db;\n.reg .b32 ta, tb, th, ah;\nadd.u32 ta, %32, %34;\nadd.u32 tb, %33, %35;\nmov.b32 th, %36;\nmov.b32 ah, 0x40000040;\nmov.b64 da, {ta, ah};\nmov.b64 db, {tb, th};\n"
        "wgmma.mma_async.sync.aligned.m64n64k16.f32.bf16.bf16 {%0,%1,%2,%3,%4,%5,%6,%7,%8,%9,%10,%11,%12,%13,%14,%15,%16,%17,%18,%19,%20,%21,%22,%23,%24,%25,%26,%27,%28,%29,%30,%31}, da, db, 0, 1, 1, 1, 1;\n}\n"
        : "=f"(d[0]),"=f"(d[1]),"=f"(d[2]),"=f"(d[3]),"=f"(d[4]),"=f"(d[5]),"=f"(d[6]),"=f"(d[7]),"=f"(d[8]),"=f"(d[9]),"=f"(d[10]),"=f"(d[11]),"=f"(d[12]),"=f"(d[13]),"=f"(d[14]),"=f"(d[15]),"=f"(d[16]),"=f"(d[17]),"=f"(d[18]),"=f"(d[19]),"=f"(d[20]),"=f"(d[21]),"=f"(d[22]),"=f"(d[23]),"=f"(d[24]),"=f"(d[25]),"=f"(d[26]),"=f"(d[27]),"=f"(d[28]),"=f"(d[29]),"=f"(d[30]),"=f"(d[31])
        : "r"(ab), "r"(bb), "n"(AO), "n"(BO), "n"(BH));
}
template <uint32_t AO, uint32_t BO, uint32_t BH> __device__ __forceinline__ void wg_ss8t(float (&d)[4], uint32_t ab, uint32_t bb) {
    asm volatile("{\n.reg .b64 da, db;\n.reg .b32 ta, tb, th, ah;\nadd.u32 ta, %4, %6;\nadd.u32 tb, %5, %7;\nmov.b32 th, %8;\nmov.b32 ah, 0x40000040;\nmov.b64 da, {ta, ah};\nmov.b64 db, {tb, th};\n"
        "wgmma.mma_async.sync.aligned.m64n8k16.f32.bf16.bf16 {%0,%1,%2,%3}, da, db, 1, 1, 1, 1, 0;\n}\n"
        : "+f"(d[0]),"+f"(d[1]),"+f"(d[2]),"+f"(d[3])
        : "r"(ab), "r"(bb), "n"(AO), "n"(BO), "n"(BH));
}
template <uint32_t AO, uint32_t BO, uint32_t BH> __device__ __forceinline__ void wg_ss8t_z(float (&d)[4], uint32_t ab, uint32_t bb) {
    asm volatile("{\n.reg .b64 da, db;\n.reg .b32 ta, tb, th, ah;\nadd.u32 ta, %4, %6;\nadd.u32 tb, %5, %7;\nmov.b32 th, %8;\nmov.b32 ah, 0x40000040;\nmov.b64 da, {ta, ah};\nmov.b64 db, {tb, th};\n"
        "wgmma.mma_async.sync.aligned.m64n8k16.f32.bf16.bf16 {%0,%1,%2,%3}, da, db, 0, 1, 1, 1, 0;\n}\n"
        : "=f"(d[0]),"=f"(d[1]),"=f"(d[2]),"=f"(d[3])
        : "r"(ab), "r"(bb), "n"(AO), "n"(BO), "n"(BH));
}
template <uint32_t BO, uint32_t BH> __device__ __forceinline__ void wg_rs24_z(float (&d)[12], uint32_t a0, uint32_t a1, uint32_t a2, uint32_t a3, uint32_t bb) {
    asm volatile("{\n.reg .b64 db;\n.reg .b32 tb, th;\nadd.u32 tb, %16, %17;\nmov.b32 th, %18;\nmov.b64 db, {tb, th};\n"
        "wgmma.mma_async.sync.aligned.m64n24k16.f32.bf16.bf16 {%0,%1,%2,%3,%4,%5,%6,%7,%8,%9,%10,%11}, {%12,%13,%14,%15}, db, 0, 1, 1, 0;\n}\n"
        : "=f"(d[0]),"=f"(d[1]),"=f"(d[2]),"=f"(d[3]),"=f"(d[4]),"=f"(d[5]),"=f"(d[6]),"=f"(d[7]),"=f"(d[8]),"=f"(d[9]),"=f"(d[10]),"=f"(d[11])
        : "r"(a0), "r"(a1), "r"(a2), "r"(a3), "r"(bb), "n"(BO), "n"(BH));
}

constexpr uint32_t DH128 = 64u | 0x40000000u;
constexpr uint32_t DH64 = 32u | 0x80000000u;
constexpr uint32_t LBO4K = (4096u >> 4) << 16, LBO8K = (8192u >> 4) << 16, LBO1 = 1u << 16;

template <uint32_t AO, uint32_t BO, bool SW64, bool FIRST> __device__ __forceinline__ void stage_ss(float (&acc)[64], uint32_t ab, uint32_t bb) {
    constexpr uint32_t KS = SW64 ? 64 : 128, BH = SW64 ? DH64 : DH128, B0 = BO + (SW64 ? LBO4K : LBO8K);
    wg_fence();
    if (FIRST) wg_ss128_z<AO, B0, BH>(acc, ab, bb); else wg_ss128<AO, B0, BH>(acc, ab, bb);
    wg_ss128<AO + 2, B0 + KS, BH>(acc, ab, bb);
    wg_ss128<AO + 4, B0 + 2 * KS, BH>(acc, ab, bb);
    wg_ss128<AO + 6, B0 + 3 * KS, BH>(acc, ab, bb);
    wg_commit();
}
template <uint32_t BO, bool FIRST> __device__ __forceinline__ void stage_rs(float (&acc)[64], const uint32_t (&f)[16], uint32_t bb) {
    wg_fence();
    if (FIRST) wg_rs128_z<BO + LBO8K, DH128>(acc, f[0], f[1], f[2], f[3], bb); else wg_rs128<BO + LBO8K, DH128>(acc, f[0], f[1], f[2], f[3], bb);
    wg_rs128<BO + LBO8K + 128, DH128>(acc, f[4], f[5], f[6], f[7], bb);
    wg_rs128<BO + LBO8K + 256, DH128>(acc, f[8], f[9], f[10], f[11], bb);
    wg_rs128<BO + LBO8K + 384, DH128>(acc, f[12], f[13], f[14], f[15], bb);
    wg_commit();
}

template <int N> __device__ __forceinline__ void stash(uint32_t base, uint32_t sw, const uint32_t (&f)[N]) {
#pragma unroll
    for (int t = 0; t < N / 4; t++) stsm4(base + ((sw ^ (2 * t)) << 4), f[4 * t], f[4 * t + 1], f[4 * t + 2], f[4 * t + 3]);
}

template <int V0, int V1, int N> __device__ __forceinline__ void send_frag(const uint32_t (&f)[N], uint4* p, uint32_t tag) {
#pragma unroll
    for (int v = V0; v < V1; v++) st_pkt(p + v * 32, (f[4 * v] & ~1u) | tag, f[4 * v + 1], f[4 * v + 2], f[4 * v + 3]);
}
template <int V0, int V1, int N> __device__ __forceinline__ void send_h(const uint32_t (&f)[N], uint4* p) {
#pragma unroll
    for (int v = V0; v < V1; v++) {
        const int h = v >> 1, hi = v & 1;
        asm volatile("st.global.v4.u32 [%0], {%1,%2,%3,%4};" :: "l"(p + 4 * h + 64 * hi),
                     "r"(f[8 * h + hi]), "r"(f[8 * h + 2 + hi]), "r"(f[8 * h + 4 + hi]), "r"(f[8 * h + 6 + hi]) : "memory");
    }
}
template <int O, int N, int M> __device__ __forceinline__ void pack_sub(uint32_t (&f)[N], const float (&acc)[M]) {
#pragma unroll
    for (int i = 0; i < N; i++) f[i] = keep(pack2(acc[O + 2 * i], acc[O + 2 * i + 1]));
}
template <int N> __device__ __forceinline__ void recv_issue(uint32_t (&q)[N], const uint4* p) {
#pragma unroll
    for (int v = 0; v < N / 4; v++) ld_pkt(p + v * 32, q[4 * v], q[4 * v + 1], q[4 * v + 2], q[4 * v + 3]);
}
template <int N> __device__ __forceinline__ void recv_check(uint32_t (&q)[N], const uint4* p, uint32_t tag) {
    uint32_t it = 0;
    while (true) {
        uint32_t bad = 0;
#pragma unroll
        for (int v = 0; v < N / 4; v++) bad |= q[4 * v] ^ tag;
        if (__all_sync(0xffffffffu, (bad & 1u) == 0) || ++it > SPIN_GLOBAL) break;
        recv_issue(q, p);
    }
}
}

__global__ void __launch_bounds__(384, 1)
fused_kernel(const __grid_constant__ Maps maps, const __nv_bfloat16* __restrict__ xg, const __nv_bfloat16* __restrict__ gate_w,
             const char* __restrict__ pf_qkv, const char* __restrict__ pf_g, const char* __restrict__ pf_u,
             const char* __restrict__ pf_d, const char* __restrict__ pf_o, __nv_bfloat16* __restrict__ out) {
    extern __shared__ __align__(1024) uint8_t smem_raw[];
    const uint32_t sb = (uint32_t)__cvta_generic_to_shared(smem_raw);
    const int tid = threadIdx.x, lane = tid & 31;
    const int warp = __shfl_sync(0xffffffffu, tid >> 5, 0);
    const int j = (blockIdx.x >> 1) & 7;
    const int r = (((blockIdx.x >> 4) << 1) | (blockIdx.x & 1)) ^ RX;
    const uint32_t rank = blockIdx.x & 1;

    if (warp == 0) { TSG(0, 30); TS(0, 0); }
    if (tid < 256) {
        const int row = tid >> 3, ch = tid & 7;
        const uint32_t so = sb + row * 128 + ((ch ^ (row & 7)) << 4);
        const char* gx = (const char*)xg + (size_t)(r * 128 + row) * 1024 + ch * 16;
        const char* gk = pf_qkv + row * 3072 + 1024 + j * 128 + ch * 16;
        const int go = row * 3584 + j * 448 + ch * 16;
#define CP16(S, G) asm volatile("cp.async.cg.shared.global [%0], [%1], 16;" :: "r"(S), "l"(G) : "memory")
#pragma unroll
        for (int i = 0; i < 4; i++) {
            CP16(so + OFF_X + i * 4096, gx + i * 32768);
            CP16(so + OFF_RING + i * 4096, gk + (i & 1) * 98304 + (i >> 1) * 1024);
        }
        asm volatile("cp.async.commit_group;" ::: "memory");
#pragma unroll
        for (int i = 0; i < 4; i++) CP16(so + OFF_RING + 16384 + i * 4096, (i < 2 ? pf_g : pf_u) + go + (i & 1) * 114688);
        asm volatile("cp.async.commit_group;" ::: "memory");
    } else if (tid == 256) {
        for (int i = 0; i < 5; i++) { mbar_init(sb + B_FULL + 8 * i, 1); mbar_init(sb + B_EMPTY + 8 * i, MC ? 4 : 2); }
        for (int i = 0; i < 9; i++) mbar_init(sb + B_XFULL + 8 * i, 1);
        asm volatile("fence.mbarrier_init.release.cluster;" ::: "memory");
        TS2(0); TS2(1);
        mbar_expect(sb + B_XFULL + 8, 16384);
        tma2(sb + OFF_X + 16384, &maps.x, 64, r * 128, sb + B_XFULL + 8);
        TS2(2);
        mbar_expect(sb + B_FULL + 16, 16384);
        tmaw3(sb + OFF_RING + 2 * 16384, &maps.kv, 64 * j, 64, 1, sb + B_FULL + 16);
        mbar_expect(sb + B_XFULL + 16, 16384);
        tma2(sb + OFF_X + 2 * 16384, &maps.x, 128, r * 128, sb + B_XFULL + 16);
        mbar_arrive(sb + B_FULL); mbar_arrive(sb + B_FULL + 8); mbar_arrive(sb + B_XFULL);
    } else if (tid == 288) {
        for (int i = 0; i < 3; i++) mbar_init(sb + B_HSENT + 8 * i, 8);
        for (int i = 0; i < 4; i++) { mbar_init(sb + B_EFULL + 8 * i, 1); mbar_init(sb + B_EEMPTY + 8 * i, MC ? 4 : 2); }
        mbar_init(sb + B_XFREE, 2); mbar_init(sb + B_XFREE + 8, 2); mbar_init(sb + B_XFREE + 16, 2);
        mbar_init(sb + B_AHEAD, 1); mbar_init(sb + B_PART, 1); mbar_init(sb + B_GRDY, 1); mbar_init(sb + B_KVDONE, 8); mbar_init(sb + B_KVRDY, 2);
        asm volatile("fence.mbarrier_init.release.cluster;" ::: "memory");
    } else if (warp == 10 && lane < 10) {
        asm volatile("prefetch.tensormap [%0];" :: "l"(&maps.gu + lane) : "memory");
    }
    __syncthreads();

    if (warp >= 8) {
        asm volatile("setmaxnreg.dec.sync.aligned.u32 56;");
        if (warp == 8) {
            if (lane == 0) {
                int slot = 3, ph = 1;
                uint32_t full, dst;
#define P_BEGIN(S, BYTES) full = sb + B_FULL + 8 * slot; dst = sb + OFF_RING + slot * 16384; \
                mbar_wait(sb + B_EMPTY + 8 * slot, ph); TS2(S); mbar_expect(full, BYTES); if (!MC || (((S) ^ rank) & 1) == 0)
#define P_END() if (++slot == 5) { slot = 0; ph ^= 1; }
                for (int s = 3; s < 16; s++) {
                    const int kb = (int)(0x7654763542312100ull >> (4 * s)) & 15;
                    P_BEGIN(s, 16384) {
                        if ((0x0DADu >> s) & 1) tmaw3(dst, &maps.kv, 64 * j, 64 * kb, 1, full);
                        else tmaw3(dst, &maps.gu, 224 * j, 64 * kb, 0, full);
                    }
                    const int xb = (int)(0x0000000765403210ull >> (4 * s)) & 15;
                    if (xb) { mbar_expect(sb + B_XFULL + 8 * xb, 16384); tma2(sb + OFF_X + xb * 16384, &maps.x, 64 * xb, r * 128, sb + B_XFULL + 8 * xb); }
                    P_END()
                }
                for (int s = 0; s < 24; s++) {
                    P_BEGIN(16 + s, 16384) {
                        if (s < 8) {
                            tmaw3(dst, &maps.q64, 0, 64 * s, 2 * j, full);
                            tmaw3(dst + 8192, &maps.gu64, 224 * j + 192, 64 * s, 0, full);
                        } else {
                            tmaw3(dst, &maps.gu, 224 * j + 64 * (s >> 3), 64 * (s & 7), 0, full);
                        }
                    }
                    P_END()
                }
                const int p = j >> 1;
#pragma unroll 1
                for (int t = 0; t < 18; t++) {
                    const int q = t >= 9, sl = (int)(0x846352107ull >> (4 * (t - 9 * q))) & 15;
                    const int u = (int)((q ? 0x432186758ull : 0x327064105ull) >> (4 * (t - 9 * q))) & 15;
                    const int cw = (j & 1) * 4 + ((p & 2) ^ ((t == 5 || t > 9) ? 0 : 2)), cc = 64 * cw;
                    if (sl < 5) {
                        full = sb + B_FULL + 8 * sl; dst = sb + OFF_RING + sl * 16384;
                        mbar_wait(sb + B_EMPTY + 8 * sl, q ^ 1);
                    } else {
                        full = sb + B_EFULL + 8 * (sl - 5); dst = sb + OFF_X + (sl == 7 ? 8 : sl == 8 ? 7 : sl) * 16384;
                        mbar_wait(sb + B_EEMPTY + 8 * (sl - 5), q);
                    }
                    TS2(40 + t);
                    mbar_expect(full, 16384);
                    if (!MC || ((t ^ rank) & 1) == 0) {
                        if (u == 4) {
                            tmaw5(dst, &maps.wdph, cc, 14 * p + 6, full); tmaw5(dst + 4096, &maps.wdph, cc, 14 * p + 13, full);
                            tmaw5(dst + 8192, &maps.wdph, cc + 64, 14 * p + 6, full); tmaw5(dst + 12288, &maps.wdph, cc + 64, 14 * p + 13, full);
                        } else if (u > 4) {
                            const int js = u > 6 ? j ^ 1 : j;
                            tmaw3(dst, (u & 1) ? &maps.wow : &maps.wdw, 0, (u & 1) ? 64 * js : 224 * js + 128, cw, full);
                        } else {
                            const int g = 14 * p + 7 * (u & 1) + (u & 2);
                            tmaw5(dst, &maps.wdp, cc, g, full); tmaw5(dst + 8192, &maps.wdp, cc + 64, g, full);
                        }
                    }
                }
            }
        } else if (warp < 11) {
            const int hx = warp - 9;
            uint32_t epoch;
            asm volatile("ld.relaxed.gpu.global.u32 %0, [%1];" : "=r"(epoch) : "l"(g_epoch + blockIdx.x) : "memory");
            {
                const uint4* xr = (const uint4*)(xg + (size_t)(r * 128 + j * 16 + hx * 8) * kD) + lane;
                const uint4 wa = __ldg((const uint4*)gate_w + lane), wb = __ldg((const uint4*)gate_w + 32 + lane);
                const uint32_t tag = (epoch + 1) & 1;
                uint4* gp = g_gx + r * 32;
                if (lane < 2) st_pkt(gp + j * 4 + hx * 2 + lane, tag ^ 1, 0, 0, 0);
                float s[8];
#pragma unroll
                for (int i0 = 0; i0 < 8; i0 += 4) {
                    uint4 va[4], vb[4];
#pragma unroll
                    for (int i = 0; i < 4; i++) { va[i] = __ldg(xr + (i0 + i) * 64); vb[i] = __ldg(xr + (i0 + i) * 64 + 32); }
#pragma unroll
                    for (int i = 0; i < 4; i++) {
                        float t0 = bf_lo(va[i].x) * bf_lo(wa.x), t1 = bf_hi(va[i].x) * bf_hi(wa.x);
                        t0 = fmaf(bf_lo(va[i].y), bf_lo(wa.y), t0); t1 = fmaf(bf_hi(va[i].y), bf_hi(wa.y), t1);
                        t0 = fmaf(bf_lo(va[i].z), bf_lo(wa.z), t0); t1 = fmaf(bf_hi(va[i].z), bf_hi(wa.z), t1);
                        t0 = fmaf(bf_lo(va[i].w), bf_lo(wa.w), t0); t1 = fmaf(bf_hi(va[i].w), bf_hi(wa.w), t1);
                        t0 = fmaf(bf_lo(vb[i].x), bf_lo(wb.x), t0); t1 = fmaf(bf_hi(vb[i].x), bf_hi(wb.x), t1);
                        t0 = fmaf(bf_lo(vb[i].y), bf_lo(wb.y), t0); t1 = fmaf(bf_hi(vb[i].y), bf_hi(wb.y), t1);
                        t0 = fmaf(bf_lo(vb[i].z), bf_lo(wb.z), t0); t1 = fmaf(bf_hi(vb[i].z), bf_hi(wb.z), t1);
                        t0 = fmaf(bf_lo(vb[i].w), bf_lo(wb.w), t0); t1 = fmaf(bf_hi(vb[i].w), bf_hi(wb.w), t1);
                        s[i0 + i] = t0 + t1;
                    }
                }
#pragma unroll
                for (int i = 0; i < 8; i++) {
#pragma unroll
                    for (int o = 16; o; o >>= 1) s[i] += __shfl_xor_sync(0xffffffffu, s[i], o);
                    s[i] = 1.f / (1.f + __expf(-s[i]));
                }
                if (lane < 2) {
                    const float v0 = lane ? s[4] : s[0], v1 = lane ? s[5] : s[1], v2 = lane ? s[6] : s[2], v3 = lane ? s[7] : s[3];
                    st_pkt(gp + j * 4 + hx * 2 + lane, (__float_as_uint(v0) & ~1u) | tag, __float_as_uint(v1), __float_as_uint(v2), __float_as_uint(v3));
                }
                if (hx == 1) {
                    asm volatile("st.shared.u32 [%0], %1;" :: "r"(sb + OFF_ONES + lane * 4), "r"(0x3f803f80u) : "memory");
                    asm volatile("fence.proxy.async.shared::cta;" ::: "memory");
                }
                asm volatile("bar.sync 3, 96;" ::: "memory");
                if (hx == 0) {
                    uint32_t q[4];
                    recv_issue(q, gp + lane);
                    recv_check(q, gp + lane, tag);
                    asm volatile("st.shared.v4.u32 [%0], {%1,%2,%3,%4};" :: "r"(sb + OFF_G + lane * 16), "r"(q[0]), "r"(q[1]), "r"(q[2]), "r"(q[3]) : "memory");
                    if (lane == 0) {
                        asm volatile("st.shared.u32 [%0], %1;" :: "r"(sb + OFF_EPOCH), "r"(epoch) : "memory");
                        g_epoch[blockIdx.x] = epoch + 1;
                    }
                    __syncwarp();
                    if (lane == 0) mbar_arrive(sb + B_GRDY);
                } else {
                    if (r == 0) {
                        float4* zp = (float4*)(g_kvacc + (((epoch & 1) ^ 1) * 8 + j) * 4 * 272);
                        for (int i = lane; i < 272; i += 32) zp[i] = make_float4(0.f, 0.f, 0.f, 0.f);
                    }
                }
            }
            TS(2 + hx, 1);
#define PUBLISH_H(B) do { mbar_wait(sb + B_HSENT + 8 * (B), 0); if (lane == 0) { \
                asm volatile("st.release.gpu.global.u32 [%0], %1;" :: "l"(g_hflag + (r * 8 + j) * 8 + (B)), "r"(epoch + 1) : "memory"); } __syncwarp(); } while (0)
            if (hx == 1) {
#pragma unroll 1
                for (int b = 0; b < 3; b++) { PUBLISH_H(b); TS(3, 5 + b); }
            } else {
                const float* accp = g_kvacc + ((epoch & 1) * 8 + j) * 4 * 272;
                unsigned* cnt = g_kvcnt + j * 32;
                mbar_wait(sb + B_KVDONE, 0);
                TS(2, 5);
                if (lane == 0) asm volatile("red.release.gpu.global.add.u32 [%0], 1;" :: "l"(cnt) : "memory");
                __syncwarp();
                TS(2, 2);
                {
                    const unsigned target = 16u * (epoch + 1);
                    uint32_t it = 0, v;
                    do {
                        asm volatile("ld.acquire.gpu.global.u32 %0, [%1];" : "=r"(v) : "l"(cnt) : "memory");
                    } while ((int)(v - target) < 0 && ++it < SPIN_GLOBAL);
                }
                TS(2, 3);
#pragma unroll
                for (int h = 0; h < 4; h++) {
                    const float4 d0 = __ldcg((const float4*)(accp + h * 272) + lane);
                    const float4 d1 = __ldcg((const float4*)(accp + h * 272 + 128) + lane);
                    const float2 z0 = __ldcg((const float2*)(accp + h * 272 + 256) + (lane & 3));
                    const float2 z1 = __ldcg((const float2*)(accp + h * 272 + 264) + (lane & 3));
                    const uint32_t ba = sb + OFF_STG + h * 768 + lane * 4;
                    asm volatile("st.shared.u32 [%0], %1;" :: "r"(ba), "r"(pack2(d0.x, d0.y)) : "memory");
                    asm volatile("st.shared.u32 [%0], %1;" :: "r"(ba + 128), "r"(pack2(d1.x, d1.y)) : "memory");
                    asm volatile("st.shared.u32 [%0], %1;" :: "r"(ba + 256), "r"(pack2(d0.z, d0.w)) : "memory");
                    asm volatile("st.shared.u32 [%0], %1;" :: "r"(ba + 384), "r"(pack2(d1.z, d1.w)) : "memory");
                    asm volatile("st.shared.u32 [%0], %1;" :: "r"(ba + 512), "r"(pack2(z0.x, z0.y)) : "memory");
                    asm volatile("st.shared.u32 [%0], %1;" :: "r"(ba + 640), "r"(pack2(z1.x, z1.y)) : "memory");
                }
                asm volatile("fence.proxy.async.shared::cta;" ::: "memory");
                __syncwarp();
                if (lane == 0) mbar_arrive(sb + B_KVRDY);
                TS(2, 4);
            }
        } else {
            uint32_t epoch;
            asm volatile("ld.relaxed.gpu.global.u32 %0, [%1];" : "=r"(epoch) : "l"(g_epoch + blockIdx.x) : "memory");
            asm volatile("bar.arrive 3, 96;" :: "r"(epoch) : "memory");
            const int b = blockIdx.x, p = j >> 1;
#pragma unroll 1
            for (int kb = 1; kb < 8; kb++) {
                mbar_wait(sb + B_XFULL + 8 * kb, 0);
                const char* base = kb < 3 ? pf_g : kb < 5 ? pf_u : kb == 5 ? pf_qkv : pf_d;
                const int off = kb == 5 ? b * 12288 : b * 14336 + ((kb < 5 ? kb - 1 : kb) & 1) * 7168;
                if (kb == 5) {
                    asm volatile("prefetch.global.L2 [%0];" :: "l"(base + off + (lane >> 3) * 3072 + (lane & 7) * 128));
                } else {
                    asm volatile("prefetch.global.L2 [%0];" :: "l"(base + off + lane * 128));
                    if (lane < 24) asm volatile("prefetch.global.L2 [%0];" :: "l"(base + off + 4096 + lane * 128));
                }
                if (kb == 7) asm volatile("prefetch.global.L2 [%0];" :: "l"(pf_o + b * 4096 + lane * 128));
            }
            {
                uint4* mb = g_part + (size_t)(r * 2 + (j & 1)) * 16384 + (((p ^ 1) * 4 + p) << 10) + lane;
#pragma unroll 1
                for (int i = 0; i < 32; i++) { st_pkt(mb + i * 32, epoch & 1, 0, 0, 0); __nanosleep(40); }
                __syncwarp();
                if (lane == 0) mbar_arrive(sb + B_KVRDY);
            }
            {
                const uint32_t want = epoch + 1;
                const int hrow = (r * 4 + p) * 5 * 128;
                const unsigned* fl = g_hflag + (r * 8 + (j & 6)) * 8 + (lane & 15);
                uint32_t it = 0;
                int i = 0;
                mbar_wait(sb + B_HSENT + 8, 0);
#pragma unroll 1
                while (i < 3 && ++it < SPIN_GLOBAL) {
                    uint32_t v;
                    asm volatile("ld.acquire.gpu.global.u32 %0, [%1];" : "=r"(v) : "l"(fl) : "memory");
                    const uint32_t rdy = __ballot_sync(0xffffffffu, v == want);
#pragma unroll 1
                    while (i < 3 && ((rdy >> i) & 0x101u) == 0x101u) {
                        if (i < 2) mbar_wait(sb + B_XFREE + 8 * i, 0);
                        if (lane == 0) {
                            const int pc = (6 - 2 * i) % 6;
                            asm volatile("fence.proxy.async.global;" ::: "memory");
                            TS2(140 + i);
                            mbar_expect(sb + B_XFULL + 8 * pc, i != 1 ? 32768 : 16384);
                            tma2(sb + OFF_X + pc * 16384, i != 1 ? &maps.hx2 : &maps.hx, 0, hrow + pc * 128, sb + B_XFULL + 8 * pc);
                        }
                        i++;
                    }
                }
            }
        }
    } else {
        asm volatile("setmaxnreg.inc.sync.aligned.u32 224;");
        const int wg = warp >> 2;
        const bool elect = (tid & 127) == 0;
        const uint32_t sbd = (sb & 0x3FFFFu) >> 4, xlo = (sbd + wg * 512) | LBO1;
        auto release = [&](uint32_t bar) {
            if (elect) {
                mbar_arrive(sb + bar);
            }
        };
#define S_SL(S) ((S) < 40 ? (S) % 5 : (int)((0x846352107ull >> (4 * (((S) - 40) % 9))) & 15))
#define S_WAIT(S) do { mbar_wait(sb + (S_SL(S) < 5 ? B_FULL + 8 * S_SL(S) : B_EFULL + 8 * (S_SL(S) - 5)), (S) < 40 ? ((S) / 5) & 1 : (S) >= 49); \
            if (PROF && tid == 0) TS2(64 + (S)); } while (0)
#define S_B(S) (S_SL(S) < 5 ? OFF_RING / 16 + S_SL(S) * 1024 : (S_SL(S) == 7 ? 8 : S_SL(S) == 8 ? 7 : S_SL(S)) * 1024)
#define S_REL(S) do { if ((S) < 49) release(S_SL(S) < 5 ? B_EMPTY + 8 * S_SL(S) : B_EEMPTY + 8 * (S_SL(S) - 5)); } while (0)
#define G1(S, acc, SW, KB) stage_ss<(KB) * 1024, S_B(S), SW, (KB) == 0>(acc, xlo, sbd)
#define RET(S) do { S_WAIT((S) + 1); wg_wait<1>(); S_REL((S) - 1); } while (0)
#define RET2(S) do { S_WAIT((S) + 1); wg_wait<2>(); S_REL((S) - 1); } while (0)
#define SCHED() mbar_wait(sb + B_XFULL + 8 * 7, 0)
#define A2_SYNC() do { asm volatile("fence.proxy.async.shared::cta;" ::: "memory"); asm volatile("bar.sync %0, 128;" :: "r"(wg + 1) : "memory"); } while (0)
#define H_EPI(acc, F, I0, I1, OG, OU) _Pragma("unroll") for (int i = (I0); i < (I1); i++) \
            F[i] = keep(hmul2(pack2(acc[(OG) + 2 * i] * acc[(OU) + 2 * i], acc[(OG) + 2 * i + 1] * acc[(OU) + 2 * i + 1]), (i & 1) ? m_hi : m_lo))
#define PHI(acc, F, I0, I1) _Pragma("unroll") for (int i = (I0); i < (I1); i++) F[i] = keep(phi2(acc[2 * i], acc[2 * i + 1]))

        float a0[64], b0[64], a1[64], a2_[64], a3[64];
#define X_WAIT(KB) do { mbar_wait(sb + B_XFULL + 8 * (KB), 0); if (PROF && tid == 0) TS2(128 + (KB)); } while (0)
#define CP_SYNC(N) do { asm volatile("cp.async.wait_group %0;" :: "n"(N) : "memory"); \
            asm volatile("fence.proxy.async.shared::cta;" ::: "memory"); asm volatile("bar.sync 4, 256;" ::: "memory"); } while (0)
        CP_SYNC(1); if (PROF && tid == 0) TS2(64);
        G1(0, b0, false, 0);
        if ((warp & 3) == 0) TS(wg, 1);
        CP_SYNC(0); if (PROF && tid == 0) TS2(65);
        G1(1, a0, false, 0); RET(1);
        X_WAIT(1); G1(2, b0, false, 1); RET(2);
        X_WAIT(2); G1(3, b0, false, 2); RET(3);
        G1(4, a0, false, 1); RET(4);
        X_WAIT(3); G1(5, b0, false, 3); RET(5);
        G1(6, a0, false, 2); RET(6);
        X_WAIT(4); G1(7, b0, false, 4); RET(7);
        X_WAIT(5); G1(8, b0, false, 5); RET(8);
        G1(9, a0, false, 3); RET(9);
        X_WAIT(6); G1(10, b0, false, 6); RET(10);
        X_WAIT(7); G1(11, b0, false, 7); RET(11);
        G1(12, a0, false, 4);
        const uint32_t lrow = ((lane & 7) + 8 * ((lane >> 3) & 1)) * 128;
        const uint32_t srow = (warp & 3) * 2048 + lrow;
        const uint32_t ssw = (lane >> 4) ^ (lane & 7);
        uint4* const hsend = g_hx + (size_t)((r * 4 + (j >> 1)) * 5 + (j & 1)) * 1024 + warp * 128 + (lane >> 2) * 8 + (lane & 3);
#define SENT_H(B) do { __syncwarp(); if (lane == 0) mbar_arrive(sb + B_HSENT + 8 * (B)); } while (0)
        RET(12);
        pin(b0);
        uint32_t fh0[16], fh1[16], fh2[16], fh3[8], fo[16], pk[16], pv[16];
        float kv[32], zs[4];
        const uint32_t stg = sb + OFF_STG + wg * 8192, stl = stg + (warp & 1) * 2048 + lrow;
#define KV_ROUND(Z) do { A2_SYNC(); wg_fence(); \
            wg_ss64t##Z<8192 + 256, 8192, DH128>(kv, xlo, xlo); wg_ss64t<8192 + 384, 8192 + 128, DH128>(kv, xlo, xlo); \
            wg_ss8t##Z<8192, OFF_ONES / 16, 0>(zs, xlo, sbd); wg_ss8t<8192 + 128, OFF_ONES / 16, 0>(zs, xlo, sbd); wg_commit(); } while (0)
        G1(13, a0, false, 5); SCHED(); pack_sub<32>(pv, b0); PHI(b0, pk, 0, 4); RET(13);
        G1(14, a0, false, 6); SCHED(); if (!(warp & 2)) stash<16>(stl + 4096, ssw, pv); PHI(b0, pk, 4, 10); RET(14);
        G1(15, a0, false, 7); SCHED(); PHI(b0, pk, 10, 16); RET(15);
        if ((warp & 3) == 0) TS(wg, 2);

        G1(16, a1, true, 0); SCHED(); if (!(warp & 2)) stash<16>(stl, ssw, pk);
        mbar_wait(sb + B_GRDY, 0);
        float g_lo, g_hi;
        uint32_t tag;
        {
            const uint32_t ga = sb + OFF_G + (warp * 16 + (lane >> 2)) * 4;
            asm volatile("ld.shared.f32 %0, [%1];" : "=f"(g_lo) : "r"(ga) : "memory");
            asm volatile("ld.shared.f32 %0, [%1];" : "=f"(g_hi) : "r"(ga + 32) : "memory");
            asm volatile("ld.shared.u32 %0, [%1];" : "=r"(tag) : "r"(sb + OFF_EPOCH) : "memory");
        }
        float* const kvp = g_kvacc + (((tag & 1) * 8 + j) * 4 + (warp & 3)) * 272;
        tag = (tag + 1) & 1;
        const uint32_t m_lo = pack2(1.f - g_lo, 1.f - g_lo), m_hi = pack2(1.f - g_hi, 1.f - g_hi);
        RET(16);
        pin(a0);
        G1(17, a1, true, 1); SCHED(); H_EPI(a0, fh0, 0, 16, 0, 32); RET(17);
        G1(18, a1, true, 2); KV_ROUND(_z); RET2(18);
        G1(19, a1, true, 3); SCHED(); send_h<0, 1>(fh0, hsend); RET(19);
        G1(20, a1, true, 4); SCHED(); if (warp & 2) { stash<16>(stl, ssw, pk); stash<16>(stl + 4096, ssw, pv); } RET(20);
        G1(21, a1, true, 5); KV_ROUND(); RET2(21);
        G1(22, a1, true, 6); RET(22);
        pin(kv); pin(zs);
        G1(23, a1, true, 7); SCHED();
#define KV_RED(W) do { asm volatile("red.global.add.v4.f32 [%0], {%1,%2,%3,%4};" :: "l"(kvp + lane * 4), "f"(kv[8 * W]), "f"(kv[8 * W + 1]), "f"(kv[8 * W + 2]), "f"(kv[8 * W + 3]) : "memory"); \
                       asm volatile("red.global.add.v4.f32 [%0], {%1,%2,%3,%4};" :: "l"(kvp + 128 + lane * 4), "f"(kv[8 * W + 4]), "f"(kv[8 * W + 5]), "f"(kv[8 * W + 6]), "f"(kv[8 * W + 7]) : "memory"); } while (0)
        if ((warp & 3) == 0) KV_RED(0); else if ((warp & 3) == 1) KV_RED(1); else if ((warp & 3) == 2) KV_RED(2); else KV_RED(3);
        if ((lane & 3) == 0) {
            asm volatile("red.global.add.f32 [%0], %1;" :: "l"(kvp + 256 + (lane >> 2)), "f"(zs[0]) : "memory");
            asm volatile("red.global.add.f32 [%0], %1;" :: "l"(kvp + 264 + (lane >> 2)), "f"(zs[2]) : "memory");
        }
        __syncwarp();
        if (lane == 0) mbar_arrive(sb + B_KVDONE);
        RET(23);
        if ((warp & 3) == 0) TS(wg, 3);

        G1(24, a2_, false, 0); SCHED(); send_h<1, 2>(fh0, hsend); RET(24);
        pin(a1);
        G1(25, a2_, false, 1); SCHED(); send_h<2, 3>(fh0, hsend); H_EPI(a1, fh3, 0, 8, 32, 48); RET(25);
        G1(26, a2_, false, 2); SCHED(); send_h<3, 4>(fh0, hsend); SENT_H(0); PHI(a1, fo, 0, 4); RET(26);
        G1(27, a2_, false, 3); SCHED(); send_h<0, 1>(fh3, hsend + 4 * 1024 - (j & 1) * 1020); PHI(a1, fo, 4, 8); RET(27);
        G1(28, a2_, false, 4); SCHED(); send_h<1, 2>(fh3, hsend + 4 * 1024 - (j & 1) * 1020); SENT_H(1); PHI(a1, fo, 8, 12); RET(28);
        G1(29, a2_, false, 5); SCHED(); PHI(a1, fo, 12, 16); RET(29);
        G1(30, a2_, false, 6); RET(30);
        G1(31, a2_, false, 7); RET(31);
        if ((warp & 3) == 0) TS(wg, 4);

        float on[4][12];
#define O_SCALE(h) do { const float s_lo = __fdividef(g_lo, on[h][8] + 1e-6f), s_hi = __fdividef(g_hi, on[h][10] + 1e-6f); \
            const uint32_t sl_ = pack2(s_lo, s_lo), sh_ = pack2(s_hi, s_hi); \
            fo[4 * h] = keep(hmul2(pack2(on[h][0], on[h][1]), sl_)); fo[4 * h + 1] = keep(hmul2(pack2(on[h][2], on[h][3]), sh_)); \
            fo[4 * h + 2] = keep(hmul2(pack2(on[h][4], on[h][5]), sl_)); fo[4 * h + 3] = keep(hmul2(pack2(on[h][6], on[h][7]), sh_)); } while (0)
        uint4* const lsend = g_lx + (size_t)(r * 8 + j) * 2048 + warp * 128 + lane;
        const uint4* const lrecv = g_lx + (size_t)(r * 8 + (j ^ 1)) * 2048 + warp * 128 + lane;
        G1(32, a3, false, 0); RET(32);
        pin(a2_);
        G1(33, a3, false, 1); SCHED(); H_EPI(a2_, fh1, 0, 16, 0, 32); send_h<0, 1>(fh1, hsend + 2 * 1024); RET(33);
        G1(34, a3, false, 2); SCHED(); send_h<1, 3>(fh1, hsend + 2 * 1024); RET(34);
        if (elect) mbar_arrive(sb + B_XFREE);
        G1(35, a3, false, 3); SCHED(); send_h<3, 4>(fh1, hsend + 2 * 1024); SENT_H(2);
        if ((warp & 3) == 0) TS(wg, 5);
        mbar_wait(sb + B_KVRDY, 0);
        if ((warp & 3) == 0) TS(wg, 6);
        wg_fence();
#define O_MMA(h) wg_rs24_z<OFF_STG / 16 + (h) * 48 + (8u << 16), 16>(on[h], fo[4 * (h)], fo[4 * (h) + 1], fo[4 * (h) + 2], fo[4 * (h) + 3], sbd)
        O_MMA(0); O_MMA(1); O_MMA(2); O_MMA(3);
        wg_commit();
        RET2(35);
        G1(36, a3, false, 4); RET(36);
        pin(on[0]); pin(on[1]); pin(on[2]); pin(on[3]);
        release(B_EEMPTY + 16);
        G1(37, a3, false, 5); SCHED(); O_SCALE(0); O_SCALE(1); O_SCALE(2); O_SCALE(3); RET(37);
        if (elect) mbar_arrive(sb + B_XFREE + 8);
        G1(38, a3, false, 6); SCHED(); send_frag<0, 2>(fo, lsend, tag); RET(38);
        release(B_EEMPTY);
        G1(39, a3, false, 7); SCHED(); send_frag<2, 4>(fo, lsend, tag); RET(39);
        release(B_EEMPTY + 8);
        if ((warp & 3) == 0) TS(wg, 7);

#define G2S(S, acc, U) stage_ss<(U) * 1024, S_B(S), false, (S) == 45>(acc, xlo, sbd)
#define G2R(S, acc, F) stage_rs<S_B(S), (S) == 40>(acc, F, sbd)
#define H_WAIT(P) do { mbar_wait(sb + B_XFULL + 8 * (P), 1); if (PROF && tid == 0) TS2(150 + (P)); } while (0)
        const int p = j >> 1, pw = (p & 2) ^ 2;
        const bool own = wg == (p & 1);
        uint4* const pbase = g_part + (size_t)(r * 2 + (j & 1)) * 16384 + (warp & 3) * 256 + lane;

        float p1[64], p2[64];
        uint32_t po[16], ph2[16];
        G2R(40, p1, fo); RET(40);
        release(B_EEMPTY + 24);
        pin(a3);
        H_WAIT(0); G2S(41, p1, 0); SCHED(); H_EPI(a3, fh2, 0, 16, 0, 32); send_frag<0, 2>(fh2, lsend + 1024, tag); RET(41);
        G2S(42, p1, 1); SCHED(); recv_issue(po, lrecv); send_frag<2, 4>(fh2, lsend + 1024, tag); RET(42);
        H_WAIT(4); G2S(43, p1, 4); RET(43);
        G2R(44, p1, fh2); RET(44);
        G2S(45, p2, 0); SCHED(); if (!(EXPT & 2)) recv_check(po, lrecv, tag); recv_issue(ph2, lrecv + 1024); RET(45);
        G2R(46, p1, po); RET(46);
        H_WAIT(2); G2S(47, p1, 2); RET(47);
        G2S(48, p1, 3); SCHED(); if (!(EXPT & 2)) recv_check(ph2, lrecv + 1024, tag); RET(48);
        G2R(49, p1, ph2); RET(49);
        if ((warp & 3) == 0) TS(wg, 8);
        uint32_t sp[32], qa[32], qb[32];
        uint4* const s1 = pbase + (((pw + wg) * 4 + p) << 10);
        G2R(50, p2, fo); RET(50);
        pin(p1);
        G2R(51, p2, po); SCHED(); pack_sub<0>(sp, p1); send_frag<0, 2>(sp, s1, tag); RET(51);
        G2R(52, p2, fh2); SCHED(); send_frag<2, 5>(sp, s1, tag); RET(52);
        if (elect) mbar_arrive(sb + B_XFREE + 16);
        G2R(53, p2, ph2); SCHED(); send_frag<5, 8>(sp, s1, tag); RET(53);
        const uint4* ra = pbase + ((p * 4 + pw) << 10);
        const uint4* rc = pbase + ((p * 4 + (p ^ 1)) << 10);
        if (own) mbar_wait(sb + B_AHEAD, 0);
        G2S(54, p2, 1); RET(54);
        G2S(55, p2, 2); RET(55);
        G2S(56, p2, 3); RET(56);
        G2S(57, p2, 4); SCHED();
        if ((warp & 3) == 0) TS(wg, 9);
#define PART_COPY() do { mbar_wait(sb + B_XFREE + 16, 0); mbar_expect(sb + B_PART, 32768); \
            asm volatile("cp.async.bulk.shared::cluster.global.mbarrier::complete_tx::bytes [%0], [%1], %2, [%3];" \
                         :: "r"(sb + OFF_RING), "l"(ra), "r"(32768), "r"(sb + B_PART) : "memory"); } while (0)
        if (!own && elect) mbar_arrive(sb + B_AHEAD);
        wg_wait<0>();
        pin(p2);
        if ((warp & 3) == 0) TS(wg, 11);
        if (!own) {
            if (COPY_AT == 0 && elect) PART_COPY();
            pack_sub<0>(sp, p2);
            if (COPY_AT == 1 && elect) PART_COPY();
            send_frag<0, 4>(sp, pbase + (((p ^ 1) * 4 + p) << 10), tag);
            if (COPY_AT == 2 && elect) PART_COPY();
            send_frag<4, 8>(sp, pbase + (((p ^ 1) * 4 + p) << 10), tag);
            if (COPY_AT == 3 && elect) PART_COPY();
        } else {
            recv_issue(sp, rc);
            uint32_t f0[16], f1[16];
            pack_sub<0>(f0, p2); pack_sub<32>(f1, p2);
            mbar_wait(sb + B_PART, 0);
            if ((warp & 3) == 0) TS(wg, 10);
            const uint32_t pa = sb + OFF_RING + (warp & 3) * 4096 + lane * 16;
#pragma unroll
            for (int v = 0; v < 8; v++) {
                asm volatile("ld.shared.v4.u32 {%0,%1,%2,%3}, [%4];" : "=r"(qa[4 * v]), "=r"(qa[4 * v + 1]), "=r"(qa[4 * v + 2]), "=r"(qa[4 * v + 3]) : "r"(pa + v * 512) : "memory");
                asm volatile("ld.shared.v4.u32 {%0,%1,%2,%3}, [%4];" : "=r"(qb[4 * v]), "=r"(qb[4 * v + 1]), "=r"(qb[4 * v + 2]), "=r"(qb[4 * v + 3]) : "r"(pa + 16384 + v * 512) : "memory");
            }
            recv_check(qa, ra, tag); recv_check(qb, ra + 1024, tag);
#pragma unroll
            for (int i = 0; i < 32; i++) qa[i] = keep(hadd2(qa[i], qb[i]));
            if ((warp & 3) == 0) TS(wg, 12);
            recv_check(sp, rc, tag);
            if ((warp & 3) == 0) TS(wg, 13);
#pragma unroll
            for (int i = 0; i < 16; i++) { f0[i] = hadd2(hadd2(f0[i], sp[i]), qa[i]); f1[i] = hadd2(hadd2(f1[i], sp[16 + i]), qa[16 + i]); }
            const uint32_t slab = sb + OFF_X + 2 * 16384 + wg * 8192;
            stash<16>(slab + srow, ssw, f0); stash<16>(slab + 16384 + srow, ssw, f1);
            __syncwarp();
            __nv_bfloat16* op = out + (size_t)(r * 128 + warp * 16 + (lane >> 4)) * kD + (j & 1) * 256 + (p & 2) * 64 + (lane & 15) * 8;
#pragma unroll
            for (int i = 0; i < 8; i++) {
                const int row = i * 2 + (lane >> 4);
                uint4 v;
                asm volatile("ld.shared.v4.u32 {%0,%1,%2,%3}, [%4];" : "=r"(v.x), "=r"(v.y), "=r"(v.z), "=r"(v.w)
                             : "r"(slab + (lane & 8) * 2048 + ((warp & 3) * 16 + row) * 128 + (((lane & 7) ^ (row & 7)) << 4)) : "memory");
                *(uint4*)(op + i * 2 * kD) = v;
            }
        }
        if ((warp & 3) == 0) { TS(wg, 14); TSG(wg, 31); }
    }
}

typedef CUresult (*EncodeFn)(CUtensorMap*, CUtensorMapDataType, cuuint32_t, void*, const cuuint64_t*, const cuuint64_t*, const cuuint32_t*,
                             const cuuint32_t*, CUtensorMapInterleave, CUtensorMapSwizzle, CUtensorMapL2promotion, CUtensorMapFloatOOBfill);

static void encode(EncodeFn fn, CUtensorMap* m, int rank, const void* base, const cuuint64_t (&gd)[5], const cuuint64_t (&gs)[4],
                   const cuuint32_t (&bd)[5], CUtensorMapSwizzle sw) {
    cuuint32_t es[5] = {1, 1, 1, 1, 1};
    fn(m, CU_TENSOR_MAP_DATA_TYPE_BFLOAT16, rank, const_cast<void*>(base), gd, gs, bd, es, CU_TENSOR_MAP_INTERLEAVE_NONE, sw,
       CU_TENSOR_MAP_L2_PROMOTION_L2_128B, CU_TENSOR_MAP_FLOAT_OOB_FILL_NONE);
}

extern "C" void kernel_launch(void* const* d_in, const int* in_sizes, int n_in, void* d_out, int out_size) {
    const char* x = (const char*)d_in[0];
    const char* wqkv = (const char*)d_in[1];
    const char* wo = (const char*)d_in[2];
    const char* wg = (const char*)d_in[4];
    const char* wu = (const char*)d_in[5];
    const char* wd = (const char*)d_in[6];
    void* fnp = nullptr;
    cudaDriverEntryPointQueryResult qr;
    cudaGetDriverEntryPoint("cuTensorMapEncodeTiled", &fnp, cudaEnableDefault, &qr);
    EncodeFn fn = (EncodeFn)fnp;
    Maps maps;
    const char* lo = wg < wu ? wg : wu;
    const uint64_t diff = wg < wu ? (uint64_t)(wu - wg) : (uint64_t)(wg - wu);
    const CUtensorMapSwizzle S128 = CU_TENSOR_MAP_SWIZZLE_128B, S64 = CU_TENSOR_MAP_SWIZZLE_64B;
    encode(fn, &maps.x, 2, x, {512, 2048, 1, 1}, {1024, 0, 0}, {64, 128, 1, 1}, S128);
    encode(fn, &maps.gu, 3, lo, {1792, 512, 2, 1}, {3584, diff, 0}, {64, 64, 2, 1}, S128);
    encode(fn, &maps.kv, 3, wqkv, {512, 512, 3, 1}, {3072, 1024, 0}, {64, 64, 2, 1}, S128);
    encode(fn, &maps.q64, 3, wqkv, {32, 512, 48, 1}, {3072, 64, 0}, {32, 64, 2, 1}, S64);
    encode(fn, &maps.gu64, 3, lo, {1792, 512, 2, 1}, {3584, diff, 0}, {32, 64, 2, 1}, S64);
    encode(fn, &maps.wdw, 3, wd, {64, 1792, 8, 1}, {1024, 128, 0}, {64, 64, 2, 1}, S128);
    encode(fn, &maps.wow, 3, wo, {64, 512, 8}, {1024, 128}, {64, 64, 2}, S128);
    encode(fn, &maps.wdp, 5, wd, {512, 2, 4, 4, 56}, {1024, 8192, 2048, 32768}, {64, 2, 4, 4, 2}, S128);
    encode(fn, &maps.wdph, 5, wd, {512, 2, 4, 4, 56}, {1024, 8192, 2048, 32768}, {64, 2, 4, 4, 1}, S128);
    void* hx = nullptr;
    cudaGetSymbolAddress(&hx, g_hx);
    encode(fn, &maps.hx, 2, hx, {64, 16 * 4 * 5 * 128}, {128}, {64, 128}, S128);
    encode(fn, &maps.hx2, 2, hx, {64, 16 * 4 * 5 * 128}, {128}, {64, 256}, S128);
    cudaFuncSetAttribute(fused_kernel, cudaFuncAttributeMaxDynamicSharedMemorySize, SMEM_BYTES);
    cudaLaunchConfig_t cfg = {};
    cfg.gridDim = dim3(128);
    cfg.blockDim = dim3(384);
    cfg.dynamicSmemBytes = SMEM_BYTES;
    cfg.stream = cudaStreamPerThread;
    cudaLaunchAttribute at[1];
    at[0].id = cudaLaunchAttributeClusterDimension;
    at[0].val.clusterDim.x = 2; at[0].val.clusterDim.y = 1; at[0].val.clusterDim.z = 1;
    cfg.attrs = at;
    cfg.numAttrs = MC ? 1 : 0;
    cudaLaunchKernelEx(&cfg, fused_kernel, maps, (const __nv_bfloat16*)d_in[0], (const __nv_bfloat16*)d_in[7], wqkv, lo, lo + diff, wd, wo, (__nv_bfloat16*)d_out);
}
```

```cpp
#include <cuda_runtime.h>
#include <cuda.h>
#include <cuda_bf16.h>
#include <stdint.h>

#define MC 0
#define PFMODE 1
#define PHI_SAT 0
#define EXPT 0
#define COPY_AT 0
#define RX 0
#define PF0 4
#define GDELAY 1
#define PROF 0

namespace {

constexpr int kD = 512;
constexpr uint32_t OFF_X = 0, OFF_STG = 131072, OFF_RING = 147456, OFF_MISC = 229376;
constexpr uint32_t B_FULL = OFF_MISC, B_EMPTY = OFF_MISC + 40, B_XFULL = OFF_MISC + 80;
constexpr uint32_t B_GRDY = OFF_MISC + 152, B_KVDONE = OFF_MISC + 160, B_KVRDY = OFF_MISC + 168;
constexpr uint32_t B_HSENT = OFF_MISC + 176, B_XFREE = OFF_MISC + 200;
constexpr uint32_t OFF_EPOCH = OFF_MISC + 240, OFF_G = OFF_MISC + 256;
constexpr uint32_t B_AHEAD = OFF_MISC + 248, B_PART = OFF_MISC + 232;
constexpr uint32_t OFF_ONES = OFF_MISC + 768;
constexpr uint32_t B_EFULL = OFF_MISC + 896, B_EEMPTY = OFF_MISC + 928;
constexpr uint32_t SMEM_BYTES = OFF_MISC + 960;
constexpr uint32_t SPIN_GLOBAL = 1u << 14;

struct alignas(64) Maps { CUtensorMap x, gu, kv, q64, gu64, wdw, wow, wdp, wdph, hx, hx2; };

}

__device__ uint4 g_part[16 * 2 * 4 * 4 * 1024];
__device__ uint4 g_hx[16 * 4 * 5 * 1024];
__device__ uint4 g_lx[16 * 8 * 2 * 1024];
__device__ unsigned g_hflag[128 * 8];
__device__ uint4 g_gx[16 * 32];
__device__ float g_kvacc[2 * 8 * 4 * 272];
__device__ unsigned g_kvcnt[8 * 32];
__device__ unsigned g_epoch[128];
#define TS(role, idx)
#define TS2(idx)
#define TSG(role, idx)

namespace {

__device__ __forceinline__ void mbar_init(uint32_t bar, uint32_t cnt) { asm volatile("mbarrier.init.shared::cta.b64 [%0], %1;" :: "r"(bar), "r"(cnt) : "memory"); }
__device__ __forceinline__ void mbar_expect(uint32_t bar, uint32_t bytes) { asm volatile("mbarrier.arrive.expect_tx.shared::cta.b64 _, [%0], %1;" :: "r"(bar), "r"(bytes) : "memory"); }
__device__ __forceinline__ void mbar_arrive(uint32_t bar) { asm volatile("mbarrier.arrive.shared::cta.b64 _, [%0];" :: "r"(bar) : "memory"); }
__device__ __forceinline__ void mbar_arrive_cta(uint32_t bar, uint32_t cta) {
    asm volatile("{\n.reg .b32 ra;\nmapa.shared::cluster.u32 ra, %0, %1;\nmbarrier.arrive.shared::cluster.b64 _, [ra];\n}" :: "r"(bar), "r"(cta) : "memory");
}
__device__ __forceinline__ void mbar_wait(uint32_t bar, uint32_t parity) {
    asm volatile("{\n.reg .pred p;\n.reg .u32 c;\n"
                 "mbarrier.try_wait.parity.shared::cta.b64 p, [%0], %1;\n@p bra DONE;\n"
                 "mov.u32 c, 0;\nLAB_WAIT:\nmbarrier.try_wait.parity.shared::cta.b64 p, [%0], %1;\n@p bra DONE;\n"
                 "add.u32 c, c, 1;\nsetp.lt.u32 p, c, 65536;\n@p bra LAB_WAIT;\nDONE:\n}" :: "r"(bar), "r"(parity) : "memory");
}
__device__ __forceinline__ void tma2(uint32_t dst, const CUtensorMap* m, int c0, int c1, uint32_t bar) {
    asm volatile("cp.async.bulk.tensor.2d.shared::cluster.global.mbarrier::complete_tx::bytes [%0], [%1, {%3, %4}], [%2];"
        :: "r"(dst), "l"(m), "r"(bar), "r"(c0), "r"(c1) : "memory");
}
__device__ __forceinline__ void tmaw2(uint32_t dst, const CUtensorMap* m, int c0, int c1, uint32_t bar) {
    tma2(dst, m, c0, c1, bar);
}
__device__ __forceinline__ void tmaw3(uint32_t dst, const CUtensorMap* m, int c0, int c1, int c2, uint32_t bar) {
    asm volatile("cp.async.bulk.tensor.3d.shared::cluster.global.mbarrier::complete_tx::bytes [%0], [%1, {%3, %4, %5}], [%2];"
        :: "r"(dst), "l"(m), "r"(bar), "r"(c0), "r"(c1), "r"(c2) : "memory");
}
__device__ __forceinline__ void tmaw5(uint32_t dst, const CUtensorMap* m, int c0, int c4, uint32_t bar) {
    asm volatile("cp.async.bulk.tensor.5d.shared::cluster.global.mbarrier::complete_tx::bytes [%0], [%1, {%3, %5, %5, %5, %4}], [%2];"
        :: "r"(dst), "l"(m), "r"(bar), "r"(c0), "r"(c4), "r"(0) : "memory");
}
__device__ __forceinline__ void wg_fence() { asm volatile("wgmma.fence.sync.aligned;" ::: "memory"); }
__device__ __forceinline__ void wg_commit() { asm volatile("wgmma.commit_group.sync.aligned;" ::: "memory"); }
template <int N> __device__ __forceinline__ void wg_wait() { asm volatile("wgmma.wait_group.sync.aligned %0;" :: "n"(N) : "memory"); }
template <int N> __device__ __forceinline__ void pin(float (&d)[N]) {
#pragma unroll
    for (int i = 0; i < N; i++) asm volatile("" : "+f"(d[i]) :: "memory");
}
__device__ __forceinline__ uint32_t pack2(float lo, float hi) { uint32_t r; asm("cvt.rn.bf16x2.f32 %0, %1, %2;" : "=r"(r) : "f"(hi), "f"(lo)); return r; }
__device__ __forceinline__ uint32_t keep(uint32_t v) { asm volatile("" : "+r"(v)); return v; }
__device__ __forceinline__ uint32_t hadd2(uint32_t a, uint32_t b) { uint32_t r; asm("add.bf16x2 %0, %1, %2;" : "=r"(r) : "r"(a), "r"(b)); return r; }
__device__ __forceinline__ uint32_t hmul2(uint32_t a, uint32_t b) { uint32_t r; asm("mul.bf16x2 %0, %1, %2;" : "=r"(r) : "r"(a), "r"(b)); return r; }
__device__ __forceinline__ uint32_t phi2(float t0, float t1) {
    float e0, e1;
    asm("ex2.approx.ftz.f32 %0, %1;" : "=f"(e0) : "f"(t0 * 1.4426950408889634f));
    asm("ex2.approx.ftz.f32 %0, %1;" : "=f"(e1) : "f"(t1 * 1.4426950408889634f));
    uint32_t e = pack2(e0, e1), t = pack2(t0, t1), r;
    asm("min.bf16x2 %0, %0, %1;" : "+r"(e) : "r"(0x3f803f80u));
    asm("max.bf16x2 %0, %0, %1;" : "+r"(t) : "r"(0x35863586u));
    asm("add.bf16x2 %0, %1, %2;" : "=r"(r) : "r"(e), "r"(t));
    return r;
}
__device__ __forceinline__ void stsm4(uint32_t a, uint32_t r0, uint32_t r1, uint32_t r2, uint32_t r3) {
    asm volatile("stmatrix.sync.aligned.m8n8.x4.shared.b16 [%0], {%1,%2,%3,%4};" :: "r"(a), "r"(r0), "r"(r1), "r"(r2), "r"(r3) : "memory");
}
__device__ __forceinline__ float bf_lo(uint32_t w) { return __uint_as_float(w << 16); }
__device__ __forceinline__ float bf_hi(uint32_t w) { return __uint_as_float(w & 0xffff0000u); }
__device__ __forceinline__ void st_pkt(uint4* p, uint32_t w0, uint32_t w1, uint32_t w2, uint32_t w3) {
    asm volatile("{\n.reg .b64 lo, hi;\n.reg .b128 v;\nmov.b64 lo, {%1, %2};\nmov.b64 hi, {%3, %4};\nmov.b128 v, {lo, hi};\nst.relaxed.gpu.global.b128 [%0], v;\n}"
        :: "l"(p), "r"(w0), "r"(w1), "r"(w2), "r"(w3) : "memory");
}
__device__ __forceinline__ void ld_pkt(const uint4* p, uint32_t& w0, uint32_t& w1, uint32_t& w2, uint32_t& w3) {
    asm volatile("{\n.reg .b64 lo, hi;\n.reg .b128 v;\nld.relaxed.gpu.global.b128 v, [%4];\nmov.b128 {lo, hi}, v;\nmov.b64 {%0, %1}, lo;\nmov.b64 {%2, %3}, hi;\n}"
        : "=r"(w0), "=r"(w1), "=r"(w2), "=r"(w3) : "l"(p) : "memory");
}

template <uint32_t AO, uint32_t BO, uint32_t BH> __device__ __forceinline__ void wg_ss128(float (&d)[64], uint32_t ab, uint32_t bb) {
    asm volatile("{\n.reg .b64 da, db;\n.reg .b32 ta, tb, th, ah;\nadd.u32 ta, %64, %66;\nadd.u32 tb, %65, %67;\nmov.b32 th, %68;\nmov.b32 ah, 0x40000040;\nmov.b64 da, {ta, ah};\nmov.b64 db, {tb, th};\n"
        "wgmma.mma_async.sync.aligned.m64n128k16.f32.bf16.bf16 {%0,%1,%2,%3,%4,%5,%6,%7,%8,%9,%10,%11,%12,%13,%14,%15,%16,%17,%18,%19,%20,%21,%22,%23,%24,%25,%26,%27,%28,%29,%30,%31,%32,%33,%34,%35,%36,%37,%38,%39,%40,%41,%42,%43,%44,%45,%46,%47,%48,%49,%50,%51,%52,%53,%54,%55,%56,%57,%58,%59,%60,%61,%62,%63}, da, db, 1, 1, 1, 0, 1;\n}\n"
        : "+f"(d[0]),"+f"(d[1]),"+f"(d[2]),"+f"(d[3]),"+f"(d[4]),"+f"(d[5]),"+f"(d[6]),"+f"(d[7]),"+f"(d[8]),"+f"(d[9]),"+f"(d[10]),"+f"(d[11]),"+f"(d[12]),"+f"(d[13]),"+f"(d[14]),"+f"(d[15]),"+f"(d[16]),"+f"(d[17]),"+f"(d[18]),"+f"(d[19]),"+f"(d[20]),"+f"(d[21]),"+f"(d[22]),"+f"(d[23]),"+f"(d[24]),"+f"(d[25]),"+f"(d[26]),"+f"(d[27]),"+f"(d[28]),"+f"(d[29]),"+f"(d[30]),"+f"(d[31]),"+f"(d[32]),"+f"(d[33]),"+f"(d[34]),"+f"(d[35]),"+f"(d[36]),"+f"(d[37]),"+f"(d[38]),"+f"(d[39]),"+f"(d[40]),"+f"(d[41]),"+f"(d[42]),"+f"(d[43]),"+f"(d[44]),"+f"(d[45]),"+f"(d[46]),"+f"(d[47]),"+f"(d[48]),"+f"(d[49]),"+f"(d[50]),"+f"(d[51]),"+f"(d[52]),"+f"(d[53]),"+f"(d[54]),"+f"(d[55]),"+f"(d[56]),"+f"(d[57]),"+f"(d[58]),"+f"(d[59]),"+f"(d[60]),"+f"(d[61]),"+f"(d[62]),"+f"(d[63])
        : "r"(ab), "r"(bb), "n"(AO), "n"(BO), "n"(BH));
}
template <uint32_t AO, uint32_t BO, uint32_t BH> __device__ __forceinline__ void wg_ss128_z(float (&d)[64], uint32_t ab, uint32_t bb) {
    asm volatile("{\n.reg .b64 da, db;\n.reg .b32 ta, tb, th, ah;\nadd.u32 ta, %64, %66;\nadd.u32 tb, %65, %67;\nmov.b32 th, %68;\nmov.b32 ah, 0x40000040;\nmov.b64 da, {ta, ah};\nmov.b64 db, {tb, th};\n"
        "wgmma.mma_async.sync.aligned.m64n128k16.f32.bf16.bf16 {%0,%1,%2,%3,%4,%5,%6,%7,%8,%9,%10,%11,%12,%13,%14,%15,%16,%17,%18,%19,%20,%21,%22,%23,%24,%25,%26,%27,%28,%29,%30,%31,%32,%33,%34,%35,%36,%37,%38,%39,%40,%41,%42,%43,%44,%45,%46,%47,%48,%49,%50,%51,%52,%53,%54,%55,%56,%57,%58,%59,%60,%61,%62,%63}, da, db, 0, 1, 1, 0, 1;\n}\n"
        : "=f"(d[0]),"=f"(d[1]),"=f"(d[2]),"=f"(d[3]),"=f"(d[4]),"=f"(d[5]),"=f"(d[6]),"=f"(d[7]),"=f"(d[8]),"=f"(d[9]),"=f"(d[10]),"=f"(d[11]),"=f"(d[12]),"=f"(d[13]),"=f"(d[14]),"=f"(d[15]),"=f"(d[16]),"=f"(d[17]),"=f"(d[18]),"=f"(d[19]),"=f"(d[20]),"=f"(d[21]),"=f"(d[22]),"=f"(d[23]),"=f"(d[24]),"=f"(d[25]),"=f"(d[26]),"=f"(d[27]),"=f"(d[28]),"=f"(d[29]),"=f"(d[30]),"=f"(d[31]),"=f"(d[32]),"=f"(d[33]),"=f"(d[34]),"=f"(d[35]),"=f"(d[36]),"=f"(d[37]),"=f"(d[38]),"=f"(d[39]),"=f"(d[40]),"=f"(d[41]),"=f"(d[42]),"=f"(d[43]),"=f"(d[44]),"=f"(d[45]),"=f"(d[46]),"=f"(d[47]),"=f"(d[48]),"=f"(d[49]),"=f"(d[50]),"=f"(d[51]),"=f"(d[52]),"=f"(d[53]),"=f"(d[54]),"=f"(d[55]),"=f"(d[56]),"=f"(d[57]),"=f"(d[58]),"=f"(d[59]),"=f"(d[60]),"=f"(d[61]),"=f"(d[62]),"=f"(d[63])
        : "r"(ab), "r"(bb), "n"(AO), "n"(BO), "n"(BH));
}
template <uint32_t BO, uint32_t BH> __device__ __forceinline__ void wg_rs128(float (&d)[64], uint32_t a0, uint32_t a1, uint32_t a2, uint32_t a3, uint32_t bb) {
    asm volatile("{\n.reg .b64 db;\n.reg .b32 tb, th;\nadd.u32 tb, %68, %69;\nmov.b32 th, %70;\nmov.b64 db, {tb, th};\n"
        "wgmma.mma_async.sync.aligned.m64n128k16.f32.bf16.bf16 {%0,%1,%2,%3,%4,%5,%6,%7,%8,%9,%10,%11,%12,%13,%14,%15,%16,%17,%18,%19,%20,%21,%22,%23,%24,%25,%26,%27,%28,%29,%30,%31,%32,%33,%34,%35,%36,%37,%38,%39,%40,%41,%42,%43,%44,%45,%46,%47,%48,%49,%50,%51,%52,%53,%54,%55,%56,%57,%58,%59,%60,%61,%62,%63}, {%64,%65,%66,%67}, db, 1, 1, 1, 1;\n}\n"
        : "+f"(d[0]),"+f"(d[1]),"+f"(d[2]),"+f"(d[3]),"+f"(d[4]),"+f"(d[5]),"+f"(d[6]),"+f"(d[7]),"+f"(d[8]),"+f"(d[9]),"+f"(d[10]),"+f"(d[11]),"+f"(d[12]),"+f"(d[13]),"+f"(d[14]),"+f"(d[15]),"+f"(d[16]),"+f"(d[17]),"+f"(d[18]),"+f"(d[19]),"+f"(d[20]),"+f"(d[21]),"+f"(d[22]),"+f"(d[23]),"+f"(d[24]),"+f"(d[25]),"+f"(d[26]),"+f"(d[27]),"+f"(d[28]),"+f"(d[29]),"+f"(d[30]),"+f"(d[31]),"+f"(d[32]),"+f"(d[33]),"+f"(d[34]),"+f"(d[35]),"+f"(d[36]),"+f"(d[37]),"+f"(d[38]),"+f"(d[39]),"+f"(d[40]),"+f"(d[41]),"+f"(d[42]),"+f"(d[43]),"+f"(d[44]),"+f"(d[45]),"+f"(d[46]),"+f"(d[47]),"+f"(d[48]),"+f"(d[49]),"+f"(d[50]),"+f"(d[51]),"+f"(d[52]),"+f"(d[53]),"+f"(d[54]),"+f"(d[55]),"+f"(d[56]),"+f"(d[57]),"+f"(d[58]),"+f"(d[59]),"+f"(d[60]),"+f"(d[61]),"+f"(d[62]),"+f"(d[63])
        : "r"(a0), "r"(a1), "r"(a2), "r"(a3), "r"(bb), "n"(BO), "n"(BH));
}
template <uint32_t BO, uint32_t BH> __device__ __forceinline__ void wg_rs128_z(float (&d)[64], uint32_t a0, uint32_t a1, uint32_t a2, uint32_t a3, uint32_t bb) {
    asm volatile("{\n.reg .b64 db;\n.reg .b32 tb, th;\nadd.u32 tb, %68, %69;\nmov.b32 th, %70;\nmov.b64 db, {tb, th};\n"
        "wgmma.mma_async.sync.aligned.m64n128k16.f32.bf16.bf16 {%0,%1,%2,%3,%4,%5,%6,%7,%8,%9,%10,%11,%12,%13,%14,%15,%16,%17,%18,%19,%20,%21,%22,%23,%24,%25,%26,%27,%28,%29,%30,%31,%32,%33,%34,%35,%36,%37,%38,%39,%40,%41,%42,%43,%44,%45,%46,%47,%48,%49,%50,%51,%52,%53,%54,%55,%56,%57,%58,%59,%60,%61,%62,%63}, {%64,%65,%66,%67}, db, 0, 1, 1, 1;\n}\n"
        : "=f"(d[0]),"=f"(d[1]),"=f"(d[2]),"=f"(d[3]),"=f"(d[4]),"=f"(d[5]),"=f"(d[6]),"=f"(d[7]),"=f"(d[8]),"=f"(d[9]),"=f"(d[10]),"=f"(d[11]),"=f"(d[12]),"=f"(d[13]),"=f"(d[14]),"=f"(d[15]),"=f"(d[16]),"=f"(d[17]),"=f"(d[18]),"=f"(d[19]),"=f"(d[20]),"=f"(d[21]),"=f"(d[22]),"=f"(d[23]),"=f"(d[24]),"=f"(d[25]),"=f"(d[26]),"=f"(d[27]),"=f"(d[28]),"=f"(d[29]),"=f"(d[30]),"=f"(d[31]),"=f"(d[32]),"=f"(d[33]),"=f"(d[34]),"=f"(d[35]),"=f"(d[36]),"=f"(d[37]),"=f"(d[38]),"=f"(d[39]),"=f"(d[40]),"=f"(d[41]),"=f"(d[42]),"=f"(d[43]),"=f"(d[44]),"=f"(d[45]),"=f"(d[46]),"=f"(d[47]),"=f"(d[48]),"=f"(d[49]),"=f"(d[50]),"=f"(d[51]),"=f"(d[52]),"=f"(d[53]),"=f"(d[54]),"=f"(d[55]),"=f"(d[56]),"=f"(d[57]),"=f"(d[58]),"=f"(d[59]),"=f"(d[60]),"=f"(d[61]),"=f"(d[62]),"=f"(d[63])
        : "r"(a0), "r"(a1), "r"(a2), "r"(a3), "r"(bb), "n"(BO), "n"(BH));
}
template <uint32_t AO, uint32_t BO, uint32_t BH> __device__ __forceinline__ void wg_ss64t(float (&d)[32], uint32_t ab, uint32_t bb) {
    asm volatile("{\n.reg .b64 da, db;\n.reg .b32 ta, tb, th, ah;\nadd.u32 ta, %32, %34;\nadd.u32 tb, %33, %35;\nmov.b32 th, %36;\nmov.b32 ah, 0x40000040;\nmov.b64 da, {ta, ah};\nmov.b64 db, {tb, th};\n"
        "wgmma.mma_async.sync.aligned.m64n64k16.f32.bf16.bf16 {%0,%1,%2,%3,%4,%5,%6,%7,%8,%9,%10,%11,%12,%13,%14,%15,%16,%17,%18,%19,%20,%21,%22,%23,%24,%25,%26,%27,%28,%29,%30,%31}, da, db, 1, 1, 1, 1, 1;\n}\n"
        : "+f"(d[0]),"+f"(d[1]),"+f"(d[2]),"+f"(d[3]),"+f"(d[4]),"+f"(d[5]),"+f"(d[6]),"+f"(d[7]),"+f"(d[8]),"+f"(d[9]),"+f"(d[10]),"+f"(d[11]),"+f"(d[12]),"+f"(d[13]),"+f"(d[14]),"+f"(d[15]),"+f"(d[16]),"+f"(d[17]),"+f"(d[18]),"+f"(d[19]),"+f"(d[20]),"+f"(d[21]),"+f"(d[22]),"+f"(d[23]),"+f"(d[24]),"+f"(d[25]),"+f"(d[26]),"+f"(d[27]),"+f"(d[28]),"+f"(d[29]),"+f"(d[30]),"+f"(d[31])
        : "r"(ab), "r"(bb), "n"(AO), "n"(BO), "n"(BH));
}
template <uint32_t AO, uint32_t BO, uint32_t BH> __device__ __forceinline__ void wg_ss64t_z(float (&d)[32], uint32_t ab, uint32_t bb) {
    asm volatile("{\n.reg .b64 da, db;\n.reg .b32 ta, tb, th, ah;\nadd.u32 ta, %32, %34;\nadd.u32 tb, %33, %35;\nmov.b32 th, %36;\nmov.b32 ah, 0x40000040;\nmov.b64 da, {ta, ah};\nmov.b64 db, {tb, th};\n"
        "wgmma.mma_async.sync.aligned.m64n64k16.f32.bf16.bf16 {%0,%1,%2,%3,%4,%5,%6,%7,%8,%9,%10,%11,%12,%13,%14,%15,%16,%17,%18,%19,%20,%21,%22,%23,%24,%25,%26,%27,%28,%29,%30,%31}, da, db, 0, 1, 1, 1, 1;\n}\n"
        : "=f"(d[0]),"=f"(d[1]),"=f"(d[2]),"=f"(d[3]),"=f"(d[4]),"=f"(d[5]),"=f"(d[6]),"=f"(d[7]),"=f"(d[8]),"=f"(d[9]),"=f"(d[10]),"=f"(d[11]),"=f"(d[12]),"=f"(d[13]),"=f"(d[14]),"=f"(d[15]),"=f"(d[16]),"=f"(d[17]),"=f"(d[18]),"=f"(d[19]),"=f"(d[20]),"=f"(d[21]),"=f"(d[22]),"=f"(d[23]),"=f"(d[24]),"=f"(d[25]),"=f"(d[26]),"=f"(d[27]),"=f"(d[28]),"=f"(d[29]),"=f"(d[30]),"=f"(d[31])
        : "r"(ab), "r"(bb), "n"(AO), "n"(BO), "n"(BH));
}
template <uint32_t AO, uint32_t BO, uint32_t BH> __device__ __forceinline__ void wg_ss8t(float (&d)[4], uint32_t ab, uint32_t bb) {
    asm volatile("{\n.reg .b64 da, db;\n.reg .b32 ta, tb, th, ah;\nadd.u32 ta, %4, %6;\nadd.u32 tb, %5, %7;\nmov.b32 th, %8;\nmov.b32 ah, 0x40000040;\nmov.b64 da, {ta, ah};\nmov.b64 db, {tb, th};\n"
        "wgmma.mma_async.sync.aligned.m64n8k16.f32.bf16.bf16 {%0,%1,%2,%3}, da, db, 1, 1, 1, 1, 0;\n}\n"
        : "+f"(d[0]),"+f"(d[1]),"+f"(d[2]),"+f"(d[3])
        : "r"(ab), "r"(bb), "n"(AO), "n"(BO), "n"(BH));
}
template <uint32_t AO, uint32_t BO, uint32_t BH> __device__ __forceinline__ void wg_ss8t_z(float (&d)[4], uint32_t ab, uint32_t bb) {
    asm volatile("{\n.reg .b64 da, db;\n.reg .b32 ta, tb, th, ah;\nadd.u32 ta, %4, %6;\nadd.u32 tb, %5, %7;\nmov.b32 th, %8;\nmov.b32 ah, 0x40000040;\nmov.b64 da, {ta, ah};\nmov.b64 db, {tb, th};\n"
        "wgmma.mma_async.sync.aligned.m64n8k16.f32.bf16.bf16 {%0,%1,%2,%3}, da, db, 0, 1, 1, 1, 0;\n}\n"
        : "=f"(d[0]),"=f"(d[1]),"=f"(d[2]),"=f"(d[3])
        : "r"(ab), "r"(bb), "n"(AO), "n"(BO), "n"(BH));
}
template <uint32_t BO, uint32_t BH> __device__ __forceinline__ void wg_rs24_z(float (&d)[12], uint32_t a0, uint32_t a1, uint32_t a2, uint32_t a3, uint32_t bb) {
    asm volatile("{\n.reg .b64 db;\n.reg .b32 tb, th;\nadd.u32 tb, %16, %17;\nmov.b32 th, %18;\nmov.b64 db, {tb, th};\n"
        "wgmma.mma_async.sync.aligned.m64n24k16.f32.bf16.bf16 {%0,%1,%2,%3,%4,%5,%6,%7,%8,%9,%10,%11}, {%12,%13,%14,%15}, db, 0, 1, 1, 0;\n}\n"
        : "=f"(d[0]),"=f"(d[1]),"=f"(d[2]),"=f"(d[3]),"=f"(d[4]),"=f"(d[5]),"=f"(d[6]),"=f"(d[7]),"=f"(d[8]),"=f"(d[9]),"=f"(d[10]),"=f"(d[11])
        : "r"(a0), "r"(a1), "r"(a2), "r"(a3), "r"(bb), "n"(BO), "n"(BH));
}

constexpr uint32_t DH128 = 64u | 0x40000000u;
constexpr uint32_t DH64 = 32u | 0x80000000u;
constexpr uint32_t LBO4K = (4096u >> 4) << 16, LBO8K = (8192u >> 4) << 16, LBO1 = 1u << 16;

template <uint32_t AO, uint32_t BO, bool SW64, bool FIRST> __device__ __forceinline__ void stage_ss(float (&acc)[64], uint32_t ab, uint32_t bb) {
    constexpr uint32_t KS = SW64 ? 64 : 128, BH = SW64 ? DH64 : DH128, B0 = BO + (SW64 ? LBO4K : LBO8K);
    wg_fence();
    if (FIRST) wg_ss128_z<AO, B0, BH>(acc, ab, bb); else wg_ss128<AO, B0, BH>(acc, ab, bb);
    wg_ss128<AO + 2, B0 + KS, BH>(acc, ab, bb);
    wg_ss128<AO + 4, B0 + 2 * KS, BH>(acc, ab, bb);
    wg_ss128<AO + 6, B0 + 3 * KS, BH>(acc, ab, bb);
    wg_commit();
}
template <uint32_t BO, bool FIRST> __device__ __forceinline__ void stage_rs(float (&acc)[64], const uint32_t (&f)[16], uint32_t bb) {
    wg_fence();
    if (FIRST) wg_rs128_z<BO + LBO8K, DH128>(acc, f[0], f[1], f[2], f[3], bb); else wg_rs128<BO + LBO8K, DH128>(acc, f[0], f[1], f[2], f[3], bb);
    wg_rs128<BO + LBO8K + 128, DH128>(acc, f[4], f[5], f[6], f[7], bb);
    wg_rs128<BO + LBO8K + 256, DH128>(acc, f[8], f[9], f[10], f[11], bb);
    wg_rs128<BO + LBO8K + 384, DH128>(acc, f[12], f[13], f[14], f[15], bb);
    wg_commit();
}

template <int N> __device__ __forceinline__ void stash(uint32_t base, uint32_t sw, const uint32_t (&f)[N]) {
#pragma unroll
    for (int t = 0; t < N / 4; t++) stsm4(base + ((sw ^ (2 * t)) << 4), f[4 * t], f[4 * t + 1], f[4 * t + 2], f[4 * t + 3]);
}

template <int V0, int V1, int N> __device__ __forceinline__ void send_frag(const uint32_t (&f)[N], uint4* p, uint32_t tag) {
#pragma unroll
    for (int v = V0; v < V1; v++) st_pkt(p + v * 32, (f[4 * v] & ~1u) | tag, f[4 * v + 1], f[4 * v + 2], f[4 * v + 3]);
}
template <int V0, int V1, int N> __device__ __forceinline__ void send_h(const uint32_t (&f)[N], uint4* p) {
#pragma unroll
    for (int v = V0; v < V1; v++) {
        const int h = v >> 1, hi = v & 1;
        asm volatile("st.global.v4.u32 [%0], {%1,%2,%3,%4};" :: "l"(p + 4 * h + 64 * hi),
                     "r"(f[8 * h + hi]), "r"(f[8 * h + 2 + hi]), "r"(f[8 * h + 4 + hi]), "r"(f[8 * h + 6 + hi]) : "memory");
    }
}
template <int O, int N, int M> __device__ __forceinline__ void pack_sub(uint32_t (&f)[N], const float (&acc)[M]) {
#pragma unroll
    for (int i = 0; i < N; i++) f[i] = keep(pack2(acc[O + 2 * i], acc[O + 2 * i + 1]));
}
template <int N> __device__ __forceinline__ void recv_issue(uint32_t (&q)[N], const uint4* p) {
#pragma unroll
    for (int v = 0; v < N / 4; v++) ld_pkt(p + v * 32, q[4 * v], q[4 * v + 1], q[4 * v + 2], q[4 * v + 3]);
}
template <int N> __device__ __forceinline__ void recv_check(uint32_t (&q)[N], const uint4* p, uint32_t tag) {
    uint32_t it = 0;
    while (true) {
        uint32_t bad = 0;
#pragma unroll
        for (int v = 0; v < N / 4; v++) bad |= q[4 * v] ^ tag;
        if (__all_sync(0xffffffffu, (bad & 1u) == 0) || ++it > SPIN_GLOBAL) break;
        recv_issue(q, p);
    }
}
}

__global__ void __launch_bounds__(384, 1)
fused_kernel(const __grid_constant__ Maps maps, const __nv_bfloat16* __restrict__ xg, const __nv_bfloat16* __restrict__ gate_w,
             const char* __restrict__ pf_qkv, const char* __restrict__ pf_g, const char* __restrict__ pf_u,
             const char* __restrict__ pf_d, const char* __restrict__ pf_o, __nv_bfloat16* __restrict__ out) {
    extern __shared__ __align__(1024) uint8_t smem_raw[];
    const uint32_t sb = (uint32_t)__cvta_generic_to_shared(smem_raw);
    const int tid = threadIdx.x, lane = tid & 31;
    const int warp = __shfl_sync(0xffffffffu, tid >> 5, 0);
    const int j = (blockIdx.x >> 1) & 7;
    const int r = (((blockIdx.x >> 4) << 1) | (blockIdx.x & 1)) ^ RX;
    const uint32_t rank = blockIdx.x & 1;

    if (warp == 0) { TSG(0, 30); TS(0, 0); }
    if (tid == 256) {
        mbar_init(sb + B_XFULL, 1); mbar_init(sb + B_FULL, 1); mbar_init(sb + B_FULL + 8, 1);
        asm volatile("fence.mbarrier_init.release.cluster;" ::: "memory");
        TS2(0);
        mbar_expect(sb + B_FULL, 16384);
        tmaw3(sb + OFF_RING, &maps.kv, 64 * j, 0, 1, sb + B_FULL);
        mbar_expect(sb + B_XFULL, 16384);
        tma2(sb + OFF_X, &maps.x, 0, r * 128, sb + B_XFULL);
        TS2(1);
        mbar_expect(sb + B_FULL + 8, 16384);
        tmaw3(sb + OFF_RING + 16384, &maps.gu, 224 * j, 0, 0, sb + B_FULL + 8);
    } else if (tid == 352) {
        for (int i = 0; i < 5; i++) { if (i > 1) mbar_init(sb + B_FULL + 8 * i, 1); mbar_init(sb + B_EMPTY + 8 * i, MC ? 4 : 2); }
        for (int i = 1; i < 9; i++) mbar_init(sb + B_XFULL + 8 * i, 1);
        asm volatile("fence.mbarrier_init.release.cluster;" ::: "memory");
    } else if (tid == 288) {
        for (int i = 0; i < 3; i++) mbar_init(sb + B_HSENT + 8 * i, 8);
        for (int i = 0; i < 4; i++) { mbar_init(sb + B_EFULL + 8 * i, 1); mbar_init(sb + B_EEMPTY + 8 * i, MC ? 4 : 2); }
        mbar_init(sb + B_XFREE, 2); mbar_init(sb + B_XFREE + 8, 2); mbar_init(sb + B_XFREE + 16, 2);
        mbar_init(sb + B_AHEAD, 1); mbar_init(sb + B_PART, 1); mbar_init(sb + B_GRDY, 1); mbar_init(sb + B_KVDONE, 8); mbar_init(sb + B_KVRDY, 2);
        asm volatile("fence.mbarrier_init.release.cluster;" ::: "memory");
    } else if (warp == 10 && lane < 11) {
        asm volatile("prefetch.tensormap [%0];" :: "l"(&maps.x + lane) : "memory");
    }
    __syncthreads();

    if (warp >= 8) {
        asm volatile("setmaxnreg.dec.sync.aligned.u32 56;");
        if (warp == 8) {
            if (lane == 0) {
                int slot = MC ? 0 : 2, ph = 1;
                uint32_t full, dst;
                if (!MC) { mbar_expect(sb + B_XFULL + 8, 16384); tma2(sb + OFF_X + 16384, &maps.x, 64, r * 128, sb + B_XFULL + 8); }
#define P_BEGIN(S, BYTES) full = sb + B_FULL + 8 * slot; dst = sb + OFF_RING + slot * 16384; \
                mbar_wait(sb + B_EMPTY + 8 * slot, ph); TS2(S); mbar_expect(full, BYTES); if (!MC || (((S) ^ rank) & 1) == 0)
#define P_END() if (++slot == 5) { slot = 0; ph ^= 1; }
                for (int s = MC ? 0 : 2; s < 16; s++) {
                    const int kb = (int)(0x7654763542312100ull >> (4 * s)) & 15;
                    P_BEGIN(s, 16384) {
                        if ((0x0DADu >> s) & 1) tmaw3(dst, &maps.kv, 64 * j, 64 * kb, 1, full);
                        else tmaw3(dst, &maps.gu, 224 * j, 64 * kb, 0, full);
                    }
                    const int xb = (int)(0x0000000765403210ull >> (4 * s)) & 15;
                    if (xb) { mbar_expect(sb + B_XFULL + 8 * xb, 16384); tma2(sb + OFF_X + xb * 16384, &maps.x, 64 * xb, r * 128, sb + B_XFULL + 8 * xb); }
                    P_END()
                }
                for (int s = 0; s < 24; s++) {
                    P_BEGIN(16 + s, 16384) {
                        if (s < 8) {
                            tmaw3(dst, &maps.q64, 0, 64 * s, 2 * j, full);
                            tmaw3(dst + 8192, &maps.gu64, 224 * j + 192, 64 * s, 0, full);
                        } else {
                            tmaw3(dst, &maps.gu, 224 * j + 64 * (s >> 3), 64 * (s & 7), 0, full);
                        }
                    }
                    P_END()
                }
                const int p = j >> 1;
#pragma unroll 1
                for (int t = 0; t < 18; t++) {
                    const int q = t >= 9, sl = (int)(0x846352107ull >> (4 * (t - 9 * q))) & 15;
                    const int u = (int)((q ? 0x432186758ull : 0x327064105ull) >> (4 * (t - 9 * q))) & 15;
                    const int cw = (j & 1) * 4 + ((p & 2) ^ ((t == 5 || t > 9) ? 0 : 2)), cc = 64 * cw;
                    if (sl < 5) {
                        full = sb + B_FULL + 8 * sl; dst = sb + OFF_RING + sl * 16384;
                        mbar_wait(sb + B_EMPTY + 8 * sl, q ^ 1);
                    } else {
                        full = sb + B_EFULL + 8 * (sl - 5); dst = sb + OFF_X + (sl == 7 ? 8 : sl == 8 ? 7 : sl) * 16384;
                        mbar_wait(sb + B_EEMPTY + 8 * (sl - 5), q);
                    }
                    TS2(40 + t);
                    mbar_expect(full, 16384);
                    if (!MC || ((t ^ rank) & 1) == 0) {
                        if (u == 4) {
                            tmaw5(dst, &maps.wdph, cc, 14 * p + 6, full); tmaw5(dst + 4096, &maps.wdph, cc, 14 * p + 13, full);
                            tmaw5(dst + 8192, &maps.wdph, cc + 64, 14 * p + 6, full); tmaw5(dst + 12288, &maps.wdph, cc + 64, 14 * p + 13, full);
                        } else if (u > 4) {
                            const int js = u > 6 ? j ^ 1 : j;
                            tmaw3(dst, (u & 1) ? &maps.wow : &maps.wdw, 0, (u & 1) ? 64 * js : 224 * js + 128, cw, full);
                        } else {
                            const int g = 14 * p + 7 * (u & 1) + (u & 2);
                            tmaw5(dst, &maps.wdp, cc, g, full); tmaw5(dst + 8192, &maps.wdp, cc + 64, g, full);
                        }
                    }
                }
            }
        } else if (warp < 11) {
            const int hx = warp - 9;
            uint32_t epoch;
            asm volatile("ld.relaxed.gpu.global.u32 %0, [%1];" : "=r"(epoch) : "l"(g_epoch + blockIdx.x) : "memory");
            {
                const uint4* xr = (const uint4*)(xg + (size_t)(r * 128 + j * 16 + hx * 8) * kD) + lane;
                const uint4 wa = __ldg((const uint4*)gate_w + lane), wb = __ldg((const uint4*)gate_w + 32 + lane);
                const uint32_t tag = (epoch + 1) & 1;
                uint4* gp = g_gx + r * 32;
                if (lane < 2) st_pkt(gp + j * 4 + hx * 2 + lane, tag ^ 1, 0, 0, 0);
                float s[8];
                if (GDELAY) mbar_wait(sb + B_XFULL, 0);
#pragma unroll
                for (int i0 = 0; i0 < 8; i0 += 4) {
                    uint4 va[4], vb[4];
#pragma unroll
                    for (int i = 0; i < 4; i++) { va[i] = __ldg(xr + (i0 + i) * 64); vb[i] = __ldg(xr + (i0 + i) * 64 + 32); }
#pragma unroll
                    for (int i = 0; i < 4; i++) {
                        float t0 = bf_lo(va[i].x) * bf_lo(wa.x), t1 = bf_hi(va[i].x) * bf_hi(wa.x);
                        t0 = fmaf(bf_lo(va[i].y), bf_lo(wa.y), t0); t1 = fmaf(bf_hi(va[i].y), bf_hi(wa.y), t1);
                        t0 = fmaf(bf_lo(va[i].z), bf_lo(wa.z), t0); t1 = fmaf(bf_hi(va[i].z), bf_hi(wa.z), t1);
                        t0 = fmaf(bf_lo(va[i].w), bf_lo(wa.w), t0); t1 = fmaf(bf_hi(va[i].w), bf_hi(wa.w), t1);
                        t0 = fmaf(bf_lo(vb[i].x), bf_lo(wb.x), t0); t1 = fmaf(bf_hi(vb[i].x), bf_hi(wb.x), t1);
                        t0 = fmaf(bf_lo(vb[i].y), bf_lo(wb.y), t0); t1 = fmaf(bf_hi(vb[i].y), bf_hi(wb.y), t1);
                        t0 = fmaf(bf_lo(vb[i].z), bf_lo(wb.z), t0); t1 = fmaf(bf_hi(vb[i].z), bf_hi(wb.z), t1);
                        t0 = fmaf(bf_lo(vb[i].w), bf_lo(wb.w), t0); t1 = fmaf(bf_hi(vb[i].w), bf_hi(wb.w), t1);
                        s[i0 + i] = t0 + t1;
                    }
                }
#pragma unroll
                for (int i = 0; i < 8; i++) {
#pragma unroll
                    for (int o = 16; o; o >>= 1) s[i] += __shfl_xor_sync(0xffffffffu, s[i], o);
                    s[i] = 1.f / (1.f + __expf(-s[i]));
                }
                if (lane < 2) {
                    const float v0 = lane ? s[4] : s[0], v1 = lane ? s[5] : s[1], v2 = lane ? s[6] : s[2], v3 = lane ? s[7] : s[3];
                    st_pkt(gp + j * 4 + hx * 2 + lane, (__float_as_uint(v0) & ~1u) | tag, __float_as_uint(v1), __float_as_uint(v2), __float_as_uint(v3));
                }
                if (hx == 1) {
                    asm volatile("st.shared.u32 [%0], %1;" :: "r"(sb + OFF_ONES + lane * 4), "r"(0x3f803f80u) : "memory");
                    asm volatile("fence.proxy.async.shared::cta;" ::: "memory");
                }
                asm volatile("bar.sync 3, 96;" ::: "memory");
                if (hx == 0) {
                    uint32_t q[4];
                    recv_issue(q, gp + lane);
                    recv_check(q, gp + lane, tag);
                    asm volatile("st.shared.v4.u32 [%0], {%1,%2,%3,%4};" :: "r"(sb + OFF_G + lane * 16), "r"(q[0]), "r"(q[1]), "r"(q[2]), "r"(q[3]) : "memory");
                    if (lane == 0) {
                        asm volatile("st.shared.u32 [%0], %1;" :: "r"(sb + OFF_EPOCH), "r"(epoch) : "memory");
                        g_epoch[blockIdx.x] = epoch + 1;
                    }
                    __syncwarp();
                    if (lane == 0) mbar_arrive(sb + B_GRDY);
                } else {
                    if (r == 0) {
                        float4* zp = (float4*)(g_kvacc + (((epoch & 1) ^ 1) * 8 + j) * 4 * 272);
                        for (int i = lane; i < 272; i += 32) zp[i] = make_float4(0.f, 0.f, 0.f, 0.f);
                    }
                }
            }
            TS(2 + hx, 1);
#define PUBLISH_H(B) do { mbar_wait(sb + B_HSENT + 8 * (B), 0); if (lane == 0) { \
                asm volatile("st.release.gpu.global.u32 [%0], %1;" :: "l"(g_hflag + (r * 8 + j) * 8 + (B)), "r"(epoch + 1) : "memory"); } __syncwarp(); } while (0)
            if (hx == 1) {
#pragma unroll 1
                for (int b = 0; b < 3; b++) { PUBLISH_H(b); TS(3, 5 + b); }
            } else {
                const float* accp = g_kvacc + ((epoch & 1) * 8 + j) * 4 * 272;
                unsigned* cnt = g_kvcnt + j * 32;
                mbar_wait(sb + B_KVDONE, 0);
                TS(2, 5);
                if (lane == 0) asm volatile("red.release.gpu.global.add.u32 [%0], 1;" :: "l"(cnt) : "memory");
                __syncwarp();
                TS(2, 2);
                {
                    const unsigned target = 16u * (epoch + 1);
                    uint32_t it = 0, v;
                    do {
                        asm volatile("ld.acquire.gpu.global.u32 %0, [%1];" : "=r"(v) : "l"(cnt) : "memory");
                    } while ((int)(v - target) < 0 && ++it < SPIN_GLOBAL);
                }
                TS(2, 3);
#pragma unroll
                for (int h = 0; h < 4; h++) {
                    const float4 d0 = __ldcg((const float4*)(accp + h * 272) + lane);
                    const float4 d1 = __ldcg((const float4*)(accp + h * 272 + 128) + lane);
                    const float2 z0 = __ldcg((const float2*)(accp + h * 272 + 256) + (lane & 3));
                    const float2 z1 = __ldcg((const float2*)(accp + h * 272 + 264) + (lane & 3));
                    const uint32_t ba = sb + OFF_STG + h * 768 + lane * 4;
                    asm volatile("st.shared.u32 [%0], %1;" :: "r"(ba), "r"(pack2(d0.x, d0.y)) : "memory");
                    asm volatile("st.shared.u32 [%0], %1;" :: "r"(ba + 128), "r"(pack2(d1.x, d1.y)) : "memory");
                    asm volatile("st.shared.u32 [%0], %1;" :: "r"(ba + 256), "r"(pack2(d0.z, d0.w)) : "memory");
                    asm volatile("st.shared.u32 [%0], %1;" :: "r"(ba + 384), "r"(pack2(d1.z, d1.w)) : "memory");
                    asm volatile("st.shared.u32 [%0], %1;" :: "r"(ba + 512), "r"(pack2(z0.x, z0.y)) : "memory");
                    asm volatile("st.shared.u32 [%0], %1;" :: "r"(ba + 640), "r"(pack2(z1.x, z1.y)) : "memory");
                }
                asm volatile("fence.proxy.async.shared::cta;" ::: "memory");
                __syncwarp();
                if (lane == 0) mbar_arrive(sb + B_KVRDY);
                TS(2, 4);
            }
        } else {
            uint32_t epoch;
            asm volatile("ld.relaxed.gpu.global.u32 %0, [%1];" : "=r"(epoch) : "l"(g_epoch + blockIdx.x) : "memory");
            asm volatile("bar.arrive 3, 96;" :: "r"(epoch) : "memory");
            const int b = blockIdx.x, p = j >> 1;
            mbar_wait(sb + B_XFULL, 0);
            if (PF0 && r >= PF0) {
                const int row = r * 32 + lane;
                asm volatile("prefetch.global.L2 [%0];" :: "l"(pf_qkv + row * 3072 + 1024 + j * 128));
                asm volatile("prefetch.global.L2 [%0];" :: "l"(pf_qkv + row * 3072 + 2048 + j * 128));
                asm volatile("prefetch.global.L2 [%0];" :: "l"(pf_g + row * 3584 + j * 448));
                asm volatile("prefetch.global.L2 [%0];" :: "l"(pf_u + row * 3584 + j * 448));
                if (j & 1) {
                    asm volatile("prefetch.global.L2 [%0];" :: "l"(pf_g + row * 3584 + j * 448 + 64));
                    asm volatile("prefetch.global.L2 [%0];" :: "l"(pf_u + row * 3584 + j * 448 + 64));
                }
            }
#pragma unroll 1
            for (int kb = 1; kb < 8; kb++) {
                mbar_wait(sb + B_XFULL + 8 * kb, 0);
                const char* base = kb < 3 ? pf_g : kb < 5 ? pf_u : kb == 5 ? pf_qkv : pf_d;
                const int off = kb == 5 ? b * 12288 : b * 14336 + ((kb < 5 ? kb - 1 : kb) & 1) * 7168;
                if (kb == 5) {
                    asm volatile("prefetch.global.L2 [%0];" :: "l"(base + off + (lane >> 3) * 3072 + (lane & 7) * 128));
                } else {
                    asm volatile("prefetch.global.L2 [%0];" :: "l"(base + off + lane * 128));
                    if (lane < 24) asm volatile("prefetch.global.L2 [%0];" :: "l"(base + off + 4096 + lane * 128));
                }
                if (kb == 7) asm volatile("prefetch.global.L2 [%0];" :: "l"(pf_o + b * 4096 + lane * 128));
            }
            {
                uint4* mb = g_part + (size_t)(r * 2 + (j & 1)) * 16384 + (((p ^ 1) * 4 + p) << 10) + lane;
#pragma unroll 1
                for (int i = 0; i < 32; i++) { st_pkt(mb + i * 32, epoch & 1, 0, 0, 0); __nanosleep(40); }
                __syncwarp();
                if (lane == 0) mbar_arrive(sb + B_KVRDY);
            }
            {
                const uint32_t want = epoch + 1;
                const int hrow = (r * 4 + p) * 5 * 128;
                const unsigned* fl = g_hflag + (r * 8 + (j & 6)) * 8 + (lane & 15);
                uint32_t it = 0;
                int i = 0;
                mbar_wait(sb + B_HSENT + 8, 0);
#pragma unroll 1
                while (i < 3 && ++it < SPIN_GLOBAL) {
                    uint32_t v;
                    asm volatile("ld.acquire.gpu.global.u32 %0, [%1];" : "=r"(v) : "l"(fl) : "memory");
                    const uint32_t rdy = __ballot_sync(0xffffffffu, v == want);
#pragma unroll 1
                    while (i < 3 && ((rdy >> i) & 0x101u) == 0x101u) {
                        if (i < 2) mbar_wait(sb + B_XFREE + 8 * i, 0);
                        if (lane == 0) {
                            const int pc = (6 - 2 * i) % 6;
                            asm volatile("fence.proxy.async.global;" ::: "memory");
                            TS2(140 + i);
                            mbar_expect(sb + B_XFULL + 8 * pc, i != 1 ? 32768 : 16384);
                            tma2(sb + OFF_X + pc * 16384, i != 1 ? &maps.hx2 : &maps.hx, 0, hrow + pc * 128, sb + B_XFULL + 8 * pc);
                        }
                        i++;
                    }
                }
            }
        }
    } else {
        asm volatile("setmaxnreg.inc.sync.aligned.u32 224;");
        const int wg = warp >> 2;
        const bool elect = (tid & 127) == 0;
        const uint32_t sbd = (sb & 0x3FFFFu) >> 4, xlo = (sbd + wg * 512) | LBO1;
        auto release = [&](uint32_t bar) {
            if (elect) {
                mbar_arrive(sb + bar);
            }
        };
#define S_SL(S) ((S) < 40 ? (S) % 5 : (int)((0x846352107ull >> (4 * (((S) - 40) % 9))) & 15))
#define S_WAIT(S) do { mbar_wait(sb + (S_SL(S) < 5 ? B_FULL + 8 * S_SL(S) : B_EFULL + 8 * (S_SL(S) - 5)), (S) < 40 ? ((S) / 5) & 1 : (S) >= 49); \
            if (PROF && tid == 0) TS2(64 + (S)); } while (0)
#define S_B(S) (S_SL(S) < 5 ? OFF_RING / 16 + S_SL(S) * 1024 : (S_SL(S) == 7 ? 8 : S_SL(S) == 8 ? 7 : S_SL(S)) * 1024)
#define S_REL(S) do { if ((S) < 49) release(S_SL(S) < 5 ? B_EMPTY + 8 * S_SL(S) : B_EEMPTY + 8 * (S_SL(S) - 5)); } while (0)
#define G1(S, acc, SW, KB) stage_ss<(KB) * 1024, S_B(S), SW, (KB) == 0>(acc, xlo, sbd)
#define RET(S) do { S_WAIT((S) + 1); wg_wait<1>(); S_REL((S) - 1); } while (0)
#define RET2(S) do { S_WAIT((S) + 1); wg_wait<2>(); S_REL((S) - 1); } while (0)
#define SCHED() mbar_wait(sb + B_XFULL + 8 * 7, 0)
#define A2_SYNC() do { asm volatile("fence.proxy.async.shared::cta;" ::: "memory"); asm volatile("bar.sync %0, 128;" :: "r"(wg + 1) : "memory"); } while (0)
#define H_EPI(acc, F, I0, I1, OG, OU) _Pragma("unroll") for (int i = (I0); i < (I1); i++) \
            F[i] = keep(hmul2(pack2(acc[(OG) + 2 * i] * acc[(OU) + 2 * i], acc[(OG) + 2 * i + 1] * acc[(OU) + 2 * i + 1]), (i & 1) ? m_hi : m_lo))
#define PHI(acc, F, I0, I1) _Pragma("unroll") for (int i = (I0); i < (I1); i++) F[i] = keep(phi2(acc[2 * i], acc[2 * i + 1]))

        float a0[64], b0[64], a1[64], a2_[64], a3[64];
        mbar_wait(sb + B_XFULL, 0);
#define X_WAIT(KB) do { mbar_wait(sb + B_XFULL + 8 * (KB), 0); if (PROF && tid == 0) TS2(128 + (KB)); } while (0)
        S_WAIT(0); G1(0, b0, false, 0);
        if ((warp & 3) == 0) TS(wg, 1);
        S_WAIT(1); G1(1, a0, false, 0); RET(1);
        X_WAIT(1); G1(2, b0, false, 1); RET(2);
        X_WAIT(2); G1(3, b0, false, 2); RET(3);
        G1(4, a0, false, 1); RET(4);
        X_WAIT(3); G1(5, b0, false, 3); RET(5);
        G1(6, a0, false, 2); RET(6);
        X_WAIT(4); G1(7, b0, false, 4); RET(7);
        X_WAIT(5); G1(8, b0, false, 5); RET(8);
        G1(9, a0, false, 3); RET(9);
        X_WAIT(6); G1(10, b0, false, 6); RET(10);
        X_WAIT(7); G1(11, b0, false, 7); RET(11);
        G1(12, a0, false, 4);
        const uint32_t lrow = ((lane & 7) + 8 * ((lane >> 3) & 1)) * 128;
        const uint32_t srow = (warp & 3) * 2048 + lrow;
        const uint32_t ssw = (lane >> 4) ^ (lane & 7);
        uint4* const hsend = g_hx + (size_t)((r * 4 + (j >> 1)) * 5 + (j & 1)) * 1024 + warp * 128 + (lane >> 2) * 8 + (lane & 3);
#define SENT_H(B) do { __syncwarp(); if (lane == 0) mbar_arrive(sb + B_HSENT + 8 * (B)); } while (0)
        RET(12);
        pin(b0);
        uint32_t fh0[16], fh1[16], fh2[16], fh3[8], fo[16], pk[16], pv[16];
        float kv[32], zs[4];
        const uint32_t stg = sb + OFF_STG + wg * 8192, stl = stg + (warp & 1) * 2048 + lrow;
#define KV_ROUND(Z) do { A2_SYNC(); wg_fence(); \
            wg_ss64t##Z<8192 + 256, 8192, DH128>(kv, xlo, xlo); wg_ss64t<8192 + 384, 8192 + 128, DH128>(kv, xlo, xlo); \
            wg_ss8t##Z<8192, OFF_ONES / 16, 0>(zs, xlo, sbd); wg_ss8t<8192 + 128, OFF_ONES / 16, 0>(zs, xlo, sbd); wg_commit(); } while (0)
        G1(13, a0, false, 5); SCHED(); pack_sub<32>(pv, b0); PHI(b0, pk, 0, 4); RET(13);
        G1(14, a0, false, 6); SCHED(); if (!(warp & 2)) stash<16>(stl + 4096, ssw, pv); PHI(b0, pk, 4, 10); RET(14);
        G1(15, a0, false, 7); SCHED(); PHI(b0, pk, 10, 16); RET(15);
        if ((warp & 3) == 0) TS(wg, 2);

        G1(16, a1, true, 0); SCHED(); if (!(warp & 2)) stash<16>(stl, ssw, pk);
        mbar_wait(sb + B_GRDY, 0);
        float g_lo, g_hi;
        uint32_t tag;
        {
            const uint32_t ga = sb + OFF_G + (warp * 16 + (lane >> 2)) * 4;
            asm volatile("ld.shared.f32 %0, [%1];" : "=f"(g_lo) : "r"(ga) : "memory");
            asm volatile("ld.shared.f32 %0, [%1];" : "=f"(g_hi) : "r"(ga + 32) : "memory");
            asm volatile("ld.shared.u32 %0, [%1];" : "=r"(tag) : "r"(sb + OFF_EPOCH) : "memory");
        }
        float* const kvp = g_kvacc + (((tag & 1) * 8 + j) * 4 + (warp & 3)) * 272;
        tag = (tag + 1) & 1;
        const uint32_t m_lo = pack2(1.f - g_lo, 1.f - g_lo), m_hi = pack2(1.f - g_hi, 1.f - g_hi);
        RET(16);
        pin(a0);
        G1(17, a1, true, 1); SCHED(); H_EPI(a0, fh0, 0, 16, 0, 32); RET(17);
        G1(18, a1, true, 2); KV_ROUND(_z); RET2(18);
        G1(19, a1, true, 3); SCHED(); send_h<0, 1>(fh0, hsend); RET(19);
        G1(20, a1, true, 4); SCHED(); if (warp & 2) { stash<16>(stl, ssw, pk); stash<16>(stl + 4096, ssw, pv); } RET(20);
        G1(21, a1, true, 5); KV_ROUND(); RET2(21);
        G1(22, a1, true, 6); RET(22);
        pin(kv); pin(zs);
        G1(23, a1, true, 7); SCHED();
#define KV_RED(W) do { asm volatile("red.global.add.v4.f32 [%0], {%1,%2,%3,%4};" :: "l"(kvp + lane * 4), "f"(kv[8 * W]), "f"(kv[8 * W + 1]), "f"(kv[8 * W + 2]), "f"(kv[8 * W + 3]) : "memory"); \
                       asm volatile("red.global.add.v4.f32 [%0], {%1,%2,%3,%4};" :: "l"(kvp + 128 + lane * 4), "f"(kv[8 * W + 4]), "f"(kv[8 * W + 5]), "f"(kv[8 * W + 6]), "f"(kv[8 * W + 7]) : "memory"); } while (0)
        if ((warp & 3) == 0) KV_RED(0); else if ((warp & 3) == 1) KV_RED(1); else if ((warp & 3) == 2) KV_RED(2); else KV_RED(3);
        if ((lane & 3) == 0) {
            asm volatile("red.global.add.f32 [%0], %1;" :: "l"(kvp + 256 + (lane >> 2)), "f"(zs[0]) : "memory");
            asm volatile("red.global.add.f32 [%0], %1;" :: "l"(kvp + 264 + (lane >> 2)), "f"(zs[2]) : "memory");
        }
        __syncwarp();
        if (lane == 0) mbar_arrive(sb + B_KVDONE);
        RET(23);
        if ((warp & 3) == 0) TS(wg, 3);

        G1(24, a2_, false, 0); SCHED(); send_h<1, 2>(fh0, hsend); RET(24);
        pin(a1);
        G1(25, a2_, false, 1); SCHED(); send_h<2, 3>(fh0, hsend); H_EPI(a1, fh3, 0, 8, 32, 48); RET(25);
        G1(26, a2_, false, 2); SCHED(); send_h<3, 4>(fh0, hsend); SENT_H(0); PHI(a1, fo, 0, 4); RET(26);
        G1(27, a2_, false, 3); SCHED(); send_h<0, 1>(fh3, hsend + 4 * 1024 - (j & 1) * 1020); PHI(a1, fo, 4, 8); RET(27);
        G1(28, a2_, false, 4); SCHED(); send_h<1, 2>(fh3, hsend + 4 * 1024 - (j & 1) * 1020); SENT_H(1); PHI(a1, fo, 8, 12); RET(28);
        G1(29, a2_, false, 5); SCHED(); PHI(a1, fo, 12, 16); RET(29);
        G1(30, a2_, false, 6); RET(30);
        G1(31, a2_, false, 7); RET(31);
        if ((warp & 3) == 0) TS(wg, 4);

        float on[4][12];
#define O_SCALE(h) do { const float s_lo = __fdividef(g_lo, on[h][8] + 1e-6f), s_hi = __fdividef(g_hi, on[h][10] + 1e-6f); \
            const uint32_t sl_ = pack2(s_lo, s_lo), sh_ = pack2(s_hi, s_hi); \
            fo[4 * h] = keep(hmul2(pack2(on[h][0], on[h][1]), sl_)); fo[4 * h + 1] = keep(hmul2(pack2(on[h][2], on[h][3]), sh_)); \
            fo[4 * h + 2] = keep(hmul2(pack2(on[h][4], on[h][5]), sl_)); fo[4 * h + 3] = keep(hmul2(pack2(on[h][6], on[h][7]), sh_)); } while (0)
        uint4* const lsend = g_lx + (size_t)(r * 8 + j) * 2048 + warp * 128 + lane;
        const uint4* const lrecv = g_lx + (size_t)(r * 8 + (j ^ 1)) * 2048 + warp * 128 + lane;
        G1(32, a3, false, 0); RET(32);
        pin(a2_);
        G1(33, a3, false, 1); SCHED(); H_EPI(a2_, fh1, 0, 16, 0, 32); send_h<0, 1>(fh1, hsend + 2 * 1024); RET(33);
        G1(34, a3, false, 2); SCHED(); send_h<1, 3>(fh1, hsend + 2 * 1024); RET(34);
        if (elect) mbar_arrive(sb + B_XFREE);
        G1(35, a3, false, 3); SCHED(); send_h<3, 4>(fh1, hsend + 2 * 1024); SENT_H(2);
        if ((warp & 3) == 0) TS(wg, 5);
        mbar_wait(sb + B_KVRDY, 0);
        if ((warp & 3) == 0) TS(wg, 6);
        wg_fence();
#define O_MMA(h) wg_rs24_z<OFF_STG / 16 + (h) * 48 + (8u << 16), 16>(on[h], fo[4 * (h)], fo[4 * (h) + 1], fo[4 * (h) + 2], fo[4 * (h) + 3], sbd)
        O_MMA(0); O_MMA(1); O_MMA(2); O_MMA(3);
        wg_commit();
        RET2(35);
        G1(36, a3, false, 4); RET(36);
        pin(on[0]); pin(on[1]); pin(on[2]); pin(on[3]);
        release(B_EEMPTY + 16);
        G1(37, a3, false, 5); SCHED(); O_SCALE(0); O_SCALE(1); O_SCALE(2); O_SCALE(3); RET(37);
        if (elect) mbar_arrive(sb + B_XFREE + 8);
        G1(38, a3, false, 6); SCHED(); send_frag<0, 2>(fo, lsend, tag); RET(38);
        release(B_EEMPTY);
        G1(39, a3, false, 7); SCHED(); send_frag<2, 4>(fo, lsend, tag); RET(39);
        release(B_EEMPTY + 8);
        if ((warp & 3) == 0) TS(wg, 7);

#define G2S(S, acc, U) stage_ss<(U) * 1024, S_B(S), false, (S) == 45>(acc, xlo, sbd)
#define G2R(S, acc, F) stage_rs<S_B(S), (S) == 40>(acc, F, sbd)
#define H_WAIT(P) do { mbar_wait(sb + B_XFULL + 8 * (P), 1); if (PROF && tid == 0) TS2(150 + (P)); } while (0)
        const int p = j >> 1, pw = (p & 2) ^ 2;
        const bool own = wg == (p & 1);
        uint4* const pbase = g_part + (size_t)(r * 2 + (j & 1)) * 16384 + (warp & 3) * 256 + lane;

        float p1[64], p2[64];
        uint32_t po[16], ph2[16];
        G2R(40, p1, fo); RET(40);
        release(B_EEMPTY + 24);
        pin(a3);
        H_WAIT(0); G2S(41, p1, 0); SCHED(); H_EPI(a3, fh2, 0, 16, 0, 32); send_frag<0, 2>(fh2, lsend + 1024, tag); RET(41);
        G2S(42, p1, 1); SCHED(); recv_issue(po, lrecv); send_frag<2, 4>(fh2, lsend + 1024, tag); RET(42);
        H_WAIT(4); G2S(43, p1, 4); RET(43);
        G2R(44, p1, fh2); RET(44);
        G2S(45, p2, 0); SCHED(); if (!(EXPT & 2)) recv_check(po, lrecv, tag); recv_issue(ph2, lrecv + 1024); RET(45);
        G2R(46, p1, po); RET(46);
        H_WAIT(2); G2S(47, p1, 2); RET(47);
        G2S(48, p1, 3); SCHED(); if (!(EXPT & 2)) recv_check(ph2, lrecv + 1024, tag); RET(48);
        G2R(49, p1, ph2); RET(49);
        if ((warp & 3) == 0) TS(wg, 8);
        uint32_t sp[32], qa[32], qb[32];
        uint4* const s1 = pbase + (((pw + wg) * 4 + p) << 10);
        G2R(50, p2, fo); RET(50);
        pin(p1);
        G2R(51, p2, po); SCHED(); pack_sub<0>(sp, p1); send_frag<0, 2>(sp, s1, tag); RET(51);
        G2R(52, p2, fh2); SCHED(); send_frag<2, 5>(sp, s1, tag); RET(52);
        if (elect) mbar_arrive(sb + B_XFREE + 16);
        G2R(53, p2, ph2); SCHED(); send_frag<5, 8>(sp, s1, tag); RET(53);
        const uint4* ra = pbase + ((p * 4 + pw) << 10);
        const uint4* rc = pbase + ((p * 4 + (p ^ 1)) << 10);
        if (own) mbar_wait(sb + B_AHEAD, 0);
        G2S(54, p2, 1); RET(54);
        G2S(55, p2, 2); RET(55);
        G2S(56, p2, 3); RET(56);
        G2S(57, p2, 4); SCHED();
        if ((warp & 3) == 0) TS(wg, 9);
#define PART_COPY() do { mbar_wait(sb + B_XFREE + 16, 0); mbar_expect(sb + B_PART, 32768); \
            asm volatile("cp.async.bulk.shared::cluster.global.mbarrier::complete_tx::bytes [%0], [%1], %2, [%3];" \
                         :: "r"(sb + OFF_RING), "l"(ra), "r"(32768), "r"(sb + B_PART) : "memory"); } while (0)
        if (!own && elect) mbar_arrive(sb + B_AHEAD);
        wg_wait<0>();
        pin(p2);
        if ((warp & 3) == 0) TS(wg, 11);
        if (!own) {
            if (COPY_AT == 0 && elect) PART_COPY();
            pack_sub<0>(sp, p2);
            if (COPY_AT == 1 && elect) PART_COPY();
            send_frag<0, 4>(sp, pbase + (((p ^ 1) * 4 + p) << 10), tag);
            if (COPY_AT == 2 && elect) PART_COPY();
            send_frag<4, 8>(sp, pbase + (((p ^ 1) * 4 + p) << 10), tag);
            if (COPY_AT == 3 && elect) PART_COPY();
        } else {
            recv_issue(sp, rc);
            uint32_t f0[16], f1[16];
            pack_sub<0>(f0, p2); pack_sub<32>(f1, p2);
            mbar_wait(sb + B_PART, 0);
            if ((warp & 3) == 0) TS(wg, 10);
            const uint32_t pa = sb + OFF_RING + (warp & 3) * 4096 + lane * 16;
#pragma unroll
            for (int v = 0; v < 8; v++) {
                asm volatile("ld.shared.v4.u32 {%0,%1,%2,%3}, [%4];" : "=r"(qa[4 * v]), "=r"(qa[4 * v + 1]), "=r"(qa[4 * v + 2]), "=r"(qa[4 * v + 3]) : "r"(pa + v * 512) : "memory");
                asm volatile("ld.shared.v4.u32 {%0,%1,%2,%3}, [%4];" : "=r"(qb[4 * v]), "=r"(qb[4 * v + 1]), "=r"(qb[4 * v + 2]), "=r"(qb[4 * v + 3]) : "r"(pa + 16384 + v * 512) : "memory");
            }
            recv_check(qa, ra, tag); recv_check(qb, ra + 1024, tag);
#pragma unroll
            for (int i = 0; i < 32; i++) qa[i] = keep(hadd2(qa[i], qb[i]));
            if ((warp & 3) == 0) TS(wg, 12);
            recv_check(sp, rc, tag);
            if ((warp & 3) == 0) TS(wg, 13);
#pragma unroll
            for (int i = 0; i < 16; i++) { f0[i] = hadd2(hadd2(f0[i], sp[i]), qa[i]); f1[i] = hadd2(hadd2(f1[i], sp[16 + i]), qa[16 + i]); }
            const uint32_t slab = sb + OFF_X + 2 * 16384 + wg * 8192;
            stash<16>(slab + srow, ssw, f0); stash<16>(slab + 16384 + srow, ssw, f1);
            __syncwarp();
            __nv_bfloat16* op = out + (size_t)(r * 128 + warp * 16 + (lane >> 4)) * kD + (j & 1) * 256 + (p & 2) * 64 + (lane & 15) * 8;
#pragma unroll
            for (int i = 0; i < 8; i++) {
                const int row = i * 2 + (lane >> 4);
                uint4 v;
                asm volatile("ld.shared.v4.u32 {%0,%1,%2,%3}, [%4];" : "=r"(v.x), "=r"(v.y), "=r"(v.z), "=r"(v.w)
                             : "r"(slab + (lane & 8) * 2048 + ((warp & 3) * 16 + row) * 128 + (((lane & 7) ^ (row & 7)) << 4)) : "memory");
                *(uint4*)(op + i * 2 * kD) = v;
            }
        }
        if ((warp & 3) == 0) { TS(wg, 14); TSG(wg, 31); }
    }
}

typedef CUresult (*EncodeFn)(CUtensorMap*, CUtensorMapDataType, cuuint32_t, void*, const cuuint64_t*, const cuuint64_t*, const cuuint32_t*,
                             const cuuint32_t*, CUtensorMapInterleave, CUtensorMapSwizzle, CUtensorMapL2promotion, CUtensorMapFloatOOBfill);

static void encode(EncodeFn fn, CUtensorMap* m, int rank, const void* base, const cuuint64_t (&gd)[5], const cuuint64_t (&gs)[4],
                   const cuuint32_t (&bd)[5], CUtensorMapSwizzle sw) {
    cuuint32_t es[5] = {1, 1, 1, 1, 1};
    fn(m, CU_TENSOR_MAP_DATA_TYPE_BFLOAT16, rank, const_cast<void*>(base), gd, gs, bd, es, CU_TENSOR_MAP_INTERLEAVE_NONE, sw,
       CU_TENSOR_MAP_L2_PROMOTION_L2_128B, CU_TENSOR_MAP_FLOAT_OOB_FILL_NONE);
}

extern "C" void kernel_launch(void* const* d_in, const int* in_sizes, int n_in, void* d_out, int out_size) {
    const char* x = (const char*)d_in[0];
    const char* wqkv = (const char*)d_in[1];
    const char* wo = (const char*)d_in[2];
    const char* wg = (const char*)d_in[4];
    const char* wu = (const char*)d_in[5];
    const char* wd = (const char*)d_in[6];
    void* fnp = nullptr;
    cudaDriverEntryPointQueryResult qr;
    cudaGetDriverEntryPoint("cuTensorMapEncodeTiled", &fnp, cudaEnableDefault, &qr);
    EncodeFn fn = (EncodeFn)fnp;
    Maps maps;
    const char* lo = wg < wu ? wg : wu;
    const uint64_t diff = wg < wu ? (uint64_t)(wu - wg) : (uint64_t)(wg - wu);
    const CUtensorMapSwizzle S128 = CU_TENSOR_MAP_SWIZZLE_128B, S64 = CU_TENSOR_MAP_SWIZZLE_64B;
    encode(fn, &maps.x, 2, x, {512, 2048, 1, 1}, {1024, 0, 0}, {64, 128, 1, 1}, S128);
    encode(fn, &maps.gu, 3, lo, {1792, 512, 2, 1}, {3584, diff, 0}, {64, 64, 2, 1}, S128);
    encode(fn, &maps.kv, 3, wqkv, {512, 512, 3, 1}, {3072, 1024, 0}, {64, 64, 2, 1}, S128);
    encode(fn, &maps.q64, 3, wqkv, {32, 512, 48, 1}, {3072, 64, 0}, {32, 64, 2, 1}, S64);
    encode(fn, &maps.gu64, 3, lo, {1792, 512, 2, 1}, {3584, diff, 0}, {32, 64, 2, 1}, S64);
    encode(fn, &maps.wdw, 3, wd, {64, 1792, 8, 1}, {1024, 128, 0}, {64, 64, 2, 1}, S128);
    encode(fn, &maps.wow, 3, wo, {64, 512, 8}, {1024, 128}, {64, 64, 2}, S128);
    encode(fn, &maps.wdp, 5, wd, {512, 2, 4, 4, 56}, {1024, 8192, 2048, 32768}, {64, 2, 4, 4, 2}, S128);
    encode(fn, &maps.wdph, 5, wd, {512, 2, 4, 4, 56}, {1024, 8192, 2048, 32768}, {64, 2, 4, 4, 1}, S128);
    void* hx = nullptr;
    cudaGetSymbolAddress(&hx, g_hx);
    encode(fn, &maps.hx, 2, hx, {64, 16 * 4 * 5 * 128}, {128}, {64, 128}, S128);
    encode(fn, &maps.hx2, 2, hx, {64, 16 * 4 * 5 * 128}, {128}, {64, 256}, S128);
    cudaFuncSetAttribute(fused_kernel, cudaFuncAttributeMaxDynamicSharedMemorySize, SMEM_BYTES);
    cudaLaunchConfig_t cfg = {};
    cfg.gridDim = dim3(128);
    cfg.blockDim = dim3(384);
    cfg.dynamicSmemBytes = SMEM_BYTES;
    cfg.stream = cudaStreamPerThread;
    cudaLaunchAttribute at[1];
    at[0].id = cudaLaunchAttributeClusterDimension;
    at[0].val.clusterDim.x = 2; at[0].val.clusterDim.y = 1; at[0].val.clusterDim.z = 1;
    cfg.attrs = at;
    cfg.numAttrs = MC ? 1 : 0;
    cudaLaunchKernelEx(&cfg, fused_kernel, maps, (const __nv_bfloat16*)d_in[0], (const __nv_bfloat16*)d_in[7], wqkv, wg, wu, wd, wo, (__nv_bfloat16*)d_out);
}
```

```cpp
#include <cuda_runtime.h>
#include <cuda.h>
#include <cuda_bf16.h>
#include <stdint.h>

#define MC 0
#define PFMODE 1
#define PHI_SAT 0
#define EXPT 0
#define COPY_AT 0
#define RX 0
#define PF0 4
#define GDELAY 1
#define PRO5 0
#define NOPRE 0
#define PROF 0

namespace {

constexpr int kD = 512;
constexpr uint32_t OFF_X = 0, OFF_STG = 131072, OFF_RING = 147456, OFF_MISC = 229376;
constexpr uint32_t B_FULL = OFF_MISC, B_EMPTY = OFF_MISC + 40, B_XFULL = OFF_MISC + 80;
constexpr uint32_t B_GRDY = OFF_MISC + 152, B_KVDONE = OFF_MISC + 160, B_KVRDY = OFF_MISC + 168;
constexpr uint32_t B_HSENT = OFF_MISC + 176, B_XFREE = OFF_MISC + 200;
constexpr uint32_t OFF_EPOCH = OFF_MISC + 240, OFF_G = OFF_MISC + 256;
constexpr uint32_t B_AHEAD = OFF_MISC + 248, B_PART = OFF_MISC + 232;
constexpr uint32_t OFF_ONES = OFF_MISC + 768;
constexpr uint32_t B_EFULL = OFF_MISC + 896, B_EEMPTY = OFF_MISC + 928;
constexpr uint32_t SMEM_BYTES = OFF_MISC + 960;
constexpr uint32_t SPIN_GLOBAL = 1u << 14;

struct alignas(64) Maps { CUtensorMap x, gu, kv, q64, gu64, wdw, wow, wdp, hx, hx2; };

}

__device__ uint4 g_part[16 * 2 * 4 * 4 * 1024];
__device__ uint4 g_hx[16 * 4 * 5 * 1024];
__device__ uint4 g_lx[16 * 8 * 2 * 1024];
__device__ unsigned g_hflag[128 * 8];
__device__ uint4 g_gx[16 * 32];
__device__ float g_kvacc[2 * 8 * 4 * 272];
__device__ unsigned g_kvcnt[8 * 32];
__device__ unsigned g_epoch[128];
#define TS(role, idx)
#define TS2(idx)
#define TSG(role, idx)

namespace {

__device__ __forceinline__ void mbar_init(uint32_t bar, uint32_t cnt) { asm volatile("mbarrier.init.shared::cta.b64 [%0], %1;" :: "r"(bar), "r"(cnt) : "memory"); }
__device__ __forceinline__ void mbar_expect(uint32_t bar, uint32_t bytes) { asm volatile("mbarrier.arrive.expect_tx.shared::cta.b64 _, [%0], %1;" :: "r"(bar), "r"(bytes) : "memory"); }
__device__ __forceinline__ void mbar_arrive(uint32_t bar) { asm volatile("mbarrier.arrive.shared::cta.b64 _, [%0];" :: "r"(bar) : "memory"); }
__device__ __forceinline__ void mbar_arrive_cta(uint32_t bar, uint32_t cta) {
    asm volatile("{\n.reg .b32 ra;\nmapa.shared::cluster.u32 ra, %0, %1;\nmbarrier.arrive.shared::cluster.b64 _, [ra];\n}" :: "r"(bar), "r"(cta) : "memory");
}
__device__ __forceinline__ void mbar_wait(uint32_t bar, uint32_t parity) {
    asm volatile("{\n.reg .pred p;\n.reg .u32 c;\n"
                 "mbarrier.try_wait.parity.shared::cta.b64 p, [%0], %1;\n@p bra DONE;\n"
                 "mov.u32 c, 0;\nLAB_WAIT:\nmbarrier.try_wait.parity.shared::cta.b64 p, [%0], %1;\n@p bra DONE;\n"
                 "add.u32 c, c, 1;\nsetp.lt.u32 p, c, 65536;\n@p bra LAB_WAIT;\nDONE:\n}" :: "r"(bar), "r"(parity) : "memory");
}
__device__ __forceinline__ void tma2(uint32_t dst, const CUtensorMap* m, int c0, int c1, uint32_t bar) {
    asm volatile("cp.async.bulk.tensor.2d.shared::cluster.global.mbarrier::complete_tx::bytes [%0], [%1, {%3, %4}], [%2];"
        :: "r"(dst), "l"(m), "r"(bar), "r"(c0), "r"(c1) : "memory");
}
__device__ __forceinline__ void tmaw2(uint32_t dst, const CUtensorMap* m, int c0, int c1, uint32_t bar) {
    tma2(dst, m, c0, c1, bar);
}
__device__ __forceinline__ void tmaw3(uint32_t dst, const CUtensorMap* m, int c0, int c1, int c2, uint32_t bar) {
    asm volatile("cp.async.bulk.tensor.3d.shared::cluster.global.mbarrier::complete_tx::bytes [%0], [%1, {%3, %4, %5}], [%2];"
        :: "r"(dst), "l"(m), "r"(bar), "r"(c0), "r"(c1), "r"(c2) : "memory");
}
__device__ __forceinline__ void tmaw5(uint32_t dst, const CUtensorMap* m, int c0, int c4, uint32_t bar) {
    asm volatile("cp.async.bulk.tensor.5d.shared::cluster.global.mbarrier::complete_tx::bytes [%0], [%1, {%3, %5, %5, %5, %4}], [%2];"
        :: "r"(dst), "l"(m), "r"(bar), "r"(c0), "r"(c4), "r"(0) : "memory");
}
__device__ __forceinline__ void wg_fence() { asm volatile("wgmma.fence.sync.aligned;" ::: "memory"); }
__device__ __forceinline__ void wg_commit() { asm volatile("wgmma.commit_group.sync.aligned;" ::: "memory"); }
template <int N> __device__ __forceinline__ void wg_wait() { asm volatile("wgmma.wait_group.sync.aligned %0;" :: "n"(N) : "memory"); }
template <int N> __device__ __forceinline__ void pin(float (&d)[N]) {
#pragma unroll
    for (int i = 0; i < N; i++) asm volatile("" : "+f"(d[i]) :: "memory");
}
__device__ __forceinline__ uint32_t pack2(float lo, float hi) { uint32_t r; asm("cvt.rn.bf16x2.f32 %0, %1, %2;" : "=r"(r) : "f"(hi), "f"(lo)); return r; }
__device__ __forceinline__ uint32_t keep(uint32_t v) { asm volatile("" : "+r"(v)); return v; }
__device__ __forceinline__ uint32_t hadd2(uint32_t a, uint32_t b) { uint32_t r; asm("add.bf16x2 %0, %1, %2;" : "=r"(r) : "r"(a), "r"(b)); return r; }
__device__ __forceinline__ uint32_t hmul2(uint32_t a, uint32_t b) { uint32_t r; asm("mul.bf16x2 %0, %1, %2;" : "=r"(r) : "r"(a), "r"(b)); return r; }
__device__ __forceinline__ uint32_t phi2(float t0, float t1) {
    float e0, e1;
    asm("ex2.approx.ftz.f32 %0, %1;" : "=f"(e0) : "f"(t0 * 1.4426950408889634f));
    asm("ex2.approx.ftz.f32 %0, %1;" : "=f"(e1) : "f"(t1 * 1.4426950408889634f));
    uint32_t e = pack2(e0, e1), t = pack2(t0, t1), r;
    asm("min.bf16x2 %0, %0, %1;" : "+r"(e) : "r"(0x3f803f80u));
    asm("max.bf16x2 %0, %0, %1;" : "+r"(t) : "r"(0x35863586u));
    asm("add.bf16x2 %0, %1, %2;" : "=r"(r) : "r"(e), "r"(t));
    return r;
}
__device__ __forceinline__ void stsm4(uint32_t a, uint32_t r0, uint32_t r1, uint32_t r2, uint32_t r3) {
    asm volatile("stmatrix.sync.aligned.m8n8.x4.shared.b16 [%0], {%1,%2,%3,%4};" :: "r"(a), "r"(r0), "r"(r1), "r"(r2), "r"(r3) : "memory");
}
__device__ __forceinline__ float bf_lo(uint32_t w) { return __uint_as_float(w << 16); }
__device__ __forceinline__ float bf_hi(uint32_t w) { return __uint_as_float(w & 0xffff0000u); }
__device__ __forceinline__ void st_pkt(uint4* p, uint32_t w0, uint32_t w1, uint32_t w2, uint32_t w3) {
    asm volatile("{\n.reg .b64 lo, hi;\n.reg .b128 v;\nmov.b64 lo, {%1, %2};\nmov.b64 hi, {%3, %4};\nmov.b128 v, {lo, hi};\nst.relaxed.gpu.global.b128 [%0], v;\n}"
        :: "l"(p), "r"(w0), "r"(w1), "r"(w2), "r"(w3) : "memory");
}
__device__ __forceinline__ void ld_pkt(const uint4* p, uint32_t& w0, uint32_t& w1, uint32_t& w2, uint32_t& w3) {
    asm volatile("{\n.reg .b64 lo, hi;\n.reg .b128 v;\nld.relaxed.gpu.global.b128 v, [%4];\nmov.b128 {lo, hi}, v;\nmov.b64 {%0, %1}, lo;\nmov.b64 {%2, %3}, hi;\n}"
        : "=r"(w0), "=r"(w1), "=r"(w2), "=r"(w3) : "l"(p) : "memory");
}

template <uint32_t AO, uint32_t BO, uint32_t BH> __device__ __forceinline__ void wg_ss128(float (&d)[64], uint32_t ab, uint32_t bb) {
    asm volatile("{\n.reg .b64 da, db;\n.reg .b32 ta, tb, th, ah;\nadd.u32 ta, %64, %66;\nadd.u32 tb, %65, %67;\nmov.b32 th, %68;\nmov.b32 ah, 0x40000040;\nmov.b64 da, {ta, ah};\nmov.b64 db, {tb, th};\n"
        "wgmma.mma_async.sync.aligned.m64n128k16.f32.bf16.bf16 {%0,%1,%2,%3,%4,%5,%6,%7,%8,%9,%10,%11,%12,%13,%14,%15,%16,%17,%18,%19,%20,%21,%22,%23,%24,%25,%26,%27,%28,%29,%30,%31,%32,%33,%34,%35,%36,%37,%38,%39,%40,%41,%42,%43,%44,%45,%46,%47,%48,%49,%50,%51,%52,%53,%54,%55,%56,%57,%58,%59,%60,%61,%62,%63}, da, db, 1, 1, 1, 0, 1;\n}\n"
        : "+f"(d[0]),"+f"(d[1]),"+f"(d[2]),"+f"(d[3]),"+f"(d[4]),"+f"(d[5]),"+f"(d[6]),"+f"(d[7]),"+f"(d[8]),"+f"(d[9]),"+f"(d[10]),"+f"(d[11]),"+f"(d[12]),"+f"(d[13]),"+f"(d[14]),"+f"(d[15]),"+f"(d[16]),"+f"(d[17]),"+f"(d[18]),"+f"(d[19]),"+f"(d[20]),"+f"(d[21]),"+f"(d[22]),"+f"(d[23]),"+f"(d[24]),"+f"(d[25]),"+f"(d[26]),"+f"(d[27]),"+f"(d[28]),"+f"(d[29]),"+f"(d[30]),"+f"(d[31]),"+f"(d[32]),"+f"(d[33]),"+f"(d[34]),"+f"(d[35]),"+f"(d[36]),"+f"(d[37]),"+f"(d[38]),"+f"(d[39]),"+f"(d[40]),"+f"(d[41]),"+f"(d[42]),"+f"(d[43]),"+f"(d[44]),"+f"(d[45]),"+f"(d[46]),"+f"(d[47]),"+f"(d[48]),"+f"(d[49]),"+f"(d[50]),"+f"(d[51]),"+f"(d[52]),"+f"(d[53]),"+f"(d[54]),"+f"(d[55]),"+f"(d[56]),"+f"(d[57]),"+f"(d[58]),"+f"(d[59]),"+f"(d[60]),"+f"(d[61]),"+f"(d[62]),"+f"(d[63])
        : "r"(ab), "r"(bb), "n"(AO), "n"(BO), "n"(BH));
}
template <uint32_t AO, uint32_t BO, uint32_t BH> __device__ __forceinline__ void wg_ss128_z(float (&d)[64], uint32_t ab, uint32_t bb) {
    asm volatile("{\n.reg .b64 da, db;\n.reg .b32 ta, tb, th, ah;\nadd.u32 ta, %64, %66;\nadd.u32 tb, %65, %67;\nmov.b32 th, %68;\nmov.b32 ah, 0x40000040;\nmov.b64 da, {ta, ah};\nmov.b64 db, {tb, th};\n"
        "wgmma.mma_async.sync.aligned.m64n128k16.f32.bf16.bf16 {%0,%1,%2,%3,%4,%5,%6,%7,%8,%9,%10,%11,%12,%13,%14,%15,%16,%17,%18,%19,%20,%21,%22,%23,%24,%25,%26,%27,%28,%29,%30,%31,%32,%33,%34,%35,%36,%37,%38,%39,%40,%41,%42,%43,%44,%45,%46,%47,%48,%49,%50,%51,%52,%53,%54,%55,%56,%57,%58,%59,%60,%61,%62,%63}, da, db, 0, 1, 1, 0, 1;\n}\n"
        : "=f"(d[0]),"=f"(d[1]),"=f"(d[2]),"=f"(d[3]),"=f"(d[4]),"=f"(d[5]),"=f"(d[6]),"=f"(d[7]),"=f"(d[8]),"=f"(d[9]),"=f"(d[10]),"=f"(d[11]),"=f"(d[12]),"=f"(d[13]),"=f"(d[14]),"=f"(d[15]),"=f"(d[16]),"=f"(d[17]),"=f"(d[18]),"=f"(d[19]),"=f"(d[20]),"=f"(d[21]),"=f"(d[22]),"=f"(d[23]),"=f"(d[24]),"=f"(d[25]),"=f"(d[26]),"=f"(d[27]),"=f"(d[28]),"=f"(d[29]),"=f"(d[30]),"=f"(d[31]),"=f"(d[32]),"=f"(d[33]),"=f"(d[34]),"=f"(d[35]),"=f"(d[36]),"=f"(d[37]),"=f"(d[38]),"=f"(d[39]),"=f"(d[40]),"=f"(d[41]),"=f"(d[42]),"=f"(d[43]),"=f"(d[44]),"=f"(d[45]),"=f"(d[46]),"=f"(d[47]),"=f"(d[48]),"=f"(d[49]),"=f"(d[50]),"=f"(d[51]),"=f"(d[52]),"=f"(d[53]),"=f"(d[54]),"=f"(d[55]),"=f"(d[56]),"=f"(d[57]),"=f"(d[58]),"=f"(d[59]),"=f"(d[60]),"=f"(d[61]),"=f"(d[62]),"=f"(d[63])
        : "r"(ab), "r"(bb), "n"(AO), "n"(BO), "n"(BH));
}
template <uint32_t BO, uint32_t BH> __device__ __forceinline__ void wg_rs128(float (&d)[64], uint32_t a0, uint32_t a1, uint32_t a2, uint32_t a3, uint32_t bb) {
    asm volatile("{\n.reg .b64 db;\n.reg .b32 tb, th;\nadd.u32 tb, %68, %69;\nmov.b32 th, %70;\nmov.b64 db, {tb, th};\n"
        "wgmma.mma_async.sync.aligned.m64n128k16.f32.bf16.bf16 {%0,%1,%2,%3,%4,%5,%6,%7,%8,%9,%10,%11,%12,%13,%14,%15,%16,%17,%18,%19,%20,%21,%22,%23,%24,%25,%26,%27,%28,%29,%30,%31,%32,%33,%34,%35,%36,%37,%38,%39,%40,%41,%42,%43,%44,%45,%46,%47,%48,%49,%50,%51,%52,%53,%54,%55,%56,%57,%58,%59,%60,%61,%62,%63}, {%64,%65,%66,%67}, db, 1, 1, 1, 1;\n}\n"
        : "+f"(d[0]),"+f"(d[1]),"+f"(d[2]),"+f"(d[3]),"+f"(d[4]),"+f"(d[5]),"+f"(d[6]),"+f"(d[7]),"+f"(d[8]),"+f"(d[9]),"+f"(d[10]),"+f"(d[11]),"+f"(d[12]),"+f"(d[13]),"+f"(d[14]),"+f"(d[15]),"+f"(d[16]),"+f"(d[17]),"+f"(d[18]),"+f"(d[19]),"+f"(d[20]),"+f"(d[21]),"+f"(d[22]),"+f"(d[23]),"+f"(d[24]),"+f"(d[25]),"+f"(d[26]),"+f"(d[27]),"+f"(d[28]),"+f"(d[29]),"+f"(d[30]),"+f"(d[31]),"+f"(d[32]),"+f"(d[33]),"+f"(d[34]),"+f"(d[35]),"+f"(d[36]),"+f"(d[37]),"+f"(d[38]),"+f"(d[39]),"+f"(d[40]),"+f"(d[41]),"+f"(d[42]),"+f"(d[43]),"+f"(d[44]),"+f"(d[45]),"+f"(d[46]),"+f"(d[47]),"+f"(d[48]),"+f"(d[49]),"+f"(d[50]),"+f"(d[51]),"+f"(d[52]),"+f"(d[53]),"+f"(d[54]),"+f"(d[55]),"+f"(d[56]),"+f"(d[57]),"+f"(d[58]),"+f"(d[59]),"+f"(d[60]),"+f"(d[61]),"+f"(d[62]),"+f"(d[63])
        : "r"(a0), "r"(a1), "r"(a2), "r"(a3), "r"(bb), "n"(BO), "n"(BH));
}
template <uint32_t BO, uint32_t BH> __device__ __forceinline__ void wg_rs128_z(float (&d)[64], uint32_t a0, uint32_t a1, uint32_t a2, uint32_t a3, uint32_t bb) {
    asm volatile("{\n.reg .b64 db;\n.reg .b32 tb, th;\nadd.u32 tb, %68, %69;\nmov.b32 th, %70;\nmov.b64 db, {tb, th};\n"
        "wgmma.mma_async.sync.aligned.m64n128k16.f32.bf16.bf16 {%0,%1,%2,%3,%4,%5,%6,%7,%8,%9,%10,%11,%12,%13,%14,%15,%16,%17,%18,%19,%20,%21,%22,%23,%24,%25,%26,%27,%28,%29,%30,%31,%32,%33,%34,%35,%36,%37,%38,%39,%40,%41,%42,%43,%44,%45,%46,%47,%48,%49,%50,%51,%52,%53,%54,%55,%56,%57,%58,%59,%60,%61,%62,%63}, {%64,%65,%66,%67}, db, 0, 1, 1, 1;\n}\n"
        : "=f"(d[0]),"=f"(d[1]),"=f"(d[2]),"=f"(d[3]),"=f"(d[4]),"=f"(d[5]),"=f"(d[6]),"=f"(d[7]),"=f"(d[8]),"=f"(d[9]),"=f"(d[10]),"=f"(d[11]),"=f"(d[12]),"=f"(d[13]),"=f"(d[14]),"=f"(d[15]),"=f"(d[16]),"=f"(d[17]),"=f"(d[18]),"=f"(d[19]),"=f"(d[20]),"=f"(d[21]),"=f"(d[22]),"=f"(d[23]),"=f"(d[24]),"=f"(d[25]),"=f"(d[26]),"=f"(d[27]),"=f"(d[28]),"=f"(d[29]),"=f"(d[30]),"=f"(d[31]),"=f"(d[32]),"=f"(d[33]),"=f"(d[34]),"=f"(d[35]),"=f"(d[36]),"=f"(d[37]),"=f"(d[38]),"=f"(d[39]),"=f"(d[40]),"=f"(d[41]),"=f"(d[42]),"=f"(d[43]),"=f"(d[44]),"=f"(d[45]),"=f"(d[46]),"=f"(d[47]),"=f"(d[48]),"=f"(d[49]),"=f"(d[50]),"=f"(d[51]),"=f"(d[52]),"=f"(d[53]),"=f"(d[54]),"=f"(d[55]),"=f"(d[56]),"=f"(d[57]),"=f"(d[58]),"=f"(d[59]),"=f"(d[60]),"=f"(d[61]),"=f"(d[62]),"=f"(d[63])
        : "r"(a0), "r"(a1), "r"(a2), "r"(a3), "r"(bb), "n"(BO), "n"(BH));
}
template <uint32_t AO, uint32_t BO, uint32_t BH> __device__ __forceinline__ void wg_ss64t(float (&d)[32], uint32_t ab, uint32_t bb) {
    asm volatile("{\n.reg .b64 da, db;\n.reg .b32 ta, tb, th, ah;\nadd.u32 ta, %32, %34;\nadd.u32 tb, %33, %35;\nmov.b32 th, %36;\nmov.b32 ah, 0x40000040;\nmov.b64 da, {ta, ah};\nmov.b64 db, {tb, th};\n"
        "wgmma.mma_async.sync.aligned.m64n64k16.f32.bf16.bf16 {%0,%1,%2,%3,%4,%5,%6,%7,%8,%9,%10,%11,%12,%13,%14,%15,%16,%17,%18,%19,%20,%21,%22,%23,%24,%25,%26,%27,%28,%29,%30,%31}, da, db, 1, 1, 1, 1, 1;\n}\n"
        : "+f"(d[0]),"+f"(d[1]),"+f"(d[2]),"+f"(d[3]),"+f"(d[4]),"+f"(d[5]),"+f"(d[6]),"+f"(d[7]),"+f"(d[8]),"+f"(d[9]),"+f"(d[10]),"+f"(d[11]),"+f"(d[12]),"+f"(d[13]),"+f"(d[14]),"+f"(d[15]),"+f"(d[16]),"+f"(d[17]),"+f"(d[18]),"+f"(d[19]),"+f"(d[20]),"+f"(d[21]),"+f"(d[22]),"+f"(d[23]),"+f"(d[24]),"+f"(d[25]),"+f"(d[26]),"+f"(d[27]),"+f"(d[28]),"+f"(d[29]),"+f"(d[30]),"+f"(d[31])
        : "r"(ab), "r"(bb), "n"(AO), "n"(BO), "n"(BH));
}
template <uint32_t AO, uint32_t BO, uint32_t BH> __device__ __forceinline__ void wg_ss64t_z(float (&d)[32], uint32_t ab, uint32_t bb) {
    asm volatile("{\n.reg .b64 da, db;\n.reg .b32 ta, tb, th, ah;\nadd.u32 ta, %32, %34;\nadd.u32 tb, %33, %35;\nmov.b32 th, %36;\nmov.b32 ah, 0x40000040;\nmov.b64 da, {ta, ah};\nmov.b64 db, {tb, th};\n"
        "wgmma.mma_async.sync.aligned.m64n64k16.f32.bf16.bf16 {%0,%1,%2,%3,%4,%5,%6,%7,%8,%9,%10,%11,%12,%13,%14,%15,%16,%17,%18,%19,%20,%21,%22,%23,%24,%25,%26,%27,%28,%29,%30,%31}, da, db, 0, 1, 1, 1, 1;\n}\n"
        : "=f"(d[0]),"=f"(d[1]),"=f"(d[2]),"=f"(d[3]),"=f"(d[4]),"=f"(d[5]),"=f"(d[6]),"=f"(d[7]),"=f"(d[8]),"=f"(d[9]),"=f"(d[10]),"=f"(d[11]),"=f"(d[12]),"=f"(d[13]),"=f"(d[14]),"=f"(d[15]),"=f"(d[16]),"=f"(d[17]),"=f"(d[18]),"=f"(d[19]),"=f"(d[20]),"=f"(d[21]),"=f"(d[22]),"=f"(d[23]),"=f"(d[24]),"=f"(d[25]),"=f"(d[26]),"=f"(d[27]),"=f"(d[28]),"=f"(d[29]),"=f"(d[30]),"=f"(d[31])
        : "r"(ab), "r"(bb), "n"(AO), "n"(BO), "n"(BH));
}
template <uint32_t AO, uint32_t BO, uint32_t BH> __device__ __forceinline__ void wg_ss8t(float (&d)[4], uint32_t ab, uint32_t bb) {
    asm volatile("{\n.reg .b64 da, db;\n.reg .b32 ta, tb, th, ah;\nadd.u32 ta, %4, %6;\nadd.u32 tb, %5, %7;\nmov.b32 th, %8;\nmov.b32 ah, 0x40000040;\nmov.b64 da, {ta, ah};\nmov.b64 db, {tb, th};\n"
        "wgmma.mma_async.sync.aligned.m64n8k16.f32.bf16.bf16 {%0,%1,%2,%3}, da, db, 1, 1, 1, 1, 0;\n}\n"
        : "+f"(d[0]),"+f"(d[1]),"+f"(d[2]),"+f"(d[3])
        : "r"(ab), "r"(bb), "n"(AO), "n"(BO), "n"(BH));
}
template <uint32_t AO, uint32_t BO, uint32_t BH> __device__ __forceinline__ void wg_ss8t_z(float (&d)[4], uint32_t ab, uint32_t bb) {
    asm volatile("{\n.reg .b64 da, db;\n.reg .b32 ta, tb, th, ah;\nadd.u32 ta, %4, %6;\nadd.u32 tb, %5, %7;\nmov.b32 th, %8;\nmov.b32 ah, 0x40000040;\nmov.b64 da, {ta, ah};\nmov.b64 db, {tb, th};\n"
        "wgmma.mma_async.sync.aligned.m64n8k16.f32.bf16.bf16 {%0,%1,%2,%3}, da, db, 0, 1, 1, 1, 0;\n}\n"
        : "=f"(d[0]),"=f"(d[1]),"=f"(d[2]),"=f"(d[3])
        : "r"(ab), "r"(bb), "n"(AO), "n"(BO), "n"(BH));
}
template <uint32_t BO, uint32_t BH> __device__ __forceinline__ void wg_rs24_z(float (&d)[12], uint32_t a0, uint32_t a1, uint32_t a2, uint32_t a3, uint32_t bb) {
    asm volatile("{\n.reg .b64 db;\n.reg .b32 tb, th;\nadd.u32 tb, %16, %17;\nmov.b32 th, %18;\nmov.b64 db, {tb, th};\n"
        "wgmma.mma_async.sync.aligned.m64n24k16.f32.bf16.bf16 {%0,%1,%2,%3,%4,%5,%6,%7,%8,%9,%10,%11}, {%12,%13,%14,%15}, db, 0, 1, 1, 0;\n}\n"
        : "=f"(d[0]),"=f"(d[1]),"=f"(d[2]),"=f"(d[3]),"=f"(d[4]),"=f"(d[5]),"=f"(d[6]),"=f"(d[7]),"=f"(d[8]),"=f"(d[9]),"=f"(d[10]),"=f"(d[11])
        : "r"(a0), "r"(a1), "r"(a2), "r"(a3), "r"(bb), "n"(BO), "n"(BH));
}

constexpr uint32_t DH128 = 64u | 0x40000000u;
constexpr uint32_t DH64 = 32u | 0x80000000u;
constexpr uint32_t LBO4K = (4096u >> 4) << 16, LBO8K = (8192u >> 4) << 16, LBO1 = 1u << 16;

template <uint32_t AO, uint32_t BO, bool SW64, bool FIRST> __device__ __forceinline__ void stage_ss(float (&acc)[64], uint32_t ab, uint32_t bb) {
    constexpr uint32_t KS = SW64 ? 64 : 128, BH = SW64 ? DH64 : DH128, B0 = BO + (SW64 ? LBO4K : LBO8K);
    wg_fence();
    if (FIRST) wg_ss128_z<AO, B0, BH>(acc, ab, bb); else wg_ss128<AO, B0, BH>(acc, ab, bb);
    wg_ss128<AO + 2, B0 + KS, BH>(acc, ab, bb);
    wg_ss128<AO + 4, B0 + 2 * KS, BH>(acc, ab, bb);
    wg_ss128<AO + 6, B0 + 3 * KS, BH>(acc, ab, bb);
    wg_commit();
}
template <uint32_t BO, bool FIRST> __device__ __forceinline__ void stage_rs(float (&acc)[64], const uint32_t (&f)[16], uint32_t bb) {
    wg_fence();
    if (FIRST) wg_rs128_z<BO + LBO8K, DH128>(acc, f[0], f[1], f[2], f[3], bb); else wg_rs128<BO + LBO8K, DH128>(acc, f[0], f[1], f[2], f[3], bb);
    wg_rs128<BO + LBO8K + 128, DH128>(acc, f[4], f[5], f[6], f[7], bb);
    wg_rs128<BO + LBO8K + 256, DH128>(acc, f[8], f[9], f[10], f[11], bb);
    wg_rs128<BO + LBO8K + 384, DH128>(acc, f[12], f[13], f[14], f[15], bb);
    wg_commit();
}

template <int N> __device__ __forceinline__ void stash(uint32_t base, uint32_t sw, const uint32_t (&f)[N]) {
#pragma unroll
    for (int t = 0; t < N / 4; t++) stsm4(base + ((sw ^ (2 * t)) << 4), f[4 * t], f[4 * t + 1], f[4 * t + 2], f[4 * t + 3]);
}

template <int V0, int V1, int N> __device__ __forceinline__ void send_frag(const uint32_t (&f)[N], uint4* p, uint32_t tag) {
#pragma unroll
    for (int v = V0; v < V1; v++) st_pkt(p + v * 32, (f[4 * v] & ~1u) | tag, f[4 * v + 1], f[4 * v + 2], f[4 * v + 3]);
}
template <int V0, int V1, int N> __device__ __forceinline__ void send_h(const uint32_t (&f)[N], uint4* p) {
#pragma unroll
    for (int v = V0; v < V1; v++) {
        const int h = v >> 1, hi = v & 1;
        asm volatile("st.global.v4.u32 [%0], {%1,%2,%3,%4};" :: "l"(p + 4 * h + 64 * hi),
                     "r"(f[8 * h + hi]), "r"(f[8 * h + 2 + hi]), "r"(f[8 * h + 4 + hi]), "r"(f[8 * h + 6 + hi]) : "memory");
    }
}
template <int O, int N, int M> __device__ __forceinline__ void pack_sub(uint32_t (&f)[N], const float (&acc)[M]) {
#pragma unroll
    for (int i = 0; i < N; i++) f[i] = keep(pack2(acc[O + 2 * i], acc[O + 2 * i + 1]));
}
template <int N> __device__ __forceinline__ void recv_issue(uint32_t (&q)[N], const uint4* p) {
#pragma unroll
    for (int v = 0; v < N / 4; v++) ld_pkt(p + v * 32, q[4 * v], q[4 * v + 1], q[4 * v + 2], q[4 * v + 3]);
}
template <int N> __device__ __forceinline__ void recv_check(uint32_t (&q)[N], const uint4* p, uint32_t tag) {
    uint32_t it = 0;
    while (true) {
        uint32_t bad = 0;
#pragma unroll
        for (int v = 0; v < N / 4; v++) bad |= q[4 * v] ^ tag;
        if (__all_sync(0xffffffffu, (bad & 1u) == 0) || ++it > SPIN_GLOBAL) break;
        recv_issue(q, p);
    }
}
}

__global__ void __launch_bounds__(384, 1)
fused_kernel(const __grid_constant__ Maps maps, const __nv_bfloat16* __restrict__ xg, const __nv_bfloat16* __restrict__ gate_w,
             const char* __restrict__ pf_qkv, const char* __restrict__ pf_g, const char* __restrict__ pf_u,
             const char* __restrict__ pf_d, const char* __restrict__ pf_o, __nv_bfloat16* __restrict__ out) {
    extern __shared__ __align__(1024) uint8_t smem_raw[];
    const uint32_t sb = (uint32_t)__cvta_generic_to_shared(smem_raw);
    const int tid = threadIdx.x, lane = tid & 31;
    const int warp = __shfl_sync(0xffffffffu, tid >> 5, 0);
    const int j = (blockIdx.x >> 1) & 7;
    const int r = (((blockIdx.x >> 4) << 1) | (blockIdx.x & 1)) ^ RX;
    const uint32_t rank = blockIdx.x & 1;

    const int fc = 448 * (j >> 1) + 256 * (j & 1);
    if (warp == 0) { TSG(0, 30); TS(0, 0); }
    if (tid == 256) {
        mbar_init(sb + B_XFULL, 1); mbar_init(sb + B_FULL, 1); mbar_init(sb + B_FULL + 8, 1); mbar_init(sb + B_XFULL + 8, 1); mbar_init(sb + B_FULL + 16, 1);
        asm volatile("fence.mbarrier_init.release.cluster;" ::: "memory");
        TS2(0);
        mbar_expect(sb + B_FULL, 16384);
        tmaw3(sb + OFF_RING, &maps.kv, 64 * j, 0, 1, sb + B_FULL);
        mbar_expect(sb + B_XFULL, 16384);
        tma2(sb + OFF_X, &maps.x, 0, r * 128, sb + B_XFULL);
        TS2(1);
        mbar_expect(sb + B_FULL + 8, 16384);
        tmaw3(sb + OFF_RING + 16384, &maps.gu, fc, 0, 0, sb + B_FULL + 8);
#define PRO_MORE() do { mbar_expect(sb + B_XFULL + 8, 16384); tma2(sb + OFF_X + 16384, &maps.x, 64, r * 128, sb + B_XFULL + 8); TS2(2); \
        mbar_expect(sb + B_FULL + 16, 16384); tmaw3(sb + OFF_RING + 2 * 16384, &maps.kv, 64 * j, 64, 1, sb + B_FULL + 16); } while (0)
        if (PRO5) PRO_MORE();
    } else if (tid == 352) {
        for (int i = 0; i < 5; i++) { if (i > 2) mbar_init(sb + B_FULL + 8 * i, 1); mbar_init(sb + B_EMPTY + 8 * i, MC ? 4 : 2); }
        for (int i = 2; i < 9; i++) mbar_init(sb + B_XFULL + 8 * i, 1);
        asm volatile("fence.mbarrier_init.release.cluster;" ::: "memory");
    } else if (tid == 288) {
        for (int i = 0; i < 3; i++) mbar_init(sb + B_HSENT + 8 * i, 8);
        for (int i = 0; i < 4; i++) { mbar_init(sb + B_EFULL + 8 * i, 1); mbar_init(sb + B_EEMPTY + 8 * i, MC ? 4 : 2); }
        mbar_init(sb + B_XFREE, 2); mbar_init(sb + B_XFREE + 8, 2); mbar_init(sb + B_XFREE + 16, 2);
        mbar_init(sb + B_AHEAD, 1); mbar_init(sb + B_PART, 1); mbar_init(sb + B_GRDY, 1); mbar_init(sb + B_KVDONE, 8); mbar_init(sb + B_KVRDY, 2);
        asm volatile("fence.mbarrier_init.release.cluster;" ::: "memory");
    } else if (warp == 10 && lane < 10) {
        asm volatile("prefetch.tensormap [%0];" :: "l"(&maps.x + lane) : "memory");
    }
    __syncthreads();

    if (warp >= 8) {
        asm volatile("setmaxnreg.dec.sync.aligned.u32 56;");
        if (warp == 8) {
            if (lane == 0) {
                int slot = 3, ph = 1;
                uint32_t full, dst;
                if (!PRO5) PRO_MORE();
                mbar_expect(sb + B_XFULL + 16, 16384); tma2(sb + OFF_X + 2 * 16384, &maps.x, 128, r * 128, sb + B_XFULL + 16);
#define P_BEGIN(S, BYTES) full = sb + B_FULL + 8 * slot; dst = sb + OFF_RING + slot * 16384; \
                mbar_wait(sb + B_EMPTY + 8 * slot, ph); TS2(S); mbar_expect(full, BYTES); if (!MC || (((S) ^ rank) & 1) == 0)
#define P_END() if (++slot == 5) { slot = 0; ph ^= 1; }
                for (int s = 3; s < 16; s++) {
                    const int kb = (int)(0x7654763542312100ull >> (4 * s)) & 15;
                    P_BEGIN(s, 16384) {
                        if ((0x0DADu >> s) & 1) tmaw3(dst, &maps.kv, 64 * j, 64 * kb, 1, full);
                        else tmaw3(dst, &maps.gu, fc, 64 * kb, 0, full);
                    }
                    const int xb = (int)(0x0000000765403210ull >> (4 * s)) & 15;
                    if (xb) { mbar_expect(sb + B_XFULL + 8 * xb, 16384); tma2(sb + OFF_X + xb * 16384, &maps.x, 64 * xb, r * 128, sb + B_XFULL + 8 * xb); }
                    P_END()
                }
                for (int s = 0; s < 24; s++) {
                    P_BEGIN(16 + s, 16384) {
                        if (s < 8) {
                            tmaw3(dst, &maps.q64, 0, 64 * s, 2 * j, full);
                            tmaw3(dst + 8192, &maps.gu64, 224 * (j & 6) + 192 + 32 * (j & 1), 64 * s, 0, full);
                        } else {
                            tmaw3(dst, &maps.gu, fc + 64 * (s >> 3), 64 * (s & 7), 0, full);
                        }
                    }
                    P_END()
                }
                const int p = j >> 1;
#pragma unroll 1
                for (int t = 0; t < 18; t++) {
                    const int q = t >= 9, sl = (int)(0x846352107ull >> (4 * (t - 9 * q))) & 15;
                    const int u = (int)((q ? 0x432186758ull : 0x327064105ull) >> (4 * (t - 9 * q))) & 15;
                    const int cw = (j & 1) * 4 + ((p & 2) ^ ((t == 5 || t > 9) ? 0 : 2)), cc = 64 * cw;
                    if (sl < 5) {
                        full = sb + B_FULL + 8 * sl; dst = sb + OFF_RING + sl * 16384;
                        mbar_wait(sb + B_EMPTY + 8 * sl, q ^ 1);
                    } else {
                        full = sb + B_EFULL + 8 * (sl - 5); dst = sb + OFF_X + (sl == 7 ? 8 : sl == 8 ? 7 : sl) * 16384;
                        mbar_wait(sb + B_EEMPTY + 8 * (sl - 5), q);
                    }
                    TS2(40 + t);
                    mbar_expect(full, 16384);
                    if (!MC || ((t ^ rank) & 1) == 0) {
                        if (u > 4) {
                            const int js = u > 6 ? j ^ 1 : j;
                            tmaw3(dst, (u & 1) ? &maps.wow : &maps.wdw, 0, (u & 1) ? 64 * js : 448 * p + 256 * (js & 1) + 128, cw, full);
                        } else {
                            const int g = 14 * p + (u == 4 ? 6 : 8 * (u & 1) + (u & 2));
                            tmaw5(dst, &maps.wdp, cc, g, full); tmaw5(dst + 8192, &maps.wdp, cc + 64, g, full);
                        }
                    }
                }
            }
        } else if (warp < 11) {
            const int hx = warp - 9;
            uint32_t epoch;
            asm volatile("ld.relaxed.gpu.global.u32 %0, [%1];" : "=r"(epoch) : "l"(g_epoch + blockIdx.x) : "memory");
            {
                const uint4* xr = (const uint4*)(xg + (size_t)(r * 128 + j * 16 + hx * 8) * kD) + lane;
                const uint4 wa = __ldg((const uint4*)gate_w + lane), wb = __ldg((const uint4*)gate_w + 32 + lane);
                const uint32_t tag = (epoch + 1) & 1;
                uint4* gp = g_gx + r * 32;
                if (lane < 2) st_pkt(gp + j * 4 + hx * 2 + lane, tag ^ 1, 0, 0, 0);
                float s[8];
                if (GDELAY) mbar_wait(sb + B_XFULL, 0);
#pragma unroll
                for (int i0 = 0; i0 < 8; i0 += 4) {
                    uint4 va[4], vb[4];
#pragma unroll
                    for (int i = 0; i < 4; i++) { va[i] = __ldg(xr + (i0 + i) * 64); vb[i] = __ldg(xr + (i0 + i) * 64 + 32); }
#pragma unroll
                    for (int i = 0; i < 4; i++) {
                        float t0 = bf_lo(va[i].x) * bf_lo(wa.x), t1 = bf_hi(va[i].x) * bf_hi(wa.x);
                        t0 = fmaf(bf_lo(va[i].y), bf_lo(wa.y), t0); t1 = fmaf(bf_hi(va[i].y), bf_hi(wa.y), t1);
                        t0 = fmaf(bf_lo(va[i].z), bf_lo(wa.z), t0); t1 = fmaf(bf_hi(va[i].z), bf_hi(wa.z), t1);
                        t0 = fmaf(bf_lo(va[i].w), bf_lo(wa.w), t0); t1 = fmaf(bf_hi(va[i].w), bf_hi(wa.w), t1);
                        t0 = fmaf(bf_lo(vb[i].x), bf_lo(wb.x), t0); t1 = fmaf(bf_hi(vb[i].x), bf_hi(wb.x), t1);
                        t0 = fmaf(bf_lo(vb[i].y), bf_lo(wb.y), t0); t1 = fmaf(bf_hi(vb[i].y), bf_hi(wb.y), t1);
                        t0 = fmaf(bf_lo(vb[i].z), bf_lo(wb.z), t0); t1 = fmaf(bf_hi(vb[i].z), bf_hi(wb.z), t1);
                        t0 = fmaf(bf_lo(vb[i].w), bf_lo(wb.w), t0); t1 = fmaf(bf_hi(vb[i].w), bf_hi(wb.w), t1);
                        s[i0 + i] = t0 + t1;
                    }
                }
#pragma unroll
                for (int i = 0; i < 8; i++) {
#pragma unroll
                    for (int o = 16; o; o >>= 1) s[i] += __shfl_xor_sync(0xffffffffu, s[i], o);
                    s[i] = 1.f / (1.f + __expf(-s[i]));
                }
                if (lane < 2) {
                    const float v0 = lane ? s[4] : s[0], v1 = lane ? s[5] : s[1], v2 = lane ? s[6] : s[2], v3 = lane ? s[7] : s[3];
                    st_pkt(gp + j * 4 + hx * 2 + lane, (__float_as_uint(v0) & ~1u) | tag, __float_as_uint(v1), __float_as_uint(v2), __float_as_uint(v3));
                }
                if (hx == 1) {
                    asm volatile("st.shared.u32 [%0], %1;" :: "r"(sb + OFF_ONES + lane * 4), "r"(0x3f803f80u) : "memory");
                    asm volatile("fence.proxy.async.shared::cta;" ::: "memory");
                }
                asm volatile("bar.sync 3, 96;" ::: "memory");
                if (hx == 0) {
                    uint32_t q[4];
                    recv_issue(q, gp + lane);
                    recv_check(q, gp + lane, tag);
                    asm volatile("st.shared.v4.u32 [%0], {%1,%2,%3,%4};" :: "r"(sb + OFF_G + lane * 16), "r"(q[0]), "r"(q[1]), "r"(q[2]), "r"(q[3]) : "memory");
                    if (lane == 0) {
                        asm volatile("st.shared.u32 [%0], %1;" :: "r"(sb + OFF_EPOCH), "r"(epoch) : "memory");
                        g_epoch[blockIdx.x] = epoch + 1;
                    }
                    __syncwarp();
                    if (lane == 0) mbar_arrive(sb + B_GRDY);
                } else {
                    if (r == 0) {
                        float4* zp = (float4*)(g_kvacc + (((epoch & 1) ^ 1) * 8 + j) * 4 * 272);
                        for (int i = lane; i < 272; i += 32) zp[i] = make_float4(0.f, 0.f, 0.f, 0.f);
                    }
                }
            }
            TS(2 + hx, 1);
#define PUBLISH_H(B) do { mbar_wait(sb + B_HSENT + 8 * (B), 0); if (lane == 0) { \
                asm volatile("st.release.gpu.global.u32 [%0], %1;" :: "l"(g_hflag + (r * 8 + j) * 8 + (B)), "r"(epoch + 1) : "memory"); } __syncwarp(); } while (0)
            if (hx == 1) {
#pragma unroll 1
                for (int b = 0; b < 3; b++) { PUBLISH_H(b); TS(3, 5 + b); }
            } else {
                const float* accp = g_kvacc + ((epoch & 1) * 8 + j) * 4 * 272;
                unsigned* cnt = g_kvcnt + j * 32;
                mbar_wait(sb + B_KVDONE, 0);
                TS(2, 5);
                if (lane == 0) asm volatile("red.release.gpu.global.add.u32 [%0], 1;" :: "l"(cnt) : "memory");
                __syncwarp();
                TS(2, 2);
                {
                    const unsigned target = 16u * (epoch + 1);
                    uint32_t it = 0, v;
                    do {
                        asm volatile("ld.acquire.gpu.global.u32 %0, [%1];" : "=r"(v) : "l"(cnt) : "memory");
                    } while ((int)(v - target) < 0 && ++it < SPIN_GLOBAL);
                }
                TS(2, 3);
#pragma unroll
                for (int h = 0; h < 4; h++) {
                    const float4 d0 = __ldcg((const float4*)(accp + h * 272) + lane);
                    const float4 d1 = __ldcg((const float4*)(accp + h * 272 + 128) + lane);
                    const float2 z0 = __ldcg((const float2*)(accp + h * 272 + 256) + (lane & 3));
                    const float2 z1 = __ldcg((const float2*)(accp + h * 272 + 264) + (lane & 3));
                    const uint32_t ba = sb + OFF_STG + h * 768 + lane * 4;
                    asm volatile("st.shared.u32 [%0], %1;" :: "r"(ba), "r"(pack2(d0.x, d0.y)) : "memory");
                    asm volatile("st.shared.u32 [%0], %1;" :: "r"(ba + 128), "r"(pack2(d1.x, d1.y)) : "memory");
                    asm volatile("st.shared.u32 [%0], %1;" :: "r"(ba + 256), "r"(pack2(d0.z, d0.w)) : "memory");
                    asm volatile("st.shared.u32 [%0], %1;" :: "r"(ba + 384), "r"(pack2(d1.z, d1.w)) : "memory");
                    asm volatile("st.shared.u32 [%0], %1;" :: "r"(ba + 512), "r"(pack2(z0.x, z0.y)) : "memory");
                    asm volatile("st.shared.u32 [%0], %1;" :: "r"(ba + 640), "r"(pack2(z1.x, z1.y)) : "memory");
                }
                asm volatile("fence.proxy.async.shared::cta;" ::: "memory");
                __syncwarp();
                if (lane == 0) mbar_arrive(sb + B_KVRDY);
                TS(2, 4);
            }
        } else {
            uint32_t epoch;
            asm volatile("ld.relaxed.gpu.global.u32 %0, [%1];" : "=r"(epoch) : "l"(g_epoch + blockIdx.x) : "memory");
            asm volatile("bar.arrive 3, 96;" :: "r"(epoch) : "memory");
            const int b = blockIdx.x, p = j >> 1;
            mbar_wait(sb + B_XFULL, 0);
            if (PF0 && r >= PF0) {
                const int row = r * 32 + lane;
                asm volatile("prefetch.global.L2 [%0];" :: "l"(pf_qkv + row * 3072 + 1024 + j * 128));
                asm volatile("prefetch.global.L2 [%0];" :: "l"(pf_qkv + row * 3072 + 2048 + j * 128));
                asm volatile("prefetch.global.L2 [%0];" :: "l"(pf_g + row * 3584 + fc * 2));
                asm volatile("prefetch.global.L2 [%0];" :: "l"(pf_u + row * 3584 + fc * 2));
            }
#pragma unroll 1
            for (int kb = 1; kb < 8; kb++) {
                mbar_wait(sb + B_XFULL + 8 * kb, 0);
                const char* base = kb < 3 ? pf_g : kb < 5 ? pf_u : kb == 5 ? pf_qkv : pf_d;
                const int off = kb == 5 ? b * 12288 : b * 14336 + ((kb < 5 ? kb - 1 : kb) & 1) * 7168;
                if (kb == 5) {
                    asm volatile("prefetch.global.L2 [%0];" :: "l"(base + off + (lane >> 3) * 3072 + (lane & 7) * 128));
                } else {
                    asm volatile("prefetch.global.L2 [%0];" :: "l"(base + off + lane * 128));
                    if (lane < 24) asm volatile("prefetch.global.L2 [%0];" :: "l"(base + off + 4096 + lane * 128));
                }
                if (kb == 7) asm volatile("prefetch.global.L2 [%0];" :: "l"(pf_o + b * 4096 + lane * 128));
            }
            {
                uint4* mb = g_part + (size_t)(r * 2 + (j & 1)) * 16384 + (((p ^ 1) * 4 + p) << 10) + lane;
#pragma unroll 1
                for (int i = 0; i < (NOPRE ? 0 : 32); i++) { st_pkt(mb + i * 32, epoch & 1, 0, 0, 0); __nanosleep(40); }
                __syncwarp();
                if (lane == 0) mbar_arrive(sb + B_KVRDY);
            }
            {
                const uint32_t want = epoch + 1;
                const int hrow = (r * 4 + p) * 5 * 128;
                const unsigned* fl = g_hflag + (r * 8 + (j & 6)) * 8 + (lane & 15);
                uint32_t it = 0;
                int i = 0;
                mbar_wait(sb + B_HSENT + 8, 0);
#pragma unroll 1
                while (i < 3 && ++it < SPIN_GLOBAL) {
                    uint32_t v;
                    asm volatile("ld.acquire.gpu.global.u32 %0, [%1];" : "=r"(v) : "l"(fl) : "memory");
                    const uint32_t rdy = __ballot_sync(0xffffffffu, v == want);
#pragma unroll 1
                    while (i < 3 && ((rdy >> i) & 0x101u) == 0x101u) {
                        if (i < 2) mbar_wait(sb + B_XFREE + 8 * i, 0);
                        if (lane == 0) {
                            const int pc = (6 - 2 * i) % 6;
                            asm volatile("fence.proxy.async.global;" ::: "memory");
                            TS2(140 + i);
                            mbar_expect(sb + B_XFULL + 8 * pc, i != 1 ? 32768 : 16384);
                            tma2(sb + OFF_X + pc * 16384, i != 1 ? &maps.hx2 : &maps.hx, 0, hrow + pc * 128, sb + B_XFULL + 8 * pc);
                        }
                        i++;
                    }
                }
            }
        }
    } else {
        asm volatile("setmaxnreg.inc.sync.aligned.u32 224;");
        const int wg = warp >> 2;
        const bool elect = (tid & 127) == 0;
        const uint32_t sbd = (sb & 0x3FFFFu) >> 4, xlo = (sbd + wg * 512) | LBO1;
        auto release = [&](uint32_t bar) {
            if (elect) {
                mbar_arrive(sb + bar);
            }
        };
#define S_SL(S) ((S) < 40 ? (S) % 5 : (int)((0x846352107ull >> (4 * (((S) - 40) % 9))) & 15))
#define S_WAIT(S) do { mbar_wait(sb + (S_SL(S) < 5 ? B_FULL + 8 * S_SL(S) : B_EFULL + 8 * (S_SL(S) - 5)), (S) < 40 ? ((S) / 5) & 1 : (S) >= 49); \
            if (PROF && tid == 0) TS2(64 + (S)); } while (0)
#define S_B(S) (S_SL(S) < 5 ? OFF_RING / 16 + S_SL(S) * 1024 : (S_SL(S) == 7 ? 8 : S_SL(S) == 8 ? 7 : S_SL(S)) * 1024)
#define S_REL(S) do { if ((S) < 49) release(S_SL(S) < 5 ? B_EMPTY + 8 * S_SL(S) : B_EEMPTY + 8 * (S_SL(S) - 5)); } while (0)
#define G1(S, acc, SW, KB) stage_ss<(KB) * 1024, S_B(S), SW, (KB) == 0>(acc, xlo, sbd)
#define RET(S) do { S_WAIT((S) + 1); wg_wait<1>(); S_REL((S) - 1); } while (0)
#define RET2(S) do { S_WAIT((S) + 1); wg_wait<2>(); S_REL((S) - 1); } while (0)
#define SCHED() mbar_wait(sb + B_XFULL + 8 * 7, 0)
#define A2_SYNC() do { asm volatile("fence.proxy.async.shared::cta;" ::: "memory"); asm volatile("bar.sync %0, 128;" :: "r"(wg + 1) : "memory"); } while (0)
#define H_EPI(acc, F, I0, I1, OG, OU) _Pragma("unroll") for (int i = (I0); i < (I1); i++) \
            F[i] = keep(hmul2(pack2(acc[(OG) + 2 * i] * acc[(OU) + 2 * i], acc[(OG) + 2 * i + 1] * acc[(OU) + 2 * i + 1]), (i & 1) ? m_hi : m_lo))
#define PHI(acc, F, I0, I1) _Pragma("unroll") for (int i = (I0); i < (I1); i++) F[i] = keep(phi2(acc[2 * i], acc[2 * i + 1]))

        float a0[64], b0[64], a1[64], a2_[64], a3[64];
        mbar_wait(sb + B_XFULL, 0);
#define X_WAIT(KB) do { mbar_wait(sb + B_XFULL + 8 * (KB), 0); if (PROF && tid == 0) TS2(128 + (KB)); } while (0)
        S_WAIT(0); G1(0, b0, false, 0);
        if ((warp & 3) == 0) TS(wg, 1);
        S_WAIT(1); G1(1, a0, false, 0); RET(1);
        X_WAIT(1); G1(2, b0, false, 1); RET(2);
        X_WAIT(2); G1(3, b0, false, 2); RET(3);
        G1(4, a0, false, 1); RET(4);
        X_WAIT(3); G1(5, b0, false, 3); RET(5);
        G1(6, a0, false, 2); RET(6);
        X_WAIT(4); G1(7, b0, false, 4); RET(7);
        X_WAIT(5); G1(8, b0, false, 5); RET(8);
        G1(9, a0, false, 3); RET(9);
        X_WAIT(6); G1(10, b0, false, 6); RET(10);
        X_WAIT(7); G1(11, b0, false, 7); RET(11);
        G1(12, a0, false, 4);
        const uint32_t lrow = ((lane & 7) + 8 * ((lane >> 3) & 1)) * 128;
        const uint32_t srow = (warp & 3) * 2048 + lrow;
        const uint32_t ssw = (lane >> 4) ^ (lane & 7);
        uint4* const hsend = g_hx + (size_t)((r * 4 + (j >> 1)) * 5 + (j & 1)) * 1024 + warp * 128 + (lane >> 2) * 8 + (lane & 3);
#define SENT_H(B) do { __syncwarp(); if (lane == 0) mbar_arrive(sb + B_HSENT + 8 * (B)); } while (0)
        RET(12);
        pin(b0);
        uint32_t fh0[16], fh1[16], fh2[16], fh3[8], fo[16], pk[16], pv[16];
        float kv[32], zs[4];
        const uint32_t stg = sb + OFF_STG + wg * 8192, stl = stg + (warp & 1) * 2048 + lrow;
#define KV_ROUND(Z) do { A2_SYNC(); wg_fence(); \
            wg_ss64t##Z<8192 + 256, 8192, DH128>(kv, xlo, xlo); wg_ss64t<8192 + 384, 8192 + 128, DH128>(kv, xlo, xlo); \
            wg_ss8t##Z<8192, OFF_ONES / 16, 0>(zs, xlo, sbd); wg_ss8t<8192 + 128, OFF_ONES / 16, 0>(zs, xlo, sbd); wg_commit(); } while (0)
        G1(13, a0, false, 5); SCHED(); pack_sub<32>(pv, b0); PHI(b0, pk, 0, 4); RET(13);
        G1(14, a0, false, 6); SCHED(); if (!(warp & 2)) stash<16>(stl + 4096, ssw, pv); PHI(b0, pk, 4, 10); RET(14);
        G1(15, a0, false, 7); SCHED(); PHI(b0, pk, 10, 16); RET(15);
        if ((warp & 3) == 0) TS(wg, 2);

        G1(16, a1, true, 0); SCHED(); if (!(warp & 2)) stash<16>(stl, ssw, pk);
        mbar_wait(sb + B_GRDY, 0);
        float g_lo, g_hi;
        uint32_t tag;
        {
            const uint32_t ga = sb + OFF_G + (warp * 16 + (lane >> 2)) * 4;
            asm volatile("ld.shared.f32 %0, [%1];" : "=f"(g_lo) : "r"(ga) : "memory");
            asm volatile("ld.shared.f32 %0, [%1];" : "=f"(g_hi) : "r"(ga + 32) : "memory");
            asm volatile("ld.shared.u32 %0, [%1];" : "=r"(tag) : "r"(sb + OFF_EPOCH) : "memory");
        }
        float* const kvp = g_kvacc + (((tag & 1) * 8 + j) * 4 + (warp & 3)) * 272;
        tag = (tag + 1) & 1;
        const uint32_t m_lo = pack2(1.f - g_lo, 1.f - g_lo), m_hi = pack2(1.f - g_hi, 1.f - g_hi);
        RET(16);
        pin(a0);
        G1(17, a1, true, 1); SCHED(); H_EPI(a0, fh0, 0, 16, 0, 32); RET(17);
        G1(18, a1, true, 2); KV_ROUND(_z); RET2(18);
        G1(19, a1, true, 3); SCHED(); send_h<0, 1>(fh0, hsend); RET(19);
        G1(20, a1, true, 4); SCHED(); if (warp & 2) { stash<16>(stl, ssw, pk); stash<16>(stl + 4096, ssw, pv); } RET(20);
        G1(21, a1, true, 5); KV_ROUND(); RET2(21);
        G1(22, a1, true, 6); RET(22);
        pin(kv); pin(zs);
        G1(23, a1, true, 7); SCHED();
#define KV_RED(W) do { asm volatile("red.global.add.v4.f32 [%0], {%1,%2,%3,%4};" :: "l"(kvp + lane * 4), "f"(kv[8 * W]), "f"(kv[8 * W + 1]), "f"(kv[8 * W + 2]), "f"(kv[8 * W + 3]) : "memory"); \
                       asm volatile("red.global.add.v4.f32 [%0], {%1,%2,%3,%4};" :: "l"(kvp + 128 + lane * 4), "f"(kv[8 * W + 4]), "f"(kv[8 * W + 5]), "f"(kv[8 * W + 6]), "f"(kv[8 * W + 7]) : "memory"); } while (0)
        if ((warp & 3) == 0) KV_RED(0); else if ((warp & 3) == 1) KV_RED(1); else if ((warp & 3) == 2) KV_RED(2); else KV_RED(3);
        if ((lane & 3) == 0) {
            asm volatile("red.global.add.f32 [%0], %1;" :: "l"(kvp + 256 + (lane >> 2)), "f"(zs[0]) : "memory");
            asm volatile("red.global.add.f32 [%0], %1;" :: "l"(kvp + 264 + (lane >> 2)), "f"(zs[2]) : "memory");
        }
        __syncwarp();
        if (lane == 0) mbar_arrive(sb + B_KVDONE);
        RET(23);
        if ((warp & 3) == 0) TS(wg, 3);

        G1(24, a2_, false, 0); SCHED(); send_h<1, 2>(fh0, hsend); RET(24);
        pin(a1);
        G1(25, a2_, false, 1); SCHED(); send_h<2, 3>(fh0, hsend); H_EPI(a1, fh3, 0, 8, 32, 48); RET(25);
        G1(26, a2_, false, 2); SCHED(); send_h<3, 4>(fh0, hsend); SENT_H(0); PHI(a1, fo, 0, 4); RET(26);
        G1(27, a2_, false, 3); SCHED(); send_h<0, 1>(fh3, hsend + 4 * 1024 - (j & 1) * 1020); PHI(a1, fo, 4, 8); RET(27);
        G1(28, a2_, false, 4); SCHED(); send_h<1, 2>(fh3, hsend + 4 * 1024 - (j & 1) * 1020); SENT_H(1); PHI(a1, fo, 8, 12); RET(28);
        G1(29, a2_, false, 5); SCHED(); PHI(a1, fo, 12, 16); RET(29);
        G1(30, a2_, false, 6); RET(30);
        G1(31, a2_, false, 7); RET(31);
        if ((warp & 3) == 0) TS(wg, 4);

        float on[4][12];
#define O_SCALE(h) do { const float s_lo = __fdividef(g_lo, on[h][8] + 1e-6f), s_hi = __fdividef(g_hi, on[h][10] + 1e-6f); \
            const uint32_t sl_ = pack2(s_lo, s_lo), sh_ = pack2(s_hi, s_hi); \
            fo[4 * h] = keep(hmul2(pack2(on[h][0], on[h][1]), sl_)); fo[4 * h + 1] = keep(hmul2(pack2(on[h][2], on[h][3]), sh_)); \
            fo[4 * h + 2] = keep(hmul2(pack2(on[h][4], on[h][5]), sl_)); fo[4 * h + 3] = keep(hmul2(pack2(on[h][6], on[h][7]), sh_)); } while (0)
        uint4* const lsend = g_lx + (size_t)(r * 8 + j) * 2048 + warp * 128 + lane;
        const uint4* const lrecv = g_lx + (size_t)(r * 8 + (j ^ 1)) * 2048 + warp * 128 + lane;
        G1(32, a3, false, 0); RET(32);
        pin(a2_);
        G1(33, a3, false, 1); SCHED(); H_EPI(a2_, fh1, 0, 16, 0, 32); send_h<0, 1>(fh1, hsend + 2 * 1024); RET(33);
        G1(34, a3, false, 2); SCHED(); send_h<1, 3>(fh1, hsend + 2 * 1024); RET(34);
        if (elect) mbar_arrive(sb + B_XFREE);
        G1(35, a3, false, 3); SCHED(); send_h<3, 4>(fh1, hsend + 2 * 1024); SENT_H(2);
        if ((warp & 3) == 0) TS(wg, 5);
        mbar_wait(sb + B_KVRDY, 0);
        if ((warp & 3) == 0) TS(wg, 6);
        wg_fence();
#define O_MMA(h) wg_rs24_z<OFF_STG / 16 + (h) * 48 + (8u << 16), 16>(on[h], fo[4 * (h)], fo[4 * (h) + 1], fo[4 * (h) + 2], fo[4 * (h) + 3], sbd)
        O_MMA(0); O_MMA(1); O_MMA(2); O_MMA(3);
        wg_commit();
        RET2(35);
        G1(36, a3, false, 4); RET(36);
        pin(on[0]); pin(on[1]); pin(on[2]); pin(on[3]);
        release(B_EEMPTY + 16);
        G1(37, a3, false, 5); SCHED(); O_SCALE(0); O_SCALE(1); O_SCALE(2); O_SCALE(3); RET(37);
        if (elect) mbar_arrive(sb + B_XFREE + 8);
        G1(38, a3, false, 6); SCHED(); send_frag<0, 2>(fo, lsend, tag); RET(38);
        release(B_EEMPTY);
        G1(39, a3, false, 7); SCHED(); send_frag<2, 4>(fo, lsend, tag); RET(39);
        release(B_EEMPTY + 8);
        if ((warp & 3) == 0) TS(wg, 7);

#define G2S(S, acc, U) stage_ss<(U) * 1024, S_B(S), false, (S) == 45>(acc, xlo, sbd)
#define G2R(S, acc, F) stage_rs<S_B(S), (S) == 40>(acc, F, sbd)
#define H_WAIT(P) do { mbar_wait(sb + B_XFULL + 8 * (P), 1); if (PROF && tid == 0) TS2(150 + (P)); } while (0)
        const int p = j >> 1, pw = (p & 2) ^ 2;
        const bool own = wg == (p & 1);
        uint4* const pbase = g_part + (size_t)(r * 2 + (j & 1)) * 16384 + (warp & 3) * 256 + lane;

        float p1[64], p2[64];
        uint32_t po[16], ph2[16];
        G2R(40, p1, fo); RET(40);
        release(B_EEMPTY + 24);
        pin(a3);
        H_WAIT(0); G2S(41, p1, 0); SCHED(); H_EPI(a3, fh2, 0, 16, 0, 32); send_frag<0, 2>(fh2, lsend + 1024, tag); RET(41);
        G2S(42, p1, 1); SCHED(); recv_issue(po, lrecv); send_frag<2, 4>(fh2, lsend + 1024, tag); RET(42);
        H_WAIT(4); G2S(43, p1, 4); RET(43);
        G2R(44, p1, fh2); RET(44);
        G2S(45, p2, 0); SCHED(); recv_check(po, lrecv, tag); recv_issue(ph2, lrecv + 1024); RET(45);
        G2R(46, p1, po); RET(46);
        H_WAIT(2); G2S(47, p1, 2); RET(47);
        G2S(48, p1, 3); SCHED(); recv_check(ph2, lrecv + 1024, tag); RET(48);
        G2R(49, p1, ph2); RET(49);
        if ((warp & 3) == 0) TS(wg, 8);
        uint32_t sp[32], qa[32], qb[32];
        uint4* const s1 = pbase + (((pw + wg) * 4 + p) << 10);
        G2R(50, p2, fo); RET(50);
        pin(p1);
        G2R(51, p2, po); SCHED(); pack_sub<0>(sp, p1); send_frag<0, 2>(sp, s1, tag); RET(51);
        G2R(52, p2, fh2); SCHED(); send_frag<2, 5>(sp, s1, tag); RET(52);
        if (elect) mbar_arrive(sb + B_XFREE + 16);
        G2R(53, p2, ph2); SCHED(); send_frag<5, 8>(sp, s1, tag); RET(53);
        const uint4* ra = pbase + ((p * 4 + pw) << 10);
        const uint4* rc = pbase + ((p * 4 + (p ^ 1)) << 10);
        if (own) mbar_wait(sb + B_AHEAD, 0);
        G2S(54, p2, 1); RET(54);
        G2S(55, p2, 2); RET(55);
        G2S(56, p2, 3); RET(56);
        G2S(57, p2, 4); SCHED();
        if ((warp & 3) == 0) TS(wg, 9);
#define PART_COPY() do { mbar_wait(sb + B_XFREE + 16, 0); mbar_expect(sb + B_PART, 32768); \
            asm volatile("cp.async.bulk.shared::cluster.global.mbarrier::complete_tx::bytes [%0], [%1], %2, [%3];" \
                         :: "r"(sb + OFF_RING), "l"(ra), "r"(32768), "r"(sb + B_PART) : "memory"); } while (0)
        if (!own && elect) mbar_arrive(sb + B_AHEAD);
        wg_wait<0>();
        pin(p2);
        if ((warp & 3) == 0) TS(wg, 11);
        if (!own) {
            if (COPY_AT == 0 && elect) PART_COPY();
            pack_sub<0>(sp, p2);
            if (COPY_AT == 1 && elect) PART_COPY();
            send_frag<0, 4>(sp, pbase + (((p ^ 1) * 4 + p) << 10), tag);
            if (COPY_AT == 2 && elect) PART_COPY();
            send_frag<4, 8>(sp, pbase + (((p ^ 1) * 4 + p) << 10), tag);
            if (COPY_AT == 3 && elect) PART_COPY();
        } else {
            recv_issue(sp, rc);
            uint32_t f0[16], f1[16];
            pack_sub<0>(f0, p2); pack_sub<32>(f1, p2);
            mbar_wait(sb + B_PART, 0);
            if ((warp & 3) == 0) TS(wg, 10);
            const uint32_t pa = sb + OFF_RING + (warp & 3) * 4096 + lane * 16;
#pragma unroll
            for (int v = 0; v < 8; v++) {
                asm volatile("ld.shared.v4.u32 {%0,%1,%2,%3}, [%4];" : "=r"(qa[4 * v]), "=r"(qa[4 * v + 1]), "=r"(qa[4 * v + 2]), "=r"(qa[4 * v + 3]) : "r"(pa + v * 512) : "memory");
                asm volatile("ld.shared.v4.u32 {%0,%1,%2,%3}, [%4];" : "=r"(qb[4 * v]), "=r"(qb[4 * v + 1]), "=r"(qb[4 * v + 2]), "=r"(qb[4 * v + 3]) : "r"(pa + 16384 + v * 512) : "memory");
            }
            recv_check(qa, ra, tag); recv_check(qb, ra + 1024, tag);
#pragma unroll
            for (int i = 0; i < 32; i++) qa[i] = keep(hadd2(qa[i], qb[i]));
            if ((warp & 3) == 0) TS(wg, 12);
            recv_check(sp, rc, tag);
            if ((warp & 3) == 0) TS(wg, 13);
#pragma unroll
            for (int i = 0; i < 16; i++) { f0[i] = hadd2(hadd2(f0[i], sp[i]), qa[i]); f1[i] = hadd2(hadd2(f1[i], sp[16 + i]), qa[16 + i]); }
            const uint32_t slab = sb + OFF_X + 2 * 16384 + wg * 8192;
            stash<16>(slab + srow, ssw, f0); stash<16>(slab + 16384 + srow, ssw, f1);
            __syncwarp();
            __nv_bfloat16* op = out + (size_t)(r * 128 + warp * 16 + (lane >> 4)) * kD + (j & 1) * 256 + (p & 2) * 64 + (lane & 15) * 8;
#pragma unroll
            for (int i = 0; i < 8; i++) {
                const int row = i * 2 + (lane >> 4);
                uint4 v;
                asm volatile("ld.shared.v4.u32 {%0,%1,%2,%3}, [%4];" : "=r"(v.x), "=r"(v.y), "=r"(v.z), "=r"(v.w)
                             : "r"(slab + (lane & 8) * 2048 + ((warp & 3) * 16 + row) * 128 + (((lane & 7) ^ (row & 7)) << 4)) : "memory");
                *(uint4*)(op + i * 2 * kD) = v;
            }
        }
        if ((warp & 3) == 0) { TS(wg, 14); TSG(wg, 31); }
    }
}

typedef CUresult (*EncodeFn)(CUtensorMap*, CUtensorMapDataType, cuuint32_t, void*, const cuuint64_t*, const cuuint64_t*, const cuuint32_t*,
                             const cuuint32_t*, CUtensorMapInterleave, CUtensorMapSwizzle, CUtensorMapL2promotion, CUtensorMapFloatOOBfill);

static void encode(EncodeFn fn, CUtensorMap* m, int rank, const void* base, const cuuint64_t (&gd)[5], const cuuint64_t (&gs)[4],
                   const cuuint32_t (&bd)[5], CUtensorMapSwizzle sw) {
    cuuint32_t es[5] = {1, 1, 1, 1, 1};
    fn(m, CU_TENSOR_MAP_DATA_TYPE_BFLOAT16, rank, const_cast<void*>(base), gd, gs, bd, es, CU_TENSOR_MAP_INTERLEAVE_NONE, sw,
       CU_TENSOR_MAP_L2_PROMOTION_L2_128B, CU_TENSOR_MAP_FLOAT_OOB_FILL_NONE);
}

extern "C" void kernel_launch(void* const* d_in, const int* in_sizes, int n_in, void* d_out, int out_size) {
    const char* x = (const char*)d_in[0];
    const char* wqkv = (const char*)d_in[1];
    const char* wo = (const char*)d_in[2];
    const char* wg = (const char*)d_in[4];
    const char* wu = (const char*)d_in[5];
    const char* wd = (const char*)d_in[6];
    void* fnp = nullptr;
    cudaDriverEntryPointQueryResult qr;
    cudaGetDriverEntryPoint("cuTensorMapEncodeTiled", &fnp, cudaEnableDefault, &qr);
    EncodeFn fn = (EncodeFn)fnp;
    Maps maps;
    const char* lo = wg < wu ? wg : wu;
    const uint64_t diff = wg < wu ? (uint64_t)(wu - wg) : (uint64_t)(wg - wu);
    const CUtensorMapSwizzle S128 = CU_TENSOR_MAP_SWIZZLE_128B, S64 = CU_TENSOR_MAP_SWIZZLE_64B;
    encode(fn, &maps.x, 2, x, {512, 2048, 1, 1}, {1024, 0, 0}, {64, 128, 1, 1}, S128);
    encode(fn, &maps.gu, 3, lo, {1792, 512, 2, 1}, {3584, diff, 0}, {64, 64, 2, 1}, S128);
    encode(fn, &maps.kv, 3, wqkv, {512, 512, 3, 1}, {3072, 1024, 0}, {64, 64, 2, 1}, S128);
    encode(fn, &maps.q64, 3, wqkv, {32, 512, 48, 1}, {3072, 64, 0}, {32, 64, 2, 1}, S64);
    encode(fn, &maps.gu64, 3, lo, {1792, 512, 2, 1}, {3584, diff, 0}, {32, 64, 2, 1}, S64);
    encode(fn, &maps.wdw, 3, wd, {64, 1792, 8, 1}, {1024, 128, 0}, {64, 64, 2, 1}, S128);
    encode(fn, &maps.wow, 3, wo, {64, 512, 8}, {1024, 128}, {64, 64, 2}, S128);
    encode(fn, &maps.wdp, 5, wd, {512, 2, 4, 4, 56}, {1024, 8192, 2048, 32768}, {64, 2, 4, 4, 2}, S128);
    void* hx = nullptr;
    cudaGetSymbolAddress(&hx, g_hx);
    encode(fn, &maps.hx, 2, hx, {64, 16 * 4 * 5 * 128}, {128}, {64, 128}, S128);
    encode(fn, &maps.hx2, 2, hx, {64, 16 * 4 * 5 * 128}, {128}, {64, 256}, S128);
    cudaFuncSetAttribute(fused_kernel, cudaFuncAttributeMaxDynamicSharedMemorySize, SMEM_BYTES);
    cudaLaunchConfig_t cfg = {};
    cfg.gridDim = dim3(128);
    cfg.blockDim = dim3(384);
    cfg.dynamicSmemBytes = SMEM_BYTES;
    cfg.stream = cudaStreamPerThread;
    cudaLaunchAttribute at[1];
    at[0].id = cudaLaunchAttributeClusterDimension;
    at[0].val.clusterDim.x = 2; at[0].val.clusterDim.y = 1; at[0].val.clusterDim.z = 1;
    cfg.attrs = at;
    cfg.numAttrs = MC ? 1 : 0;
    cudaLaunchKernelEx(&cfg, fused_kernel, maps, (const __nv_bfloat16*)d_in[0], (const __nv_bfloat16*)d_in[7], wqkv, wg, wu, wd, wo, (__nv_bfloat16*)d_out);
}
```

```cpp
#include <cuda_runtime.h>
#include <cuda.h>
#include <cuda_bf16.h>
#include <stdint.h>

#define MC 0
#define PFMODE 1
#define PHI_SAT 0
#define EXPT 0
#define RX 0
#define PF0 4
#define GDELAY 1
#define PRO5 0
#define NOPRE 0
#define PROF 0

namespace {

constexpr int kD = 512;
constexpr uint32_t OFF_X = 0, OFF_STG = 131072, OFF_RING = 147456, OFF_MISC = 229376;
constexpr uint32_t B_FULL = OFF_MISC, B_EMPTY = OFF_MISC + 40, B_XFULL = OFF_MISC + 80;
constexpr uint32_t B_GRDY = OFF_MISC + 152, B_KVDONE = OFF_MISC + 160, B_KVRDY = OFF_MISC + 168;
constexpr uint32_t B_HSENT = OFF_MISC + 176, B_XFREE = OFF_MISC + 200;
constexpr uint32_t OFF_EPOCH = OFF_MISC + 240, OFF_G = OFF_MISC + 256;
constexpr uint32_t B_AHEAD = OFF_MISC + 248, B_PART = OFF_MISC + 232;
constexpr uint32_t OFF_ONES = OFF_MISC + 768;
constexpr uint32_t B_EFULL = OFF_MISC + 896, B_EEMPTY = OFF_MISC + 928;
constexpr uint32_t B_LATE = OFF_MISC + 960, B_WARP = OFF_MISC + 992;
constexpr uint32_t SMEM_BYTES = OFF_MISC + 1056;
constexpr uint32_t SPIN_GLOBAL = 1u << 14;

struct alignas(64) Maps { CUtensorMap x, gu, kv, q64, gu64, wdw, wow, wdp, hx, hx2; };

}

__device__ uint4 g_part[16 * 2 * 4 * 4 * 1024];
__device__ uint4 g_hx[16 * 4 * 5 * 1024];
__device__ uint4 g_lx[16 * 8 * 2 * 1024];
__device__ unsigned g_hflag[128 * 8];
__device__ uint4 g_gx[16 * 32];
__device__ float g_kvacc[2 * 8 * 4 * 272];
__device__ unsigned g_kvcnt[8 * 32];
__device__ unsigned g_epoch[128];
#define TS(role, idx)
#define TS2(idx)
#define CNT(idx, v) (void)(v)
#define TSG(role, idx)

namespace {

__device__ __forceinline__ void mbar_init(uint32_t bar, uint32_t cnt) { asm volatile("mbarrier.init.shared::cta.b64 [%0], %1;" :: "r"(bar), "r"(cnt) : "memory"); }
__device__ __forceinline__ void mbar_expect(uint32_t bar, uint32_t bytes) { asm volatile("mbarrier.arrive.expect_tx.shared::cta.b64 _, [%0], %1;" :: "r"(bar), "r"(bytes) : "memory"); }
__device__ __forceinline__ void mbar_arrive(uint32_t bar) { asm volatile("mbarrier.arrive.shared::cta.b64 _, [%0];" :: "r"(bar) : "memory"); }
__device__ __forceinline__ void mbar_arrive_cta(uint32_t bar, uint32_t cta) {
    asm volatile("{\n.reg .b32 ra;\nmapa.shared::cluster.u32 ra, %0, %1;\nmbarrier.arrive.shared::cluster.b64 _, [ra];\n}" :: "r"(bar), "r"(cta) : "memory");
}
__device__ __forceinline__ void mbar_wait(uint32_t bar, uint32_t parity) {
    asm volatile("{\n.reg .pred p;\n.reg .u32 c;\n"
                 "mbarrier.try_wait.parity.shared::cta.b64 p, [%0], %1;\n@p bra DONE;\n"
                 "mov.u32 c, 0;\nLAB_WAIT:\nmbarrier.try_wait.parity.shared::cta.b64 p, [%0], %1;\n@p bra DONE;\n"
                 "add.u32 c, c, 1;\nsetp.lt.u32 p, c, 65536;\n@p bra LAB_WAIT;\nDONE:\n}" :: "r"(bar), "r"(parity) : "memory");
}
__device__ __forceinline__ void tma2(uint32_t dst, const CUtensorMap* m, int c0, int c1, uint32_t bar) {
    asm volatile("cp.async.bulk.tensor.2d.shared::cluster.global.mbarrier::complete_tx::bytes [%0], [%1, {%3, %4}], [%2];"
        :: "r"(dst), "l"(m), "r"(bar), "r"(c0), "r"(c1) : "memory");
}
__device__ __forceinline__ void tmaw2(uint32_t dst, const CUtensorMap* m, int c0, int c1, uint32_t bar) {
    tma2(dst, m, c0, c1, bar);
}
__device__ __forceinline__ void tmaw3(uint32_t dst, const CUtensorMap* m, int c0, int c1, int c2, uint32_t bar) {
    asm volatile("cp.async.bulk.tensor.3d.shared::cluster.global.mbarrier::complete_tx::bytes [%0], [%1, {%3, %4, %5}], [%2];"
        :: "r"(dst), "l"(m), "r"(bar), "r"(c0), "r"(c1), "r"(c2) : "memory");
}
__device__ __forceinline__ void tmaw5(uint32_t dst, const CUtensorMap* m, int c0, int c4, uint32_t bar) {
    asm volatile("cp.async.bulk.tensor.5d.shared::cluster.global.mbarrier::complete_tx::bytes [%0], [%1, {%3, %5, %5, %5, %4}], [%2];"
        :: "r"(dst), "l"(m), "r"(bar), "r"(c0), "r"(c4), "r"(0) : "memory");
}
__device__ __forceinline__ void bulk_in(uint32_t dst, const void* src, uint32_t bytes, uint32_t bar) {
    mbar_expect(bar, bytes);
    asm volatile("cp.async.bulk.shared::cluster.global.mbarrier::complete_tx::bytes [%0], [%1], %2, [%3];" :: "r"(dst), "l"(src), "r"(bytes), "r"(bar) : "memory");
}
__device__ __forceinline__ void wg_fence() { asm volatile("wgmma.fence.sync.aligned;" ::: "memory"); }
__device__ __forceinline__ void wg_commit() { asm volatile("wgmma.commit_group.sync.aligned;" ::: "memory"); }
template <int N> __device__ __forceinline__ void wg_wait() { asm volatile("wgmma.wait_group.sync.aligned %0;" :: "n"(N) : "memory"); }
template <int N> __device__ __forceinline__ void pin(float (&d)[N]) {
#pragma unroll
    for (int i = 0; i < N; i++) asm volatile("" : "+f"(d[i]) :: "memory");
}
__device__ __forceinline__ uint32_t pack2(float lo, float hi) { uint32_t r; asm("cvt.rn.bf16x2.f32 %0, %1, %2;" : "=r"(r) : "f"(hi), "f"(lo)); return r; }
__device__ __forceinline__ uint32_t keep(uint32_t v) { asm volatile("" : "+r"(v)); return v; }
__device__ __forceinline__ uint32_t hadd2(uint32_t a, uint32_t b) { uint32_t r; asm("add.bf16x2 %0, %1, %2;" : "=r"(r) : "r"(a), "r"(b)); return r; }
__device__ __forceinline__ uint32_t hmul2(uint32_t a, uint32_t b) { uint32_t r; asm("mul.bf16x2 %0, %1, %2;" : "=r"(r) : "r"(a), "r"(b)); return r; }
__device__ __forceinline__ uint32_t phi2(float t0, float t1) {
    float e0, e1;
    asm("ex2.approx.ftz.f32 %0, %1;" : "=f"(e0) : "f"(t0 * 1.4426950408889634f));
    asm("ex2.approx.ftz.f32 %0, %1;" : "=f"(e1) : "f"(t1 * 1.4426950408889634f));
    uint32_t e = pack2(e0, e1), t = pack2(t0, t1), r;
    asm("min.bf16x2 %0, %0, %1;" : "+r"(e) : "r"(0x3f803f80u));
    asm("max.bf16x2 %0, %0, %1;" : "+r"(t) : "r"(0x35863586u));
    asm("add.bf16x2 %0, %1, %2;" : "=r"(r) : "r"(e), "r"(t));
    return r;
}
__device__ __forceinline__ void stsm4(uint32_t a, uint32_t r0, uint32_t r1, uint32_t r2, uint32_t r3) {
    asm volatile("stmatrix.sync.aligned.m8n8.x4.shared.b16 [%0], {%1,%2,%3,%4};" :: "r"(a), "r"(r0), "r"(r1), "r"(r2), "r"(r3) : "memory");
}
__device__ __forceinline__ float bf_lo(uint32_t w) { return __uint_as_float(w << 16); }
__device__ __forceinline__ float bf_hi(uint32_t w) { return __uint_as_float(w & 0xffff0000u); }
__device__ __forceinline__ void st_pkt(uint4* p, uint32_t w0, uint32_t w1, uint32_t w2, uint32_t w3) {
    asm volatile("{\n.reg .b64 lo, hi;\n.reg .b128 v;\nmov.b64 lo, {%1, %2};\nmov.b64 hi, {%3, %4};\nmov.b128 v, {lo, hi};\nst.relaxed.gpu.global.b128 [%0], v;\n}"
        :: "l"(p), "r"(w0), "r"(w1), "r"(w2), "r"(w3) : "memory");
}
__device__ __forceinline__ void ld_pkt(const uint4* p, uint32_t& w0, uint32_t& w1, uint32_t& w2, uint32_t& w3) {
    asm volatile("{\n.reg .b64 lo, hi;\n.reg .b128 v;\nld.relaxed.gpu.global.b128 v, [%4];\nmov.b128 {lo, hi}, v;\nmov.b64 {%0, %1}, lo;\nmov.b64 {%2, %3}, hi;\n}"
        : "=r"(w0), "=r"(w1), "=r"(w2), "=r"(w3) : "l"(p) : "memory");
}

template <uint32_t AO, uint32_t BO, uint32_t BH> __device__ __forceinline__ void wg_ss128(float (&d)[64], uint32_t ab, uint32_t bb) {
    asm volatile("{\n.reg .b64 da, db;\n.reg .b32 ta, tb, th, ah;\nadd.u32 ta, %64, %66;\nadd.u32 tb, %65, %67;\nmov.b32 th, %68;\nmov.b32 ah, 0x40000040;\nmov.b64 da, {ta, ah};\nmov.b64 db, {tb, th};\n"
        "wgmma.mma_async.sync.aligned.m64n128k16.f32.bf16.bf16 {%0,%1,%2,%3,%4,%5,%6,%7,%8,%9,%10,%11,%12,%13,%14,%15,%16,%17,%18,%19,%20,%21,%22,%23,%24,%25,%26,%27,%28,%29,%30,%31,%32,%33,%34,%35,%36,%37,%38,%39,%40,%41,%42,%43,%44,%45,%46,%47,%48,%49,%50,%51,%52,%53,%54,%55,%56,%57,%58,%59,%60,%61,%62,%63}, da, db, 1, 1, 1, 0, 1;\n}\n"
        : "+f"(d[0]),"+f"(d[1]),"+f"(d[2]),"+f"(d[3]),"+f"(d[4]),"+f"(d[5]),"+f"(d[6]),"+f"(d[7]),"+f"(d[8]),"+f"(d[9]),"+f"(d[10]),"+f"(d[11]),"+f"(d[12]),"+f"(d[13]),"+f"(d[14]),"+f"(d[15]),"+f"(d[16]),"+f"(d[17]),"+f"(d[18]),"+f"(d[19]),"+f"(d[20]),"+f"(d[21]),"+f"(d[22]),"+f"(d[23]),"+f"(d[24]),"+f"(d[25]),"+f"(d[26]),"+f"(d[27]),"+f"(d[28]),"+f"(d[29]),"+f"(d[30]),"+f"(d[31]),"+f"(d[32]),"+f"(d[33]),"+f"(d[34]),"+f"(d[35]),"+f"(d[36]),"+f"(d[37]),"+f"(d[38]),"+f"(d[39]),"+f"(d[40]),"+f"(d[41]),"+f"(d[42]),"+f"(d[43]),"+f"(d[44]),"+f"(d[45]),"+f"(d[46]),"+f"(d[47]),"+f"(d[48]),"+f"(d[49]),"+f"(d[50]),"+f"(d[51]),"+f"(d[52]),"+f"(d[53]),"+f"(d[54]),"+f"(d[55]),"+f"(d[56]),"+f"(d[57]),"+f"(d[58]),"+f"(d[59]),"+f"(d[60]),"+f"(d[61]),"+f"(d[62]),"+f"(d[63])
        : "r"(ab), "r"(bb), "n"(AO), "n"(BO), "n"(BH));
}
template <uint32_t AO, uint32_t BO, uint32_t BH> __device__ __forceinline__ void wg_ss128_z(float (&d)[64], uint32_t ab, uint32_t bb) {
    asm volatile("{\n.reg .b64 da, db;\n.reg .b32 ta, tb, th, ah;\nadd.u32 ta, %64, %66;\nadd.u32 tb, %65, %67;\nmov.b32 th, %68;\nmov.b32 ah, 0x40000040;\nmov.b64 da, {ta, ah};\nmov.b64 db, {tb, th};\n"
        "wgmma.mma_async.sync.aligned.m64n128k16.f32.bf16.bf16 {%0,%1,%2,%3,%4,%5,%6,%7,%8,%9,%10,%11,%12,%13,%14,%15,%16,%17,%18,%19,%20,%21,%22,%23,%24,%25,%26,%27,%28,%29,%30,%31,%32,%33,%34,%35,%36,%37,%38,%39,%40,%41,%42,%43,%44,%45,%46,%47,%48,%49,%50,%51,%52,%53,%54,%55,%56,%57,%58,%59,%60,%61,%62,%63}, da, db, 0, 1, 1, 0, 1;\n}\n"
        : "=f"(d[0]),"=f"(d[1]),"=f"(d[2]),"=f"(d[3]),"=f"(d[4]),"=f"(d[5]),"=f"(d[6]),"=f"(d[7]),"=f"(d[8]),"=f"(d[9]),"=f"(d[10]),"=f"(d[11]),"=f"(d[12]),"=f"(d[13]),"=f"(d[14]),"=f"(d[15]),"=f"(d[16]),"=f"(d[17]),"=f"(d[18]),"=f"(d[19]),"=f"(d[20]),"=f"(d[21]),"=f"(d[22]),"=f"(d[23]),"=f"(d[24]),"=f"(d[25]),"=f"(d[26]),"=f"(d[27]),"=f"(d[28]),"=f"(d[29]),"=f"(d[30]),"=f"(d[31]),"=f"(d[32]),"=f"(d[33]),"=f"(d[34]),"=f"(d[35]),"=f"(d[36]),"=f"(d[37]),"=f"(d[38]),"=f"(d[39]),"=f"(d[40]),"=f"(d[41]),"=f"(d[42]),"=f"(d[43]),"=f"(d[44]),"=f"(d[45]),"=f"(d[46]),"=f"(d[47]),"=f"(d[48]),"=f"(d[49]),"=f"(d[50]),"=f"(d[51]),"=f"(d[52]),"=f"(d[53]),"=f"(d[54]),"=f"(d[55]),"=f"(d[56]),"=f"(d[57]),"=f"(d[58]),"=f"(d[59]),"=f"(d[60]),"=f"(d[61]),"=f"(d[62]),"=f"(d[63])
        : "r"(ab), "r"(bb), "n"(AO), "n"(BO), "n"(BH));
}
template <uint32_t BO, uint32_t BH> __device__ __forceinline__ void wg_rs128(float (&d)[64], uint32_t a0, uint32_t a1, uint32_t a2, uint32_t a3, uint32_t bb) {
    asm volatile("{\n.reg .b64 db;\n.reg .b32 tb, th;\nadd.u32 tb, %68, %69;\nmov.b32 th, %70;\nmov.b64 db, {tb, th};\n"
        "wgmma.mma_async.sync.aligned.m64n128k16.f32.bf16.bf16 {%0,%1,%2,%3,%4,%5,%6,%7,%8,%9,%10,%11,%12,%13,%14,%15,%16,%17,%18,%19,%20,%21,%22,%23,%24,%25,%26,%27,%28,%29,%30,%31,%32,%33,%34,%35,%36,%37,%38,%39,%40,%41,%42,%43,%44,%45,%46,%47,%48,%49,%50,%51,%52,%53,%54,%55,%56,%57,%58,%59,%60,%61,%62,%63}, {%64,%65,%66,%67}, db, 1, 1, 1, 1;\n}\n"
        : "+f"(d[0]),"+f"(d[1]),"+f"(d[2]),"+f"(d[3]),"+f"(d[4]),"+f"(d[5]),"+f"(d[6]),"+f"(d[7]),"+f"(d[8]),"+f"(d[9]),"+f"(d[10]),"+f"(d[11]),"+f"(d[12]),"+f"(d[13]),"+f"(d[14]),"+f"(d[15]),"+f"(d[16]),"+f"(d[17]),"+f"(d[18]),"+f"(d[19]),"+f"(d[20]),"+f"(d[21]),"+f"(d[22]),"+f"(d[23]),"+f"(d[24]),"+f"(d[25]),"+f"(d[26]),"+f"(d[27]),"+f"(d[28]),"+f"(d[29]),"+f"(d[30]),"+f"(d[31]),"+f"(d[32]),"+f"(d[33]),"+f"(d[34]),"+f"(d[35]),"+f"(d[36]),"+f"(d[37]),"+f"(d[38]),"+f"(d[39]),"+f"(d[40]),"+f"(d[41]),"+f"(d[42]),"+f"(d[43]),"+f"(d[44]),"+f"(d[45]),"+f"(d[46]),"+f"(d[47]),"+f"(d[48]),"+f"(d[49]),"+f"(d[50]),"+f"(d[51]),"+f"(d[52]),"+f"(d[53]),"+f"(d[54]),"+f"(d[55]),"+f"(d[56]),"+f"(d[57]),"+f"(d[58]),"+f"(d[59]),"+f"(d[60]),"+f"(d[61]),"+f"(d[62]),"+f"(d[63])
        : "r"(a0), "r"(a1), "r"(a2), "r"(a3), "r"(bb), "n"(BO), "n"(BH));
}
template <uint32_t BO, uint32_t BH> __device__ __forceinline__ void wg_rs128_z(float (&d)[64], uint32_t a0, uint32_t a1, uint32_t a2, uint32_t a3, uint32_t bb) {
    asm volatile("{\n.reg .b64 db;\n.reg .b32 tb, th;\nadd.u32 tb, %68, %69;\nmov.b32 th, %70;\nmov.b64 db, {tb, th};\n"
        "wgmma.mma_async.sync.aligned.m64n128k16.f32.bf16.bf16 {%0,%1,%2,%3,%4,%5,%6,%7,%8,%9,%10,%11,%12,%13,%14,%15,%16,%17,%18,%19,%20,%21,%22,%23,%24,%25,%26,%27,%28,%29,%30,%31,%32,%33,%34,%35,%36,%37,%38,%39,%40,%41,%42,%43,%44,%45,%46,%47,%48,%49,%50,%51,%52,%53,%54,%55,%56,%57,%58,%59,%60,%61,%62,%63}, {%64,%65,%66,%67}, db, 0, 1, 1, 1;\n}\n"
        : "=f"(d[0]),"=f"(d[1]),"=f"(d[2]),"=f"(d[3]),"=f"(d[4]),"=f"(d[5]),"=f"(d[6]),"=f"(d[7]),"=f"(d[8]),"=f"(d[9]),"=f"(d[10]),"=f"(d[11]),"=f"(d[12]),"=f"(d[13]),"=f"(d[14]),"=f"(d[15]),"=f"(d[16]),"=f"(d[17]),"=f"(d[18]),"=f"(d[19]),"=f"(d[20]),"=f"(d[21]),"=f"(d[22]),"=f"(d[23]),"=f"(d[24]),"=f"(d[25]),"=f"(d[26]),"=f"(d[27]),"=f"(d[28]),"=f"(d[29]),"=f"(d[30]),"=f"(d[31]),"=f"(d[32]),"=f"(d[33]),"=f"(d[34]),"=f"(d[35]),"=f"(d[36]),"=f"(d[37]),"=f"(d[38]),"=f"(d[39]),"=f"(d[40]),"=f"(d[41]),"=f"(d[42]),"=f"(d[43]),"=f"(d[44]),"=f"(d[45]),"=f"(d[46]),"=f"(d[47]),"=f"(d[48]),"=f"(d[49]),"=f"(d[50]),"=f"(d[51]),"=f"(d[52]),"=f"(d[53]),"=f"(d[54]),"=f"(d[55]),"=f"(d[56]),"=f"(d[57]),"=f"(d[58]),"=f"(d[59]),"=f"(d[60]),"=f"(d[61]),"=f"(d[62]),"=f"(d[63])
        : "r"(a0), "r"(a1), "r"(a2), "r"(a3), "r"(bb), "n"(BO), "n"(BH));
}
template <uint32_t AO, uint32_t BO, uint32_t BH> __device__ __forceinline__ void wg_ss64t(float (&d)[32], uint32_t ab, uint32_t bb) {
    asm volatile("{\n.reg .b64 da, db;\n.reg .b32 ta, tb, th, ah;\nadd.u32 ta, %32, %34;\nadd.u32 tb, %33, %35;\nmov.b32 th, %36;\nmov.b32 ah, 0x40000040;\nmov.b64 da, {ta, ah};\nmov.b64 db, {tb, th};\n"
        "wgmma.mma_async.sync.aligned.m64n64k16.f32.bf16.bf16 {%0,%1,%2,%3,%4,%5,%6,%7,%8,%9,%10,%11,%12,%13,%14,%15,%16,%17,%18,%19,%20,%21,%22,%23,%24,%25,%26,%27,%28,%29,%30,%31}, da, db, 1, 1, 1, 1, 1;\n}\n"
        : "+f"(d[0]),"+f"(d[1]),"+f"(d[2]),"+f"(d[3]),"+f"(d[4]),"+f"(d[5]),"+f"(d[6]),"+f"(d[7]),"+f"(d[8]),"+f"(d[9]),"+f"(d[10]),"+f"(d[11]),"+f"(d[12]),"+f"(d[13]),"+f"(d[14]),"+f"(d[15]),"+f"(d[16]),"+f"(d[17]),"+f"(d[18]),"+f"(d[19]),"+f"(d[20]),"+f"(d[21]),"+f"(d[22]),"+f"(d[23]),"+f"(d[24]),"+f"(d[25]),"+f"(d[26]),"+f"(d[27]),"+f"(d[28]),"+f"(d[29]),"+f"(d[30]),"+f"(d[31])
        : "r"(ab), "r"(bb), "n"(AO), "n"(BO), "n"(BH));
}
template <uint32_t AO, uint32_t BO, uint32_t BH> __device__ __forceinline__ void wg_ss64t_z(float (&d)[32], uint32_t ab, uint32_t bb) {
    asm volatile("{\n.reg .b64 da, db;\n.reg .b32 ta, tb, th, ah;\nadd.u32 ta, %32, %34;\nadd.u32 tb, %33, %35;\nmov.b32 th, %36;\nmov.b32 ah, 0x40000040;\nmov.b64 da, {ta, ah};\nmov.b64 db, {tb, th};\n"
        "wgmma.mma_async.sync.aligned.m64n64k16.f32.bf16.bf16 {%0,%1,%2,%3,%4,%5,%6,%7,%8,%9,%10,%11,%12,%13,%14,%15,%16,%17,%18,%19,%20,%21,%22,%23,%24,%25,%26,%27,%28,%29,%30,%31}, da, db, 0, 1, 1, 1, 1;\n}\n"
        : "=f"(d[0]),"=f"(d[1]),"=f"(d[2]),"=f"(d[3]),"=f"(d[4]),"=f"(d[5]),"=f"(d[6]),"=f"(d[7]),"=f"(d[8]),"=f"(d[9]),"=f"(d[10]),"=f"(d[11]),"=f"(d[12]),"=f"(d[13]),"=f"(d[14]),"=f"(d[15]),"=f"(d[16]),"=f"(d[17]),"=f"(d[18]),"=f"(d[19]),"=f"(d[20]),"=f"(d[21]),"=f"(d[22]),"=f"(d[23]),"=f"(d[24]),"=f"(d[25]),"=f"(d[26]),"=f"(d[27]),"=f"(d[28]),"=f"(d[29]),"=f"(d[30]),"=f"(d[31])
        : "r"(ab), "r"(bb), "n"(AO), "n"(BO), "n"(BH));
}
template <uint32_t AO, uint32_t BO, uint32_t BH> __device__ __forceinline__ void wg_ss8t(float (&d)[4], uint32_t ab, uint32_t bb) {
    asm volatile("{\n.reg .b64 da, db;\n.reg .b32 ta, tb, th, ah;\nadd.u32 ta, %4, %6;\nadd.u32 tb, %5, %7;\nmov.b32 th, %8;\nmov.b32 ah, 0x40000040;\nmov.b64 da, {ta, ah};\nmov.b64 db, {tb, th};\n"
        "wgmma.mma_async.sync.aligned.m64n8k16.f32.bf16.bf16 {%0,%1,%2,%3}, da, db, 1, 1, 1, 1, 0;\n}\n"
        : "+f"(d[0]),"+f"(d[1]),"+f"(d[2]),"+f"(d[3])
        : "r"(ab), "r"(bb), "n"(AO), "n"(BO), "n"(BH));
}
template <uint32_t AO, uint32_t BO, uint32_t BH> __device__ __forceinline__ void wg_ss8t_z(float (&d)[4], uint32_t ab, uint32_t bb) {
    asm volatile("{\n.reg .b64 da, db;\n.reg .b32 ta, tb, th, ah;\nadd.u32 ta, %4, %6;\nadd.u32 tb, %5, %7;\nmov.b32 th, %8;\nmov.b32 ah, 0x40000040;\nmov.b64 da, {ta, ah};\nmov.b64 db, {tb, th};\n"
        "wgmma.mma_async.sync.aligned.m64n8k16.f32.bf16.bf16 {%0,%1,%2,%3}, da, db, 0, 1, 1, 1, 0;\n}\n"
        : "=f"(d[0]),"=f"(d[1]),"=f"(d[2]),"=f"(d[3])
        : "r"(ab), "r"(bb), "n"(AO), "n"(BO), "n"(BH));
}
template <uint32_t BO, uint32_t BH> __device__ __forceinline__ void wg_rs24_z(float (&d)[12], uint32_t a0, uint32_t a1, uint32_t a2, uint32_t a3, uint32_t bb) {
    asm volatile("{\n.reg .b64 db;\n.reg .b32 tb, th;\nadd.u32 tb, %16, %17;\nmov.b32 th, %18;\nmov.b64 db, {tb, th};\n"
        "wgmma.mma_async.sync.aligned.m64n24k16.f32.bf16.bf16 {%0,%1,%2,%3,%4,%5,%6,%7,%8,%9,%10,%11}, {%12,%13,%14,%15}, db, 0, 1, 1, 0;\n}\n"
        : "=f"(d[0]),"=f"(d[1]),"=f"(d[2]),"=f"(d[3]),"=f"(d[4]),"=f"(d[5]),"=f"(d[6]),"=f"(d[7]),"=f"(d[8]),"=f"(d[9]),"=f"(d[10]),"=f"(d[11])
        : "r"(a0), "r"(a1), "r"(a2), "r"(a3), "r"(bb), "n"(BO), "n"(BH));
}

constexpr uint32_t DH128 = 64u | 0x40000000u;
constexpr uint32_t DH64 = 32u | 0x80000000u;
constexpr uint32_t LBO4K = (4096u >> 4) << 16, LBO8K = (8192u >> 4) << 16, LBO1 = 1u << 16;

template <uint32_t AO, uint32_t BO, bool SW64, bool FIRST> __device__ __forceinline__ void stage_ss(float (&acc)[64], uint32_t ab, uint32_t bb) {
    constexpr uint32_t KS = SW64 ? 64 : 128, BH = SW64 ? DH64 : DH128, B0 = BO + (SW64 ? LBO4K : LBO8K);
    wg_fence();
    if (FIRST) wg_ss128_z<AO, B0, BH>(acc, ab, bb); else wg_ss128<AO, B0, BH>(acc, ab, bb);
    wg_ss128<AO + 2, B0 + KS, BH>(acc, ab, bb);
    wg_ss128<AO + 4, B0 + 2 * KS, BH>(acc, ab, bb);
    wg_ss128<AO + 6, B0 + 3 * KS, BH>(acc, ab, bb);
    wg_commit();
}
template <uint32_t BO, bool FIRST> __device__ __forceinline__ void stage_rs(float (&acc)[64], const uint32_t (&f)[16], uint32_t bb) {
    wg_fence();
    if (FIRST) wg_rs128_z<BO + LBO8K, DH128>(acc, f[0], f[1], f[2], f[3], bb); else wg_rs128<BO + LBO8K, DH128>(acc, f[0], f[1], f[2], f[3], bb);
    wg_rs128<BO + LBO8K + 128, DH128>(acc, f[4], f[5], f[6], f[7], bb);
    wg_rs128<BO + LBO8K + 256, DH128>(acc, f[8], f[9], f[10], f[11], bb);
    wg_rs128<BO + LBO8K + 384, DH128>(acc, f[12], f[13], f[14], f[15], bb);
    wg_commit();
}

template <int N> __device__ __forceinline__ void stash(uint32_t base, uint32_t sw, const uint32_t (&f)[N]) {
#pragma unroll
    for (int t = 0; t < N / 4; t++) stsm4(base + ((sw ^ (2 * t)) << 4), f[4 * t], f[4 * t + 1], f[4 * t + 2], f[4 * t + 3]);
}

template <int V0, int V1, int N> __device__ __forceinline__ void send_frag(const uint32_t (&f)[N], uint4* p, uint32_t tag) {
#pragma unroll
    for (int v = V0; v < V1; v++) st_pkt(p + v * 32, (f[4 * v] & ~1u) | tag, f[4 * v + 1], f[4 * v + 2], f[4 * v + 3]);
}
template <int V0, int V1, int N> __device__ __forceinline__ void send_h(const uint32_t (&f)[N], uint4* p) {
#pragma unroll
    for (int v = V0; v < V1; v++) {
        const int h = v >> 1, hi = v & 1;
        asm volatile("st.global.v4.u32 [%0], {%1,%2,%3,%4};" :: "l"(p + 4 * h + 64 * hi),
                     "r"(f[8 * h + hi]), "r"(f[8 * h + 2 + hi]), "r"(f[8 * h + 4 + hi]), "r"(f[8 * h + 6 + hi]) : "memory");
    }
}
template <int O, int N, int M> __device__ __forceinline__ void pack_sub(uint32_t (&f)[N], const float (&acc)[M]) {
#pragma unroll
    for (int i = 0; i < N; i++) f[i] = keep(pack2(acc[O + 2 * i], acc[O + 2 * i + 1]));
}
template <int N> __device__ __forceinline__ void recv_issue(uint32_t (&q)[N], const uint4* p) {
#pragma unroll
    for (int v = 0; v < N / 4; v++) ld_pkt(p + v * 32, q[4 * v], q[4 * v + 1], q[4 * v + 2], q[4 * v + 3]);
}
template <int N> __device__ __forceinline__ void lds_pkts(uint32_t (&q)[N], uint32_t a) {
#pragma unroll
    for (int v = 0; v < N / 4; v++)
        asm volatile("ld.shared.v4.u32 {%0,%1,%2,%3}, [%4];" : "=r"(q[4 * v]), "=r"(q[4 * v + 1]), "=r"(q[4 * v + 2]), "=r"(q[4 * v + 3]) : "r"(a + v * 512) : "memory");
}
template <int N> __device__ __forceinline__ bool pkts_ok(const uint32_t (&q)[N], uint32_t tag) {
    uint32_t bad = 0;
#pragma unroll
    for (int v = 0; v < N / 4; v++) bad |= q[4 * v] ^ tag;
    return __all_sync(0xffffffffu, (bad & 1u) == 0);
}
template <int N> __device__ __forceinline__ uint32_t recv_retry(uint32_t (&q)[N], const uint4* src, uint32_t dst, uint32_t bar, uint32_t& ph, uint32_t tag) {
    uint32_t it = 0;
    while (!pkts_ok(q, tag) && ++it < SPIN_GLOBAL) {
        if ((threadIdx.x & 31) == 0) bulk_in(dst, src, N * 128, bar);
        mbar_wait(bar, ph);
        ph ^= 1;
        lds_pkts(q, dst + (threadIdx.x & 31) * 16);
    }
    return it;
}
template <int N> __device__ __forceinline__ uint32_t recv_check(uint32_t (&q)[N], const uint4* p, uint32_t tag) {
    uint32_t it = 0;
    while (true) {
        uint32_t bad = 0;
#pragma unroll
        for (int v = 0; v < N / 4; v++) bad |= q[4 * v] ^ tag;
        if (__all_sync(0xffffffffu, (bad & 1u) == 0) || ++it > SPIN_GLOBAL) break;
        recv_issue(q, p);
    }
    return it;
}
}

__global__ void __launch_bounds__(384, 1)
fused_kernel(const __grid_constant__ Maps maps, const __nv_bfloat16* __restrict__ xg, const __nv_bfloat16* __restrict__ gate_w,
             const char* __restrict__ pf_qkv, const char* __restrict__ pf_g, const char* __restrict__ pf_u,
             const char* __restrict__ pf_d, const char* __restrict__ pf_o, __nv_bfloat16* __restrict__ out) {
    extern __shared__ __align__(1024) uint8_t smem_raw[];
    const uint32_t sb = (uint32_t)__cvta_generic_to_shared(smem_raw);
    const int tid = threadIdx.x, lane = tid & 31;
    const int warp = __shfl_sync(0xffffffffu, tid >> 5, 0);
    const int j = (blockIdx.x >> 1) & 7;
    const int r = (((blockIdx.x >> 4) << 1) | (blockIdx.x & 1)) ^ RX;
    const uint32_t rank = blockIdx.x & 1;

    const int fc = 448 * (j >> 1) + 256 * (j & 1);
    if (warp == 0) { TSG(0, 30); TS(0, 0); }
    if (tid == 256) {
        mbar_init(sb + B_XFULL, 1); mbar_init(sb + B_FULL, 1); mbar_init(sb + B_FULL + 8, 1); mbar_init(sb + B_XFULL + 8, 1); mbar_init(sb + B_FULL + 16, 1);
        asm volatile("fence.mbarrier_init.release.cluster;" ::: "memory");
        TS2(0);
        mbar_expect(sb + B_FULL, 16384);
        tmaw3(sb + OFF_RING, &maps.kv, 64 * j, 0, 1, sb + B_FULL);
        mbar_expect(sb + B_XFULL, 16384);
        tma2(sb + OFF_X, &maps.x, 0, r * 128, sb + B_XFULL);
        TS2(1);
        mbar_expect(sb + B_FULL + 8, 16384);
        tmaw3(sb + OFF_RING + 16384, &maps.gu, fc, 0, 0, sb + B_FULL + 8);
#define PRO_MORE() do { mbar_expect(sb + B_XFULL + 8, 16384); tma2(sb + OFF_X + 16384, &maps.x, 64, r * 128, sb + B_XFULL + 8); TS2(2); \
        mbar_expect(sb + B_FULL + 16, 16384); tmaw3(sb + OFF_RING + 2 * 16384, &maps.kv, 64 * j, 64, 1, sb + B_FULL + 16); } while (0)
        if (PRO5) PRO_MORE();
    } else if (tid == 352) {
        for (int i = 0; i < 5; i++) { if (i > 2) mbar_init(sb + B_FULL + 8 * i, 1); mbar_init(sb + B_EMPTY + 8 * i, MC ? 4 : 2); }
        for (int i = 2; i < 9; i++) mbar_init(sb + B_XFULL + 8 * i, 1);
        asm volatile("fence.mbarrier_init.release.cluster;" ::: "memory");
    } else if (tid == 288) {
        for (int i = 0; i < 3; i++) mbar_init(sb + B_HSENT + 8 * i, 8);
        for (int i = 0; i < 4; i++) { mbar_init(sb + B_EFULL + 8 * i, 1); mbar_init(sb + B_EEMPTY + 8 * i, MC ? 4 : 2); }
        mbar_init(sb + B_XFREE, 2); mbar_init(sb + B_XFREE + 8, 2); mbar_init(sb + B_XFREE + 16, 2);
        for (int i = 0; i < 12; i++) mbar_init(sb + B_LATE + 8 * i, 1);
        mbar_init(sb + B_AHEAD, 1); mbar_init(sb + B_PART, 1); mbar_init(sb + B_GRDY, 1); mbar_init(sb + B_KVDONE, 8); mbar_init(sb + B_KVRDY, 2);
        asm volatile("fence.mbarrier_init.release.cluster;" ::: "memory");
    } else if (warp == 10 && lane < 10) {
        asm volatile("prefetch.tensormap [%0];" :: "l"(&maps.x + lane) : "memory");
    }
    __syncthreads();

    if (warp >= 8) {
        asm volatile("setmaxnreg.dec.sync.aligned.u32 56;");
        if (warp == 8) {
            if (lane == 0) {
                int slot = 3, ph = 1;
                uint32_t full, dst;
                if (!PRO5) PRO_MORE();
                mbar_expect(sb + B_XFULL + 16, 16384); tma2(sb + OFF_X + 2 * 16384, &maps.x, 128, r * 128, sb + B_XFULL + 16);
#define P_BEGIN(S, BYTES) full = sb + B_FULL + 8 * slot; dst = sb + OFF_RING + slot * 16384; \
                mbar_wait(sb + B_EMPTY + 8 * slot, ph); TS2(S); mbar_expect(full, BYTES); if (!MC || (((S) ^ rank) & 1) == 0)
#define P_END() if (++slot == 5) { slot = 0; ph ^= 1; }
                for (int s = 3; s < 16; s++) {
                    const int kb = (int)(0x7654763542312100ull >> (4 * s)) & 15;
                    P_BEGIN(s, 16384) {
                        if ((0x0DADu >> s) & 1) tmaw3(dst, &maps.kv, 64 * j, 64 * kb, 1, full);
                        else tmaw3(dst, &maps.gu, fc, 64 * kb, 0, full);
                    }
                    const int xb = (int)(0x0000000765403210ull >> (4 * s)) & 15;
                    if (xb) { mbar_expect(sb + B_XFULL + 8 * xb, 16384); tma2(sb + OFF_X + xb * 16384, &maps.x, 64 * xb, r * 128, sb + B_XFULL + 8 * xb); }
                    P_END()
                }
                for (int s = 0; s < 24; s++) {
                    P_BEGIN(16 + s, 16384) {
                        if (s < 8) {
                            tmaw3(dst, &maps.q64, 0, 64 * s, 2 * j, full);
                            tmaw3(dst + 8192, &maps.gu64, 224 * (j & 6) + 192 + 32 * (j & 1), 64 * s, 0, full);
                        } else {
                            tmaw3(dst, &maps.gu, fc + 64 * (s >> 3), 64 * (s & 7), 0, full);
                        }
                    }
                    P_END()
                }
                const int p = j >> 1;
#pragma unroll 1
                for (int t = 0; t < 18; t++) {
                    const int q = t >= 9, rnd = t / 7, sl = (int)(0x4352106u >> (4 * (t - 7 * rnd))) & 15;
                    const int u = (int)((q ? 0x432186758ull : 0x327064105ull) >> (4 * (t - 9 * q))) & 15;
                    const int cw = (j & 1) * 4 + ((p & 2) ^ ((t == 5 || t > 9) ? 0 : 2)), cc = 64 * cw;
                    if (sl < 5) {
                        full = sb + B_FULL + 8 * sl; dst = sb + OFF_RING + sl * 16384;
                        mbar_wait(sb + B_EMPTY + 8 * sl, (rnd & 1) ^ 1);
                    } else {
                        full = sb + B_EFULL + 8 * (sl - 5); dst = sb + OFF_X + (sl == 6 ? 8 : 5) * 16384;
                        mbar_wait(sb + B_EEMPTY + 8 * (sl - 5), rnd & 1);
                    }
                    TS2(40 + t);
                    mbar_expect(full, 16384);
                    if (!MC || ((t ^ rank) & 1) == 0) {
                        if (u > 4) {
                            const int js = u > 6 ? j ^ 1 : j;
                            tmaw3(dst, (u & 1) ? &maps.wow : &maps.wdw, 0, (u & 1) ? 64 * js : 448 * p + 256 * (js & 1) + 128, cw, full);
                        } else {
                            const int g = 14 * p + (u == 4 ? 6 : 8 * (u & 1) + (u & 2));
                            tmaw5(dst, &maps.wdp, cc, g, full); tmaw5(dst + 8192, &maps.wdp, cc + 64, g, full);
                        }
                    }
                }
            }
        } else if (warp < 11) {
            const int hx = warp - 9;
            uint32_t epoch;
            asm volatile("ld.relaxed.gpu.global.u32 %0, [%1];" : "=r"(epoch) : "l"(g_epoch + blockIdx.x) : "memory");
            {
                const uint4* xr = (const uint4*)(xg + (size_t)(r * 128 + j * 16 + hx * 8) * kD) + lane;
                const uint4 wa = __ldg((const uint4*)gate_w + lane), wb = __ldg((const uint4*)gate_w + 32 + lane);
                const uint32_t tag = (epoch + 1) & 1;
                uint4* gp = g_gx + r * 32;
                if (lane < 2) st_pkt(gp + j * 4 + hx * 2 + lane, tag ^ 1, 0, 0, 0);
                float s[8];
                if (GDELAY) mbar_wait(sb + B_XFULL, 0);
#pragma unroll
                for (int i0 = 0; i0 < 8; i0 += 4) {
                    uint4 va[4], vb[4];
#pragma unroll
                    for (int i = 0; i < 4; i++) { va[i] = __ldg(xr + (i0 + i) * 64); vb[i] = __ldg(xr + (i0 + i) * 64 + 32); }
#pragma unroll
                    for (int i = 0; i < 4; i++) {
                        float t0 = bf_lo(va[i].x) * bf_lo(wa.x), t1 = bf_hi(va[i].x) * bf_hi(wa.x);
                        t0 = fmaf(bf_lo(va[i].y), bf_lo(wa.y), t0); t1 = fmaf(bf_hi(va[i].y), bf_hi(wa.y), t1);
                        t0 = fmaf(bf_lo(va[i].z), bf_lo(wa.z), t0); t1 = fmaf(bf_hi(va[i].z), bf_hi(wa.z), t1);
                        t0 = fmaf(bf_lo(va[i].w), bf_lo(wa.w), t0); t1 = fmaf(bf_hi(va[i].w), bf_hi(wa.w), t1);
                        t0 = fmaf(bf_lo(vb[i].x), bf_lo(wb.x), t0); t1 = fmaf(bf_hi(vb[i].x), bf_hi(wb.x), t1);
                        t0 = fmaf(bf_lo(vb[i].y), bf_lo(wb.y), t0); t1 = fmaf(bf_hi(vb[i].y), bf_hi(wb.y), t1);
                        t0 = fmaf(bf_lo(vb[i].z), bf_lo(wb.z), t0); t1 = fmaf(bf_hi(vb[i].z), bf_hi(wb.z), t1);
                        t0 = fmaf(bf_lo(vb[i].w), bf_lo(wb.w), t0); t1 = fmaf(bf_hi(vb[i].w), bf_hi(wb.w), t1);
                        s[i0 + i] = t0 + t1;
                    }
                }
#pragma unroll
                for (int i = 0; i < 8; i++) {
#pragma unroll
                    for (int o = 16; o; o >>= 1) s[i] += __shfl_xor_sync(0xffffffffu, s[i], o);
                    s[i] = 1.f / (1.f + __expf(-s[i]));
                }
                if (lane < 2) {
                    const float v0 = lane ? s[4] : s[0], v1 = lane ? s[5] : s[1], v2 = lane ? s[6] : s[2], v3 = lane ? s[7] : s[3];
                    st_pkt(gp + j * 4 + hx * 2 + lane, (__float_as_uint(v0) & ~1u) | tag, __float_as_uint(v1), __float_as_uint(v2), __float_as_uint(v3));
                }
                if (hx == 1) {
                    asm volatile("st.shared.u32 [%0], %1;" :: "r"(sb + OFF_ONES + lane * 4), "r"(0x3f803f80u) : "memory");
                    asm volatile("fence.proxy.async.shared::cta;" ::: "memory");
                }
                asm volatile("bar.sync 3, 96;" ::: "memory");
                if (hx == 0) {
                    uint32_t q[4];
                    recv_issue(q, gp + lane);
                    recv_check(q, gp + lane, tag);
                    asm volatile("st.shared.v4.u32 [%0], {%1,%2,%3,%4};" :: "r"(sb + OFF_G + lane * 16), "r"(q[0]), "r"(q[1]), "r"(q[2]), "r"(q[3]) : "memory");
                    if (lane == 0) {
                        asm volatile("st.shared.u32 [%0], %1;" :: "r"(sb + OFF_EPOCH), "r"(epoch) : "memory");
                        g_epoch[blockIdx.x] = epoch + 1;
                    }
                    __syncwarp();
                    if (lane == 0) mbar_arrive(sb + B_GRDY);
                } else {
                    if (r == 0) {
                        float4* zp = (float4*)(g_kvacc + (((epoch & 1) ^ 1) * 8 + j) * 4 * 272);
                        for (int i = lane; i < 272; i += 32) zp[i] = make_float4(0.f, 0.f, 0.f, 0.f);
                    }
                }
            }
            TS(2 + hx, 1);
#define PUBLISH_H(B) do { mbar_wait(sb + B_HSENT + 8 * (B), 0); if (lane == 0) { \
                asm volatile("st.release.gpu.global.u32 [%0], %1;" :: "l"(g_hflag + (r * 8 + j) * 8 + (B)), "r"(epoch + 1) : "memory"); } __syncwarp(); } while (0)
            if (hx == 1) {
#pragma unroll 1
                for (int b = 0; b < 3; b++) { PUBLISH_H(b); TS(3, 5 + b); }
            } else {
                const float* accp = g_kvacc + ((epoch & 1) * 8 + j) * 4 * 272;
                unsigned* cnt = g_kvcnt + j * 32;
                mbar_wait(sb + B_KVDONE, 0);
                TS(2, 5);
                if (lane == 0) asm volatile("red.release.gpu.global.add.u32 [%0], 1;" :: "l"(cnt) : "memory");
                __syncwarp();
                TS(2, 2);
                {
                    const unsigned target = 16u * (epoch + 1);
                    uint32_t it = 0, v;
                    do {
                        asm volatile("ld.acquire.gpu.global.u32 %0, [%1];" : "=r"(v) : "l"(cnt) : "memory");
                    } while ((int)(v - target) < 0 && ++it < SPIN_GLOBAL);
                }
                TS(2, 3);
#pragma unroll
                for (int h = 0; h < 4; h++) {
                    const float4 d0 = __ldcg((const float4*)(accp + h * 272) + lane);
                    const float4 d1 = __ldcg((const float4*)(accp + h * 272 + 128) + lane);
                    const float2 z0 = __ldcg((const float2*)(accp + h * 272 + 256) + (lane & 3));
                    const float2 z1 = __ldcg((const float2*)(accp + h * 272 + 264) + (lane & 3));
                    const uint32_t ba = sb + OFF_STG + h * 768 + lane * 4;
                    asm volatile("st.shared.u32 [%0], %1;" :: "r"(ba), "r"(pack2(d0.x, d0.y)) : "memory");
                    asm volatile("st.shared.u32 [%0], %1;" :: "r"(ba + 128), "r"(pack2(d1.x, d1.y)) : "memory");
                    asm volatile("st.shared.u32 [%0], %1;" :: "r"(ba + 256), "r"(pack2(d0.z, d0.w)) : "memory");
                    asm volatile("st.shared.u32 [%0], %1;" :: "r"(ba + 384), "r"(pack2(d1.z, d1.w)) : "memory");
                    asm volatile("st.shared.u32 [%0], %1;" :: "r"(ba + 512), "r"(pack2(z0.x, z0.y)) : "memory");
                    asm volatile("st.shared.u32 [%0], %1;" :: "r"(ba + 640), "r"(pack2(z1.x, z1.y)) : "memory");
                }
                asm volatile("fence.proxy.async.shared::cta;" ::: "memory");
                __syncwarp();
                if (lane == 0) mbar_arrive(sb + B_KVRDY);
                TS(2, 4);
            }
        } else {
            uint32_t epoch;
            asm volatile("ld.relaxed.gpu.global.u32 %0, [%1];" : "=r"(epoch) : "l"(g_epoch + blockIdx.x) : "memory");
            asm volatile("bar.arrive 3, 96;" :: "r"(epoch) : "memory");
            const int b = blockIdx.x, p = j >> 1;
            mbar_wait(sb + B_XFULL, 0);
            if (PF0 && r >= PF0) {
                const int row = r * 32 + lane;
                asm volatile("prefetch.global.L2 [%0];" :: "l"(pf_qkv + row * 3072 + 1024 + j * 128));
                asm volatile("prefetch.global.L2 [%0];" :: "l"(pf_qkv + row * 3072 + 2048 + j * 128));
                asm volatile("prefetch.global.L2 [%0];" :: "l"(pf_g + row * 3584 + fc * 2));
                asm volatile("prefetch.global.L2 [%0];" :: "l"(pf_u + row * 3584 + fc * 2));
            }
#pragma unroll 1
            for (int kb = 1; kb < 8; kb++) {
                mbar_wait(sb + B_XFULL + 8 * kb, 0);
                const char* base = kb < 3 ? pf_g : kb < 5 ? pf_u : kb == 5 ? pf_qkv : pf_d;
                const int off = kb == 5 ? b * 12288 : b * 14336 + ((kb < 5 ? kb - 1 : kb) & 1) * 7168;
                if (kb == 5) {
                    asm volatile("prefetch.global.L2 [%0];" :: "l"(base + off + (lane >> 3) * 3072 + (lane & 7) * 128));
                } else {
                    asm volatile("prefetch.global.L2 [%0];" :: "l"(base + off + lane * 128));
                    if (lane < 24) asm volatile("prefetch.global.L2 [%0];" :: "l"(base + off + 4096 + lane * 128));
                }
                if (kb == 7) asm volatile("prefetch.global.L2 [%0];" :: "l"(pf_o + b * 4096 + lane * 128));
            }
            {
                uint4* mb = g_part + (size_t)(r * 2 + (j & 1)) * 16384 + (((p ^ 1) * 4 + p) << 10) + lane;
#pragma unroll 1
                for (int i = 0; i < (NOPRE ? 0 : 32); i++) { st_pkt(mb + i * 32, epoch & 1, 0, 0, 0); __nanosleep(40); }
                __syncwarp();
                if (lane == 0) mbar_arrive(sb + B_KVRDY);
            }
            {
                const uint32_t want = epoch + 1;
                const int hrow = (r * 4 + p) * 5 * 128;
                const unsigned* fl = g_hflag + (r * 8 + (j & 6)) * 8 + (lane & 15);
                uint32_t it = 0;
                int i = 0;
                mbar_wait(sb + B_HSENT + 8, 0);
#pragma unroll 1
                while (i < 3 && ++it < SPIN_GLOBAL) {
                    uint32_t v;
                    asm volatile("ld.acquire.gpu.global.u32 %0, [%1];" : "=r"(v) : "l"(fl) : "memory");
                    const uint32_t rdy = __ballot_sync(0xffffffffu, v == want);
#pragma unroll 1
                    while (i < 3 && ((rdy >> i) & 0x101u) == 0x101u) {
                        if (i < 2) mbar_wait(sb + B_XFREE + 8 * i, 0);
                        if (lane == 0) {
                            const int pc = (6 - 2 * i) % 6;
                            asm volatile("fence.proxy.async.global;" ::: "memory");
                            TS2(140 + i);
                            mbar_expect(sb + B_XFULL + 8 * pc, i != 1 ? 32768 : 16384);
                            tma2(sb + OFF_X + pc * 16384, i != 1 ? &maps.hx2 : &maps.hx, 0, hrow + pc * 128, sb + B_XFULL + 8 * pc);
                        }
                        i++;
                    }
                }
            }
        }
    } else {
        asm volatile("setmaxnreg.inc.sync.aligned.u32 224;");
        const int wg = warp >> 2;
        const bool elect = (tid & 127) == 0;
        const uint32_t sbd = (sb & 0x3FFFFu) >> 4, xlo = (sbd + wg * 512) | LBO1;
        auto release = [&](uint32_t bar) {
            if (elect) {
                mbar_arrive(sb + bar);
            }
        };
#define S_SL(S) ((S) < 40 ? (S) % 5 : (int)((0x4352106u >> (4 * (((S) - 40) % 7))) & 15))
#define S_WAIT(S) do { mbar_wait(sb + (S_SL(S) < 5 ? B_FULL + 8 * S_SL(S) : B_EFULL + 8 * (S_SL(S) - 5)), (S) < 40 ? ((S) / 5) & 1 : (((S) - 40) / 7) & 1); \
            if (PROF && tid == 0) TS2(64 + (S)); } while (0)
#define S_B(S) (S_SL(S) < 5 ? OFF_RING / 16 + S_SL(S) * 1024 : (S_SL(S) == 6 ? 8 : 5) * 1024)
#define S_REL(S) do { if ((S) < 51) release(S_SL(S) < 5 ? B_EMPTY + 8 * S_SL(S) : B_EEMPTY + 8 * (S_SL(S) - 5)); } while (0)
#define G1(S, acc, SW, KB) stage_ss<(KB) * 1024, S_B(S), SW, (KB) == 0>(acc, xlo, sbd)
#define RET(S) do { S_WAIT((S) + 1); wg_wait<1>(); S_REL((S) - 1); } while (0)
#define RET2(S) do { S_WAIT((S) + 1); wg_wait<2>(); S_REL((S) - 1); } while (0)
#define SCHED() mbar_wait(sb + B_XFULL + 8 * 7, 0)
#define A2_SYNC() do { asm volatile("fence.proxy.async.shared::cta;" ::: "memory"); asm volatile("bar.sync %0, 128;" :: "r"(wg + 1) : "memory"); } while (0)
#define H_EPI(acc, F, I0, I1, OG, OU) _Pragma("unroll") for (int i = (I0); i < (I1); i++) \
            F[i] = keep(hmul2(pack2(acc[(OG) + 2 * i] * acc[(OU) + 2 * i], acc[(OG) + 2 * i + 1] * acc[(OU) + 2 * i + 1]), (i & 1) ? m_hi : m_lo))
#define PHI(acc, F, I0, I1) _Pragma("unroll") for (int i = (I0); i < (I1); i++) F[i] = keep(phi2(acc[2 * i], acc[2 * i + 1]))

        float a0[64], b0[64], a1[64], a2_[64], a3[64];
        mbar_wait(sb + B_XFULL, 0);
#define X_WAIT(KB) do { mbar_wait(sb + B_XFULL + 8 * (KB), 0); if (PROF && tid == 0) TS2(128 + (KB)); } while (0)
        S_WAIT(0); G1(0, b0, false, 0);
        if ((warp & 3) == 0) TS(wg, 1);
        S_WAIT(1); G1(1, a0, false, 0); RET(1);
        X_WAIT(1); G1(2, b0, false, 1); RET(2);
        X_WAIT(2); G1(3, b0, false, 2); RET(3);
        G1(4, a0, false, 1); RET(4);
        X_WAIT(3); G1(5, b0, false, 3); RET(5);
        G1(6, a0, false, 2); RET(6);
        X_WAIT(4); G1(7, b0, false, 4); RET(7);
        X_WAIT(5); G1(8, b0, false, 5); RET(8);
        G1(9, a0, false, 3); RET(9);
        X_WAIT(6); G1(10, b0, false, 6); RET(10);
        X_WAIT(7); G1(11, b0, false, 7); RET(11);
        G1(12, a0, false, 4);
        const uint32_t lrow = ((lane & 7) + 8 * ((lane >> 3) & 1)) * 128;
        const uint32_t srow = (warp & 3) * 2048 + lrow;
        const uint32_t ssw = (lane >> 4) ^ (lane & 7);
        uint4* const hsend = g_hx + (size_t)((r * 4 + (j >> 1)) * 5 + (j & 1)) * 1024 + warp * 128 + (lane >> 2) * 8 + (lane & 3);
#define SENT_H(B) do { __syncwarp(); if (lane == 0) mbar_arrive(sb + B_HSENT + 8 * (B)); } while (0)
        RET(12);
        pin(b0);
        uint32_t fh0[16], fh1[16], fh2[16], fh3[8], fo[16], pk[16], pv[16];
        float kv[32], zs[4];
        const uint32_t stg = sb + OFF_STG + wg * 8192, stl = stg + (warp & 1) * 2048 + lrow;
#define KV_ROUND(Z) do { A2_SYNC(); wg_fence(); \
            wg_ss64t##Z<8192 + 256, 8192, DH128>(kv, xlo, xlo); wg_ss64t<8192 + 384, 8192 + 128, DH128>(kv, xlo, xlo); \
            wg_ss8t##Z<8192, OFF_ONES / 16, 0>(zs, xlo, sbd); wg_ss8t<8192 + 128, OFF_ONES / 16, 0>(zs, xlo, sbd); wg_commit(); } while (0)
        G1(13, a0, false, 5); SCHED(); pack_sub<32>(pv, b0); PHI(b0, pk, 0, 4); RET(13);
        G1(14, a0, false, 6); SCHED(); if (!(warp & 2)) stash<16>(stl + 4096, ssw, pv); PHI(b0, pk, 4, 10); RET(14);
        G1(15, a0, false, 7); SCHED(); PHI(b0, pk, 10, 16); RET(15);
        if ((warp & 3) == 0) TS(wg, 2);

        G1(16, a1, true, 0); SCHED(); if (!(warp & 2)) stash<16>(stl, ssw, pk);
        mbar_wait(sb + B_GRDY, 0);
        float g_lo, g_hi;
        uint32_t tag;
        {
            const uint32_t ga = sb + OFF_G + (warp * 16 + (lane >> 2)) * 4;
            asm volatile("ld.shared.f32 %0, [%1];" : "=f"(g_lo) : "r"(ga) : "memory");
            asm volatile("ld.shared.f32 %0, [%1];" : "=f"(g_hi) : "r"(ga + 32) : "memory");
            asm volatile("ld.shared.u32 %0, [%1];" : "=r"(tag) : "r"(sb + OFF_EPOCH) : "memory");
        }
        float* const kvp = g_kvacc + (((tag & 1) * 8 + j) * 4 + (warp & 3)) * 272;
        tag = (tag + 1) & 1;
        const uint32_t m_lo = pack2(1.f - g_lo, 1.f - g_lo), m_hi = pack2(1.f - g_hi, 1.f - g_hi);
        RET(16);
        pin(a0);
        G1(17, a1, true, 1); SCHED(); H_EPI(a0, fh0, 0, 16, 0, 32); RET(17);
        G1(18, a1, true, 2); KV_ROUND(_z); RET2(18);
        G1(19, a1, true, 3); SCHED(); send_h<0, 1>(fh0, hsend); RET(19);
        G1(20, a1, true, 4); SCHED(); if (warp & 2) { stash<16>(stl, ssw, pk); stash<16>(stl + 4096, ssw, pv); } RET(20);
        G1(21, a1, true, 5); KV_ROUND(); RET2(21);
        G1(22, a1, true, 6); RET(22);
        pin(kv); pin(zs);
        G1(23, a1, true, 7); SCHED();
#define KV_RED(W) do { asm volatile("red.global.add.v4.f32 [%0], {%1,%2,%3,%4};" :: "l"(kvp + lane * 4), "f"(kv[8 * W]), "f"(kv[8 * W + 1]), "f"(kv[8 * W + 2]), "f"(kv[8 * W + 3]) : "memory"); \
                       asm volatile("red.global.add.v4.f32 [%0], {%1,%2,%3,%4};" :: "l"(kvp + 128 + lane * 4), "f"(kv[8 * W + 4]), "f"(kv[8 * W + 5]), "f"(kv[8 * W + 6]), "f"(kv[8 * W + 7]) : "memory"); } while (0)
        if ((warp & 3) == 0) KV_RED(0); else if ((warp & 3) == 1) KV_RED(1); else if ((warp & 3) == 2) KV_RED(2); else KV_RED(3);
        if ((lane & 3) == 0) {
            asm volatile("red.global.add.f32 [%0], %1;" :: "l"(kvp + 256 + (lane >> 2)), "f"(zs[0]) : "memory");
            asm volatile("red.global.add.f32 [%0], %1;" :: "l"(kvp + 264 + (lane >> 2)), "f"(zs[2]) : "memory");
        }
        __syncwarp();
        if (lane == 0) mbar_arrive(sb + B_KVDONE);
        RET(23);
        if ((warp & 3) == 0) TS(wg, 3);

        G1(24, a2_, false, 0); SCHED(); send_h<1, 2>(fh0, hsend); RET(24);
        pin(a1);
        G1(25, a2_, false, 1); SCHED(); send_h<2, 3>(fh0, hsend); H_EPI(a1, fh3, 0, 8, 32, 48); RET(25);
        G1(26, a2_, false, 2); SCHED(); send_h<3, 4>(fh0, hsend); SENT_H(0); PHI(a1, fo, 0, 4); RET(26);
        G1(27, a2_, false, 3); SCHED(); send_h<0, 1>(fh3, hsend + 4 * 1024 - (j & 1) * 1020); PHI(a1, fo, 4, 8); RET(27);
        G1(28, a2_, false, 4); SCHED(); send_h<1, 2>(fh3, hsend + 4 * 1024 - (j & 1) * 1020); SENT_H(1); PHI(a1, fo, 8, 12); RET(28);
        G1(29, a2_, false, 5); SCHED(); PHI(a1, fo, 12, 16); RET(29);
        G1(30, a2_, false, 6); RET(30);
        G1(31, a2_, false, 7); RET(31);
        if ((warp & 3) == 0) TS(wg, 4);

        float on[4][12];
#define O_SCALE(h) do { const float s_lo = __fdividef(g_lo, on[h][8] + 1e-6f), s_hi = __fdividef(g_hi, on[h][10] + 1e-6f); \
            const uint32_t sl_ = pack2(s_lo, s_lo), sh_ = pack2(s_hi, s_hi); \
            fo[4 * h] = keep(hmul2(pack2(on[h][0], on[h][1]), sl_)); fo[4 * h + 1] = keep(hmul2(pack2(on[h][2], on[h][3]), sh_)); \
            fo[4 * h + 2] = keep(hmul2(pack2(on[h][4], on[h][5]), sl_)); fo[4 * h + 3] = keep(hmul2(pack2(on[h][6], on[h][7]), sh_)); } while (0)
        uint4* const lsend = g_lx + (size_t)(r * 8 + j) * 2048 + warp * 128 + lane;
        const uint4* const lrecv = g_lx + (size_t)(r * 8 + (j ^ 1)) * 2048 + warp * 128 + lane;
        G1(32, a3, false, 0); RET(32);
        pin(a2_);
        G1(33, a3, false, 1); SCHED(); H_EPI(a2_, fh1, 0, 16, 0, 32); send_h<0, 1>(fh1, hsend + 2 * 1024); RET(33);
        G1(34, a3, false, 2); SCHED(); send_h<1, 3>(fh1, hsend + 2 * 1024); RET(34);
        if (elect) mbar_arrive(sb + B_XFREE);
        G1(35, a3, false, 3); SCHED(); send_h<3, 4>(fh1, hsend + 2 * 1024); SENT_H(2);
        if ((warp & 3) == 0) TS(wg, 5);
        mbar_wait(sb + B_KVRDY, 0);
        if ((warp & 3) == 0) TS(wg, 6);
        wg_fence();
#define O_MMA(h) wg_rs24_z<OFF_STG / 16 + (h) * 48 + (8u << 16), 16>(on[h], fo[4 * (h)], fo[4 * (h) + 1], fo[4 * (h) + 2], fo[4 * (h) + 3], sbd)
        O_MMA(0); O_MMA(1); O_MMA(2); O_MMA(3);
        wg_commit();
        RET2(35);
        G1(36, a3, false, 4); RET(36);
        pin(on[0]); pin(on[1]); pin(on[2]); pin(on[3]);
        release(B_EEMPTY + 8);
        G1(37, a3, false, 5); SCHED(); O_SCALE(0); O_SCALE(1); O_SCALE(2); O_SCALE(3); RET(37);
        if (elect) mbar_arrive(sb + B_XFREE + 8);
        G1(38, a3, false, 6); SCHED(); send_frag<0, 2>(fo, lsend, tag); RET(38);
        release(B_EEMPTY);
        G1(39, a3, false, 7); SCHED(); send_frag<2, 4>(fo, lsend, tag); RET(39);
        if ((warp & 3) == 0) TS(wg, 7);

#define G2S(S, acc, U) stage_ss<(U) * 1024, S_B(S), false, (S) == 45>(acc, xlo, sbd)
#define G2R(S, acc, F) stage_rs<S_B(S), (S) == 40>(acc, F, sbd)
#define H_WAIT(P) do { mbar_wait(sb + B_XFULL + 8 * (P), 1); if (PROF && tid == 0) TS2(150 + (P)); } while (0)
        const int p = j >> 1, pw = (p & 2) ^ 2;
        const bool own = wg == (p & 1);
        uint4* const pbase = g_part + (size_t)(r * 2 + (j & 1)) * 16384 + (warp & 3) * 256 + lane;

        float p1[64], p2[64];
        uint32_t po[16], ph2[16];
        G2R(40, p1, fo); RET(40);
        pin(a3);
        H_WAIT(0); G2S(41, p1, 0); SCHED(); H_EPI(a3, fh2, 0, 16, 0, 32); send_frag<0, 2>(fh2, lsend + 1024, tag); RET(41);
        const uint32_t la = sb + OFF_X + 6 * 16384 + warp * 2048 + lane * 16;
        G2S(42, p1, 1); SCHED(); if (elect) bulk_in(la, lrecv, 8192, sb + B_LATE + 8 * wg); send_frag<2, 4>(fh2, lsend + 1024, tag); RET(42);
        H_WAIT(4); G2S(43, p1, 4); RET(43);
        G2R(44, p1, fh2); mbar_wait(sb + B_LATE + 8 * wg, 0); lds_pkts(po, la); RET(44);
        G2S(45, p2, 0); SCHED(); if (elect) bulk_in(la + 16384, lrecv + 1024, 8192, sb + B_LATE + 16 + 8 * wg);
        CNT(170, recv_check(po, lrecv, tag)); RET(45);
        G2R(46, p1, po); RET(46);
        H_WAIT(2); G2S(47, p1, 2); mbar_wait(sb + B_LATE + 16 + 8 * wg, 0); lds_pkts(ph2, la + 16384); RET(47);
        G2S(48, p1, 3); SCHED(); CNT(171, recv_check(ph2, lrecv + 1024, tag)); RET(48);
        G2R(49, p1, ph2); RET(49);
        if ((warp & 3) == 0) TS(wg, 8);
        uint32_t sp[32], qa[32], qb[32];
        uint4* const s1 = pbase + (((pw + wg) * 4 + p) << 10);
        G2R(50, p2, fo); RET(50);
        pin(p1);
        G2R(51, p2, po); SCHED(); pack_sub<0>(sp, p1); send_frag<0, 2>(sp, s1, tag); RET(51);
        G2R(52, p2, fh2); SCHED(); send_frag<2, 5>(sp, s1, tag); RET(52);
        if (elect) mbar_arrive(sb + B_XFREE + 16);
        G2R(53, p2, ph2); SCHED(); send_frag<5, 8>(sp, s1, tag); RET(53);
        const uint4* ra = pbase + ((p * 4 + pw) << 10);
        const uint4* rc = pbase + ((p * 4 + (p ^ 1)) << 10);
        if (own) mbar_wait(sb + B_AHEAD, 0);
        G2S(54, p2, 1); RET(54);
        G2S(55, p2, 2); RET(55);
        G2S(56, p2, 3); RET(56);
        G2S(57, p2, 4); SCHED();
        if ((warp & 3) == 0) TS(wg, 9);
        if (!own && elect) mbar_arrive(sb + B_AHEAD);
        wg_wait<0>();
        pin(p2);
        if ((warp & 3) == 0) TS(wg, 11);
        if (!own) {
            if (elect) { mbar_wait(sb + B_XFREE + 16, 0); bulk_in(sb + OFF_X + 6 * 16384, ra, 32768, sb + B_PART); }
            pack_sub<0>(sp, p2);
            send_frag<0, 8>(sp, pbase + (((p ^ 1) * 4 + p) << 10), tag);
        } else {
            const uint32_t wb = sb + B_WARP + 8 * warp, pa = sb + OFF_X + (warp & 3) * 4096;
            uint32_t wph = 1;
            if (lane == 0) bulk_in(pa, rc, 4096, wb);
            uint32_t f0[16], f1[16];
            pack_sub<0>(f0, p2); pack_sub<32>(f1, p2);
            mbar_wait(sb + B_PART, 0);
            if ((warp & 3) == 0) TS(wg, 10);
            lds_pkts(qa, pa + 6 * 16384 + lane * 16); lds_pkts(qb, pa + 7 * 16384 + lane * 16);
            mbar_wait(wb, 0);
            lds_pkts(sp, pa + lane * 16);
            CNT(174, recv_retry(sp, rc - lane, pa, wb, wph, tag));
            CNT(172, recv_retry(qa, ra - lane, pa + 6 * 16384, wb, wph, tag));
            CNT(173, recv_retry(qb, ra + 1024 - lane, pa + 7 * 16384, wb, wph, tag));
            if ((warp & 3) == 0) TS(wg, 13);
#pragma unroll
            for (int i = 0; i < 16; i++) {
                f0[i] = hadd2(hadd2(f0[i], sp[i]), hadd2(qa[i], qb[i])); f1[i] = hadd2(hadd2(f1[i], sp[16 + i]), hadd2(qa[16 + i], qb[16 + i]));
            }
            const uint32_t slab = sb + OFF_X + 2 * 16384 + wg * 8192;
            stash<16>(slab + srow, ssw, f0); stash<16>(slab + 16384 + srow, ssw, f1);
            __syncwarp();
            __nv_bfloat16* op = out + (size_t)(r * 128 + warp * 16 + (lane >> 4)) * kD + (j & 1) * 256 + (p & 2) * 64 + (lane & 15) * 8;
#pragma unroll
            for (int i = 0; i < 8; i++) {
                const int row = i * 2 + (lane >> 4);
                uint4 v;
                asm volatile("ld.shared.v4.u32 {%0,%1,%2,%3}, [%4];" : "=r"(v.x), "=r"(v.y), "=r"(v.z), "=r"(v.w)
                             : "r"(slab + (lane & 8) * 2048 + ((warp & 3) * 16 + row) * 128 + (((lane & 7) ^ (row & 7)) << 4)) : "memory");
                *(uint4*)(op + i * 2 * kD) = v;
            }
        }
        if ((warp & 3) == 0) { TS(wg, 14); TSG(wg, 31); }
    }
}

typedef CUresult (*EncodeFn)(CUtensorMap*, CUtensorMapDataType, cuuint32_t, void*, const cuuint64_t*, const cuuint64_t*, const cuuint32_t*,
                             const cuuint32_t*, CUtensorMapInterleave, CUtensorMapSwizzle, CUtensorMapL2promotion, CUtensorMapFloatOOBfill);

static void encode(EncodeFn fn, CUtensorMap* m, int rank, const void* base, const cuuint64_t (&gd)[5], const cuuint64_t (&gs)[4],
                   const cuuint32_t (&bd)[5], CUtensorMapSwizzle sw) {
    cuuint32_t es[5] = {1, 1, 1, 1, 1};
    fn(m, CU_TENSOR_MAP_DATA_TYPE_BFLOAT16, rank, const_cast<void*>(base), gd, gs, bd, es, CU_TENSOR_MAP_INTERLEAVE_NONE, sw,
       CU_TENSOR_MAP_L2_PROMOTION_L2_128B, CU_TENSOR_MAP_FLOAT_OOB_FILL_NONE);
}

extern "C" void kernel_launch(void* const* d_in, const int* in_sizes, int n_in, void* d_out, int out_size) {
    const char* x = (const char*)d_in[0];
    const char* wqkv = (const char*)d_in[1];
    const char* wo = (const char*)d_in[2];
    const char* wg = (const char*)d_in[4];
    const char* wu = (const char*)d_in[5];
    const char* wd = (const char*)d_in[6];
    void* fnp = nullptr;
    cudaDriverEntryPointQueryResult qr;
    cudaGetDriverEntryPoint("cuTensorMapEncodeTiled", &fnp, cudaEnableDefault, &qr);
    EncodeFn fn = (EncodeFn)fnp;
    Maps maps;
    const char* lo = wg < wu ? wg : wu;
    const uint64_t diff = wg < wu ? (uint64_t)(wu - wg) : (uint64_t)(wg - wu);
    const CUtensorMapSwizzle S128 = CU_TENSOR_MAP_SWIZZLE_128B, S64 = CU_TENSOR_MAP_SWIZZLE_64B;
    encode(fn, &maps.x, 2, x, {512, 2048, 1, 1}, {1024, 0, 0}, {64, 128, 1, 1}, S128);
    encode(fn, &maps.gu, 3, lo, {1792, 512, 2, 1}, {3584, diff, 0}, {64, 64, 2, 1}, S128);
    encode(fn, &maps.kv, 3, wqkv, {512, 512, 3, 1}, {3072, 1024, 0}, {64, 64, 2, 1}, S128);
    encode(fn, &maps.q64, 3, wqkv, {32, 512, 48, 1}, {3072, 64, 0}, {32, 64, 2, 1}, S64);
    encode(fn, &maps.gu64, 3, lo, {1792, 512, 2, 1}, {3584, diff, 0}, {32, 64, 2, 1}, S64);
    encode(fn, &maps.wdw, 3, wd, {64, 1792, 8, 1}, {1024, 128, 0}, {64, 64, 2, 1}, S128);
    encode(fn, &maps.wow, 3, wo, {64, 512, 8}, {1024, 128}, {64, 64, 2}, S128);
    encode(fn, &maps.wdp, 5, wd, {512, 2, 4, 4, 56}, {1024, 8192, 2048, 32768}, {64, 2, 4, 4, 2}, S128);
    void* hx = nullptr;
    cudaGetSymbolAddress(&hx, g_hx);
    encode(fn, &maps.hx, 2, hx, {64, 16 * 4 * 5 * 128}, {128}, {64, 128}, S128);
    encode(fn, &maps.hx2, 2, hx, {64, 16 * 4 * 5 * 128}, {128}, {64, 256}, S128);
    cudaFuncSetAttribute(fused_kernel, cudaFuncAttributeMaxDynamicSharedMemorySize, SMEM_BYTES);
    cudaLaunchConfig_t cfg = {};
    cfg.gridDim = dim3(128);
    cfg.blockDim = dim3(384);
    cfg.dynamicSmemBytes = SMEM_BYTES;
    cfg.stream = cudaStreamPerThread;
    cudaLaunchAttribute at[1];
    at[0].id = cudaLaunchAttributeClusterDimension;
    at[0].val.clusterDim.x = 2; at[0].val.clusterDim.y = 1; at[0].val.clusterDim.z = 1;
    cfg.attrs = at;
    cfg.numAttrs = MC ? 1 : 0;
    cudaLaunchKernelEx(&cfg, fused_kernel, maps, (const __nv_bfloat16*)d_in[0], (const __nv_bfloat16*)d_in[7], wqkv, wg, wu, wd, wo, (__nv_bfloat16*)d_out);
}
```

```cpp
#include <cuda_runtime.h>
#include <cuda.h>
#include <cuda_bf16.h>
#include <stdint.h>

#define MC 0
#define PFMODE 1
#define PHI_SAT 0
#define EXPT 0
#define COPY_AT 0
#define RX 0
#define PF0 4
#define GDELAY 1
#define PRO5 0
#define NOPRE 0
#define CL 0
#define FORCECL 0
#define MAPV 0x6510432
#define PROF 0

namespace {

constexpr int kD = 512;
constexpr uint32_t OFF_X = 0, OFF_STG = 131072, OFF_RING = 147456, OFF_MISC = 229376;
constexpr uint32_t B_FULL = OFF_MISC, B_EMPTY = OFF_MISC + 40, B_XFULL = OFF_MISC + 80;
constexpr uint32_t B_GRDY = OFF_MISC + 152, B_KVDONE = OFF_MISC + 160, B_KVRDY = OFF_MISC + 168;
constexpr uint32_t B_HSENT = OFF_MISC + 176, B_XFREE = OFF_MISC + 200;
constexpr uint32_t OFF_EPOCH = OFF_MISC + 240, OFF_G = OFF_MISC + 256;
constexpr uint32_t B_AHEAD = OFF_MISC + 248, B_PART = OFF_MISC + 232;
constexpr uint32_t OFF_ONES = OFF_MISC + 768;
constexpr uint32_t B_EFULL = OFF_MISC + 896, B_EEMPTY = OFF_MISC + 928;
constexpr uint32_t B_LAST = OFF_MISC + 224, B_RFREE = OFF_MISC + 960;
constexpr uint32_t SMEM_BYTES = OFF_MISC + 968;
constexpr uint32_t SPIN_GLOBAL = 1u << 14;

struct alignas(64) Maps { CUtensorMap x, gu, kv, q64, gu64, wdw, wow, wdp, hx, hx2; };

}

__device__ uint4 g_part[16 * 2 * 4 * 4 * 1024];
__device__ uint4 g_hx[16 * 4 * 5 * 1024];
__device__ uint4 g_lx[16 * 8 * 2 * 1024];
__device__ unsigned g_hflag[128 * 8];
__device__ uint4 g_gx[16 * 32];
__device__ float g_kvacc[2 * 8 * 4 * 272];
__device__ unsigned g_kvcnt[8 * 32];
__device__ unsigned g_epoch[128];
#define TS(role, idx)
#define TS2(idx)
#define CNT(idx, v) (void)(v)
#define TSG(role, idx)

namespace {

__device__ __forceinline__ void mbar_init(uint32_t bar, uint32_t cnt) { asm volatile("mbarrier.init.shared::cta.b64 [%0], %1;" :: "r"(bar), "r"(cnt) : "memory"); }
__device__ __forceinline__ void mbar_expect(uint32_t bar, uint32_t bytes) { asm volatile("mbarrier.arrive.expect_tx.shared::cta.b64 _, [%0], %1;" :: "r"(bar), "r"(bytes) : "memory"); }
__device__ __forceinline__ void mbar_arrive(uint32_t bar) { asm volatile("mbarrier.arrive.shared::cta.b64 _, [%0];" :: "r"(bar) : "memory"); }
__device__ __forceinline__ void mbar_arrive_cta(uint32_t bar, uint32_t cta) {
    asm volatile("{\n.reg .b32 ra;\nmapa.shared::cluster.u32 ra, %0, %1;\nmbarrier.arrive.shared::cluster.b64 _, [ra];\n}" :: "r"(bar), "r"(cta) : "memory");
}
__device__ __forceinline__ void mbar_wait(uint32_t bar, uint32_t parity) {
    asm volatile("{\n.reg .pred p;\n.reg .u32 c;\n"
                 "mbarrier.try_wait.parity.shared::cta.b64 p, [%0], %1;\n@p bra DONE;\n"
                 "mov.u32 c, 0;\nLAB_WAIT:\nmbarrier.try_wait.parity.shared::cta.b64 p, [%0], %1;\n@p bra DONE;\n"
                 "add.u32 c, c, 1;\nsetp.lt.u32 p, c, 65536;\n@p bra LAB_WAIT;\nDONE:\n}" :: "r"(bar), "r"(parity) : "memory");
}
__device__ __forceinline__ void tma2(uint32_t dst, const CUtensorMap* m, int c0, int c1, uint32_t bar) {
    asm volatile("cp.async.bulk.tensor.2d.shared::cluster.global.mbarrier::complete_tx::bytes [%0], [%1, {%3, %4}], [%2];"
        :: "r"(dst), "l"(m), "r"(bar), "r"(c0), "r"(c1) : "memory");
}
__device__ __forceinline__ void tmaw2(uint32_t dst, const CUtensorMap* m, int c0, int c1, uint32_t bar) {
    tma2(dst, m, c0, c1, bar);
}
__device__ __forceinline__ void tmaw3(uint32_t dst, const CUtensorMap* m, int c0, int c1, int c2, uint32_t bar) {
    asm volatile("cp.async.bulk.tensor.3d.shared::cluster.global.mbarrier::complete_tx::bytes [%0], [%1, {%3, %4, %5}], [%2];"
        :: "r"(dst), "l"(m), "r"(bar), "r"(c0), "r"(c1), "r"(c2) : "memory");
}
__device__ __forceinline__ void tmaw5(uint32_t dst, const CUtensorMap* m, int c0, int c4, uint32_t bar) {
    asm volatile("cp.async.bulk.tensor.5d.shared::cluster.global.mbarrier::complete_tx::bytes [%0], [%1, {%3, %5, %5, %5, %4}], [%2];"
        :: "r"(dst), "l"(m), "r"(bar), "r"(c0), "r"(c4), "r"(0) : "memory");
}
__device__ __forceinline__ void wg_fence() { asm volatile("wgmma.fence.sync.aligned;" ::: "memory"); }
__device__ __forceinline__ void wg_commit() { asm volatile("wgmma.commit_group.sync.aligned;" ::: "memory"); }
template <int N> __device__ __forceinline__ void wg_wait() { asm volatile("wgmma.wait_group.sync.aligned %0;" :: "n"(N) : "memory"); }
template <int N> __device__ __forceinline__ void pin(float (&d)[N]) {
#pragma unroll
    for (int i = 0; i < N; i++) asm volatile("" : "+f"(d[i]) :: "memory");
}
__device__ __forceinline__ uint32_t pack2(float lo, float hi) { uint32_t r; asm("cvt.rn.bf16x2.f32 %0, %1, %2;" : "=r"(r) : "f"(hi), "f"(lo)); return r; }
__device__ __forceinline__ uint32_t keep(uint32_t v) { asm volatile("" : "+r"(v)); return v; }
__device__ __forceinline__ uint32_t hadd2(uint32_t a, uint32_t b) { uint32_t r; asm("add.bf16x2 %0, %1, %2;" : "=r"(r) : "r"(a), "r"(b)); return r; }
__device__ __forceinline__ uint32_t hmul2(uint32_t a, uint32_t b) { uint32_t r; asm("mul.bf16x2 %0, %1, %2;" : "=r"(r) : "r"(a), "r"(b)); return r; }
__device__ __forceinline__ uint32_t phi2(float t0, float t1) {
    float e0, e1;
    asm("ex2.approx.ftz.f32 %0, %1;" : "=f"(e0) : "f"(t0 * 1.4426950408889634f));
    asm("ex2.approx.ftz.f32 %0, %1;" : "=f"(e1) : "f"(t1 * 1.4426950408889634f));
    uint32_t e = pack2(e0, e1), t = pack2(t0, t1), r;
    asm("min.bf16x2 %0, %0, %1;" : "+r"(e) : "r"(0x3f803f80u));
    asm("max.bf16x2 %0, %0, %1;" : "+r"(t) : "r"(0x35863586u));
    asm("add.bf16x2 %0, %1, %2;" : "=r"(r) : "r"(e), "r"(t));
    return r;
}
__device__ __forceinline__ void stsm4(uint32_t a, uint32_t r0, uint32_t r1, uint32_t r2, uint32_t r3) {
    asm volatile("stmatrix.sync.aligned.m8n8.x4.shared.b16 [%0], {%1,%2,%3,%4};" :: "r"(a), "r"(r0), "r"(r1), "r"(r2), "r"(r3) : "memory");
}
__device__ __forceinline__ float bf_lo(uint32_t w) { return __uint_as_float(w << 16); }
__device__ __forceinline__ float bf_hi(uint32_t w) { return __uint_as_float(w & 0xffff0000u); }
__device__ __forceinline__ void st_pkt(uint4* p, uint32_t w0, uint32_t w1, uint32_t w2, uint32_t w3) {
    asm volatile("{\n.reg .b64 lo, hi;\n.reg .b128 v;\nmov.b64 lo, {%1, %2};\nmov.b64 hi, {%3, %4};\nmov.b128 v, {lo, hi};\nst.relaxed.gpu.global.b128 [%0], v;\n}"
        :: "l"(p), "r"(w0), "r"(w1), "r"(w2), "r"(w3) : "memory");
}
__device__ __forceinline__ void ld_pkt(const uint4* p, uint32_t& w0, uint32_t& w1, uint32_t& w2, uint32_t& w3) {
    asm volatile("{\n.reg .b64 lo, hi;\n.reg .b128 v;\nld.relaxed.gpu.global.b128 v, [%4];\nmov.b128 {lo, hi}, v;\nmov.b64 {%0, %1}, lo;\nmov.b64 {%2, %3}, hi;\n}"
        : "=r"(w0), "=r"(w1), "=r"(w2), "=r"(w3) : "l"(p) : "memory");
}

template <uint32_t AO, uint32_t BO, uint32_t BH> __device__ __forceinline__ void wg_ss128(float (&d)[64], uint32_t ab, uint32_t bb) {
    asm volatile("{\n.reg .b64 da, db;\n.reg .b32 ta, tb, th, ah;\nadd.u32 ta, %64, %66;\nadd.u32 tb, %65, %67;\nmov.b32 th, %68;\nmov.b32 ah, 0x40000040;\nmov.b64 da, {ta, ah};\nmov.b64 db, {tb, th};\n"
        "wgmma.mma_async.sync.aligned.m64n128k16.f32.bf16.bf16 {%0,%1,%2,%3,%4,%5,%6,%7,%8,%9,%10,%11,%12,%13,%14,%15,%16,%17,%18,%19,%20,%21,%22,%23,%24,%25,%26,%27,%28,%29,%30,%31,%32,%33,%34,%35,%36,%37,%38,%39,%40,%41,%42,%43,%44,%45,%46,%47,%48,%49,%50,%51,%52,%53,%54,%55,%56,%57,%58,%59,%60,%61,%62,%63}, da, db, 1, 1, 1, 0, 1;\n}\n"
        : "+f"(d[0]),"+f"(d[1]),"+f"(d[2]),"+f"(d[3]),"+f"(d[4]),"+f"(d[5]),"+f"(d[6]),"+f"(d[7]),"+f"(d[8]),"+f"(d[9]),"+f"(d[10]),"+f"(d[11]),"+f"(d[12]),"+f"(d[13]),"+f"(d[14]),"+f"(d[15]),"+f"(d[16]),"+f"(d[17]),"+f"(d[18]),"+f"(d[19]),"+f"(d[20]),"+f"(d[21]),"+f"(d[22]),"+f"(d[23]),"+f"(d[24]),"+f"(d[25]),"+f"(d[26]),"+f"(d[27]),"+f"(d[28]),"+f"(d[29]),"+f"(d[30]),"+f"(d[31]),"+f"(d[32]),"+f"(d[33]),"+f"(d[34]),"+f"(d[35]),"+f"(d[36]),"+f"(d[37]),"+f"(d[38]),"+f"(d[39]),"+f"(d[40]),"+f"(d[41]),"+f"(d[42]),"+f"(d[43]),"+f"(d[44]),"+f"(d[45]),"+f"(d[46]),"+f"(d[47]),"+f"(d[48]),"+f"(d[49]),"+f"(d[50]),"+f"(d[51]),"+f"(d[52]),"+f"(d[53]),"+f"(d[54]),"+f"(d[55]),"+f"(d[56]),"+f"(d[57]),"+f"(d[58]),"+f"(d[59]),"+f"(d[60]),"+f"(d[61]),"+f"(d[62]),"+f"(d[63])
        : "r"(ab), "r"(bb), "n"(AO), "n"(BO), "n"(BH));
}
template <uint32_t AO, uint32_t BO, uint32_t BH> __device__ __forceinline__ void wg_ss128_z(float (&d)[64], uint32_t ab, uint32_t bb) {
    asm volatile("{\n.reg .b64 da, db;\n.reg .b32 ta, tb, th, ah;\nadd.u32 ta, %64, %66;\nadd.u32 tb, %65, %67;\nmov.b32 th, %68;\nmov.b32 ah, 0x40000040;\nmov.b64 da, {ta, ah};\nmov.b64 db, {tb, th};\n"
        "wgmma.mma_async.sync.aligned.m64n128k16.f32.bf16.bf16 {%0,%1,%2,%3,%4,%5,%6,%7,%8,%9,%10,%11,%12,%13,%14,%15,%16,%17,%18,%19,%20,%21,%22,%23,%24,%25,%26,%27,%28,%29,%30,%31,%32,%33,%34,%35,%36,%37,%38,%39,%40,%41,%42,%43,%44,%45,%46,%47,%48,%49,%50,%51,%52,%53,%54,%55,%56,%57,%58,%59,%60,%61,%62,%63}, da, db, 0, 1, 1, 0, 1;\n}\n"
        : "=f"(d[0]),"=f"(d[1]),"=f"(d[2]),"=f"(d[3]),"=f"(d[4]),"=f"(d[5]),"=f"(d[6]),"=f"(d[7]),"=f"(d[8]),"=f"(d[9]),"=f"(d[10]),"=f"(d[11]),"=f"(d[12]),"=f"(d[13]),"=f"(d[14]),"=f"(d[15]),"=f"(d[16]),"=f"(d[17]),"=f"(d[18]),"=f"(d[19]),"=f"(d[20]),"=f"(d[21]),"=f"(d[22]),"=f"(d[23]),"=f"(d[24]),"=f"(d[25]),"=f"(d[26]),"=f"(d[27]),"=f"(d[28]),"=f"(d[29]),"=f"(d[30]),"=f"(d[31]),"=f"(d[32]),"=f"(d[33]),"=f"(d[34]),"=f"(d[35]),"=f"(d[36]),"=f"(d[37]),"=f"(d[38]),"=f"(d[39]),"=f"(d[40]),"=f"(d[41]),"=f"(d[42]),"=f"(d[43]),"=f"(d[44]),"=f"(d[45]),"=f"(d[46]),"=f"(d[47]),"=f"(d[48]),"=f"(d[49]),"=f"(d[50]),"=f"(d[51]),"=f"(d[52]),"=f"(d[53]),"=f"(d[54]),"=f"(d[55]),"=f"(d[56]),"=f"(d[57]),"=f"(d[58]),"=f"(d[59]),"=f"(d[60]),"=f"(d[61]),"=f"(d[62]),"=f"(d[63])
        : "r"(ab), "r"(bb), "n"(AO), "n"(BO), "n"(BH));
}
template <uint32_t BO, uint32_t BH> __device__ __forceinline__ void wg_rs128(float (&d)[64], uint32_t a0, uint32_t a1, uint32_t a2, uint32_t a3, uint32_t bb) {
    asm volatile("{\n.reg .b64 db;\n.reg .b32 tb, th;\nadd.u32 tb, %68, %69;\nmov.b32 th, %70;\nmov.b64 db, {tb, th};\n"
        "wgmma.mma_async.sync.aligned.m64n128k16.f32.bf16.bf16 {%0,%1,%2,%3,%4,%5,%6,%7,%8,%9,%10,%11,%12,%13,%14,%15,%16,%17,%18,%19,%20,%21,%22,%23,%24,%25,%26,%27,%28,%29,%30,%31,%32,%33,%34,%35,%36,%37,%38,%39,%40,%41,%42,%43,%44,%45,%46,%47,%48,%49,%50,%51,%52,%53,%54,%55,%56,%57,%58,%59,%60,%61,%62,%63}, {%64,%65,%66,%67}, db, 1, 1, 1, 1;\n}\n"
        : "+f"(d[0]),"+f"(d[1]),"+f"(d[2]),"+f"(d[3]),"+f"(d[4]),"+f"(d[5]),"+f"(d[6]),"+f"(d[7]),"+f"(d[8]),"+f"(d[9]),"+f"(d[10]),"+f"(d[11]),"+f"(d[12]),"+f"(d[13]),"+f"(d[14]),"+f"(d[15]),"+f"(d[16]),"+f"(d[17]),"+f"(d[18]),"+f"(d[19]),"+f"(d[20]),"+f"(d[21]),"+f"(d[22]),"+f"(d[23]),"+f"(d[24]),"+f"(d[25]),"+f"(d[26]),"+f"(d[27]),"+f"(d[28]),"+f"(d[29]),"+f"(d[30]),"+f"(d[31]),"+f"(d[32]),"+f"(d[33]),"+f"(d[34]),"+f"(d[35]),"+f"(d[36]),"+f"(d[37]),"+f"(d[38]),"+f"(d[39]),"+f"(d[40]),"+f"(d[41]),"+f"(d[42]),"+f"(d[43]),"+f"(d[44]),"+f"(d[45]),"+f"(d[46]),"+f"(d[47]),"+f"(d[48]),"+f"(d[49]),"+f"(d[50]),"+f"(d[51]),"+f"(d[52]),"+f"(d[53]),"+f"(d[54]),"+f"(d[55]),"+f"(d[56]),"+f"(d[57]),"+f"(d[58]),"+f"(d[59]),"+f"(d[60]),"+f"(d[61]),"+f"(d[62]),"+f"(d[63])
        : "r"(a0), "r"(a1), "r"(a2), "r"(a3), "r"(bb), "n"(BO), "n"(BH));
}
template <uint32_t BO, uint32_t BH> __device__ __forceinline__ void wg_rs128_z(float (&d)[64], uint32_t a0, uint32_t a1, uint32_t a2, uint32_t a3, uint32_t bb) {
    asm volatile("{\n.reg .b64 db;\n.reg .b32 tb, th;\nadd.u32 tb, %68, %69;\nmov.b32 th, %70;\nmov.b64 db, {tb, th};\n"
        "wgmma.mma_async.sync.aligned.m64n128k16.f32.bf16.bf16 {%0,%1,%2,%3,%4,%5,%6,%7,%8,%9,%10,%11,%12,%13,%14,%15,%16,%17,%18,%19,%20,%21,%22,%23,%24,%25,%26,%27,%28,%29,%30,%31,%32,%33,%34,%35,%36,%37,%38,%39,%40,%41,%42,%43,%44,%45,%46,%47,%48,%49,%50,%51,%52,%53,%54,%55,%56,%57,%58,%59,%60,%61,%62,%63}, {%64,%65,%66,%67}, db, 0, 1, 1, 1;\n}\n"
        : "=f"(d[0]),"=f"(d[1]),"=f"(d[2]),"=f"(d[3]),"=f"(d[4]),"=f"(d[5]),"=f"(d[6]),"=f"(d[7]),"=f"(d[8]),"=f"(d[9]),"=f"(d[10]),"=f"(d[11]),"=f"(d[12]),"=f"(d[13]),"=f"(d[14]),"=f"(d[15]),"=f"(d[16]),"=f"(d[17]),"=f"(d[18]),"=f"(d[19]),"=f"(d[20]),"=f"(d[21]),"=f"(d[22]),"=f"(d[23]),"=f"(d[24]),"=f"(d[25]),"=f"(d[26]),"=f"(d[27]),"=f"(d[28]),"=f"(d[29]),"=f"(d[30]),"=f"(d[31]),"=f"(d[32]),"=f"(d[33]),"=f"(d[34]),"=f"(d[35]),"=f"(d[36]),"=f"(d[37]),"=f"(d[38]),"=f"(d[39]),"=f"(d[40]),"=f"(d[41]),"=f"(d[42]),"=f"(d[43]),"=f"(d[44]),"=f"(d[45]),"=f"(d[46]),"=f"(d[47]),"=f"(d[48]),"=f"(d[49]),"=f"(d[50]),"=f"(d[51]),"=f"(d[52]),"=f"(d[53]),"=f"(d[54]),"=f"(d[55]),"=f"(d[56]),"=f"(d[57]),"=f"(d[58]),"=f"(d[59]),"=f"(d[60]),"=f"(d[61]),"=f"(d[62]),"=f"(d[63])
        : "r"(a0), "r"(a1), "r"(a2), "r"(a3), "r"(bb), "n"(BO), "n"(BH));
}
template <uint32_t AO, uint32_t BO, uint32_t BH> __device__ __forceinline__ void wg_ss64t(float (&d)[32], uint32_t ab, uint32_t bb) {
    asm volatile("{\n.reg .b64 da, db;\n.reg .b32 ta, tb, th, ah;\nadd.u32 ta, %32, %34;\nadd.u32 tb, %33, %35;\nmov.b32 th, %36;\nmov.b32 ah, 0x40000040;\nmov.b64 da, {ta, ah};\nmov.b64 db, {tb, th};\n"
        "wgmma.mma_async.sync.aligned.m64n64k16.f32.bf16.bf16 {%0,%1,%2,%3,%4,%5,%6,%7,%8,%9,%10,%11,%12,%13,%14,%15,%16,%17,%18,%19,%20,%21,%22,%23,%24,%25,%26,%27,%28,%29,%30,%31}, da, db, 1, 1, 1, 1, 1;\n}\n"
        : "+f"(d[0]),"+f"(d[1]),"+f"(d[2]),"+f"(d[3]),"+f"(d[4]),"+f"(d[5]),"+f"(d[6]),"+f"(d[7]),"+f"(d[8]),"+f"(d[9]),"+f"(d[10]),"+f"(d[11]),"+f"(d[12]),"+f"(d[13]),"+f"(d[14]),"+f"(d[15]),"+f"(d[16]),"+f"(d[17]),"+f"(d[18]),"+f"(d[19]),"+f"(d[20]),"+f"(d[21]),"+f"(d[22]),"+f"(d[23]),"+f"(d[24]),"+f"(d[25]),"+f"(d[26]),"+f"(d[27]),"+f"(d[28]),"+f"(d[29]),"+f"(d[30]),"+f"(d[31])
        : "r"(ab), "r"(bb), "n"(AO), "n"(BO), "n"(BH));
}
template <uint32_t AO, uint32_t BO, uint32_t BH> __device__ __forceinline__ void wg_ss64t_z(float (&d)[32], uint32_t ab, uint32_t bb) {
    asm volatile("{\n.reg .b64 da, db;\n.reg .b32 ta, tb, th, ah;\nadd.u32 ta, %32, %34;\nadd.u32 tb, %33, %35;\nmov.b32 th, %36;\nmov.b32 ah, 0x40000040;\nmov.b64 da, {ta, ah};\nmov.b64 db, {tb, th};\n"
        "wgmma.mma_async.sync.aligned.m64n64k16.f32.bf16.bf16 {%0,%1,%2,%3,%4,%5,%6,%7,%8,%9,%10,%11,%12,%13,%14,%15,%16,%17,%18,%19,%20,%21,%22,%23,%24,%25,%26,%27,%28,%29,%30,%31}, da, db, 0, 1, 1, 1, 1;\n}\n"
        : "=f"(d[0]),"=f"(d[1]),"=f"(d[2]),"=f"(d[3]),"=f"(d[4]),"=f"(d[5]),"=f"(d[6]),"=f"(d[7]),"=f"(d[8]),"=f"(d[9]),"=f"(d[10]),"=f"(d[11]),"=f"(d[12]),"=f"(d[13]),"=f"(d[14]),"=f"(d[15]),"=f"(d[16]),"=f"(d[17]),"=f"(d[18]),"=f"(d[19]),"=f"(d[20]),"=f"(d[21]),"=f"(d[22]),"=f"(d[23]),"=f"(d[24]),"=f"(d[25]),"=f"(d[26]),"=f"(d[27]),"=f"(d[28]),"=f"(d[29]),"=f"(d[30]),"=f"(d[31])
        : "r"(ab), "r"(bb), "n"(AO), "n"(BO), "n"(BH));
}
template <uint32_t AO, uint32_t BO, uint32_t BH> __device__ __forceinline__ void wg_ss8t(float (&d)[4], uint32_t ab, uint32_t bb) {
    asm volatile("{\n.reg .b64 da, db;\n.reg .b32 ta, tb, th, ah;\nadd.u32 ta, %4, %6;\nadd.u32 tb, %5, %7;\nmov.b32 th, %8;\nmov.b32 ah, 0x40000040;\nmov.b64 da, {ta, ah};\nmov.b64 db, {tb, th};\n"
        "wgmma.mma_async.sync.aligned.m64n8k16.f32.bf16.bf16 {%0,%1,%2,%3}, da, db, 1, 1, 1, 1, 0;\n}\n"
        : "+f"(d[0]),"+f"(d[1]),"+f"(d[2]),"+f"(d[3])
        : "r"(ab), "r"(bb), "n"(AO), "n"(BO), "n"(BH));
}
template <uint32_t AO, uint32_t BO, uint32_t BH> __device__ __forceinline__ void wg_ss8t_z(float (&d)[4], uint32_t ab, uint32_t bb) {
    asm volatile("{\n.reg .b64 da, db;\n.reg .b32 ta, tb, th, ah;\nadd.u32 ta, %4, %6;\nadd.u32 tb, %5, %7;\nmov.b32 th, %8;\nmov.b32 ah, 0x40000040;\nmov.b64 da, {ta, ah};\nmov.b64 db, {tb, th};\n"
        "wgmma.mma_async.sync.aligned.m64n8k16.f32.bf16.bf16 {%0,%1,%2,%3}, da, db, 0, 1, 1, 1, 0;\n}\n"
        : "=f"(d[0]),"=f"(d[1]),"=f"(d[2]),"=f"(d[3])
        : "r"(ab), "r"(bb), "n"(AO), "n"(BO), "n"(BH));
}
template <uint32_t BO, uint32_t BH> __device__ __forceinline__ void wg_rs24_z(float (&d)[12], uint32_t a0, uint32_t a1, uint32_t a2, uint32_t a3, uint32_t bb) {
    asm volatile("{\n.reg .b64 db;\n.reg .b32 tb, th;\nadd.u32 tb, %16, %17;\nmov.b32 th, %18;\nmov.b64 db, {tb, th};\n"
        "wgmma.mma_async.sync.aligned.m64n24k16.f32.bf16.bf16 {%0,%1,%2,%3,%4,%5,%6,%7,%8,%9,%10,%11}, {%12,%13,%14,%15}, db, 0, 1, 1, 0;\n}\n"
        : "=f"(d[0]),"=f"(d[1]),"=f"(d[2]),"=f"(d[3]),"=f"(d[4]),"=f"(d[5]),"=f"(d[6]),"=f"(d[7]),"=f"(d[8]),"=f"(d[9]),"=f"(d[10]),"=f"(d[11])
        : "r"(a0), "r"(a1), "r"(a2), "r"(a3), "r"(bb), "n"(BO), "n"(BH));
}

constexpr uint32_t DH128 = 64u | 0x40000000u;
constexpr uint32_t DH64 = 32u | 0x80000000u;
constexpr uint32_t LBO4K = (4096u >> 4) << 16, LBO8K = (8192u >> 4) << 16, LBO1 = 1u << 16;

template <uint32_t AO, uint32_t BO, bool SW64, bool FIRST> __device__ __forceinline__ void stage_ss(float (&acc)[64], uint32_t ab, uint32_t bb) {
    constexpr uint32_t KS = SW64 ? 64 : 128, BH = SW64 ? DH64 : DH128, B0 = BO + (SW64 ? LBO4K : LBO8K);
    wg_fence();
    if (FIRST) wg_ss128_z<AO, B0, BH>(acc, ab, bb); else wg_ss128<AO, B0, BH>(acc, ab, bb);
    wg_ss128<AO + 2, B0 + KS, BH>(acc, ab, bb);
    wg_ss128<AO + 4, B0 + 2 * KS, BH>(acc, ab, bb);
    wg_ss128<AO + 6, B0 + 3 * KS, BH>(acc, ab, bb);
    wg_commit();
}
template <uint32_t BO, bool FIRST> __device__ __forceinline__ void stage_rs(float (&acc)[64], const uint32_t (&f)[16], uint32_t bb) {
    wg_fence();
    if (FIRST) wg_rs128_z<BO + LBO8K, DH128>(acc, f[0], f[1], f[2], f[3], bb); else wg_rs128<BO + LBO8K, DH128>(acc, f[0], f[1], f[2], f[3], bb);
    wg_rs128<BO + LBO8K + 128, DH128>(acc, f[4], f[5], f[6], f[7], bb);
    wg_rs128<BO + LBO8K + 256, DH128>(acc, f[8], f[9], f[10], f[11], bb);
    wg_rs128<BO + LBO8K + 384, DH128>(acc, f[12], f[13], f[14], f[15], bb);
    wg_commit();
}

template <int N> __device__ __forceinline__ void stash(uint32_t base, uint32_t sw, const uint32_t (&f)[N]) {
#pragma unroll
    for (int t = 0; t < N / 4; t++) stsm4(base + ((sw ^ (2 * t)) << 4), f[4 * t], f[4 * t + 1], f[4 * t + 2], f[4 * t + 3]);
}

template <int V0, int V1, int N> __device__ __forceinline__ void send_frag(const uint32_t (&f)[N], uint4* p, uint32_t tag) {
#pragma unroll
    for (int v = V0; v < V1; v++) st_pkt(p + v * 32, (f[4 * v] & ~1u) | tag, f[4 * v + 1], f[4 * v + 2], f[4 * v + 3]);
}
template <int V0, int V1, int N> __device__ __forceinline__ void send_h(const uint32_t (&f)[N], uint4* p) {
#pragma unroll
    for (int v = V0; v < V1; v++) {
        const int h = v >> 1, hi = v & 1;
        asm volatile("st.global.v4.u32 [%0], {%1,%2,%3,%4};" :: "l"(p + 4 * h + 64 * hi),
                     "r"(f[8 * h + hi]), "r"(f[8 * h + 2 + hi]), "r"(f[8 * h + 4 + hi]), "r"(f[8 * h + 6 + hi]) : "memory");
    }
}
template <int O, int N, int M> __device__ __forceinline__ void pack_sub(uint32_t (&f)[N], const float (&acc)[M]) {
#pragma unroll
    for (int i = 0; i < N; i++) f[i] = keep(pack2(acc[O + 2 * i], acc[O + 2 * i + 1]));
}
template <int N> __device__ __forceinline__ void recv_issue(uint32_t (&q)[N], const uint4* p) {
#pragma unroll
    for (int v = 0; v < N / 4; v++) ld_pkt(p + v * 32, q[4 * v], q[4 * v + 1], q[4 * v + 2], q[4 * v + 3]);
}
template <int N> __device__ __forceinline__ uint32_t recv_check(uint32_t (&q)[N], const uint4* p, uint32_t tag) {
    uint32_t it = 0;
    while (true) {
        uint32_t bad = 0;
#pragma unroll
        for (int v = 0; v < N / 4; v++) bad |= q[4 * v] ^ tag;
        if (__all_sync(0xffffffffu, (bad & 1u) == 0) || ++it > SPIN_GLOBAL) break;
        recv_issue(q, p);
    }
    return it;
}
}

__global__ void __launch_bounds__(384, 1)
fused_kernel(const __grid_constant__ Maps maps, const __nv_bfloat16* __restrict__ xg, const __nv_bfloat16* __restrict__ gate_w,
             const char* __restrict__ pf_qkv, const char* __restrict__ pf_g, const char* __restrict__ pf_u,
             const char* __restrict__ pf_d, const char* __restrict__ pf_o, __nv_bfloat16* __restrict__ out) {
    extern __shared__ __align__(1024) uint8_t smem_raw[];
    const uint32_t sb = (uint32_t)__cvta_generic_to_shared(smem_raw);
    const int tid = threadIdx.x, lane = tid & 31;
    const int warp = __shfl_sync(0xffffffffu, tid >> 5, 0);
#define MB(i) ((blockIdx.x >> ((MAPV >> (4 * (i))) & 15)) & 1)
    const int j = MB(0) | (MB(1) << 1) | (MB(2) << 2), r = MB(3) | (MB(4) << 1) | (MB(5) << 2) | (MB(6) << 3);
    const uint32_t rank = blockIdx.x & 1;

    const int fc = 448 * (j >> 1) + 256 * (j & 1);
    if (warp == 0) { TSG(0, 30); TS(0, 0); }
    if (tid == 256) {
        mbar_init(sb + B_XFULL, 1); mbar_init(sb + B_FULL, 1); mbar_init(sb + B_FULL + 8, 1); mbar_init(sb + B_XFULL + 8, 1); mbar_init(sb + B_FULL + 16, 1);
        asm volatile("fence.mbarrier_init.release.cluster;" ::: "memory");
        TS2(0);
        mbar_expect(sb + B_FULL, 16384);
        tmaw3(sb + OFF_RING, &maps.kv, 64 * j, 0, 1, sb + B_FULL);
        mbar_expect(sb + B_XFULL, 16384);
        tma2(sb + OFF_X, &maps.x, 0, r * 128, sb + B_XFULL);
        TS2(1);
        mbar_expect(sb + B_FULL + 8, 16384);
        tmaw3(sb + OFF_RING + 16384, &maps.gu, fc, 0, 0, sb + B_FULL + 8);
#define PRO_MORE() do { mbar_expect(sb + B_XFULL + 8, 16384); tma2(sb + OFF_X + 16384, &maps.x, 64, r * 128, sb + B_XFULL + 8); TS2(2); \
        mbar_expect(sb + B_FULL + 16, 16384); tmaw3(sb + OFF_RING + 2 * 16384, &maps.kv, 64 * j, 64, 1, sb + B_FULL + 16); } while (0)
        if (PRO5) PRO_MORE();
    } else if (tid == 352) {
        for (int i = 0; i < 5; i++) { if (i > 2) mbar_init(sb + B_FULL + 8 * i, 1); mbar_init(sb + B_EMPTY + 8 * i, MC ? 4 : 2); }
        for (int i = 2; i < 9; i++) mbar_init(sb + B_XFULL + 8 * i, 1);
        asm volatile("fence.mbarrier_init.release.cluster;" ::: "memory");
    } else if (tid == 288) {
        for (int i = 0; i < 3; i++) mbar_init(sb + B_HSENT + 8 * i, 8);
        for (int i = 0; i < 4; i++) { mbar_init(sb + B_EFULL + 8 * i, 1); mbar_init(sb + B_EEMPTY + 8 * i, MC ? 4 : 2); }
        mbar_init(sb + B_XFREE, 2); mbar_init(sb + B_XFREE + 8, 2); mbar_init(sb + B_XFREE + 16, 2);
        mbar_init(sb + B_AHEAD, 1); mbar_init(sb + B_PART, 1); mbar_init(sb + B_LAST, 1); mbar_init(sb + B_RFREE, 2);
        if (CL) mbar_expect(sb + B_LAST, 16384); mbar_init(sb + B_GRDY, 1); mbar_init(sb + B_KVDONE, 8); mbar_init(sb + B_KVRDY, 2);
        asm volatile("fence.mbarrier_init.release.cluster;" ::: "memory");
    } else if (warp == 10 && lane < 10) {
        asm volatile("prefetch.tensormap [%0];" :: "l"(&maps.x + lane) : "memory");
    }
    __syncthreads();
    if (CL) asm volatile("barrier.cluster.arrive.relaxed.aligned;" ::: "memory");

    if (warp >= 8) {
        asm volatile("setmaxnreg.dec.sync.aligned.u32 56;");
        if (warp == 8) {
            if (lane == 0) {
                int slot = 3, ph = 1;
                uint32_t full, dst;
                if (!PRO5) PRO_MORE();
                mbar_expect(sb + B_XFULL + 16, 16384); tma2(sb + OFF_X + 2 * 16384, &maps.x, 128, r * 128, sb + B_XFULL + 16);
#define P_BEGIN(S, BYTES) full = sb + B_FULL + 8 * slot; dst = sb + OFF_RING + slot * 16384; \
                mbar_wait(sb + B_EMPTY + 8 * slot, ph); TS2(S); mbar_expect(full, BYTES); if (!MC || (((S) ^ rank) & 1) == 0)
#define P_END() if (++slot == 5) { slot = 0; ph ^= 1; }
                for (int s = 3; s < 16; s++) {
                    const int kb = (int)(0x7654763542312100ull >> (4 * s)) & 15;
                    P_BEGIN(s, 16384) {
                        if ((0x0DADu >> s) & 1) tmaw3(dst, &maps.kv, 64 * j, 64 * kb, 1, full);
                        else tmaw3(dst, &maps.gu, fc, 64 * kb, 0, full);
                    }
                    const int xb = (int)(0x0000000765403210ull >> (4 * s)) & 15;
                    if (xb) { mbar_expect(sb + B_XFULL + 8 * xb, 16384); tma2(sb + OFF_X + xb * 16384, &maps.x, 64 * xb, r * 128, sb + B_XFULL + 8 * xb); }
                    P_END()
                }
                for (int s = 0; s < 24; s++) {
                    P_BEGIN(16 + s, 16384) {
                        if (s < 8) {
                            tmaw3(dst, &maps.q64, 0, 64 * s, 2 * j, full);
                            tmaw3(dst + 8192, &maps.gu64, 224 * (j & 6) + 192 + 32 * (j & 1), 64 * s, 0, full);
                        } else {
                            tmaw3(dst, &maps.gu, fc + 64 * (s >> 3), 64 * (s & 7), 0, full);
                        }
                    }
                    P_END()
                }
                const int p = j >> 1;
#pragma unroll 1
                for (int t = 0; t < 18; t++) {
                    const int q = t >= 9, sl = (int)(0x846352107ull >> (4 * (t - 9 * q))) & 15;
                    const int u = (int)((q ? 0x432186758ull : 0x327064105ull) >> (4 * (t - 9 * q))) & 15;
                    const int cw = (j & 1) * 4 + ((p & 2) ^ ((t == 5 || t > 9) ? 0 : 2)), cc = 64 * cw;
                    if (sl < 5) {
                        full = sb + B_FULL + 8 * sl; dst = sb + OFF_RING + sl * 16384;
                        mbar_wait(sb + B_EMPTY + 8 * sl, q ^ 1);
                    } else {
                        full = sb + B_EFULL + 8 * (sl - 5); dst = sb + OFF_X + (sl == 7 ? 8 : sl == 8 ? 7 : sl) * 16384;
                        mbar_wait(sb + B_EEMPTY + 8 * (sl - 5), q);
                    }
                    TS2(40 + t);
                    mbar_expect(full, 16384);
                    if (!MC || ((t ^ rank) & 1) == 0) {
                        if (u > 4) {
                            const int js = u > 6 ? j ^ 1 : j;
                            tmaw3(dst, (u & 1) ? &maps.wow : &maps.wdw, 0, (u & 1) ? 64 * js : 448 * p + 256 * (js & 1) + 128, cw, full);
                        } else {
                            const int g = 14 * p + (u == 4 ? 6 : 8 * (u & 1) + (u & 2));
                            tmaw5(dst, &maps.wdp, cc, g, full); tmaw5(dst + 8192, &maps.wdp, cc + 64, g, full);
                        }
                    }
                }
            }
        } else if (warp < 11) {
            const int hx = warp - 9;
            uint32_t epoch;
            asm volatile("ld.relaxed.gpu.global.u32 %0, [%1];" : "=r"(epoch) : "l"(g_epoch + blockIdx.x) : "memory");
            {
                const uint4* xr = (const uint4*)(xg + (size_t)(r * 128 + j * 16 + hx * 8) * kD) + lane;
                const uint4 wa = __ldg((const uint4*)gate_w + lane), wb = __ldg((const uint4*)gate_w + 32 + lane);
                const uint32_t tag = (epoch + 1) & 1;
                uint4* gp = g_gx + r * 32;
                if (lane < 2) st_pkt(gp + j * 4 + hx * 2 + lane, tag ^ 1, 0, 0, 0);
                float s[8];
                if (GDELAY) mbar_wait(sb + B_XFULL, 0);
#pragma unroll
                for (int i0 = 0; i0 < 8; i0 += 4) {
                    uint4 va[4], vb[4];
#pragma unroll
                    for (int i = 0; i < 4; i++) { va[i] = __ldg(xr + (i0 + i) * 64); vb[i] = __ldg(xr + (i0 + i) * 64 + 32); }
#pragma unroll
                    for (int i = 0; i < 4; i++) {
                        float t0 = bf_lo(va[i].x) * bf_lo(wa.x), t1 = bf_hi(va[i].x) * bf_hi(wa.x);
                        t0 = fmaf(bf_lo(va[i].y), bf_lo(wa.y), t0); t1 = fmaf(bf_hi(va[i].y), bf_hi(wa.y), t1);
                        t0 = fmaf(bf_lo(va[i].z), bf_lo(wa.z), t0); t1 = fmaf(bf_hi(va[i].z), bf_hi(wa.z), t1);
                        t0 = fmaf(bf_lo(va[i].w), bf_lo(wa.w), t0); t1 = fmaf(bf_hi(va[i].w), bf_hi(wa.w), t1);
                        t0 = fmaf(bf_lo(vb[i].x), bf_lo(wb.x), t0); t1 = fmaf(bf_hi(vb[i].x), bf_hi(wb.x), t1);
                        t0 = fmaf(bf_lo(vb[i].y), bf_lo(wb.y), t0); t1 = fmaf(bf_hi(vb[i].y), bf_hi(wb.y), t1);
                        t0 = fmaf(bf_lo(vb[i].z), bf_lo(wb.z), t0); t1 = fmaf(bf_hi(vb[i].z), bf_hi(wb.z), t1);
                        t0 = fmaf(bf_lo(vb[i].w), bf_lo(wb.w), t0); t1 = fmaf(bf_hi(vb[i].w), bf_hi(wb.w), t1);
                        s[i0 + i] = t0 + t1;
                    }
                }
#pragma unroll
                for (int i = 0; i < 8; i++) {
#pragma unroll
                    for (int o = 16; o; o >>= 1) s[i] += __shfl_xor_sync(0xffffffffu, s[i], o);
                    s[i] = 1.f / (1.f + __expf(-s[i]));
                }
                if (lane < 2) {
                    const float v0 = lane ? s[4] : s[0], v1 = lane ? s[5] : s[1], v2 = lane ? s[6] : s[2], v3 = lane ? s[7] : s[3];
                    st_pkt(gp + j * 4 + hx * 2 + lane, (__float_as_uint(v0) & ~1u) | tag, __float_as_uint(v1), __float_as_uint(v2), __float_as_uint(v3));
                }
                if (hx == 1) {
                    asm volatile("st.shared.u32 [%0], %1;" :: "r"(sb + OFF_ONES + lane * 4), "r"(0x3f803f80u) : "memory");
                    asm volatile("fence.proxy.async.shared::cta;" ::: "memory");
                }
                asm volatile("bar.sync 3, 96;" ::: "memory");
                if (hx == 0) {
                    uint32_t q[4];
                    recv_issue(q, gp + lane);
                    recv_check(q, gp + lane, tag);
                    asm volatile("st.shared.v4.u32 [%0], {%1,%2,%3,%4};" :: "r"(sb + OFF_G + lane * 16), "r"(q[0]), "r"(q[1]), "r"(q[2]), "r"(q[3]) : "memory");
                    if (lane == 0) {
                        asm volatile("st.shared.u32 [%0], %1;" :: "r"(sb + OFF_EPOCH), "r"(epoch) : "memory");
                        g_epoch[blockIdx.x] = epoch + 1;
                    }
                    __syncwarp();
                    if (lane == 0) mbar_arrive(sb + B_GRDY);
                } else {
                    if (r == 0) {
                        float4* zp = (float4*)(g_kvacc + (((epoch & 1) ^ 1) * 8 + j) * 4 * 272);
                        for (int i = lane; i < 272; i += 32) zp[i] = make_float4(0.f, 0.f, 0.f, 0.f);
                    }
                }
            }
            TS(2 + hx, 1);
#define PUBLISH_H(B) do { mbar_wait(sb + B_HSENT + 8 * (B), 0); if (lane == 0) { \
                asm volatile("st.release.gpu.global.u32 [%0], %1;" :: "l"(g_hflag + (r * 8 + j) * 8 + (B)), "r"(epoch + 1) : "memory"); } __syncwarp(); } while (0)
            if (hx == 1) {
#pragma unroll 1
                for (int b = 0; b < 3; b++) { PUBLISH_H(b); TS(3, 5 + b); }
            } else {
                const float* accp = g_kvacc + ((epoch & 1) * 8 + j) * 4 * 272;
                unsigned* cnt = g_kvcnt + j * 32;
                mbar_wait(sb + B_KVDONE, 0);
                TS(2, 5);
                if (lane == 0) asm volatile("red.release.gpu.global.add.u32 [%0], 1;" :: "l"(cnt) : "memory");
                __syncwarp();
                TS(2, 2);
                {
                    const unsigned target = 16u * (epoch + 1);
                    uint32_t it = 0, v;
                    do {
                        asm volatile("ld.acquire.gpu.global.u32 %0, [%1];" : "=r"(v) : "l"(cnt) : "memory");
                    } while ((int)(v - target) < 0 && ++it < SPIN_GLOBAL);
                }
                TS(2, 3);
#pragma unroll
                for (int h = 0; h < 4; h++) {
                    const float4 d0 = __ldcg((const float4*)(accp + h * 272) + lane);
                    const float4 d1 = __ldcg((const float4*)(accp + h * 272 + 128) + lane);
                    const float2 z0 = __ldcg((const float2*)(accp + h * 272 + 256) + (lane & 3));
                    const float2 z1 = __ldcg((const float2*)(accp + h * 272 + 264) + (lane & 3));
                    const uint32_t ba = sb + OFF_STG + h * 768 + lane * 4;
                    asm volatile("st.shared.u32 [%0], %1;" :: "r"(ba), "r"(pack2(d0.x, d0.y)) : "memory");
                    asm volatile("st.shared.u32 [%0], %1;" :: "r"(ba + 128), "r"(pack2(d1.x, d1.y)) : "memory");
                    asm volatile("st.shared.u32 [%0], %1;" :: "r"(ba + 256), "r"(pack2(d0.z, d0.w)) : "memory");
                    asm volatile("st.shared.u32 [%0], %1;" :: "r"(ba + 384), "r"(pack2(d1.z, d1.w)) : "memory");
                    asm volatile("st.shared.u32 [%0], %1;" :: "r"(ba + 512), "r"(pack2(z0.x, z0.y)) : "memory");
                    asm volatile("st.shared.u32 [%0], %1;" :: "r"(ba + 640), "r"(pack2(z1.x, z1.y)) : "memory");
                }
                asm volatile("fence.proxy.async.shared::cta;" ::: "memory");
                __syncwarp();
                if (lane == 0) mbar_arrive(sb + B_KVRDY);
                TS(2, 4);
            }
        } else {
            uint32_t epoch;
            asm volatile("ld.relaxed.gpu.global.u32 %0, [%1];" : "=r"(epoch) : "l"(g_epoch + blockIdx.x) : "memory");
            asm volatile("bar.arrive 3, 96;" :: "r"(epoch) : "memory");
            const int b = blockIdx.x, p = j >> 1;
            mbar_wait(sb + B_XFULL, 0);
            if (PF0 && r >= PF0) {
                const int row = r * 32 + lane;
                asm volatile("prefetch.global.L2 [%0];" :: "l"(pf_qkv + row * 3072 + 1024 + j * 128));
                asm volatile("prefetch.global.L2 [%0];" :: "l"(pf_qkv + row * 3072 + 2048 + j * 128));
                asm volatile("prefetch.global.L2 [%0];" :: "l"(pf_g + row * 3584 + fc * 2));
                asm volatile("prefetch.global.L2 [%0];" :: "l"(pf_u + row * 3584 + fc * 2));
            }
#pragma unroll 1
            for (int kb = 1; kb < 8; kb++) {
                mbar_wait(sb + B_XFULL + 8 * kb, 0);
                const char* base = kb < 3 ? pf_g : kb < 5 ? pf_u : kb == 5 ? pf_qkv : pf_d;
                const int off = kb == 5 ? b * 12288 : b * 14336 + ((kb < 5 ? kb - 1 : kb) & 1) * 7168;
                if (kb == 5) {
                    asm volatile("prefetch.global.L2 [%0];" :: "l"(base + off + (lane >> 3) * 3072 + (lane & 7) * 128));
                } else {
                    asm volatile("prefetch.global.L2 [%0];" :: "l"(base + off + lane * 128));
                    if (lane < 24) asm volatile("prefetch.global.L2 [%0];" :: "l"(base + off + 4096 + lane * 128));
                }
                if (kb == 7) asm volatile("prefetch.global.L2 [%0];" :: "l"(pf_o + b * 4096 + lane * 128));
            }
            {
                uint4* mb = g_part + (size_t)(r * 2 + (j & 1)) * 16384 + (((p ^ 1) * 4 + p) << 10) + lane;
#pragma unroll 1
                for (int i = 0; i < ((NOPRE || CL) ? 0 : 32); i++) { st_pkt(mb + i * 32, epoch & 1, 0, 0, 0); __nanosleep(40); }
                __syncwarp();
                if (lane == 0) mbar_arrive(sb + B_KVRDY);
            }
            {
                const uint32_t want = epoch + 1;
                const int hrow = (r * 4 + p) * 5 * 128;
                const unsigned* fl = g_hflag + (r * 8 + (j & 6)) * 8 + (lane & 15);
                uint32_t it = 0;
                int i = 0;
                mbar_wait(sb + B_HSENT + 8, 0);
#pragma unroll 1
                while (i < 3 && ++it < SPIN_GLOBAL) {
                    uint32_t v;
                    asm volatile("ld.acquire.gpu.global.u32 %0, [%1];" : "=r"(v) : "l"(fl) : "memory");
                    const uint32_t rdy = __ballot_sync(0xffffffffu, v == want);
#pragma unroll 1
                    while (i < 3 && ((rdy >> i) & 0x101u) == 0x101u) {
                        if (i < 2) mbar_wait(sb + B_XFREE + 8 * i, 0);
                        if (lane == 0) {
                            const int pc = (6 - 2 * i) % 6;
                            asm volatile("fence.proxy.async.global;" ::: "memory");
                            TS2(140 + i);
                            mbar_expect(sb + B_XFULL + 8 * pc, i != 1 ? 32768 : 16384);
                            tma2(sb + OFF_X + pc * 16384, i != 1 ? &maps.hx2 : &maps.hx, 0, hrow + pc * 128, sb + B_XFULL + 8 * pc);
                        }
                        i++;
                    }
                }
            }
        }
        if (CL) asm volatile("barrier.cluster.wait;" ::: "memory");
    } else {
        asm volatile("setmaxnreg.inc.sync.aligned.u32 224;");
        const int wg = warp >> 2;
        const bool elect = (tid & 127) == 0;
        const uint32_t sbd = (sb & 0x3FFFFu) >> 4, xlo = (sbd + wg * 512) | LBO1;
        auto release = [&](uint32_t bar) {
            if (elect) {
                mbar_arrive(sb + bar);
            }
        };
#define S_SL(S) ((S) < 40 ? (S) % 5 : (int)((0x846352107ull >> (4 * (((S) - 40) % 9))) & 15))
#define S_WAIT(S) do { mbar_wait(sb + (S_SL(S) < 5 ? B_FULL + 8 * S_SL(S) : B_EFULL + 8 * (S_SL(S) - 5)), (S) < 40 ? ((S) / 5) & 1 : (S) >= 49); \
            if (PROF && tid == 0) TS2(64 + (S)); } while (0)
#define S_B(S) (S_SL(S) < 5 ? OFF_RING / 16 + S_SL(S) * 1024 : (S_SL(S) == 7 ? 8 : S_SL(S) == 8 ? 7 : S_SL(S)) * 1024)
#define S_REL(S) do { if ((S) < 49) release(S_SL(S) < 5 ? B_EMPTY + 8 * S_SL(S) : B_EEMPTY + 8 * (S_SL(S) - 5)); } while (0)
#define G1(S, acc, SW, KB) stage_ss<(KB) * 1024, S_B(S), SW, (KB) == 0>(acc, xlo, sbd)
#define RET(S) do { S_WAIT((S) + 1); wg_wait<1>(); S_REL((S) - 1); } while (0)
#define RET2(S) do { S_WAIT((S) + 1); wg_wait<2>(); S_REL((S) - 1); } while (0)
#define SCHED() mbar_wait(sb + B_XFULL + 8 * 7, 0)
#define A2_SYNC() do { asm volatile("fence.proxy.async.shared::cta;" ::: "memory"); asm volatile("bar.sync %0, 128;" :: "r"(wg + 1) : "memory"); } while (0)
#define H_EPI(acc, F, I0, I1, OG, OU) _Pragma("unroll") for (int i = (I0); i < (I1); i++) \
            F[i] = keep(hmul2(pack2(acc[(OG) + 2 * i] * acc[(OU) + 2 * i], acc[(OG) + 2 * i + 1] * acc[(OU) + 2 * i + 1]), (i & 1) ? m_hi : m_lo))
#define PHI(acc, F, I0, I1) _Pragma("unroll") for (int i = (I0); i < (I1); i++) F[i] = keep(phi2(acc[2 * i], acc[2 * i + 1]))

        float a0[64], b0[64], a1[64], a2_[64], a3[64];
        mbar_wait(sb + B_XFULL, 0);
#define X_WAIT(KB) do { mbar_wait(sb + B_XFULL + 8 * (KB), 0); if (PROF && tid == 0) TS2(128 + (KB)); } while (0)
        S_WAIT(0); G1(0, b0, false, 0);
        if ((warp & 3) == 0) TS(wg, 1);
        S_WAIT(1); G1(1, a0, false, 0); RET(1);
        X_WAIT(1); G1(2, b0, false, 1); RET(2);
        X_WAIT(2); G1(3, b0, false, 2); RET(3);
        G1(4, a0, false, 1); RET(4);
        X_WAIT(3); G1(5, b0, false, 3); RET(5);
        G1(6, a0, false, 2); RET(6);
        X_WAIT(4); G1(7, b0, false, 4); RET(7);
        X_WAIT(5); G1(8, b0, false, 5); RET(8);
        G1(9, a0, false, 3); RET(9);
        X_WAIT(6); G1(10, b0, false, 6); RET(10);
        X_WAIT(7); G1(11, b0, false, 7); RET(11);
        G1(12, a0, false, 4);
        const uint32_t lrow = ((lane & 7) + 8 * ((lane >> 3) & 1)) * 128;
        const uint32_t srow = (warp & 3) * 2048 + lrow;
        const uint32_t ssw = (lane >> 4) ^ (lane & 7);
        uint4* const hsend = g_hx + (size_t)((r * 4 + (j >> 1)) * 5 + (j & 1)) * 1024 + warp * 128 + (lane >> 2) * 8 + (lane & 3);
#define SENT_H(B) do { __syncwarp(); if (lane == 0) mbar_arrive(sb + B_HSENT + 8 * (B)); } while (0)
        RET(12);
        pin(b0);
        uint32_t fh0[16], fh1[16], fh2[16], fh3[8], fo[16], pk[16], pv[16];
        float kv[32], zs[4];
        const uint32_t stg = sb + OFF_STG + wg * 8192, stl = stg + (warp & 1) * 2048 + lrow;
#define KV_ROUND(Z) do { A2_SYNC(); wg_fence(); \
            wg_ss64t##Z<8192 + 256, 8192, DH128>(kv, xlo, xlo); wg_ss64t<8192 + 384, 8192 + 128, DH128>(kv, xlo, xlo); \
            wg_ss8t##Z<8192, OFF_ONES / 16, 0>(zs, xlo, sbd); wg_ss8t<8192 + 128, OFF_ONES / 16, 0>(zs, xlo, sbd); wg_commit(); } while (0)
        G1(13, a0, false, 5); SCHED(); pack_sub<32>(pv, b0); PHI(b0, pk, 0, 4); RET(13);
        G1(14, a0, false, 6); SCHED(); if (!(warp & 2)) stash<16>(stl + 4096, ssw, pv); PHI(b0, pk, 4, 10); RET(14);
        G1(15, a0, false, 7); SCHED(); PHI(b0, pk, 10, 16); RET(15);
        if ((warp & 3) == 0) TS(wg, 2);

        G1(16, a1, true, 0); SCHED(); if (!(warp & 2)) stash<16>(stl, ssw, pk);
        mbar_wait(sb + B_GRDY, 0);
        float g_lo, g_hi;
        uint32_t tag;
        {
            const uint32_t ga = sb + OFF_G + (warp * 16 + (lane >> 2)) * 4;
            asm volatile("ld.shared.f32 %0, [%1];" : "=f"(g_lo) : "r"(ga) : "memory");
            asm volatile("ld.shared.f32 %0, [%1];" : "=f"(g_hi) : "r"(ga + 32) : "memory");
            asm volatile("ld.shared.u32 %0, [%1];" : "=r"(tag) : "r"(sb + OFF_EPOCH) : "memory");
        }
        float* const kvp = g_kvacc + (((tag & 1) * 8 + j) * 4 + (warp & 3)) * 272;
        tag = (tag + 1) & 1;
        const uint32_t m_lo = pack2(1.f - g_lo, 1.f - g_lo), m_hi = pack2(1.f - g_hi, 1.f - g_hi);
        RET(16);
        pin(a0);
        G1(17, a1, true, 1); SCHED(); H_EPI(a0, fh0, 0, 16, 0, 32); RET(17);
        G1(18, a1, true, 2); KV_ROUND(_z); RET2(18);
        G1(19, a1, true, 3); SCHED(); send_h<0, 1>(fh0, hsend); RET(19);
        G1(20, a1, true, 4); SCHED(); if (warp & 2) { stash<16>(stl, ssw, pk); stash<16>(stl + 4096, ssw, pv); } RET(20);
        G1(21, a1, true, 5); KV_ROUND(); RET2(21);
        G1(22, a1, true, 6); RET(22);
        pin(kv); pin(zs);
        G1(23, a1, true, 7); SCHED();
#define KV_RED(W) do { asm volatile("red.global.add.v4.f32 [%0], {%1,%2,%3,%4};" :: "l"(kvp + lane * 4), "f"(kv[8 * W]), "f"(kv[8 * W + 1]), "f"(kv[8 * W + 2]), "f"(kv[8 * W + 3]) : "memory"); \
                       asm volatile("red.global.add.v4.f32 [%0], {%1,%2,%3,%4};" :: "l"(kvp + 128 + lane * 4), "f"(kv[8 * W + 4]), "f"(kv[8 * W + 5]), "f"(kv[8 * W + 6]), "f"(kv[8 * W + 7]) : "memory"); } while (0)
        if ((warp & 3) == 0) KV_RED(0); else if ((warp & 3) == 1) KV_RED(1); else if ((warp & 3) == 2) KV_RED(2); else KV_RED(3);
        if ((lane & 3) == 0) {
            asm volatile("red.global.add.f32 [%0], %1;" :: "l"(kvp + 256 + (lane >> 2)), "f"(zs[0]) : "memory");
            asm volatile("red.global.add.f32 [%0], %1;" :: "l"(kvp + 264 + (lane >> 2)), "f"(zs[2]) : "memory");
        }
        __syncwarp();
        if (lane == 0) mbar_arrive(sb + B_KVDONE);
        RET(23);
        if ((warp & 3) == 0) TS(wg, 3);

        G1(24, a2_, false, 0); SCHED(); send_h<1, 2>(fh0, hsend); RET(24);
        pin(a1);
        G1(25, a2_, false, 1); SCHED(); send_h<2, 3>(fh0, hsend); H_EPI(a1, fh3, 0, 8, 32, 48); RET(25);
        G1(26, a2_, false, 2); SCHED(); send_h<3, 4>(fh0, hsend); SENT_H(0); PHI(a1, fo, 0, 4); RET(26);
        G1(27, a2_, false, 3); SCHED(); send_h<0, 1>(fh3, hsend + 4 * 1024 - (j & 1) * 1020); PHI(a1, fo, 4, 8); RET(27);
        G1(28, a2_, false, 4); SCHED(); send_h<1, 2>(fh3, hsend + 4 * 1024 - (j & 1) * 1020); SENT_H(1); PHI(a1, fo, 8, 12); RET(28);
        G1(29, a2_, false, 5); SCHED(); PHI(a1, fo, 12, 16); RET(29);
        G1(30, a2_, false, 6); RET(30);
        G1(31, a2_, false, 7); RET(31);
        if ((warp & 3) == 0) TS(wg, 4);

        float on[4][12];
#define O_SCALE(h) do { const float s_lo = __fdividef(g_lo, on[h][8] + 1e-6f), s_hi = __fdividef(g_hi, on[h][10] + 1e-6f); \
            const uint32_t sl_ = pack2(s_lo, s_lo), sh_ = pack2(s_hi, s_hi); \
            fo[4 * h] = keep(hmul2(pack2(on[h][0], on[h][1]), sl_)); fo[4 * h + 1] = keep(hmul2(pack2(on[h][2], on[h][3]), sh_)); \
            fo[4 * h + 2] = keep(hmul2(pack2(on[h][4], on[h][5]), sl_)); fo[4 * h + 3] = keep(hmul2(pack2(on[h][6], on[h][7]), sh_)); } while (0)
        uint4* const lsend = g_lx + (size_t)(r * 8 + j) * 2048 + warp * 128 + lane;
        const uint4* const lrecv = g_lx + (size_t)(r * 8 + (j ^ 1)) * 2048 + warp * 128 + lane;
        G1(32, a3, false, 0); RET(32);
        pin(a2_);
        G1(33, a3, false, 1); SCHED(); H_EPI(a2_, fh1, 0, 16, 0, 32); send_h<0, 1>(fh1, hsend + 2 * 1024); RET(33);
        G1(34, a3, false, 2); SCHED(); send_h<1, 3>(fh1, hsend + 2 * 1024); RET(34);
        if (elect) mbar_arrive(sb + B_XFREE);
        G1(35, a3, false, 3); SCHED(); send_h<3, 4>(fh1, hsend + 2 * 1024); SENT_H(2);
        if ((warp & 3) == 0) TS(wg, 5);
        mbar_wait(sb + B_KVRDY, 0);
        if ((warp & 3) == 0) TS(wg, 6);
        wg_fence();
#define O_MMA(h) wg_rs24_z<OFF_STG / 16 + (h) * 48 + (8u << 16), 16>(on[h], fo[4 * (h)], fo[4 * (h) + 1], fo[4 * (h) + 2], fo[4 * (h) + 3], sbd)
        O_MMA(0); O_MMA(1); O_MMA(2); O_MMA(3);
        wg_commit();
        RET2(35);
        G1(36, a3, false, 4); RET(36);
        pin(on[0]); pin(on[1]); pin(on[2]); pin(on[3]);
        release(B_EEMPTY + 16);
        G1(37, a3, false, 5); SCHED(); O_SCALE(0); O_SCALE(1); O_SCALE(2); O_SCALE(3); RET(37);
        if (elect) mbar_arrive(sb + B_XFREE + 8);
        G1(38, a3, false, 6); SCHED(); send_frag<0, 2>(fo, lsend, tag); RET(38);
        release(B_EEMPTY);
        G1(39, a3, false, 7); SCHED(); send_frag<2, 4>(fo, lsend, tag); RET(39);
        release(B_EEMPTY + 8);
        if ((warp & 3) == 0) TS(wg, 7);

#define G2S(S, acc, U) stage_ss<(U) * 1024, S_B(S), false, (S) == 45>(acc, xlo, sbd)
#define G2R(S, acc, F) stage_rs<S_B(S), (S) == 40>(acc, F, sbd)
#define H_WAIT(P) do { mbar_wait(sb + B_XFULL + 8 * (P), 1); if (PROF && tid == 0) TS2(150 + (P)); } while (0)
        const int p = j >> 1, pw = (p & 2) ^ 2;
        const bool own = wg == (p & 1);
        uint4* const pbase = g_part + (size_t)(r * 2 + (j & 1)) * 16384 + (warp & 3) * 256 + lane;

        float p1[64], p2[64];
        uint32_t po[16], ph2[16];
        G2R(40, p1, fo); RET(40);
        release(B_EEMPTY + 24);
        pin(a3);
        H_WAIT(0); G2S(41, p1, 0); SCHED(); H_EPI(a3, fh2, 0, 16, 0, 32); send_frag<0, 2>(fh2, lsend + 1024, tag); RET(41);
        G2S(42, p1, 1); SCHED(); recv_issue(po, lrecv); send_frag<2, 4>(fh2, lsend + 1024, tag); RET(42);
        H_WAIT(4); G2S(43, p1, 4); RET(43);
        G2R(44, p1, fh2); RET(44);
        G2S(45, p2, 0); SCHED(); if (PROF && tid == 0) TS2(160); CNT(170, recv_check(po, lrecv, tag)); if (PROF && tid == 0) TS2(161); recv_issue(ph2, lrecv + 1024); RET(45);
        G2R(46, p1, po); RET(46);
        if (CL) {
            asm volatile("barrier.cluster.wait.aligned;" ::: "memory");
            if (elect) mbar_arrive_cta(sb + B_RFREE, (blockIdx.x & 1) ^ 1);
        }
        H_WAIT(2); G2S(47, p1, 2); RET(47);
        G2S(48, p1, 3); SCHED(); if (PROF && tid == 0) TS2(162); CNT(171, recv_check(ph2, lrecv + 1024, tag)); if (PROF && tid == 0) TS2(163); RET(48);
        G2R(49, p1, ph2); RET(49);
        if ((warp & 3) == 0) TS(wg, 8);
        uint32_t sp[32], qa[32], qb[32];
        uint4* const s1 = pbase + (((pw + wg) * 4 + p) << 10);
        G2R(50, p2, fo); RET(50);
        pin(p1);
        G2R(51, p2, po); SCHED(); pack_sub<0>(sp, p1); send_frag<0, 2>(sp, s1, tag); RET(51);
        G2R(52, p2, fh2); SCHED(); send_frag<2, 5>(sp, s1, tag); RET(52);
        if (elect) mbar_arrive(sb + B_XFREE + 16);
        G2R(53, p2, ph2); SCHED(); send_frag<5, 8>(sp, s1, tag); RET(53);
        const uint4* ra = pbase + ((p * 4 + pw) << 10);
        const uint4* rc = pbase + ((p * 4 + (p ^ 1)) << 10);
        if (own) mbar_wait(sb + B_AHEAD, 0);
        G2S(54, p2, 1); RET(54);
        G2S(55, p2, 2); RET(55);
        G2S(56, p2, 3); RET(56);
        G2S(57, p2, 4); SCHED();
        if ((warp & 3) == 0) TS(wg, 9);
#define PART_COPY() do { mbar_wait(sb + B_XFREE + 16, 0); mbar_expect(sb + B_PART, 32768); \
            asm volatile("cp.async.bulk.shared::cluster.global.mbarrier::complete_tx::bytes [%0], [%1], %2, [%3];" \
                         :: "r"(sb + OFF_RING), "l"(ra), "r"(32768), "r"(sb + B_PART) : "memory"); } while (0)
        if (!own && elect) mbar_arrive(sb + B_AHEAD);
        wg_wait<0>();
        pin(p2);
        if ((warp & 3) == 0) TS(wg, 11);
        if (!own) {
            if (COPY_AT == 0 && elect) PART_COPY();
            pack_sub<0>(sp, p2);
            send_frag<0, 8>(sp, pbase + (((p ^ 1) * 4 + p) << 10), tag);
        } else {
            if (!CL) recv_issue(sp, rc);
            uint32_t f0[16], f1[16];
            pack_sub<0>(f0, p2); pack_sub<32>(f1, p2);
            mbar_wait(sb + B_PART, 0);
            if ((warp & 3) == 0) TS(wg, 10);
            const uint32_t pa = sb + OFF_RING + (warp & 3) * 4096 + lane * 16;
#pragma unroll
            for (int v = 0; v < 8; v++) {
                asm volatile("ld.shared.v4.u32 {%0,%1,%2,%3}, [%4];" : "=r"(qa[4 * v]), "=r"(qa[4 * v + 1]), "=r"(qa[4 * v + 2]), "=r"(qa[4 * v + 3]) : "r"(pa + v * 512) : "memory");
                asm volatile("ld.shared.v4.u32 {%0,%1,%2,%3}, [%4];" : "=r"(qb[4 * v]), "=r"(qb[4 * v + 1]), "=r"(qb[4 * v + 2]), "=r"(qb[4 * v + 3]) : "r"(pa + 16384 + v * 512) : "memory");
            }
            CNT(172, recv_check(qa, ra, tag)); CNT(173, recv_check(qb, ra + 1024, tag));
#pragma unroll
            for (int i = 0; i < 32; i++) qa[i] = keep(hadd2(qa[i], qb[i]));
            if ((warp & 3) == 0) TS(wg, 12);
            CNT(174, recv_check(sp, rc, tag));
            if ((warp & 3) == 0) TS(wg, 13);
#pragma unroll
            for (int i = 0; i < 16; i++) { f0[i] = hadd2(hadd2(f0[i], sp[i]), qa[i]); f1[i] = hadd2(hadd2(f1[i], sp[16 + i]), qa[16 + i]); }
            const uint32_t slab = sb + OFF_X + 2 * 16384 + wg * 8192;
            stash<16>(slab + srow, ssw, f0); stash<16>(slab + 16384 + srow, ssw, f1);
            __syncwarp();
            __nv_bfloat16* op = out + (size_t)(r * 128 + warp * 16 + (lane >> 4)) * kD + (j & 1) * 256 + (p & 2) * 64 + (lane & 15) * 8;
#pragma unroll
            for (int i = 0; i < 8; i++) {
                const int row = i * 2 + (lane >> 4);
                uint4 v;
                asm volatile("ld.shared.v4.u32 {%0,%1,%2,%3}, [%4];" : "=r"(v.x), "=r"(v.y), "=r"(v.z), "=r"(v.w)
                             : "r"(slab + (lane & 8) * 2048 + ((warp & 3) * 16 + row) * 128 + (((lane & 7) ^ (row & 7)) << 4)) : "memory");
                *(uint4*)(op + i * 2 * kD) = v;
            }
        }
        if ((warp & 3) == 0) { TS(wg, 14); TSG(wg, 31); }
    }
}

typedef CUresult (*EncodeFn)(CUtensorMap*, CUtensorMapDataType, cuuint32_t, void*, const cuuint64_t*, const cuuint64_t*, const cuuint32_t*,
                             const cuuint32_t*, CUtensorMapInterleave, CUtensorMapSwizzle, CUtensorMapL2promotion, CUtensorMapFloatOOBfill);

static void encode(EncodeFn fn, CUtensorMap* m, int rank, const void* base, const cuuint64_t (&gd)[5], const cuuint64_t (&gs)[4],
                   const cuuint32_t (&bd)[5], CUtensorMapSwizzle sw) {
    cuuint32_t es[5] = {1, 1, 1, 1, 1};
    fn(m, CU_TENSOR_MAP_DATA_TYPE_BFLOAT16, rank, const_cast<void*>(base), gd, gs, bd, es, CU_TENSOR_MAP_INTERLEAVE_NONE, sw,
       CU_TENSOR_MAP_L2_PROMOTION_L2_128B, CU_TENSOR_MAP_FLOAT_OOB_FILL_NONE);
}

extern "C" void kernel_launch(void* const* d_in, const int* in_sizes, int n_in, void* d_out, int out_size) {
    const char* x = (const char*)d_in[0];
    const char* wqkv = (const char*)d_in[1];
    const char* wo = (const char*)d_in[2];
    const char* wg = (const char*)d_in[4];
    const char* wu = (const char*)d_in[5];
    const char* wd = (const char*)d_in[6];
    void* fnp = nullptr;
    cudaDriverEntryPointQueryResult qr;
    cudaGetDriverEntryPoint("cuTensorMapEncodeTiled", &fnp, cudaEnableDefault, &qr);
    EncodeFn fn = (EncodeFn)fnp;
    Maps maps;
    const char* lo = wg < wu ? wg : wu;
    const uint64_t diff = wg < wu ? (uint64_t)(wu - wg) : (uint64_t)(wg - wu);
    const CUtensorMapSwizzle S128 = CU_TENSOR_MAP_SWIZZLE_128B, S64 = CU_TENSOR_MAP_SWIZZLE_64B;
    encode(fn, &maps.x, 2, x, {512, 2048, 1, 1}, {1024, 0, 0}, {64, 128, 1, 1}, S128);
    encode(fn, &maps.gu, 3, lo, {1792, 512, 2, 1}, {3584, diff, 0}, {64, 64, 2, 1}, S128);
    encode(fn, &maps.kv, 3, wqkv, {512, 512, 3, 1}, {3072, 1024, 0}, {64, 64, 2, 1}, S128);
    encode(fn, &maps.q64, 3, wqkv, {32, 512, 48, 1}, {3072, 64, 0}, {32, 64, 2, 1}, S64);
    encode(fn, &maps.gu64, 3, lo, {1792, 512, 2, 1}, {3584, diff, 0}, {32, 64, 2, 1}, S64);
    encode(fn, &maps.wdw, 3, wd, {64, 1792, 8, 1}, {1024, 128, 0}, {64, 64, 2, 1}, S128);
    encode(fn, &maps.wow, 3, wo, {64, 512, 8}, {1024, 128}, {64, 64, 2}, S128);
    encode(fn, &maps.wdp, 5, wd, {512, 2, 4, 4, 56}, {1024, 8192, 2048, 32768}, {64, 2, 4, 4, 2}, S128);
    void* hx = nullptr;
    cudaGetSymbolAddress(&hx, g_hx);
    encode(fn, &maps.hx, 2, hx, {64, 16 * 4 * 5 * 128}, {128}, {64, 128}, S128);
    encode(fn, &maps.hx2, 2, hx, {64, 16 * 4 * 5 * 128}, {128}, {64, 256}, S128);
    cudaFuncSetAttribute(fused_kernel, cudaFuncAttributeMaxDynamicSharedMemorySize, SMEM_BYTES);
    cudaLaunchConfig_t cfg = {};
    cfg.gridDim = dim3(128);
    cfg.blockDim = dim3(384);
    cfg.dynamicSmemBytes = SMEM_BYTES;
    cfg.stream = cudaStreamPerThread;
    cudaLaunchAttribute at[1];
    at[0].id = cudaLaunchAttributeClusterDimension;
    at[0].val.clusterDim.x = 2; at[0].val.clusterDim.y = 1; at[0].val.clusterDim.z = 1;
    cfg.attrs = at;
    cfg.numAttrs = (MC || CL || FORCECL) ? 1 : 0;
    cudaLaunchKernelEx(&cfg, fused_kernel, maps, (const __nv_bfloat16*)d_in[0], (const __nv_bfloat16*)d_in[7], wqkv, wg, wu, wd, wo, (__nv_bfloat16*)d_out);
}
```

```cpp
#include <cuda_runtime.h>
#include <cuda.h>
#include <cuda_bf16.h>
#include <stdint.h>

#define MC 0
#define PFMODE 1
#define PHI_SAT 0
#define EXPT 0
#define RX 0
#define PF0 4
#define GDELAY 1
#define PRO5 0
#define NOPRE 0
#define CL 0
#define FORCECL 0
#define MAPV 0x6510432
#define PROF 0

namespace {

constexpr int kD = 512;
constexpr uint32_t OFF_X = 0, OFF_STG = 131072, OFF_RING = 147456, OFF_MISC = 229376;
constexpr uint32_t B_FULL = OFF_MISC, B_EMPTY = OFF_MISC + 40, B_XFULL = OFF_MISC + 80;
constexpr uint32_t B_GRDY = OFF_MISC + 152, B_KVDONE = OFF_MISC + 160, B_KVRDY = OFF_MISC + 168;
constexpr uint32_t B_HSENT = OFF_MISC + 176, B_XFREE = OFF_MISC + 200;
constexpr uint32_t OFF_EPOCH = OFF_MISC + 240, OFF_G = OFF_MISC + 256;
constexpr uint32_t B_AHEAD = OFF_MISC + 248, B_PART = OFF_MISC + 232;
constexpr uint32_t OFF_ONES = OFF_MISC + 768;
constexpr uint32_t B_EFULL = OFF_MISC + 896, B_EEMPTY = OFF_MISC + 928;
constexpr uint32_t B_LAST = OFF_MISC + 224, B_RFREE = OFF_MISC + 960;
constexpr uint32_t B_WARP = OFF_MISC + 968;
constexpr uint32_t SMEM_BYTES = OFF_MISC + 1032;
constexpr uint32_t SPIN_GLOBAL = 1u << 14;

struct alignas(64) Maps { CUtensorMap x, gu, kv, q64, gu64, wdw, wow, wdp, hx, hx2; };

}

__device__ uint4 g_part[16 * 2 * 4 * 4 * 1024];
__device__ uint4 g_hx[16 * 4 * 5 * 1024];
__device__ uint4 g_lx[16 * 8 * 2 * 1024];
__device__ unsigned g_hflag[128 * 8];
__device__ uint4 g_gx[16 * 32];
__device__ float g_kvacc[2 * 8 * 4 * 272];
__device__ unsigned g_kvcnt[8 * 32];
__device__ unsigned g_epoch[128];
#define TS(role, idx)
#define TS2(idx)
#define CNT(idx, v) (void)(v)
#define TSG(role, idx)

namespace {

__device__ __forceinline__ void mbar_init(uint32_t bar, uint32_t cnt) { asm volatile("mbarrier.init.shared::cta.b64 [%0], %1;" :: "r"(bar), "r"(cnt) : "memory"); }
__device__ __forceinline__ void mbar_expect(uint32_t bar, uint32_t bytes) { asm volatile("mbarrier.arrive.expect_tx.shared::cta.b64 _, [%0], %1;" :: "r"(bar), "r"(bytes) : "memory"); }
__device__ __forceinline__ void mbar_arrive(uint32_t bar) { asm volatile("mbarrier.arrive.shared::cta.b64 _, [%0];" :: "r"(bar) : "memory"); }
__device__ __forceinline__ void mbar_arrive_cta(uint32_t bar, uint32_t cta) {
    asm volatile("{\n.reg .b32 ra;\nmapa.shared::cluster.u32 ra, %0, %1;\nmbarrier.arrive.shared::cluster.b64 _, [ra];\n}" :: "r"(bar), "r"(cta) : "memory");
}
__device__ __forceinline__ void mbar_wait(uint32_t bar, uint32_t parity) {
    asm volatile("{\n.reg .pred p;\n.reg .u32 c;\n"
                 "mbarrier.try_wait.parity.shared::cta.b64 p, [%0], %1;\n@p bra DONE;\n"
                 "mov.u32 c, 0;\nLAB_WAIT:\nmbarrier.try_wait.parity.shared::cta.b64 p, [%0], %1;\n@p bra DONE;\n"
                 "add.u32 c, c, 1;\nsetp.lt.u32 p, c, 65536;\n@p bra LAB_WAIT;\nDONE:\n}" :: "r"(bar), "r"(parity) : "memory");
}
__device__ __forceinline__ void tma2(uint32_t dst, const CUtensorMap* m, int c0, int c1, uint32_t bar) {
    asm volatile("cp.async.bulk.tensor.2d.shared::cluster.global.mbarrier::complete_tx::bytes [%0], [%1, {%3, %4}], [%2];"
        :: "r"(dst), "l"(m), "r"(bar), "r"(c0), "r"(c1) : "memory");
}
__device__ __forceinline__ void tmaw2(uint32_t dst, const CUtensorMap* m, int c0, int c1, uint32_t bar) {
    tma2(dst, m, c0, c1, bar);
}
__device__ __forceinline__ void tmaw3(uint32_t dst, const CUtensorMap* m, int c0, int c1, int c2, uint32_t bar) {
    asm volatile("cp.async.bulk.tensor.3d.shared::cluster.global.mbarrier::complete_tx::bytes [%0], [%1, {%3, %4, %5}], [%2];"
        :: "r"(dst), "l"(m), "r"(bar), "r"(c0), "r"(c1), "r"(c2) : "memory");
}
__device__ __forceinline__ void tmaw5(uint32_t dst, const CUtensorMap* m, int c0, int c4, uint32_t bar) {
    asm volatile("cp.async.bulk.tensor.5d.shared::cluster.global.mbarrier::complete_tx::bytes [%0], [%1, {%3, %5, %5, %5, %4}], [%2];"
        :: "r"(dst), "l"(m), "r"(bar), "r"(c0), "r"(c4), "r"(0) : "memory");
}
__device__ __forceinline__ void bulk_in(uint32_t dst, const void* src, uint32_t bytes, uint32_t bar) {
    mbar_expect(bar, bytes);
    asm volatile("cp.async.bulk.shared::cluster.global.mbarrier::complete_tx::bytes [%0], [%1], %2, [%3];" :: "r"(dst), "l"(src), "r"(bytes), "r"(bar) : "memory");
}
__device__ __forceinline__ void wg_fence() { asm volatile("wgmma.fence.sync.aligned;" ::: "memory"); }
__device__ __forceinline__ void wg_commit() { asm volatile("wgmma.commit_group.sync.aligned;" ::: "memory"); }
template <int N> __device__ __forceinline__ void wg_wait() { asm volatile("wgmma.wait_group.sync.aligned %0;" :: "n"(N) : "memory"); }
template <int N> __device__ __forceinline__ void pin(float (&d)[N]) {
#pragma unroll
    for (int i = 0; i < N; i++) asm volatile("" : "+f"(d[i]) :: "memory");
}
__device__ __forceinline__ uint32_t pack2(float lo, float hi) { uint32_t r; asm("cvt.rn.bf16x2.f32 %0, %1, %2;" : "=r"(r) : "f"(hi), "f"(lo)); return r; }
__device__ __forceinline__ uint32_t keep(uint32_t v) { asm volatile("" : "+r"(v)); return v; }
__device__ __forceinline__ uint32_t hadd2(uint32_t a, uint32_t b) { uint32_t r; asm("add.bf16x2 %0, %1, %2;" : "=r"(r) : "r"(a), "r"(b)); return r; }
__device__ __forceinline__ uint32_t hmul2(uint32_t a, uint32_t b) { uint32_t r; asm("mul.bf16x2 %0, %1, %2;" : "=r"(r) : "r"(a), "r"(b)); return r; }
__device__ __forceinline__ uint32_t phi2(float t0, float t1) {
    float e0, e1;
    asm("ex2.approx.ftz.f32 %0, %1;" : "=f"(e0) : "f"(t0 * 1.4426950408889634f));
    asm("ex2.approx.ftz.f32 %0, %1;" : "=f"(e1) : "f"(t1 * 1.4426950408889634f));
    uint32_t e = pack2(e0, e1), t = pack2(t0, t1), r;
    asm("min.bf16x2 %0, %0, %1;" : "+r"(e) : "r"(0x3f803f80u));
    asm("max.bf16x2 %0, %0, %1;" : "+r"(t) : "r"(0x35863586u));
    asm("add.bf16x2 %0, %1, %2;" : "=r"(r) : "r"(e), "r"(t));
    return r;
}
__device__ __forceinline__ void stsm4(uint32_t a, uint32_t r0, uint32_t r1, uint32_t r2, uint32_t r3) {
    asm volatile("stmatrix.sync.aligned.m8n8.x4.shared.b16 [%0], {%1,%2,%3,%4};" :: "r"(a), "r"(r0), "r"(r1), "r"(r2), "r"(r3) : "memory");
}
__device__ __forceinline__ float bf_lo(uint32_t w) { return __uint_as_float(w << 16); }
__device__ __forceinline__ float bf_hi(uint32_t w) { return __uint_as_float(w & 0xffff0000u); }
__device__ __forceinline__ void st_pkt(uint4* p, uint32_t w0, uint32_t w1, uint32_t w2, uint32_t w3) {
    asm volatile("{\n.reg .b64 lo, hi;\n.reg .b128 v;\nmov.b64 lo, {%1, %2};\nmov.b64 hi, {%3, %4};\nmov.b128 v, {lo, hi};\nst.relaxed.gpu.global.b128 [%0], v;\n}"
        :: "l"(p), "r"(w0), "r"(w1), "r"(w2), "r"(w3) : "memory");
}
__device__ __forceinline__ void ld_pkt(const uint4* p, uint32_t& w0, uint32_t& w1, uint32_t& w2, uint32_t& w3) {
    asm volatile("{\n.reg .b64 lo, hi;\n.reg .b128 v;\nld.relaxed.gpu.global.b128 v, [%4];\nmov.b128 {lo, hi}, v;\nmov.b64 {%0, %1}, lo;\nmov.b64 {%2, %3}, hi;\n}"
        : "=r"(w0), "=r"(w1), "=r"(w2), "=r"(w3) : "l"(p) : "memory");
}

template <uint32_t AO, uint32_t BO, uint32_t BH> __device__ __forceinline__ void wg_ss128(float (&d)[64], uint32_t ab, uint32_t bb) {
    asm volatile("{\n.reg .b64 da, db;\n.reg .b32 ta, tb, th, ah;\nadd.u32 ta, %64, %66;\nadd.u32 tb, %65, %67;\nmov.b32 th, %68;\nmov.b32 ah, 0x40000040;\nmov.b64 da, {ta, ah};\nmov.b64 db, {tb, th};\n"
        "wgmma.mma_async.sync.aligned.m64n128k16.f32.bf16.bf16 {%0,%1,%2,%3,%4,%5,%6,%7,%8,%9,%10,%11,%12,%13,%14,%15,%16,%17,%18,%19,%20,%21,%22,%23,%24,%25,%26,%27,%28,%29,%30,%31,%32,%33,%34,%35,%36,%37,%38,%39,%40,%41,%42,%43,%44,%45,%46,%47,%48,%49,%50,%51,%52,%53,%54,%55,%56,%57,%58,%59,%60,%61,%62,%63}, da, db, 1, 1, 1, 0, 1;\n}\n"
        : "+f"(d[0]),"+f"(d[1]),"+f"(d[2]),"+f"(d[3]),"+f"(d[4]),"+f"(d[5]),"+f"(d[6]),"+f"(d[7]),"+f"(d[8]),"+f"(d[9]),"+f"(d[10]),"+f"(d[11]),"+f"(d[12]),"+f"(d[13]),"+f"(d[14]),"+f"(d[15]),"+f"(d[16]),"+f"(d[17]),"+f"(d[18]),"+f"(d[19]),"+f"(d[20]),"+f"(d[21]),"+f"(d[22]),"+f"(d[23]),"+f"(d[24]),"+f"(d[25]),"+f"(d[26]),"+f"(d[27]),"+f"(d[28]),"+f"(d[29]),"+f"(d[30]),"+f"(d[31]),"+f"(d[32]),"+f"(d[33]),"+f"(d[34]),"+f"(d[35]),"+f"(d[36]),"+f"(d[37]),"+f"(d[38]),"+f"(d[39]),"+f"(d[40]),"+f"(d[41]),"+f"(d[42]),"+f"(d[43]),"+f"(d[44]),"+f"(d[45]),"+f"(d[46]),"+f"(d[47]),"+f"(d[48]),"+f"(d[49]),"+f"(d[50]),"+f"(d[51]),"+f"(d[52]),"+f"(d[53]),"+f"(d[54]),"+f"(d[55]),"+f"(d[56]),"+f"(d[57]),"+f"(d[58]),"+f"(d[59]),"+f"(d[60]),"+f"(d[61]),"+f"(d[62]),"+f"(d[63])
        : "r"(ab), "r"(bb), "n"(AO), "n"(BO), "n"(BH));
}
template <uint32_t AO, uint32_t BO, uint32_t BH> __device__ __forceinline__ void wg_ss128_z(float (&d)[64], uint32_t ab, uint32_t bb) {
    asm volatile("{\n.reg .b64 da, db;\n.reg .b32 ta, tb, th, ah;\nadd.u32 ta, %64, %66;\nadd.u32 tb, %65, %67;\nmov.b32 th, %68;\nmov.b32 ah, 0x40000040;\nmov.b64 da, {ta, ah};\nmov.b64 db, {tb, th};\n"
        "wgmma.mma_async.sync.aligned.m64n128k16.f32.bf16.bf16 {%0,%1,%2,%3,%4,%5,%6,%7,%8,%9,%10,%11,%12,%13,%14,%15,%16,%17,%18,%19,%20,%21,%22,%23,%24,%25,%26,%27,%28,%29,%30,%31,%32,%33,%34,%35,%36,%37,%38,%39,%40,%41,%42,%43,%44,%45,%46,%47,%48,%49,%50,%51,%52,%53,%54,%55,%56,%57,%58,%59,%60,%61,%62,%63}, da, db, 0, 1, 1, 0, 1;\n}\n"
        : "=f"(d[0]),"=f"(d[1]),"=f"(d[2]),"=f"(d[3]),"=f"(d[4]),"=f"(d[5]),"=f"(d[6]),"=f"(d[7]),"=f"(d[8]),"=f"(d[9]),"=f"(d[10]),"=f"(d[11]),"=f"(d[12]),"=f"(d[13]),"=f"(d[14]),"=f"(d[15]),"=f"(d[16]),"=f"(d[17]),"=f"(d[18]),"=f"(d[19]),"=f"(d[20]),"=f"(d[21]),"=f"(d[22]),"=f"(d[23]),"=f"(d[24]),"=f"(d[25]),"=f"(d[26]),"=f"(d[27]),"=f"(d[28]),"=f"(d[29]),"=f"(d[30]),"=f"(d[31]),"=f"(d[32]),"=f"(d[33]),"=f"(d[34]),"=f"(d[35]),"=f"(d[36]),"=f"(d[37]),"=f"(d[38]),"=f"(d[39]),"=f"(d[40]),"=f"(d[41]),"=f"(d[42]),"=f"(d[43]),"=f"(d[44]),"=f"(d[45]),"=f"(d[46]),"=f"(d[47]),"=f"(d[48]),"=f"(d[49]),"=f"(d[50]),"=f"(d[51]),"=f"(d[52]),"=f"(d[53]),"=f"(d[54]),"=f"(d[55]),"=f"(d[56]),"=f"(d[57]),"=f"(d[58]),"=f"(d[59]),"=f"(d[60]),"=f"(d[61]),"=f"(d[62]),"=f"(d[63])
        : "r"(ab), "r"(bb), "n"(AO), "n"(BO), "n"(BH));
}
template <uint32_t BO, uint32_t BH> __device__ __forceinline__ void wg_rs128(float (&d)[64], uint32_t a0, uint32_t a1, uint32_t a2, uint32_t a3, uint32_t bb) {
    asm volatile("{\n.reg .b64 db;\n.reg .b32 tb, th;\nadd.u32 tb, %68, %69;\nmov.b32 th, %70;\nmov.b64 db, {tb, th};\n"
        "wgmma.mma_async.sync.aligned.m64n128k16.f32.bf16.bf16 {%0,%1,%2,%3,%4,%5,%6,%7,%8,%9,%10,%11,%12,%13,%14,%15,%16,%17,%18,%19,%20,%21,%22,%23,%24,%25,%26,%27,%28,%29,%30,%31,%32,%33,%34,%35,%36,%37,%38,%39,%40,%41,%42,%43,%44,%45,%46,%47,%48,%49,%50,%51,%52,%53,%54,%55,%56,%57,%58,%59,%60,%61,%62,%63}, {%64,%65,%66,%67}, db, 1, 1, 1, 1;\n}\n"
        : "+f"(d[0]),"+f"(d[1]),"+f"(d[2]),"+f"(d[3]),"+f"(d[4]),"+f"(d[5]),"+f"(d[6]),"+f"(d[7]),"+f"(d[8]),"+f"(d[9]),"+f"(d[10]),"+f"(d[11]),"+f"(d[12]),"+f"(d[13]),"+f"(d[14]),"+f"(d[15]),"+f"(d[16]),"+f"(d[17]),"+f"(d[18]),"+f"(d[19]),"+f"(d[20]),"+f"(d[21]),"+f"(d[22]),"+f"(d[23]),"+f"(d[24]),"+f"(d[25]),"+f"(d[26]),"+f"(d[27]),"+f"(d[28]),"+f"(d[29]),"+f"(d[30]),"+f"(d[31]),"+f"(d[32]),"+f"(d[33]),"+f"(d[34]),"+f"(d[35]),"+f"(d[36]),"+f"(d[37]),"+f"(d[38]),"+f"(d[39]),"+f"(d[40]),"+f"(d[41]),"+f"(d[42]),"+f"(d[43]),"+f"(d[44]),"+f"(d[45]),"+f"(d[46]),"+f"(d[47]),"+f"(d[48]),"+f"(d[49]),"+f"(d[50]),"+f"(d[51]),"+f"(d[52]),"+f"(d[53]),"+f"(d[54]),"+f"(d[55]),"+f"(d[56]),"+f"(d[57]),"+f"(d[58]),"+f"(d[59]),"+f"(d[60]),"+f"(d[61]),"+f"(d[62]),"+f"(d[63])
        : "r"(a0), "r"(a1), "r"(a2), "r"(a3), "r"(bb), "n"(BO), "n"(BH));
}
template <uint32_t BO, uint32_t BH> __device__ __forceinline__ void wg_rs128_z(float (&d)[64], uint32_t a0, uint32_t a1, uint32_t a2, uint32_t a3, uint32_t bb) {
    asm volatile("{\n.reg .b64 db;\n.reg .b32 tb, th;\nadd.u32 tb, %68, %69;\nmov.b32 th, %70;\nmov.b64 db, {tb, th};\n"
        "wgmma.mma_async.sync.aligned.m64n128k16.f32.bf16.bf16 {%0,%1,%2,%3,%4,%5,%6,%7,%8,%9,%10,%11,%12,%13,%14,%15,%16,%17,%18,%19,%20,%21,%22,%23,%24,%25,%26,%27,%28,%29,%30,%31,%32,%33,%34,%35,%36,%37,%38,%39,%40,%41,%42,%43,%44,%45,%46,%47,%48,%49,%50,%51,%52,%53,%54,%55,%56,%57,%58,%59,%60,%61,%62,%63}, {%64,%65,%66,%67}, db, 0, 1, 1, 1;\n}\n"
        : "=f"(d[0]),"=f"(d[1]),"=f"(d[2]),"=f"(d[3]),"=f"(d[4]),"=f"(d[5]),"=f"(d[6]),"=f"(d[7]),"=f"(d[8]),"=f"(d[9]),"=f"(d[10]),"=f"(d[11]),"=f"(d[12]),"=f"(d[13]),"=f"(d[14]),"=f"(d[15]),"=f"(d[16]),"=f"(d[17]),"=f"(d[18]),"=f"(d[19]),"=f"(d[20]),"=f"(d[21]),"=f"(d[22]),"=f"(d[23]),"=f"(d[24]),"=f"(d[25]),"=f"(d[26]),"=f"(d[27]),"=f"(d[28]),"=f"(d[29]),"=f"(d[30]),"=f"(d[31]),"=f"(d[32]),"=f"(d[33]),"=f"(d[34]),"=f"(d[35]),"=f"(d[36]),"=f"(d[37]),"=f"(d[38]),"=f"(d[39]),"=f"(d[40]),"=f"(d[41]),"=f"(d[42]),"=f"(d[43]),"=f"(d[44]),"=f"(d[45]),"=f"(d[46]),"=f"(d[47]),"=f"(d[48]),"=f"(d[49]),"=f"(d[50]),"=f"(d[51]),"=f"(d[52]),"=f"(d[53]),"=f"(d[54]),"=f"(d[55]),"=f"(d[56]),"=f"(d[57]),"=f"(d[58]),"=f"(d[59]),"=f"(d[60]),"=f"(d[61]),"=f"(d[62]),"=f"(d[63])
        : "r"(a0), "r"(a1), "r"(a2), "r"(a3), "r"(bb), "n"(BO), "n"(BH));
}
template <uint32_t AO, uint32_t BO, uint32_t BH> __device__ __forceinline__ void wg_ss64t(float (&d)[32], uint32_t ab, uint32_t bb) {
    asm volatile("{\n.reg .b64 da, db;\n.reg .b32 ta, tb, th, ah;\nadd.u32 ta, %32, %34;\nadd.u32 tb, %33, %35;\nmov.b32 th, %36;\nmov.b32 ah, 0x40000040;\nmov.b64 da, {ta, ah};\nmov.b64 db, {tb, th};\n"
        "wgmma.mma_async.sync.aligned.m64n64k16.f32.bf16.bf16 {%0,%1,%2,%3,%4,%5,%6,%7,%8,%9,%10,%11,%12,%13,%14,%15,%16,%17,%18,%19,%20,%21,%22,%23,%24,%25,%26,%27,%28,%29,%30,%31}, da, db, 1, 1, 1, 1, 1;\n}\n"
        : "+f"(d[0]),"+f"(d[1]),"+f"(d[2]),"+f"(d[3]),"+f"(d[4]),"+f"(d[5]),"+f"(d[6]),"+f"(d[7]),"+f"(d[8]),"+f"(d[9]),"+f"(d[10]),"+f"(d[11]),"+f"(d[12]),"+f"(d[13]),"+f"(d[14]),"+f"(d[15]),"+f"(d[16]),"+f"(d[17]),"+f"(d[18]),"+f"(d[19]),"+f"(d[20]),"+f"(d[21]),"+f"(d[22]),"+f"(d[23]),"+f"(d[24]),"+f"(d[25]),"+f"(d[26]),"+f"(d[27]),"+f"(d[28]),"+f"(d[29]),"+f"(d[30]),"+f"(d[31])
        : "r"(ab), "r"(bb), "n"(AO), "n"(BO), "n"(BH));
}
template <uint32_t AO, uint32_t BO, uint32_t BH> __device__ __forceinline__ void wg_ss64t_z(float (&d)[32], uint32_t ab, uint32_t bb) {
    asm volatile("{\n.reg .b64 da, db;\n.reg .b32 ta, tb, th, ah;\nadd.u32 ta, %32, %34;\nadd.u32 tb, %33, %35;\nmov.b32 th, %36;\nmov.b32 ah, 0x40000040;\nmov.b64 da, {ta, ah};\nmov.b64 db, {tb, th};\n"
        "wgmma.mma_async.sync.aligned.m64n64k16.f32.bf16.bf16 {%0,%1,%2,%3,%4,%5,%6,%7,%8,%9,%10,%11,%12,%13,%14,%15,%16,%17,%18,%19,%20,%21,%22,%23,%24,%25,%26,%27,%28,%29,%30,%31}, da, db, 0, 1, 1, 1, 1;\n}\n"
        : "=f"(d[0]),"=f"(d[1]),"=f"(d[2]),"=f"(d[3]),"=f"(d[4]),"=f"(d[5]),"=f"(d[6]),"=f"(d[7]),"=f"(d[8]),"=f"(d[9]),"=f"(d[10]),"=f"(d[11]),"=f"(d[12]),"=f"(d[13]),"=f"(d[14]),"=f"(d[15]),"=f"(d[16]),"=f"(d[17]),"=f"(d[18]),"=f"(d[19]),"=f"(d[20]),"=f"(d[21]),"=f"(d[22]),"=f"(d[23]),"=f"(d[24]),"=f"(d[25]),"=f"(d[26]),"=f"(d[27]),"=f"(d[28]),"=f"(d[29]),"=f"(d[30]),"=f"(d[31])
        : "r"(ab), "r"(bb), "n"(AO), "n"(BO), "n"(BH));
}
template <uint32_t AO, uint32_t BO, uint32_t BH> __device__ __forceinline__ void wg_ss8t(float (&d)[4], uint32_t ab, uint32_t bb) {
    asm volatile("{\n.reg .b64 da, db;\n.reg .b32 ta, tb, th, ah;\nadd.u32 ta, %4, %6;\nadd.u32 tb, %5, %7;\nmov.b32 th, %8;\nmov.b32 ah, 0x40000040;\nmov.b64 da, {ta, ah};\nmov.b64 db, {tb, th};\n"
        "wgmma.mma_async.sync.aligned.m64n8k16.f32.bf16.bf16 {%0,%1,%2,%3}, da, db, 1, 1, 1, 1, 0;\n}\n"
        : "+f"(d[0]),"+f"(d[1]),"+f"(d[2]),"+f"(d[3])
        : "r"(ab), "r"(bb), "n"(AO), "n"(BO), "n"(BH));
}
template <uint32_t AO, uint32_t BO, uint32_t BH> __device__ __forceinline__ void wg_ss8t_z(float (&d)[4], uint32_t ab, uint32_t bb) {
    asm volatile("{\n.reg .b64 da, db;\n.reg .b32 ta, tb, th, ah;\nadd.u32 ta, %4, %6;\nadd.u32 tb, %5, %7;\nmov.b32 th, %8;\nmov.b32 ah, 0x40000040;\nmov.b64 da, {ta, ah};\nmov.b64 db, {tb, th};\n"
        "wgmma.mma_async.sync.aligned.m64n8k16.f32.bf16.bf16 {%0,%1,%2,%3}, da, db, 0, 1, 1, 1, 0;\n}\n"
        : "=f"(d[0]),"=f"(d[1]),"=f"(d[2]),"=f"(d[3])
        : "r"(ab), "r"(bb), "n"(AO), "n"(BO), "n"(BH));
}
template <uint32_t BO, uint32_t BH> __device__ __forceinline__ void wg_rs24_z(float (&d)[12], uint32_t a0, uint32_t a1, uint32_t a2, uint32_t a3, uint32_t bb) {
    asm volatile("{\n.reg .b64 db;\n.reg .b32 tb, th;\nadd.u32 tb, %16, %17;\nmov.b32 th, %18;\nmov.b64 db, {tb, th};\n"
        "wgmma.mma_async.sync.aligned.m64n24k16.f32.bf16.bf16 {%0,%1,%2,%3,%4,%5,%6,%7,%8,%9,%10,%11}, {%12,%13,%14,%15}, db, 0, 1, 1, 0;\n}\n"
        : "=f"(d[0]),"=f"(d[1]),"=f"(d[2]),"=f"(d[3]),"=f"(d[4]),"=f"(d[5]),"=f"(d[6]),"=f"(d[7]),"=f"(d[8]),"=f"(d[9]),"=f"(d[10]),"=f"(d[11])
        : "r"(a0), "r"(a1), "r"(a2), "r"(a3), "r"(bb), "n"(BO), "n"(BH));
}

constexpr uint32_t DH128 = 64u | 0x40000000u;
constexpr uint32_t DH64 = 32u | 0x80000000u;
constexpr uint32_t LBO4K = (4096u >> 4) << 16, LBO8K = (8192u >> 4) << 16, LBO1 = 1u << 16;

template <uint32_t AO, uint32_t BO, bool SW64, bool FIRST> __device__ __forceinline__ void stage_ss(float (&acc)[64], uint32_t ab, uint32_t bb) {
    constexpr uint32_t KS = SW64 ? 64 : 128, BH = SW64 ? DH64 : DH128, B0 = BO + (SW64 ? LBO4K : LBO8K);
    wg_fence();
    if (FIRST) wg_ss128_z<AO, B0, BH>(acc, ab, bb); else wg_ss128<AO, B0, BH>(acc, ab, bb);
    wg_ss128<AO + 2, B0 + KS, BH>(acc, ab, bb);
    wg_ss128<AO + 4, B0 + 2 * KS, BH>(acc, ab, bb);
    wg_ss128<AO + 6, B0 + 3 * KS, BH>(acc, ab, bb);
    wg_commit();
}
template <uint32_t BO, bool FIRST> __device__ __forceinline__ void stage_rs(float (&acc)[64], const uint32_t (&f)[16], uint32_t bb) {
    wg_fence();
    if (FIRST) wg_rs128_z<BO + LBO8K, DH128>(acc, f[0], f[1], f[2], f[3], bb); else wg_rs128<BO + LBO8K, DH128>(acc, f[0], f[1], f[2], f[3], bb);
    wg_rs128<BO + LBO8K + 128, DH128>(acc, f[4], f[5], f[6], f[7], bb);
    wg_rs128<BO + LBO8K + 256, DH128>(acc, f[8], f[9], f[10], f[11], bb);
    wg_rs128<BO + LBO8K + 384, DH128>(acc, f[12], f[13], f[14], f[15], bb);
    wg_commit();
}

template <int N> __device__ __forceinline__ void stash(uint32_t base, uint32_t sw, const uint32_t (&f)[N]) {
#pragma unroll
    for (int t = 0; t < N / 4; t++) stsm4(base + ((sw ^ (2 * t)) << 4), f[4 * t], f[4 * t + 1], f[4 * t + 2], f[4 * t + 3]);
}

template <int V0, int V1, int N> __device__ __forceinline__ void send_frag(const uint32_t (&f)[N], uint4* p, uint32_t tag) {
#pragma unroll
    for (int v = V0; v < V1; v++) st_pkt(p + v * 32, (f[4 * v] & ~1u) | tag, f[4 * v + 1], f[4 * v + 2], f[4 * v + 3]);
}
template <int V0, int V1, int N> __device__ __forceinline__ void send_h(const uint32_t (&f)[N], uint4* p) {
#pragma unroll
    for (int v = V0; v < V1; v++) {
        const int h = v >> 1, hi = v & 1;
        asm volatile("st.global.v4.u32 [%0], {%1,%2,%3,%4};" :: "l"(p + 4 * h + 64 * hi),
                     "r"(f[8 * h + hi]), "r"(f[8 * h + 2 + hi]), "r"(f[8 * h + 4 + hi]), "r"(f[8 * h + 6 + hi]) : "memory");
    }
}
template <int O, int N, int M> __device__ __forceinline__ void pack_sub(uint32_t (&f)[N], const float (&acc)[M]) {
#pragma unroll
    for (int i = 0; i < N; i++) f[i] = keep(pack2(acc[O + 2 * i], acc[O + 2 * i + 1]));
}
template <int N> __device__ __forceinline__ void recv_issue(uint32_t (&q)[N], const uint4* p) {
#pragma unroll
    for (int v = 0; v < N / 4; v++) ld_pkt(p + v * 32, q[4 * v], q[4 * v + 1], q[4 * v + 2], q[4 * v + 3]);
}
template <int N> __device__ __forceinline__ void lds_pkts(uint32_t (&q)[N], uint32_t a) {
#pragma unroll
    for (int v = 0; v < N / 4; v++)
        asm volatile("ld.shared.v4.u32 {%0,%1,%2,%3}, [%4];" : "=r"(q[4 * v]), "=r"(q[4 * v + 1]), "=r"(q[4 * v + 2]), "=r"(q[4 * v + 3]) : "r"(a + v * 512) : "memory");
}
template <int N> __device__ __forceinline__ bool pkts_ok(const uint32_t (&q)[N], uint32_t tag) {
    uint32_t bad = 0;
#pragma unroll
    for (int v = 0; v < N / 4; v++) bad |= q[4 * v] ^ tag;
    return __all_sync(0xffffffffu, (bad & 1u) == 0);
}
template <int N> __device__ __forceinline__ uint32_t recv_retry(uint32_t (&q)[N], const uint4* src, uint32_t dst, uint32_t bar, uint32_t& ph, uint32_t tag) {
    uint32_t it = 0;
    while (!pkts_ok(q, tag) && ++it < SPIN_GLOBAL) {
        if ((threadIdx.x & 31) == 0) bulk_in(dst, src, N * 128, bar);
        mbar_wait(bar, ph);
        ph ^= 1;
        lds_pkts(q, dst + (threadIdx.x & 31) * 16);
    }
    return it;
}
template <int N> __device__ __forceinline__ uint32_t recv_check(uint32_t (&q)[N], const uint4* p, uint32_t tag) {
    uint32_t it = 0;
    while (true) {
        uint32_t bad = 0;
#pragma unroll
        for (int v = 0; v < N / 4; v++) bad |= q[4 * v] ^ tag;
        if (__all_sync(0xffffffffu, (bad & 1u) == 0) || ++it > SPIN_GLOBAL) break;
        recv_issue(q, p);
    }
    return it;
}
}

__global__ void __launch_bounds__(384, 1)
fused_kernel(const __grid_constant__ Maps maps, const __nv_bfloat16* __restrict__ xg, const __nv_bfloat16* __restrict__ gate_w,
             const char* __restrict__ pf_qkv, const char* __restrict__ pf_g, const char* __restrict__ pf_u,
             const char* __restrict__ pf_d, const char* __restrict__ pf_o, __nv_bfloat16* __restrict__ out) {
    extern __shared__ __align__(1024) uint8_t smem_raw[];
    const uint32_t sb = (uint32_t)__cvta_generic_to_shared(smem_raw);
    const int tid = threadIdx.x, lane = tid & 31;
    const int warp = __shfl_sync(0xffffffffu, tid >> 5, 0);
#define MB(i) ((blockIdx.x >> ((MAPV >> (4 * (i))) & 15)) & 1)
    const int j = MB(0) | (MB(1) << 1) | (MB(2) << 2), r = MB(3) | (MB(4) << 1) | (MB(5) << 2) | (MB(6) << 3);
    const uint32_t rank = blockIdx.x & 1;

    const int fc = 448 * (j >> 1) + 256 * (j & 1);
    if (warp == 0) { TSG(0, 30); TS(0, 0); }
    if (tid == 256) {
        mbar_init(sb + B_XFULL, 1); mbar_init(sb + B_FULL, 1); mbar_init(sb + B_FULL + 8, 1); mbar_init(sb + B_XFULL + 8, 1); mbar_init(sb + B_FULL + 16, 1);
        asm volatile("fence.mbarrier_init.release.cluster;" ::: "memory");
        TS2(0);
        mbar_expect(sb + B_FULL, 16384);
        tmaw3(sb + OFF_RING, &maps.kv, 64 * j, 0, 1, sb + B_FULL);
        mbar_expect(sb + B_XFULL, 16384);
        tma2(sb + OFF_X, &maps.x, 0, r * 128, sb + B_XFULL);
        TS2(1);
        mbar_expect(sb + B_FULL + 8, 16384);
        tmaw3(sb + OFF_RING + 16384, &maps.gu, fc, 0, 0, sb + B_FULL + 8);
#define PRO_MORE() do { mbar_expect(sb + B_XFULL + 8, 16384); tma2(sb + OFF_X + 16384, &maps.x, 64, r * 128, sb + B_XFULL + 8); TS2(2); \
        mbar_expect(sb + B_FULL + 16, 16384); tmaw3(sb + OFF_RING + 2 * 16384, &maps.kv, 64 * j, 64, 1, sb + B_FULL + 16); } while (0)
        if (PRO5) PRO_MORE();
    } else if (tid == 352) {
        for (int i = 0; i < 5; i++) { if (i > 2) mbar_init(sb + B_FULL + 8 * i, 1); mbar_init(sb + B_EMPTY + 8 * i, MC ? 4 : 2); }
        for (int i = 2; i < 9; i++) mbar_init(sb + B_XFULL + 8 * i, 1);
        asm volatile("fence.mbarrier_init.release.cluster;" ::: "memory");
    } else if (tid == 288) {
        for (int i = 0; i < 3; i++) mbar_init(sb + B_HSENT + 8 * i, 8);
        for (int i = 0; i < 4; i++) { mbar_init(sb + B_EFULL + 8 * i, 1); mbar_init(sb + B_EEMPTY + 8 * i, MC ? 4 : 2); }
        mbar_init(sb + B_XFREE, 2); mbar_init(sb + B_XFREE + 8, 2); mbar_init(sb + B_XFREE + 16, 2);
        for (int i = 0; i < 8; i++) mbar_init(sb + B_WARP + 8 * i, 1);
        mbar_init(sb + B_AHEAD, 1); mbar_init(sb + B_PART, 1); mbar_init(sb + B_LAST, 1); mbar_init(sb + B_RFREE, 2);
        if (CL) mbar_expect(sb + B_LAST, 16384); mbar_init(sb + B_GRDY, 1); mbar_init(sb + B_KVDONE, 8); mbar_init(sb + B_KVRDY, 2);
        asm volatile("fence.mbarrier_init.release.cluster;" ::: "memory");
    } else if (warp == 10 && lane < 10) {
        asm volatile("prefetch.tensormap [%0];" :: "l"(&maps.x + lane) : "memory");
    }
    __syncthreads();
    if (CL) asm volatile("barrier.cluster.arrive.relaxed.aligned;" ::: "memory");

    if (warp >= 8) {
        asm volatile("setmaxnreg.dec.sync.aligned.u32 56;");
        if (warp == 8) {
            if (lane == 0) {
                int slot = 3, ph = 1;
                uint32_t full, dst;
                if (!PRO5) PRO_MORE();
                mbar_expect(sb + B_XFULL + 16, 16384); tma2(sb + OFF_X + 2 * 16384, &maps.x, 128, r * 128, sb + B_XFULL + 16);
#define P_BEGIN(S, BYTES) full = sb + B_FULL + 8 * slot; dst = sb + OFF_RING + slot * 16384; \
                mbar_wait(sb + B_EMPTY + 8 * slot, ph); TS2(S); mbar_expect(full, BYTES); if (!MC || (((S) ^ rank) & 1) == 0)
#define P_END() if (++slot == 5) { slot = 0; ph ^= 1; }
                for (int s = 3; s < 16; s++) {
                    const int kb = (int)(0x7654763542312100ull >> (4 * s)) & 15;
                    P_BEGIN(s, 16384) {
                        if ((0x0DADu >> s) & 1) tmaw3(dst, &maps.kv, 64 * j, 64 * kb, 1, full);
                        else tmaw3(dst, &maps.gu, fc, 64 * kb, 0, full);
                    }
                    const int xb = (int)(0x0000000765403210ull >> (4 * s)) & 15;
                    if (xb) { mbar_expect(sb + B_XFULL + 8 * xb, 16384); tma2(sb + OFF_X + xb * 16384, &maps.x, 64 * xb, r * 128, sb + B_XFULL + 8 * xb); }
                    P_END()
                }
                for (int s = 0; s < 24; s++) {
                    P_BEGIN(16 + s, 16384) {
                        if (s < 8) {
                            tmaw3(dst, &maps.q64, 0, 64 * s, 2 * j, full);
                            tmaw3(dst + 8192, &maps.gu64, 224 * (j & 6) + 192 + 32 * (j & 1), 64 * s, 0, full);
                        } else {
                            tmaw3(dst, &maps.gu, fc + 64 * (s >> 3), 64 * (s & 7), 0, full);
                        }
                    }
                    P_END()
                }
                const int p = j >> 1;
#pragma unroll 1
                for (int t = 0; t < 18; t++) {
                    const int q = t >= 9, sl = (int)(0x846352107ull >> (4 * (t - 9 * q))) & 15;
                    const int u = (int)((q ? 0x432186758ull : 0x327064105ull) >> (4 * (t - 9 * q))) & 15;
                    const int cw = (j & 1) * 4 + ((p & 2) ^ ((t == 5 || t > 9) ? 0 : 2)), cc = 64 * cw;
                    if (sl < 5) {
                        full = sb + B_FULL + 8 * sl; dst = sb + OFF_RING + sl * 16384;
                        mbar_wait(sb + B_EMPTY + 8 * sl, q ^ 1);
                    } else {
                        full = sb + B_EFULL + 8 * (sl - 5); dst = sb + OFF_X + (sl == 7 ? 8 : sl == 8 ? 7 : sl) * 16384;
                        mbar_wait(sb + B_EEMPTY + 8 * (sl - 5), q);
                    }
                    TS2(40 + t);
                    mbar_expect(full, 16384);
                    if (!MC || ((t ^ rank) & 1) == 0) {
                        if (u > 4) {
                            const int js = u > 6 ? j ^ 1 : j;
                            tmaw3(dst, (u & 1) ? &maps.wow : &maps.wdw, 0, (u & 1) ? 64 * js : 448 * p + 256 * (js & 1) + 128, cw, full);
                        } else {
                            const int g = 14 * p + (u == 4 ? 6 : 8 * (u & 1) + (u & 2));
                            tmaw5(dst, &maps.wdp, cc, g, full); tmaw5(dst + 8192, &maps.wdp, cc + 64, g, full);
                        }
                    }
                }
            }
        } else if (warp < 11) {
            const int hx = warp - 9;
            uint32_t epoch;
            asm volatile("ld.relaxed.gpu.global.u32 %0, [%1];" : "=r"(epoch) : "l"(g_epoch + blockIdx.x) : "memory");
            {
                const uint4* xr = (const uint4*)(xg + (size_t)(r * 128 + j * 16 + hx * 8) * kD) + lane;
                const uint4 wa = __ldg((const uint4*)gate_w + lane), wb = __ldg((const uint4*)gate_w + 32 + lane);
                const uint32_t tag = (epoch + 1) & 1;
                uint4* gp = g_gx + r * 32;
                if (lane < 2) st_pkt(gp + j * 4 + hx * 2 + lane, tag ^ 1, 0, 0, 0);
                float s[8];
                if (GDELAY) mbar_wait(sb + B_XFULL, 0);
#pragma unroll
                for (int i0 = 0; i0 < 8; i0 += 4) {
                    uint4 va[4], vb[4];
#pragma unroll
                    for (int i = 0; i < 4; i++) { va[i] = __ldg(xr + (i0 + i) * 64); vb[i] = __ldg(xr + (i0 + i) * 64 + 32); }
#pragma unroll
                    for (int i = 0; i < 4; i++) {
                        float t0 = bf_lo(va[i].x) * bf_lo(wa.x), t1 = bf_hi(va[i].x) * bf_hi(wa.x);
                        t0 = fmaf(bf_lo(va[i].y), bf_lo(wa.y), t0); t1 = fmaf(bf_hi(va[i].y), bf_hi(wa.y), t1);
                        t0 = fmaf(bf_lo(va[i].z), bf_lo(wa.z), t0); t1 = fmaf(bf_hi(va[i].z), bf_hi(wa.z), t1);
                        t0 = fmaf(bf_lo(va[i].w), bf_lo(wa.w), t0); t1 = fmaf(bf_hi(va[i].w), bf_hi(wa.w), t1);
                        t0 = fmaf(bf_lo(vb[i].x), bf_lo(wb.x), t0); t1 = fmaf(bf_hi(vb[i].x), bf_hi(wb.x), t1);
                        t0 = fmaf(bf_lo(vb[i].y), bf_lo(wb.y), t0); t1 = fmaf(bf_hi(vb[i].y), bf_hi(wb.y), t1);
                        t0 = fmaf(bf_lo(vb[i].z), bf_lo(wb.z), t0); t1 = fmaf(bf_hi(vb[i].z), bf_hi(wb.z), t1);
                        t0 = fmaf(bf_lo(vb[i].w), bf_lo(wb.w), t0); t1 = fmaf(bf_hi(vb[i].w), bf_hi(wb.w), t1);
                        s[i0 + i] = t0 + t1;
                    }
                }
#pragma unroll
                for (int i = 0; i < 8; i++) {
#pragma unroll
                    for (int o = 16; o; o >>= 1) s[i] += __shfl_xor_sync(0xffffffffu, s[i], o);
                    s[i] = 1.f / (1.f + __expf(-s[i]));
                }
                if (lane < 2) {
                    const float v0 = lane ? s[4] : s[0], v1 = lane ? s[5] : s[1], v2 = lane ? s[6] : s[2], v3 = lane ? s[7] : s[3];
                    st_pkt(gp + j * 4 + hx * 2 + lane, (__float_as_uint(v0) & ~1u) | tag, __float_as_uint(v1), __float_as_uint(v2), __float_as_uint(v3));
                }
                if (hx == 1) {
                    asm volatile("st.shared.u32 [%0], %1;" :: "r"(sb + OFF_ONES + lane * 4), "r"(0x3f803f80u) : "memory");
                    asm volatile("fence.proxy.async.shared::cta;" ::: "memory");
                }
                asm volatile("bar.sync 3, 96;" ::: "memory");
                if (hx == 0) {
                    uint32_t q[4];
                    recv_issue(q, gp + lane);
                    recv_check(q, gp + lane, tag);
                    asm volatile("st.shared.v4.u32 [%0], {%1,%2,%3,%4};" :: "r"(sb + OFF_G + lane * 16), "r"(q[0]), "r"(q[1]), "r"(q[2]), "r"(q[3]) : "memory");
                    if (lane == 0) {
                        asm volatile("st.shared.u32 [%0], %1;" :: "r"(sb + OFF_EPOCH), "r"(epoch) : "memory");
                        g_epoch[blockIdx.x] = epoch + 1;
                    }
                    __syncwarp();
                    if (lane == 0) mbar_arrive(sb + B_GRDY);
                } else {
                    if (r == 0) {
                        float4* zp = (float4*)(g_kvacc + (((epoch & 1) ^ 1) * 8 + j) * 4 * 272);
                        for (int i = lane; i < 272; i += 32) zp[i] = make_float4(0.f, 0.f, 0.f, 0.f);
                    }
                }
            }
            TS(2 + hx, 1);
#define PUBLISH_H(B) do { mbar_wait(sb + B_HSENT + 8 * (B), 0); if (lane == 0) { \
                asm volatile("st.release.gpu.global.u32 [%0], %1;" :: "l"(g_hflag + (r * 8 + j) * 8 + (B)), "r"(epoch + 1) : "memory"); } __syncwarp(); } while (0)
            if (hx == 1) {
#pragma unroll 1
                for (int b = 0; b < 3; b++) { PUBLISH_H(b); TS(3, 5 + b); }
            } else {
                const float* accp = g_kvacc + ((epoch & 1) * 8 + j) * 4 * 272;
                unsigned* cnt = g_kvcnt + j * 32;
                mbar_wait(sb + B_KVDONE, 0);
                TS(2, 5);
                if (lane == 0) asm volatile("red.release.gpu.global.add.u32 [%0], 1;" :: "l"(cnt) : "memory");
                __syncwarp();
                TS(2, 2);
                {
                    const unsigned target = 16u * (epoch + 1);
                    uint32_t it = 0, v;
                    do {
                        asm volatile("ld.acquire.gpu.global.u32 %0, [%1];" : "=r"(v) : "l"(cnt) : "memory");
                    } while ((int)(v - target) < 0 && ++it < SPIN_GLOBAL);
                }
                TS(2, 3);
#pragma unroll
                for (int h = 0; h < 4; h++) {
                    const float4 d0 = __ldcg((const float4*)(accp + h * 272) + lane);
                    const float4 d1 = __ldcg((const float4*)(accp + h * 272 + 128) + lane);
                    const float4 zz = __ldcg((const float4*)(accp + h * 272 + 256) + (lane & 3));
                    const uint32_t ba = sb + OFF_STG + h * 768 + lane * 4;
                    asm volatile("st.shared.u32 [%0], %1;" :: "r"(ba), "r"(pack2(d0.x, d0.y)) : "memory");
                    asm volatile("st.shared.u32 [%0], %1;" :: "r"(ba + 128), "r"(pack2(d1.x, d1.y)) : "memory");
                    asm volatile("st.shared.u32 [%0], %1;" :: "r"(ba + 256), "r"(pack2(d0.z, d0.w)) : "memory");
                    asm volatile("st.shared.u32 [%0], %1;" :: "r"(ba + 384), "r"(pack2(d1.z, d1.w)) : "memory");
                    asm volatile("st.shared.u32 [%0], %1;" :: "r"(ba + 512), "r"(pack2(zz.x, zz.z)) : "memory");
                    asm volatile("st.shared.u32 [%0], %1;" :: "r"(ba + 640), "r"(pack2(zz.y, zz.w)) : "memory");
                }
                asm volatile("fence.proxy.async.shared::cta;" ::: "memory");
                __syncwarp();
                if (lane == 0) mbar_arrive(sb + B_KVRDY);
                TS(2, 4);
            }
        } else {
            uint32_t epoch;
            asm volatile("ld.relaxed.gpu.global.u32 %0, [%1];" : "=r"(epoch) : "l"(g_epoch + blockIdx.x) : "memory");
            asm volatile("bar.arrive 3, 96;" :: "r"(epoch) : "memory");
            const int b = blockIdx.x, p = j >> 1;
            mbar_wait(sb + B_XFULL, 0);
            if (PF0 && r >= PF0) {
                const int row = r * 32 + lane;
                asm volatile("prefetch.global.L2 [%0];" :: "l"(pf_qkv + row * 3072 + 1024 + j * 128));
                asm volatile("prefetch.global.L2 [%0];" :: "l"(pf_qkv + row * 3072 + 2048 + j * 128));
                asm volatile("prefetch.global.L2 [%0];" :: "l"(pf_g + row * 3584 + fc * 2));
                asm volatile("prefetch.global.L2 [%0];" :: "l"(pf_u + row * 3584 + fc * 2));
            }
#pragma unroll 1
            for (int kb = 1; kb < 8; kb++) {
                mbar_wait(sb + B_XFULL + 8 * kb, 0);
                const char* base = kb < 3 ? pf_g : kb < 5 ? pf_u : kb == 5 ? pf_qkv : pf_d;
                const int off = kb == 5 ? b * 12288 : b * 14336 + ((kb < 5 ? kb - 1 : kb) & 1) * 7168;
                if (kb == 5) {
                    asm volatile("prefetch.global.L2 [%0];" :: "l"(base + off + (lane >> 3) * 3072 + (lane & 7) * 128));
                } else {
                    asm volatile("prefetch.global.L2 [%0];" :: "l"(base + off + lane * 128));
                    if (lane < 24) asm volatile("prefetch.global.L2 [%0];" :: "l"(base + off + 4096 + lane * 128));
                }
                if (kb == 7) asm volatile("prefetch.global.L2 [%0];" :: "l"(pf_o + b * 4096 + lane * 128));
            }
            {
                uint4* mb = g_part + (size_t)(r * 2 + (j & 1)) * 16384 + (((p ^ 1) * 4 + p) << 10) + lane;
#pragma unroll 1
                for (int i = 0; i < ((NOPRE || CL) ? 0 : 32); i++) { st_pkt(mb + i * 32, epoch & 1, 0, 0, 0); __nanosleep(40); }
                __syncwarp();
                if (lane == 0) mbar_arrive(sb + B_KVRDY);
            }
            {
                const uint32_t want = epoch + 1;
                const int hrow = (r * 4 + p) * 5 * 128;
                const unsigned* fl = g_hflag + (r * 8 + (j & 6)) * 8 + (lane & 15);
                uint32_t it = 0;
                int i = 0;
                mbar_wait(sb + B_HSENT + 8, 0);
#pragma unroll 1
                while (i < 3 && ++it < SPIN_GLOBAL) {
                    uint32_t v;
                    asm volatile("ld.acquire.gpu.global.u32 %0, [%1];" : "=r"(v) : "l"(fl) : "memory");
                    const uint32_t rdy = __ballot_sync(0xffffffffu, v == want);
#pragma unroll 1
                    while (i < 3 && ((rdy >> i) & 0x101u) == 0x101u) {
                        if (i < 2) mbar_wait(sb + B_XFREE + 8 * i, 0);
                        if (lane == 0) {
                            const int pc = (6 - 2 * i) % 6;
                            asm volatile("fence.proxy.async.global;" ::: "memory");
                            TS2(140 + i);
                            mbar_expect(sb + B_XFULL + 8 * pc, i != 1 ? 32768 : 16384);
                            tma2(sb + OFF_X + pc * 16384, i != 1 ? &maps.hx2 : &maps.hx, 0, hrow + pc * 128, sb + B_XFULL + 8 * pc);
                        }
                        i++;
                    }
                }
            }
        }
        if (CL) asm volatile("barrier.cluster.wait;" ::: "memory");
    } else {
        asm volatile("setmaxnreg.inc.sync.aligned.u32 224;");
        const int wg = warp >> 2;
        const bool elect = (tid & 127) == 0;
        const uint32_t sbd = (sb & 0x3FFFFu) >> 4, xlo = (sbd + wg * 512) | LBO1;
        auto release = [&](uint32_t bar) {
            if (elect) {
                mbar_arrive(sb + bar);
            }
        };
#define S_SL(S) ((S) < 40 ? (S) % 5 : (int)((0x846352107ull >> (4 * (((S) - 40) % 9))) & 15))
#define S_WAIT(S) do { mbar_wait(sb + (S_SL(S) < 5 ? B_FULL + 8 * S_SL(S) : B_EFULL + 8 * (S_SL(S) - 5)), (S) < 40 ? ((S) / 5) & 1 : (S) >= 49); \
            if (PROF && tid == 0) TS2(64 + (S)); } while (0)
#define S_B(S) (S_SL(S) < 5 ? OFF_RING / 16 + S_SL(S) * 1024 : (S_SL(S) == 7 ? 8 : S_SL(S) == 8 ? 7 : S_SL(S)) * 1024)
#define S_REL(S) do { if ((S) < 49) release(S_SL(S) < 5 ? B_EMPTY + 8 * S_SL(S) : B_EEMPTY + 8 * (S_SL(S) - 5)); } while (0)
#define G1(S, acc, SW, KB) stage_ss<(KB) * 1024, S_B(S), SW, (KB) == 0>(acc, xlo, sbd)
#define RET(S) do { S_WAIT((S) + 1); wg_wait<1>(); S_REL((S) - 1); } while (0)
#define RET2(S) do { S_WAIT((S) + 1); wg_wait<2>(); S_REL((S) - 1); } while (0)
#define SCHED() mbar_wait(sb + B_XFULL + 8 * 7, 0)
#define A2_SYNC() do { asm volatile("fence.proxy.async.shared::cta;" ::: "memory"); asm volatile("bar.sync %0, 128;" :: "r"(wg + 1) : "memory"); } while (0)
#define H_EPI(acc, F, I0, I1, OG, OU) _Pragma("unroll") for (int i = (I0); i < (I1); i++) \
            F[i] = keep(hmul2(pack2(acc[(OG) + 2 * i] * acc[(OU) + 2 * i], acc[(OG) + 2 * i + 1] * acc[(OU) + 2 * i + 1]), (i & 1) ? m_hi : m_lo))
#define PHI(acc, F, I0, I1) _Pragma("unroll") for (int i = (I0); i < (I1); i++) F[i] = keep(phi2(acc[2 * i], acc[2 * i + 1]))

        float a0[64], b0[64], a1[64], a2_[64], a3[64];
        mbar_wait(sb + B_XFULL, 0);
#define X_WAIT(KB) do { mbar_wait(sb + B_XFULL + 8 * (KB), 0); if (PROF && tid == 0) TS2(128 + (KB)); } while (0)
        S_WAIT(0); G1(0, b0, false, 0);
        if ((warp & 3) == 0) TS(wg, 1);
        S_WAIT(1); G1(1, a0, false, 0); RET(1);
        X_WAIT(1); G1(2, b0, false, 1); RET(2);
        X_WAIT(2); G1(3, b0, false, 2); RET(3);
        G1(4, a0, false, 1); RET(4);
        X_WAIT(3); G1(5, b0, false, 3); RET(5);
        G1(6, a0, false, 2); RET(6);
        X_WAIT(4); G1(7, b0, false, 4); RET(7);
        X_WAIT(5); G1(8, b0, false, 5); RET(8);
        G1(9, a0, false, 3); RET(9);
        X_WAIT(6); G1(10, b0, false, 6); RET(10);
        X_WAIT(7); G1(11, b0, false, 7); RET(11);
        G1(12, a0, false, 4);
        const uint32_t lrow = ((lane & 7) + 8 * ((lane >> 3) & 1)) * 128;
        const uint32_t srow = (warp & 3) * 2048 + lrow;
        const uint32_t ssw = (lane >> 4) ^ (lane & 7);
        uint4* const hsend = g_hx + (size_t)((r * 4 + (j >> 1)) * 5 + (j & 1)) * 1024 + warp * 128 + (lane >> 2) * 8 + (lane & 3);
#define SENT_H(B) do { __syncwarp(); if (lane == 0) mbar_arrive(sb + B_HSENT + 8 * (B)); } while (0)
        uint32_t fh0[16], fh1[16], fh2[16], fh3[8], fo[16], pk[16], pv[16];
        float kv[32], zs[4];
        const uint32_t stg = sb + OFF_STG + wg * 8192, stl = stg + (warp & 1) * 2048 + lrow;
#define KV_ROUND(Z) do { A2_SYNC(); wg_fence(); \
            wg_ss64t##Z<8192 + 256, 8192, DH128>(kv, xlo, xlo); wg_ss64t<8192 + 384, 8192 + 128, DH128>(kv, xlo, xlo); \
            wg_ss8t##Z<8192, OFF_ONES / 16, 0>(zs, xlo, sbd); wg_ss8t<8192 + 128, OFF_ONES / 16, 0>(zs, xlo, sbd); wg_commit(); } while (0)
        wg_wait<1>(); S_REL(11);
        pin(b0);
        pack_sub<32>(pv, b0);
        S_WAIT(13);
        G1(13, a0, false, 5); SCHED(); if (!(warp & 2)) stash<16>(stl + 4096, ssw, pv); PHI(b0, pk, 0, 5); RET(13);
        G1(14, a0, false, 6); SCHED(); PHI(b0, pk, 5, 11); RET(14);
        G1(15, a0, false, 7); SCHED(); PHI(b0, pk, 11, 16); RET(15);
        if ((warp & 3) == 0) TS(wg, 2);

        G1(16, a1, true, 0); SCHED(); if (!(warp & 2)) stash<16>(stl, ssw, pk);
        mbar_wait(sb + B_GRDY, 0);
        float g_lo, g_hi;
        uint32_t tag;
        {
            const uint32_t ga = sb + OFF_G + (warp * 16 + (lane >> 2)) * 4;
            asm volatile("ld.shared.f32 %0, [%1];" : "=f"(g_lo) : "r"(ga) : "memory");
            asm volatile("ld.shared.f32 %0, [%1];" : "=f"(g_hi) : "r"(ga + 32) : "memory");
            asm volatile("ld.shared.u32 %0, [%1];" : "=r"(tag) : "r"(sb + OFF_EPOCH) : "memory");
        }
        float* const kvp = g_kvacc + (((tag & 1) * 8 + j) * 4 + (warp & 3)) * 272;
        tag = (tag + 1) & 1;
        const uint32_t m_lo = pack2(1.f - g_lo, 1.f - g_lo), m_hi = pack2(1.f - g_hi, 1.f - g_hi);
        RET(16);
        pin(a0);
        G1(17, a1, true, 1); SCHED(); H_EPI(a0, fh0, 0, 16, 0, 32); RET(17);
        G1(18, a1, true, 2); KV_ROUND(_z); RET2(18);
        G1(19, a1, true, 3); SCHED(); send_h<0, 1>(fh0, hsend); RET(19);
        G1(20, a1, true, 4); SCHED(); if (warp & 2) stash<16>(stl, ssw, pk); RET(20);
        G1(21, a1, true, 5); SCHED(); if (warp & 2) stash<16>(stl + 4096, ssw, pv); RET(21);
        G1(22, a1, true, 6); KV_ROUND(); RET2(22);
        G1(23, a1, true, 7); RET(23);
        pin(kv); pin(zs);
        if ((warp & 3) == 0) TS(wg, 3);

        G1(24, a2_, false, 0); SCHED();
#define KV_RED(W) do { asm volatile("red.global.add.v4.f32 [%0], {%1,%2,%3,%4};" :: "l"(kvp + lane * 4), "f"(kv[8 * W]), "f"(kv[8 * W + 1]), "f"(kv[8 * W + 2]), "f"(kv[8 * W + 3]) : "memory"); \
                       asm volatile("red.global.add.v4.f32 [%0], {%1,%2,%3,%4};" :: "l"(kvp + 128 + lane * 4), "f"(kv[8 * W + 4]), "f"(kv[8 * W + 5]), "f"(kv[8 * W + 6]), "f"(kv[8 * W + 7]) : "memory"); } while (0)
        if ((warp & 3) == 0) KV_RED(0); else if ((warp & 3) == 1) KV_RED(1); else if ((warp & 3) == 2) KV_RED(2); else KV_RED(3);
        if ((lane & 3) == 0) asm volatile("red.global.add.v2.f32 [%0], {%1,%2};" :: "l"(kvp + 256 + (lane >> 1)), "f"(zs[0]), "f"(zs[2]) : "memory");
        __syncwarp();
        if (lane == 0) mbar_arrive(sb + B_KVDONE);
        RET(24);
        pin(a1);
        G1(25, a2_, false, 1); SCHED(); send_h<1, 2>(fh0, hsend); H_EPI(a1, fh3, 0, 8, 32, 48); RET(25);
        G1(26, a2_, false, 2); SCHED(); send_h<2, 3>(fh0, hsend); PHI(a1, fo, 0, 3); RET(26);
        G1(27, a2_, false, 3); SCHED(); send_h<3, 4>(fh0, hsend); SENT_H(0); PHI(a1, fo, 3, 6); RET(27);
        G1(28, a2_, false, 4); SCHED(); send_h<0, 1>(fh3, hsend + 4 * 1024 - (j & 1) * 1020); PHI(a1, fo, 6, 9); RET(28);
        G1(29, a2_, false, 5); SCHED(); send_h<1, 2>(fh3, hsend + 4 * 1024 - (j & 1) * 1020); SENT_H(1); PHI(a1, fo, 9, 12); RET(29);
        G1(30, a2_, false, 6); SCHED(); PHI(a1, fo, 12, 16); RET(30);
        G1(31, a2_, false, 7); RET(31);
        if ((warp & 3) == 0) TS(wg, 4);

        float on[4][12];
#define O_SCALE(h) do { const float s_lo = __fdividef(g_lo, on[h][8] + 1e-6f), s_hi = __fdividef(g_hi, on[h][10] + 1e-6f); \
            const uint32_t sl_ = pack2(s_lo, s_lo), sh_ = pack2(s_hi, s_hi); \
            fo[4 * h] = keep(hmul2(pack2(on[h][0], on[h][1]), sl_)); fo[4 * h + 1] = keep(hmul2(pack2(on[h][2], on[h][3]), sh_)); \
            fo[4 * h + 2] = keep(hmul2(pack2(on[h][4], on[h][5]), sl_)); fo[4 * h + 3] = keep(hmul2(pack2(on[h][6], on[h][7]), sh_)); } while (0)
        uint4* const lsend = g_lx + (size_t)(r * 8 + j) * 2048 + warp * 128 + lane;
        const uint4* const lrecv = g_lx + (size_t)(r * 8 + (j ^ 1)) * 2048 + warp * 128 + lane;
        G1(32, a3, false, 0); RET(32);
        pin(a2_);
        G1(33, a3, false, 1); SCHED(); H_EPI(a2_, fh1, 0, 16, 0, 32); send_h<0, 1>(fh1, hsend + 2 * 1024); RET(33);
        G1(34, a3, false, 2); SCHED(); send_h<1, 3>(fh1, hsend + 2 * 1024); RET(34);
        if (elect) mbar_arrive(sb + B_XFREE);
        G1(35, a3, false, 3); SCHED(); send_h<3, 4>(fh1, hsend + 2 * 1024); SENT_H(2);
        if ((warp & 3) == 0) TS(wg, 5);
        mbar_wait(sb + B_KVRDY, 0);
        if ((warp & 3) == 0) TS(wg, 6);
        wg_fence();
#define O_MMA(h) wg_rs24_z<OFF_STG / 16 + (h) * 48 + (8u << 16), 16>(on[h], fo[4 * (h)], fo[4 * (h) + 1], fo[4 * (h) + 2], fo[4 * (h) + 3], sbd)
        O_MMA(0); O_MMA(1); O_MMA(2); O_MMA(3);
        wg_commit();
        RET2(35);
        G1(36, a3, false, 4); RET(36);
        pin(on[0]); pin(on[1]); pin(on[2]); pin(on[3]);
        release(B_EEMPTY + 16);
        G1(37, a3, false, 5); SCHED(); O_SCALE(0); O_SCALE(1); RET(37);
        if (elect) mbar_arrive(sb + B_XFREE + 8);
        G1(38, a3, false, 6); SCHED(); send_frag<0, 2>(fo, lsend, tag); O_SCALE(2); O_SCALE(3); RET(38);
        release(B_EEMPTY);
        G1(39, a3, false, 7); SCHED(); send_frag<2, 4>(fo, lsend, tag); RET(39);
        release(B_EEMPTY + 8);
        if ((warp & 3) == 0) TS(wg, 7);

#define G2S(S, acc, U) stage_ss<(U) * 1024, S_B(S), false, (S) == 45>(acc, xlo, sbd)
#define G2R(S, acc, F) stage_rs<S_B(S), (S) == 40>(acc, F, sbd)
#define H_WAIT(P) do { mbar_wait(sb + B_XFULL + 8 * (P), 1); if (PROF && tid == 0) TS2(150 + (P)); } while (0)
        const int p = j >> 1, pw = (p & 2) ^ 2;
        const bool own = wg == (p & 1);
        uint4* const pbase = g_part + (size_t)(r * 2 + (j & 1)) * 16384 + (warp & 3) * 256 + lane;

        float p1[64], p2[64];
        uint32_t po[16], ph2[16];
        G2R(40, p1, fo); RET(40);
        release(B_EEMPTY + 24);
        pin(a3);
        H_WAIT(0); G2S(41, p1, 0); SCHED(); H_EPI(a3, fh2, 0, 16, 0, 32); send_frag<0, 2>(fh2, lsend + 1024, tag); RET(41);
        G2S(42, p1, 1); SCHED(); recv_issue(po, lrecv); send_frag<2, 4>(fh2, lsend + 1024, tag); RET(42);
        H_WAIT(4); G2S(43, p1, 4); RET(43);
        G2R(44, p1, fh2); RET(44);
        G2S(45, p2, 0); SCHED(); if (PROF && tid == 0) TS2(160); CNT(170, recv_check(po, lrecv, tag)); if (PROF && tid == 0) TS2(161); recv_issue(ph2, lrecv + 1024); RET(45);
        G2R(46, p1, po); RET(46);
        if (CL) {
            asm volatile("barrier.cluster.wait.aligned;" ::: "memory");
            if (elect) mbar_arrive_cta(sb + B_RFREE, (blockIdx.x & 1) ^ 1);
        }
        H_WAIT(2); G2S(47, p1, 2); RET(47);
        G2S(48, p1, 3); SCHED(); if (PROF && tid == 0) TS2(162); CNT(171, recv_check(ph2, lrecv + 1024, tag)); if (PROF && tid == 0) TS2(163); RET(48);
        G2R(49, p1, ph2); RET(49);
        if ((warp & 3) == 0) TS(wg, 8);
        uint32_t sp[32], qa[16], qb[16], qc[16];
        uint4* const s1 = pbase + (((pw + wg) * 4 + p) << 10);
        G2R(50, p2, fo); RET(50);
        pin(p1);
        const uint4* ra = pbase + ((p * 4 + pw) << 10);
        const uint4* rc = pbase + ((p * 4 + (p ^ 1)) << 10);
        G2R(51, p2, po); SCHED(); pack_sub<0>(sp, p1); send_frag<0, 4>(sp, s1, tag); RET(51);
        G2R(52, p2, fh2); SCHED(); send_frag<4, 8>(sp, s1, tag); RET(52);
        if (elect) mbar_arrive(sb + B_XFREE + 16);
        if (own) mbar_wait(sb + B_AHEAD, 0);
        G2R(53, p2, ph2); RET(53);
        G2S(54, p2, 1); RET(54);
        G2S(55, p2, 2); RET(55);
        G2S(56, p2, 3); RET(56);
        G2S(57, p2, 4); SCHED();
        if ((warp & 3) == 0) TS(wg, 9);
        if (!own && elect) {
            mbar_arrive(sb + B_AHEAD);
            mbar_wait(sb + B_XFREE + 16, 0);
            bulk_in(sb + OFF_RING, ra, 32768, sb + B_PART);
        }
        wg_wait<0>();
        pin(p2);
        if ((warp & 3) == 0) TS(wg, 11);
        uint32_t f[16];
        const uint32_t ho = sb + OFF_X + (warp & 3) * 2048 + lane * 16;
        const int hv = own ? 0 : 128;
        if (!own) {
            pack_sub<0>(sp, p2);
            send_frag<0, 8>(sp, pbase + (((p ^ 1) * 4 + p) << 10), tag);
        } else {
            pack_sub<32>(f, p2);
#pragma unroll
            for (int v = 0; v < 4; v++)
                asm volatile("st.shared.v4.u32 [%0], {%1,%2,%3,%4};" :: "r"(ho + v * 512), "r"(f[4 * v]), "r"(f[4 * v + 1]), "r"(f[4 * v + 2]), "r"(f[4 * v + 3]) : "memory");
            asm volatile("bar.arrive 5, 256;" ::: "memory");
            pack_sub<0>(f, p2);
        }
        recv_issue(qc, rc + hv);
        mbar_wait(sb + B_PART, 0);
        if ((warp & 3) == 0) TS(wg, 10);
        lds_pkts(qa, sb + OFF_RING + (warp & 3) * 4096 + lane * 16 + hv * 16);
        lds_pkts(qb, sb + OFF_RING + 16384 + (warp & 3) * 4096 + lane * 16 + hv * 16);
        CNT(172, recv_check(qa, ra + hv, tag)); CNT(173, recv_check(qb, ra + 1024 + hv, tag));
#pragma unroll
        for (int i = 0; i < 16; i++) qa[i] = keep(hadd2(qa[i], qb[i]));
        if ((warp & 3) == 0) TS(wg, 12);
        CNT(174, recv_check(qc, rc + hv, tag));
        if (!own) { asm volatile("bar.sync 5, 256;" ::: "memory"); lds_pkts(f, ho); }
        if ((warp & 3) == 0) TS(wg, 13);
#pragma unroll
        for (int i = 0; i < 16; i++) f[i] = hadd2(hadd2(f[i], qc[i]), qa[i]);
        {
            const uint32_t slab = sb + OFF_RING + 2 * 16384 + wg * 8192;
            stash<16>(slab + srow, ssw, f);
            __syncwarp();
            __nv_bfloat16* op = out + (size_t)(r * 128 + (p & 1) * 64 + (warp & 3) * 16 + (lane >> 3)) * kD + (j & 1) * 256 + (p & 2) * 64 + (hv >> 1) + (lane & 7) * 8;
#pragma unroll
            for (int i = 0; i < 4; i++) {
                const int row = i * 4 + (lane >> 3);
                uint4 v;
                asm volatile("ld.shared.v4.u32 {%0,%1,%2,%3}, [%4];" : "=r"(v.x), "=r"(v.y), "=r"(v.z), "=r"(v.w)
                             : "r"(slab + ((warp & 3) * 16 + row) * 128 + (((lane & 7) ^ (row & 7)) << 4)) : "memory");
                *(uint4*)(op + i * 4 * kD) = v;
            }
        }
        if ((warp & 3) == 0) { TS(wg, 14); TSG(wg, 31); }
    }
}

typedef CUresult (*EncodeFn)(CUtensorMap*, CUtensorMapDataType, cuuint32_t, void*, const cuuint64_t*, const cuuint64_t*, const cuuint32_t*,
                             const cuuint32_t*, CUtensorMapInterleave, CUtensorMapSwizzle, CUtensorMapL2promotion, CUtensorMapFloatOOBfill);

static void encode(EncodeFn fn, CUtensorMap* m, int rank, const void* base, const cuuint64_t (&gd)[5], const cuuint64_t (&gs)[4],
                   const cuuint32_t (&bd)[5], CUtensorMapSwizzle sw) {
    cuuint32_t es[5] = {1, 1, 1, 1, 1};
    fn(m, CU_TENSOR_MAP_DATA_TYPE_BFLOAT16, rank, const_cast<void*>(base), gd, gs, bd, es, CU_TENSOR_MAP_INTERLEAVE_NONE, sw,
       CU_TENSOR_MAP_L2_PROMOTION_L2_128B, CU_TENSOR_MAP_FLOAT_OOB_FILL_NONE);
}

extern "C" void kernel_launch(void* const* d_in, const int* in_sizes, int n_in, void* d_out, int out_size) {
    const char* x = (const char*)d_in[0];
    const char* wqkv = (const char*)d_in[1];
    const char* wo = (const char*)d_in[2];
    const char* wg = (const char*)d_in[4];
    const char* wu = (const char*)d_in[5];
    const char* wd = (const char*)d_in[6];
    void* fnp = nullptr;
    cudaDriverEntryPointQueryResult qr;
    cudaGetDriverEntryPoint("cuTensorMapEncodeTiled", &fnp, cudaEnableDefault, &qr);
    EncodeFn fn = (EncodeFn)fnp;
    Maps maps;
    const char* lo = wg < wu ? wg : wu;
    const uint64_t diff = wg < wu ? (uint64_t)(wu - wg) : (uint64_t)(wg - wu);
    const CUtensorMapSwizzle S128 = CU_TENSOR_MAP_SWIZZLE_128B, S64 = CU_TENSOR_MAP_SWIZZLE_64B;
    encode(fn, &maps.x, 2, x, {512, 2048, 1, 1}, {1024, 0, 0}, {64, 128, 1, 1}, S128);
    encode(fn, &maps.gu, 3, lo, {1792, 512, 2, 1}, {3584, diff, 0}, {64, 64, 2, 1}, S128);
    encode(fn, &maps.kv, 3, wqkv, {512, 512, 3, 1}, {3072, 1024, 0}, {64, 64, 2, 1}, S128);
    encode(fn, &maps.q64, 3, wqkv, {32, 512, 48, 1}, {3072, 64, 0}, {32, 64, 2, 1}, S64);
    encode(fn, &maps.gu64, 3, lo, {1792, 512, 2, 1}, {3584, diff, 0}, {32, 64, 2, 1}, S64);
    encode(fn, &maps.wdw, 3, wd, {64, 1792, 8, 1}, {1024, 128, 0}, {64, 64, 2, 1}, S128);
    encode(fn, &maps.wow, 3, wo, {64, 512, 8}, {1024, 128}, {64, 64, 2}, S128);
    encode(fn, &maps.wdp, 5, wd, {512, 2, 4, 4, 56}, {1024, 8192, 2048, 32768}, {64, 2, 4, 4, 2}, S128);
    void* hx = nullptr;
    cudaGetSymbolAddress(&hx, g_hx);
    encode(fn, &maps.hx, 2, hx, {64, 16 * 4 * 5 * 128}, {128}, {64, 128}, S128);
    encode(fn, &maps.hx2, 2, hx, {64, 16 * 4 * 5 * 128}, {128}, {64, 256}, S128);
    cudaFuncSetAttribute(fused_kernel, cudaFuncAttributeMaxDynamicSharedMemorySize, SMEM_BYTES);
    cudaLaunchConfig_t cfg = {};
    cfg.gridDim = dim3(128);
    cfg.blockDim = dim3(384);
    cfg.dynamicSmemBytes = SMEM_BYTES;
    cfg.stream = cudaStreamPerThread;
    cudaLaunchAttribute at[1];
    at[0].id = cudaLaunchAttributeClusterDimension;
    at[0].val.clusterDim.x = 2; at[0].val.clusterDim.y = 1; at[0].val.clusterDim.z = 1;
    cfg.attrs = at;
    cfg.numAttrs = (MC || CL || FORCECL) ? 1 : 0;
    cudaLaunchKernelEx(&cfg, fused_kernel, maps, (const __nv_bfloat16*)d_in[0], (const __nv_bfloat16*)d_in[7], wqkv, wg, wu, wd, wo, (__nv_bfloat16*)d_out);
}
```

```cpp
#include <cuda_runtime.h>
#include <cuda.h>
#include <cuda_bf16.h>
#include <stdint.h>

#define MC 0
#define PFMODE 1
#define PHI_SAT 0
#define EXPT 0
#define RX 0
#define PF0 4
#define GDELAY 1
#define PRO5 0
#define NOPRE 0
#define CL 0
#define FORCECL 0
#define MAPV 0x6510432
#define OA 2
#define OB 0
#define OD 0
#define OE 1
#define PROF 0

namespace {

constexpr int kD = 512;
constexpr uint32_t OFF_X = 0, OFF_STG = 131072, OFF_RING = 147456, OFF_MISC = 229376;
constexpr uint32_t B_FULL = OFF_MISC, B_EMPTY = OFF_MISC + 40, B_XFULL = OFF_MISC + 80;
constexpr uint32_t B_GRDY = OFF_MISC + 152, B_KVDONE = OFF_MISC + 160, B_KVRDY = OFF_MISC + 168;
constexpr uint32_t B_HSENT = OFF_MISC + 176, B_XFREE = OFF_MISC + 200;
constexpr uint32_t OFF_EPOCH = OFF_MISC + 240, OFF_G = OFF_MISC + 256;
constexpr uint32_t B_AHEAD = OFF_MISC + 248, B_PART = OFF_MISC + 232;
constexpr uint32_t OFF_ONES = OFF_MISC + 768;
constexpr uint32_t B_EFULL = OFF_MISC + 896, B_EEMPTY = OFF_MISC + 928;
constexpr uint32_t B_LAST = OFF_MISC + 224, B_RFREE = OFF_MISC + 960;
constexpr uint32_t B_WARP = OFF_MISC + 968;
constexpr uint32_t SMEM_BYTES = OFF_MISC + 1032;
constexpr uint32_t SPIN_GLOBAL = 1u << 14;

struct alignas(64) Maps { CUtensorMap x, gu, kv, q64, gu64, wdw, wow, wdp, hx, hx2; };

}

__device__ uint4 g_part[16 * 2 * 4 * 4 * 1024];
__device__ uint4 g_hx[16 * 4 * 5 * 1024];
__device__ uint4 g_lx[16 * 8 * 2 * 1024];
__device__ unsigned g_hflag[128 * 8];
__device__ uint4 g_gx[16 * 32];
__device__ float g_kvacc[2 * 8 * 4 * 272];
__device__ unsigned g_kvcnt[8 * 32];
__device__ unsigned g_epoch[128];
#define TS(role, idx)
#define TS2(idx)
#define CNT(idx, v) (void)(v)
#define TSG(role, idx)

namespace {

__device__ __forceinline__ void mbar_init(uint32_t bar, uint32_t cnt) { asm volatile("mbarrier.init.shared::cta.b64 [%0], %1;" :: "r"(bar), "r"(cnt) : "memory"); }
__device__ __forceinline__ void mbar_expect(uint32_t bar, uint32_t bytes) { asm volatile("mbarrier.arrive.expect_tx.shared::cta.b64 _, [%0], %1;" :: "r"(bar), "r"(bytes) : "memory"); }
__device__ __forceinline__ void mbar_arrive(uint32_t bar) { asm volatile("mbarrier.arrive.shared::cta.b64 _, [%0];" :: "r"(bar) : "memory"); }
__device__ __forceinline__ void mbar_arrive_cta(uint32_t bar, uint32_t cta) {
    asm volatile("{\n.reg .b32 ra;\nmapa.shared::cluster.u32 ra, %0, %1;\nmbarrier.arrive.shared::cluster.b64 _, [ra];\n}" :: "r"(bar), "r"(cta) : "memory");
}
__device__ __forceinline__ void mbar_wait(uint32_t bar, uint32_t parity) {
    asm volatile("{\n.reg .pred p;\n.reg .u32 c;\n"
                 "mbarrier.try_wait.parity.shared::cta.b64 p, [%0], %1;\n@p bra DONE;\n"
                 "mov.u32 c, 0;\nLAB_WAIT:\nmbarrier.try_wait.parity.shared::cta.b64 p, [%0], %1;\n@p bra DONE;\n"
                 "add.u32 c, c, 1;\nsetp.lt.u32 p, c, 65536;\n@p bra LAB_WAIT;\nDONE:\n}" :: "r"(bar), "r"(parity) : "memory");
}
__device__ __forceinline__ void tma2(uint32_t dst, const CUtensorMap* m, int c0, int c1, uint32_t bar) {
    asm volatile("cp.async.bulk.tensor.2d.shared::cluster.global.mbarrier::complete_tx::bytes [%0], [%1, {%3, %4}], [%2];"
        :: "r"(dst), "l"(m), "r"(bar), "r"(c0), "r"(c1) : "memory");
}
__device__ __forceinline__ void tmaw2(uint32_t dst, const CUtensorMap* m, int c0, int c1, uint32_t bar) {
    tma2(dst, m, c0, c1, bar);
}
__device__ __forceinline__ void tmaw3(uint32_t dst, const CUtensorMap* m, int c0, int c1, int c2, uint32_t bar) {
    asm volatile("cp.async.bulk.tensor.3d.shared::cluster.global.mbarrier::complete_tx::bytes [%0], [%1, {%3, %4, %5}], [%2];"
        :: "r"(dst), "l"(m), "r"(bar), "r"(c0), "r"(c1), "r"(c2) : "memory");
}
__device__ __forceinline__ void tmaw5(uint32_t dst, const CUtensorMap* m, int c0, int c4, uint32_t bar) {
    asm volatile("cp.async.bulk.tensor.5d.shared::cluster.global.mbarrier::complete_tx::bytes [%0], [%1, {%3, %5, %5, %5, %4}], [%2];"
        :: "r"(dst), "l"(m), "r"(bar), "r"(c0), "r"(c4), "r"(0) : "memory");
}
__device__ __forceinline__ void bulk_in(uint32_t dst, const void* src, uint32_t bytes, uint32_t bar) {
    mbar_expect(bar, bytes);
    asm volatile("cp.async.bulk.shared::cluster.global.mbarrier::complete_tx::bytes [%0], [%1], %2, [%3];" :: "r"(dst), "l"(src), "r"(bytes), "r"(bar) : "memory");
}
__device__ __forceinline__ void wg_fence() { asm volatile("wgmma.fence.sync.aligned;" ::: "memory"); }
__device__ __forceinline__ void wg_commit() { asm volatile("wgmma.commit_group.sync.aligned;" ::: "memory"); }
template <int N> __device__ __forceinline__ void wg_wait() { asm volatile("wgmma.wait_group.sync.aligned %0;" :: "n"(N) : "memory"); }
template <int N> __device__ __forceinline__ void pin(float (&d)[N]) {
#pragma unroll
    for (int i = 0; i < N; i++) asm volatile("" : "+f"(d[i]) :: "memory");
}
__device__ __forceinline__ uint32_t pack2(float lo, float hi) { uint32_t r; asm("cvt.rn.bf16x2.f32 %0, %1, %2;" : "=r"(r) : "f"(hi), "f"(lo)); return r; }
__device__ __forceinline__ uint32_t keep(uint32_t v) { asm volatile("" : "+r"(v)); return v; }
__device__ __forceinline__ uint32_t hadd2(uint32_t a, uint32_t b) { uint32_t r; asm("add.bf16x2 %0, %1, %2;" : "=r"(r) : "r"(a), "r"(b)); return r; }
__device__ __forceinline__ uint32_t hmul2(uint32_t a, uint32_t b) { uint32_t r; asm("mul.bf16x2 %0, %1, %2;" : "=r"(r) : "r"(a), "r"(b)); return r; }
__device__ __forceinline__ uint32_t phi2(float t0, float t1) {
    float e0, e1;
    asm("ex2.approx.ftz.f32 %0, %1;" : "=f"(e0) : "f"(t0 * 1.4426950408889634f));
    asm("ex2.approx.ftz.f32 %0, %1;" : "=f"(e1) : "f"(t1 * 1.4426950408889634f));
    uint32_t e = pack2(e0, e1), t = pack2(t0, t1), r;
    asm("min.bf16x2 %0, %0, %1;" : "+r"(e) : "r"(0x3f803f80u));
    asm("max.bf16x2 %0, %0, %1;" : "+r"(t) : "r"(0x35863586u));
    asm("add.bf16x2 %0, %1, %2;" : "=r"(r) : "r"(e), "r"(t));
    return r;
}
__device__ __forceinline__ void stsm4(uint32_t a, uint32_t r0, uint32_t r1, uint32_t r2, uint32_t r3) {
    asm volatile("stmatrix.sync.aligned.m8n8.x4.shared.b16 [%0], {%1,%2,%3,%4};" :: "r"(a), "r"(r0), "r"(r1), "r"(r2), "r"(r3) : "memory");
}
__device__ __forceinline__ float bf_lo(uint32_t w) { return __uint_as_float(w << 16); }
__device__ __forceinline__ float bf_hi(uint32_t w) { return __uint_as_float(w & 0xffff0000u); }
__device__ __forceinline__ void st_pkt(uint4* p, uint32_t w0, uint32_t w1, uint32_t w2, uint32_t w3) {
    asm volatile("{\n.reg .b64 lo, hi;\n.reg .b128 v;\nmov.b64 lo, {%1, %2};\nmov.b64 hi, {%3, %4};\nmov.b128 v, {lo, hi};\nst.relaxed.gpu.global.b128 [%0], v;\n}"
        :: "l"(p), "r"(w0), "r"(w1), "r"(w2), "r"(w3) : "memory");
}
__device__ __forceinline__ void ld_pkt(const uint4* p, uint32_t& w0, uint32_t& w1, uint32_t& w2, uint32_t& w3) {
    asm volatile("{\n.reg .b64 lo, hi;\n.reg .b128 v;\nld.relaxed.gpu.global.b128 v, [%4];\nmov.b128 {lo, hi}, v;\nmov.b64 {%0, %1}, lo;\nmov.b64 {%2, %3}, hi;\n}"
        : "=r"(w0), "=r"(w1), "=r"(w2), "=r"(w3) : "l"(p) : "memory");
}

template <uint32_t AO, uint32_t BO, uint32_t BH> __device__ __forceinline__ void wg_ss128(float (&d)[64], uint32_t ab, uint32_t bb) {
    asm volatile("{\n.reg .b64 da, db;\n.reg .b32 ta, tb, th, ah;\nadd.u32 ta, %64, %66;\nadd.u32 tb, %65, %67;\nmov.b32 th, %68;\nmov.b32 ah, 0x40000040;\nmov.b64 da, {ta, ah};\nmov.b64 db, {tb, th};\n"
        "wgmma.mma_async.sync.aligned.m64n128k16.f32.bf16.bf16 {%0,%1,%2,%3,%4,%5,%6,%7,%8,%9,%10,%11,%12,%13,%14,%15,%16,%17,%18,%19,%20,%21,%22,%23,%24,%25,%26,%27,%28,%29,%30,%31,%32,%33,%34,%35,%36,%37,%38,%39,%40,%41,%42,%43,%44,%45,%46,%47,%48,%49,%50,%51,%52,%53,%54,%55,%56,%57,%58,%59,%60,%61,%62,%63}, da, db, 1, 1, 1, 0, 1;\n}\n"
        : "+f"(d[0]),"+f"(d[1]),"+f"(d[2]),"+f"(d[3]),"+f"(d[4]),"+f"(d[5]),"+f"(d[6]),"+f"(d[7]),"+f"(d[8]),"+f"(d[9]),"+f"(d[10]),"+f"(d[11]),"+f"(d[12]),"+f"(d[13]),"+f"(d[14]),"+f"(d[15]),"+f"(d[16]),"+f"(d[17]),"+f"(d[18]),"+f"(d[19]),"+f"(d[20]),"+f"(d[21]),"+f"(d[22]),"+f"(d[23]),"+f"(d[24]),"+f"(d[25]),"+f"(d[26]),"+f"(d[27]),"+f"(d[28]),"+f"(d[29]),"+f"(d[30]),"+f"(d[31]),"+f"(d[32]),"+f"(d[33]),"+f"(d[34]),"+f"(d[35]),"+f"(d[36]),"+f"(d[37]),"+f"(d[38]),"+f"(d[39]),"+f"(d[40]),"+f"(d[41]),"+f"(d[42]),"+f"(d[43]),"+f"(d[44]),"+f"(d[45]),"+f"(d[46]),"+f"(d[47]),"+f"(d[48]),"+f"(d[49]),"+f"(d[50]),"+f"(d[51]),"+f"(d[52]),"+f"(d[53]),"+f"(d[54]),"+f"(d[55]),"+f"(d[56]),"+f"(d[57]),"+f"(d[58]),"+f"(d[59]),"+f"(d[60]),"+f"(d[61]),"+f"(d[62]),"+f"(d[63])
        : "r"(ab), "r"(bb), "n"(AO), "n"(BO), "n"(BH));
}
template <uint32_t AO, uint32_t BO, uint32_t BH> __device__ __forceinline__ void wg_ss128_z(float (&d)[64], uint32_t ab, uint32_t bb) {
    asm volatile("{\n.reg .b64 da, db;\n.reg .b32 ta, tb, th, ah;\nadd.u32 ta, %64, %66;\nadd.u32 tb, %65, %67;\nmov.b32 th, %68;\nmov.b32 ah, 0x40000040;\nmov.b64 da, {ta, ah};\nmov.b64 db, {tb, th};\n"
        "wgmma.mma_async.sync.aligned.m64n128k16.f32.bf16.bf16 {%0,%1,%2,%3,%4,%5,%6,%7,%8,%9,%10,%11,%12,%13,%14,%15,%16,%17,%18,%19,%20,%21,%22,%23,%24,%25,%26,%27,%28,%29,%30,%31,%32,%33,%34,%35,%36,%37,%38,%39,%40,%41,%42,%43,%44,%45,%46,%47,%48,%49,%50,%51,%52,%53,%54,%55,%56,%57,%58,%59,%60,%61,%62,%63}, da, db, 0, 1, 1, 0, 1;\n}\n"
        : "=f"(d[0]),"=f"(d[1]),"=f"(d[2]),"=f"(d[3]),"=f"(d[4]),"=f"(d[5]),"=f"(d[6]),"=f"(d[7]),"=f"(d[8]),"=f"(d[9]),"=f"(d[10]),"=f"(d[11]),"=f"(d[12]),"=f"(d[13]),"=f"(d[14]),"=f"(d[15]),"=f"(d[16]),"=f"(d[17]),"=f"(d[18]),"=f"(d[19]),"=f"(d[20]),"=f"(d[21]),"=f"(d[22]),"=f"(d[23]),"=f"(d[24]),"=f"(d[25]),"=f"(d[26]),"=f"(d[27]),"=f"(d[28]),"=f"(d[29]),"=f"(d[30]),"=f"(d[31]),"=f"(d[32]),"=f"(d[33]),"=f"(d[34]),"=f"(d[35]),"=f"(d[36]),"=f"(d[37]),"=f"(d[38]),"=f"(d[39]),"=f"(d[40]),"=f"(d[41]),"=f"(d[42]),"=f"(d[43]),"=f"(d[44]),"=f"(d[45]),"=f"(d[46]),"=f"(d[47]),"=f"(d[48]),"=f"(d[49]),"=f"(d[50]),"=f"(d[51]),"=f"(d[52]),"=f"(d[53]),"=f"(d[54]),"=f"(d[55]),"=f"(d[56]),"=f"(d[57]),"=f"(d[58]),"=f"(d[59]),"=f"(d[60]),"=f"(d[61]),"=f"(d[62]),"=f"(d[63])
        : "r"(ab), "r"(bb), "n"(AO), "n"(BO), "n"(BH));
}
template <uint32_t BO, uint32_t BH> __device__ __forceinline__ void wg_rs128(float (&d)[64], uint32_t a0, uint32_t a1, uint32_t a2, uint32_t a3, uint32_t bb) {
    asm volatile("{\n.reg .b64 db;\n.reg .b32 tb, th;\nadd.u32 tb, %68, %69;\nmov.b32 th, %70;\nmov.b64 db, {tb, th};\n"
        "wgmma.mma_async.sync.aligned.m64n128k16.f32.bf16.bf16 {%0,%1,%2,%3,%4,%5,%6,%7,%8,%9,%10,%11,%12,%13,%14,%15,%16,%17,%18,%19,%20,%21,%22,%23,%24,%25,%26,%27,%28,%29,%30,%31,%32,%33,%34,%35,%36,%37,%38,%39,%40,%41,%42,%43,%44,%45,%46,%47,%48,%49,%50,%51,%52,%53,%54,%55,%56,%57,%58,%59,%60,%61,%62,%63}, {%64,%65,%66,%67}, db, 1, 1, 1, 1;\n}\n"
        : "+f"(d[0]),"+f"(d[1]),"+f"(d[2]),"+f"(d[3]),"+f"(d[4]),"+f"(d[5]),"+f"(d[6]),"+f"(d[7]),"+f"(d[8]),"+f"(d[9]),"+f"(d[10]),"+f"(d[11]),"+f"(d[12]),"+f"(d[13]),"+f"(d[14]),"+f"(d[15]),"+f"(d[16]),"+f"(d[17]),"+f"(d[18]),"+f"(d[19]),"+f"(d[20]),"+f"(d[21]),"+f"(d[22]),"+f"(d[23]),"+f"(d[24]),"+f"(d[25]),"+f"(d[26]),"+f"(d[27]),"+f"(d[28]),"+f"(d[29]),"+f"(d[30]),"+f"(d[31]),"+f"(d[32]),"+f"(d[33]),"+f"(d[34]),"+f"(d[35]),"+f"(d[36]),"+f"(d[37]),"+f"(d[38]),"+f"(d[39]),"+f"(d[40]),"+f"(d[41]),"+f"(d[42]),"+f"(d[43]),"+f"(d[44]),"+f"(d[45]),"+f"(d[46]),"+f"(d[47]),"+f"(d[48]),"+f"(d[49]),"+f"(d[50]),"+f"(d[51]),"+f"(d[52]),"+f"(d[53]),"+f"(d[54]),"+f"(d[55]),"+f"(d[56]),"+f"(d[57]),"+f"(d[58]),"+f"(d[59]),"+f"(d[60]),"+f"(d[61]),"+f"(d[62]),"+f"(d[63])
        : "r"(a0), "r"(a1), "r"(a2), "r"(a3), "r"(bb), "n"(BO), "n"(BH));
}
template <uint32_t BO, uint32_t BH> __device__ __forceinline__ void wg_rs128_z(float (&d)[64], uint32_t a0, uint32_t a1, uint32_t a2, uint32_t a3, uint32_t bb) {
    asm volatile("{\n.reg .b64 db;\n.reg .b32 tb, th;\nadd.u32 tb, %68, %69;\nmov.b32 th, %70;\nmov.b64 db, {tb, th};\n"
        "wgmma.mma_async.sync.aligned.m64n128k16.f32.bf16.bf16 {%0,%1,%2,%3,%4,%5,%6,%7,%8,%9,%10,%11,%12,%13,%14,%15,%16,%17,%18,%19,%20,%21,%22,%23,%24,%25,%26,%27,%28,%29,%30,%31,%32,%33,%34,%35,%36,%37,%38,%39,%40,%41,%42,%43,%44,%45,%46,%47,%48,%49,%50,%51,%52,%53,%54,%55,%56,%57,%58,%59,%60,%61,%62,%63}, {%64,%65,%66,%67}, db, 0, 1, 1, 1;\n}\n"
        : "=f"(d[0]),"=f"(d[1]),"=f"(d[2]),"=f"(d[3]),"=f"(d[4]),"=f"(d[5]),"=f"(d[6]),"=f"(d[7]),"=f"(d[8]),"=f"(d[9]),"=f"(d[10]),"=f"(d[11]),"=f"(d[12]),"=f"(d[13]),"=f"(d[14]),"=f"(d[15]),"=f"(d[16]),"=f"(d[17]),"=f"(d[18]),"=f"(d[19]),"=f"(d[20]),"=f"(d[21]),"=f"(d[22]),"=f"(d[23]),"=f"(d[24]),"=f"(d[25]),"=f"(d[26]),"=f"(d[27]),"=f"(d[28]),"=f"(d[29]),"=f"(d[30]),"=f"(d[31]),"=f"(d[32]),"=f"(d[33]),"=f"(d[34]),"=f"(d[35]),"=f"(d[36]),"=f"(d[37]),"=f"(d[38]),"=f"(d[39]),"=f"(d[40]),"=f"(d[41]),"=f"(d[42]),"=f"(d[43]),"=f"(d[44]),"=f"(d[45]),"=f"(d[46]),"=f"(d[47]),"=f"(d[48]),"=f"(d[49]),"=f"(d[50]),"=f"(d[51]),"=f"(d[52]),"=f"(d[53]),"=f"(d[54]),"=f"(d[55]),"=f"(d[56]),"=f"(d[57]),"=f"(d[58]),"=f"(d[59]),"=f"(d[60]),"=f"(d[61]),"=f"(d[62]),"=f"(d[63])
        : "r"(a0), "r"(a1), "r"(a2), "r"(a3), "r"(bb), "n"(BO), "n"(BH));
}
template <uint32_t AO, uint32_t BO, uint32_t BH> __device__ __forceinline__ void wg_ss64t(float (&d)[32], uint32_t ab, uint32_t bb) {
    asm volatile("{\n.reg .b64 da, db;\n.reg .b32 ta, tb, th, ah;\nadd.u32 ta, %32, %34;\nadd.u32 tb, %33, %35;\nmov.b32 th, %36;\nmov.b32 ah, 0x40000040;\nmov.b64 da, {ta, ah};\nmov.b64 db, {tb, th};\n"
        "wgmma.mma_async.sync.aligned.m64n64k16.f32.bf16.bf16 {%0,%1,%2,%3,%4,%5,%6,%7,%8,%9,%10,%11,%12,%13,%14,%15,%16,%17,%18,%19,%20,%21,%22,%23,%24,%25,%26,%27,%28,%29,%30,%31}, da, db, 1, 1, 1, 1, 1;\n}\n"
        : "+f"(d[0]),"+f"(d[1]),"+f"(d[2]),"+f"(d[3]),"+f"(d[4]),"+f"(d[5]),"+f"(d[6]),"+f"(d[7]),"+f"(d[8]),"+f"(d[9]),"+f"(d[10]),"+f"(d[11]),"+f"(d[12]),"+f"(d[13]),"+f"(d[14]),"+f"(d[15]),"+f"(d[16]),"+f"(d[17]),"+f"(d[18]),"+f"(d[19]),"+f"(d[20]),"+f"(d[21]),"+f"(d[22]),"+f"(d[23]),"+f"(d[24]),"+f"(d[25]),"+f"(d[26]),"+f"(d[27]),"+f"(d[28]),"+f"(d[29]),"+f"(d[30]),"+f"(d[31])
        : "r"(ab), "r"(bb), "n"(AO), "n"(BO), "n"(BH));
}
template <uint32_t AO, uint32_t BO, uint32_t BH> __device__ __forceinline__ void wg_ss64t_z(float (&d)[32], uint32_t ab, uint32_t bb) {
    asm volatile("{\n.reg .b64 da, db;\n.reg .b32 ta, tb, th, ah;\nadd.u32 ta, %32, %34;\nadd.u32 tb, %33, %35;\nmov.b32 th, %36;\nmov.b32 ah, 0x40000040;\nmov.b64 da, {ta, ah};\nmov.b64 db, {tb, th};\n"
        "wgmma.mma_async.sync.aligned.m64n64k16.f32.bf16.bf16 {%0,%1,%2,%3,%4,%5,%6,%7,%8,%9,%10,%11,%12,%13,%14,%15,%16,%17,%18,%19,%20,%21,%22,%23,%24,%25,%26,%27,%28,%29,%30,%31}, da, db, 0, 1, 1, 1, 1;\n}\n"
        : "=f"(d[0]),"=f"(d[1]),"=f"(d[2]),"=f"(d[3]),"=f"(d[4]),"=f"(d[5]),"=f"(d[6]),"=f"(d[7]),"=f"(d[8]),"=f"(d[9]),"=f"(d[10]),"=f"(d[11]),"=f"(d[12]),"=f"(d[13]),"=f"(d[14]),"=f"(d[15]),"=f"(d[16]),"=f"(d[17]),"=f"(d[18]),"=f"(d[19]),"=f"(d[20]),"=f"(d[21]),"=f"(d[22]),"=f"(d[23]),"=f"(d[24]),"=f"(d[25]),"=f"(d[26]),"=f"(d[27]),"=f"(d[28]),"=f"(d[29]),"=f"(d[30]),"=f"(d[31])
        : "r"(ab), "r"(bb), "n"(AO), "n"(BO), "n"(BH));
}
template <uint32_t AO, uint32_t BO, uint32_t BH> __device__ __forceinline__ void wg_ss8t(float (&d)[4], uint32_t ab, uint32_t bb) {
    asm volatile("{\n.reg .b64 da, db;\n.reg .b32 ta, tb, th, ah;\nadd.u32 ta, %4, %6;\nadd.u32 tb, %5, %7;\nmov.b32 th, %8;\nmov.b32 ah, 0x40000040;\nmov.b64 da, {ta, ah};\nmov.b64 db, {tb, th};\n"
        "wgmma.mma_async.sync.aligned.m64n8k16.f32.bf16.bf16 {%0,%1,%2,%3}, da, db, 1, 1, 1, 1, 0;\n}\n"
        : "+f"(d[0]),"+f"(d[1]),"+f"(d[2]),"+f"(d[3])
        : "r"(ab), "r"(bb), "n"(AO), "n"(BO), "n"(BH));
}
template <uint32_t AO, uint32_t BO, uint32_t BH> __device__ __forceinline__ void wg_ss8t_z(float (&d)[4], uint32_t ab, uint32_t bb) {
    asm volatile("{\n.reg .b64 da, db;\n.reg .b32 ta, tb, th, ah;\nadd.u32 ta, %4, %6;\nadd.u32 tb, %5, %7;\nmov.b32 th, %8;\nmov.b32 ah, 0x40000040;\nmov.b64 da, {ta, ah};\nmov.b64 db, {tb, th};\n"
        "wgmma.mma_async.sync.aligned.m64n8k16.f32.bf16.bf16 {%0,%1,%2,%3}, da, db, 0, 1, 1, 1, 0;\n}\n"
        : "=f"(d[0]),"=f"(d[1]),"=f"(d[2]),"=f"(d[3])
        : "r"(ab), "r"(bb), "n"(AO), "n"(BO), "n"(BH));
}
template <uint32_t BO, uint32_t BH> __device__ __forceinline__ void wg_rs24_z(float (&d)[12], uint32_t a0, uint32_t a1, uint32_t a2, uint32_t a3, uint32_t bb) {
    asm volatile("{\n.reg .b64 db;\n.reg .b32 tb, th;\nadd.u32 tb, %16, %17;\nmov.b32 th, %18;\nmov.b64 db, {tb, th};\n"
        "wgmma.mma_async.sync.aligned.m64n24k16.f32.bf16.bf16 {%0,%1,%2,%3,%4,%5,%6,%7,%8,%9,%10,%11}, {%12,%13,%14,%15}, db, 0, 1, 1, 0;\n}\n"
        : "=f"(d[0]),"=f"(d[1]),"=f"(d[2]),"=f"(d[3]),"=f"(d[4]),"=f"(d[5]),"=f"(d[6]),"=f"(d[7]),"=f"(d[8]),"=f"(d[9]),"=f"(d[10]),"=f"(d[11])
        : "r"(a0), "r"(a1), "r"(a2), "r"(a3), "r"(bb), "n"(BO), "n"(BH));
}

constexpr uint32_t DH128 = 64u | 0x40000000u;
constexpr uint32_t DH64 = 32u | 0x80000000u;
constexpr uint32_t LBO4K = (4096u >> 4) << 16, LBO8K = (8192u >> 4) << 16, LBO1 = 1u << 16;

template <uint32_t AO, uint32_t BO, bool SW64, bool FIRST> __device__ __forceinline__ void stage_ss(float (&acc)[64], uint32_t ab, uint32_t bb) {
    constexpr uint32_t KS = SW64 ? 64 : 128, BH = SW64 ? DH64 : DH128, B0 = BO + (SW64 ? LBO4K : LBO8K);
    wg_fence();
    if (FIRST) wg_ss128_z<AO, B0, BH>(acc, ab, bb); else wg_ss128<AO, B0, BH>(acc, ab, bb);
    wg_ss128<AO + 2, B0 + KS, BH>(acc, ab, bb);
    wg_ss128<AO + 4, B0 + 2 * KS, BH>(acc, ab, bb);
    wg_ss128<AO + 6, B0 + 3 * KS, BH>(acc, ab, bb);
    wg_commit();
}
template <uint32_t BO, bool FIRST> __device__ __forceinline__ void stage_rs(float (&acc)[64], const uint32_t (&f)[16], uint32_t bb) {
    wg_fence();
    if (FIRST) wg_rs128_z<BO + LBO8K, DH128>(acc, f[0], f[1], f[2], f[3], bb); else wg_rs128<BO + LBO8K, DH128>(acc, f[0], f[1], f[2], f[3], bb);
    wg_rs128<BO + LBO8K + 128, DH128>(acc, f[4], f[5], f[6], f[7], bb);
    wg_rs128<BO + LBO8K + 256, DH128>(acc, f[8], f[9], f[10], f[11], bb);
    wg_rs128<BO + LBO8K + 384, DH128>(acc, f[12], f[13], f[14], f[15], bb);
    wg_commit();
}

template <int N> __device__ __forceinline__ void stash(uint32_t base, uint32_t sw, const uint32_t (&f)[N]) {
#pragma unroll
    for (int t = 0; t < N / 4; t++) stsm4(base + ((sw ^ (2 * t)) << 4), f[4 * t], f[4 * t + 1], f[4 * t + 2], f[4 * t + 3]);
}

template <int V0, int V1, int N> __device__ __forceinline__ void send_frag(const uint32_t (&f)[N], uint4* p, uint32_t tag) {
#pragma unroll
    for (int v = V0; v < V1; v++) st_pkt(p + v * 32, (f[4 * v] & ~1u) | tag, f[4 * v + 1], f[4 * v + 2], f[4 * v + 3]);
}
template <int V0, int V1, int N> __device__ __forceinline__ void send_h(const uint32_t (&f)[N], uint4* p) {
#pragma unroll
    for (int v = V0; v < V1; v++) {
        const int h = v >> 1, hi = v & 1;
        asm volatile("st.global.v4.u32 [%0], {%1,%2,%3,%4};" :: "l"(p + 4 * h + 64 * hi),
                     "r"(f[8 * h + hi]), "r"(f[8 * h + 2 + hi]), "r"(f[8 * h + 4 + hi]), "r"(f[8 * h + 6 + hi]) : "memory");
    }
}
template <int O, int N, int M> __device__ __forceinline__ void pack_sub(uint32_t (&f)[N], const float (&acc)[M]) {
#pragma unroll
    for (int i = 0; i < N; i++) f[i] = keep(pack2(acc[O + 2 * i], acc[O + 2 * i + 1]));
}
template <int N> __device__ __forceinline__ void recv_issue(uint32_t (&q)[N], const uint4* p) {
#pragma unroll
    for (int v = 0; v < N / 4; v++) ld_pkt(p + v * 32, q[4 * v], q[4 * v + 1], q[4 * v + 2], q[4 * v + 3]);
}
template <int N> __device__ __forceinline__ void lds_pkts(uint32_t (&q)[N], uint32_t a) {
#pragma unroll
    for (int v = 0; v < N / 4; v++)
        asm volatile("ld.shared.v4.u32 {%0,%1,%2,%3}, [%4];" : "=r"(q[4 * v]), "=r"(q[4 * v + 1]), "=r"(q[4 * v + 2]), "=r"(q[4 * v + 3]) : "r"(a + v * 512) : "memory");
}
template <int N> __device__ __forceinline__ bool pkts_ok(const uint32_t (&q)[N], uint32_t tag) {
    uint32_t bad = 0;
#pragma unroll
    for (int v = 0; v < N / 4; v++) bad |= q[4 * v] ^ tag;
    return __all_sync(0xffffffffu, (bad & 1u) == 0);
}
template <int N> __device__ __forceinline__ uint32_t recv_retry(uint32_t (&q)[N], const uint4* src, uint32_t dst, uint32_t bar, uint32_t& ph, uint32_t tag) {
    uint32_t it = 0;
    while (!pkts_ok(q, tag) && ++it < SPIN_GLOBAL) {
        if ((threadIdx.x & 31) == 0) bulk_in(dst, src, N * 128, bar);
        mbar_wait(bar, ph);
        ph ^= 1;
        lds_pkts(q, dst + (threadIdx.x & 31) * 16);
    }
    return it;
}
template <int N> __device__ __forceinline__ uint32_t recv_check(uint32_t (&q)[N], const uint4* p, uint32_t tag) {
    uint32_t it = 0;
    while (true) {
        uint32_t bad = 0;
#pragma unroll
        for (int v = 0; v < N / 4; v++) bad |= q[4 * v] ^ tag;
        if (__all_sync(0xffffffffu, (bad & 1u) == 0) || ++it > SPIN_GLOBAL) break;
        recv_issue(q, p);
    }
    return it;
}
}

__global__ void __launch_bounds__(384, 1)
fused_kernel(const __grid_constant__ Maps maps, const __nv_bfloat16* __restrict__ xg, const __nv_bfloat16* __restrict__ gate_w,
             const char* __restrict__ pf_qkv, const char* __restrict__ pf_g, const char* __restrict__ pf_u,
             const char* __restrict__ pf_d, const char* __restrict__ pf_o, __nv_bfloat16* __restrict__ out) {
    extern __shared__ __align__(1024) uint8_t smem_raw[];
    const uint32_t sb = (uint32_t)__cvta_generic_to_shared(smem_raw);
    const int tid = threadIdx.x, lane = tid & 31;
    const int warp = __shfl_sync(0xffffffffu, tid >> 5, 0);
#define MB(i) ((blockIdx.x >> ((MAPV >> (4 * (i))) & 15)) & 1)
    const int j = MB(0) | (MB(1) << 1) | (MB(2) << 2), r = MB(3) | (MB(4) << 1) | (MB(5) << 2) | (MB(6) << 3);
    const uint32_t rank = blockIdx.x & 1;

    const int fc = 448 * (j >> 1) + 256 * (j & 1);
    if (warp == 0) { TSG(0, 30); TS(0, 0); }
    if (tid == 256) {
        mbar_init(sb + B_XFULL, 1); mbar_init(sb + B_FULL, 1); mbar_init(sb + B_FULL + 8, 1); mbar_init(sb + B_XFULL + 8, 1); mbar_init(sb + B_FULL + 16, 1);
        asm volatile("fence.mbarrier_init.release.cluster;" ::: "memory");
        TS2(0);
        mbar_expect(sb + B_FULL, 16384);
        tmaw3(sb + OFF_RING, &maps.kv, 64 * j, 0, 1, sb + B_FULL);
        mbar_expect(sb + B_XFULL, 16384);
        tma2(sb + OFF_X, &maps.x, 0, r * 128, sb + B_XFULL);
        TS2(1);
        mbar_expect(sb + B_FULL + 8, 16384);
        tmaw3(sb + OFF_RING + 16384, &maps.gu, fc, 0, 0, sb + B_FULL + 8);
#define PRO_MORE() do { mbar_expect(sb + B_XFULL + 8, 16384); tma2(sb + OFF_X + 16384, &maps.x, 64, r * 128, sb + B_XFULL + 8); TS2(2); \
        mbar_expect(sb + B_FULL + 16, 16384); tmaw3(sb + OFF_RING + 2 * 16384, &maps.kv, 64 * j, 64, 1, sb + B_FULL + 16); } while (0)
        if (PRO5) PRO_MORE();
    } else if (tid == 352) {
        for (int i = 0; i < 5; i++) { if (i > 2) mbar_init(sb + B_FULL + 8 * i, 1); mbar_init(sb + B_EMPTY + 8 * i, MC ? 4 : 2); }
        for (int i = 2; i < 9; i++) mbar_init(sb + B_XFULL + 8 * i, 1);
        asm volatile("fence.mbarrier_init.release.cluster;" ::: "memory");
    } else if (tid == 288) {
        for (int i = 0; i < 3; i++) mbar_init(sb + B_HSENT + 8 * i, 8);
        for (int i = 0; i < 4; i++) { mbar_init(sb + B_EFULL + 8 * i, 1); mbar_init(sb + B_EEMPTY + 8 * i, MC ? 4 : 2); }
        mbar_init(sb + B_XFREE, 2); mbar_init(sb + B_XFREE + 8, 2); mbar_init(sb + B_XFREE + 16, 2);
        for (int i = 0; i < 8; i++) mbar_init(sb + B_WARP + 8 * i, 1);
        mbar_init(sb + B_AHEAD, 1); mbar_init(sb + B_PART, 1); mbar_init(sb + B_LAST, 1); mbar_init(sb + B_RFREE, 2);
        if (CL) mbar_expect(sb + B_LAST, 16384); mbar_init(sb + B_GRDY, 1); mbar_init(sb + B_KVDONE, 8); mbar_init(sb + B_KVRDY, 2);
        asm volatile("fence.mbarrier_init.release.cluster;" ::: "memory");
    } else if (warp == 10 && lane < 10) {
        asm volatile("prefetch.tensormap [%0];" :: "l"(&maps.x + lane) : "memory");
    }
    __syncthreads();
    if (CL) asm volatile("barrier.cluster.arrive.relaxed.aligned;" ::: "memory");

    if (warp >= 8) {
        asm volatile("setmaxnreg.dec.sync.aligned.u32 56;");
        if (warp == 8) {
            if (lane == 0) {
                int slot = 3, ph = 1;
                uint32_t full, dst;
                if (!PRO5) PRO_MORE();
                mbar_expect(sb + B_XFULL + 16, 16384); tma2(sb + OFF_X + 2 * 16384, &maps.x, 128, r * 128, sb + B_XFULL + 16);
#define P_BEGIN(S, BYTES) full = sb + B_FULL + 8 * slot; dst = sb + OFF_RING + slot * 16384; \
                mbar_wait(sb + B_EMPTY + 8 * slot, ph); TS2(S); mbar_expect(full, BYTES); if (!MC || (((S) ^ rank) & 1) == 0)
#define P_END() if (++slot == 5) { slot = 0; ph ^= 1; }
                for (int s = 3; s < 16; s++) {
                    const int kb = (int)(0x7654763542312100ull >> (4 * s)) & 15;
                    P_BEGIN(s, 16384) {
                        if ((0x0DADu >> s) & 1) tmaw3(dst, &maps.kv, 64 * j, 64 * kb, 1, full);
                        else tmaw3(dst, &maps.gu, fc, 64 * kb, 0, full);
                    }
                    const int xb = (int)(0x0000000765403210ull >> (4 * s)) & 15;
                    if (xb) { mbar_expect(sb + B_XFULL + 8 * xb, 16384); tma2(sb + OFF_X + xb * 16384, &maps.x, 64 * xb, r * 128, sb + B_XFULL + 8 * xb); }
                    P_END()
                }
                for (int s = 0; s < 24; s++) {
                    P_BEGIN(16 + s, 16384) {
                        if (s < 8) {
                            tmaw3(dst, &maps.q64, 0, 64 * s, 2 * j, full);
                            tmaw3(dst + 8192, &maps.gu64, 224 * (j & 6) + 192 + 32 * (j & 1), 64 * s, 0, full);
                        } else {
                            tmaw3(dst, &maps.gu, fc + 64 * (s >> 3), 64 * (s & 7), 0, full);
                        }
                    }
                    P_END()
                }
                const int p = j >> 1;
#pragma unroll 1
                for (int t = 0; t < 18; t++) {
                    const int q = t >= 9, sl = (int)(0x846352107ull >> (4 * (t - 9 * q))) & 15;
                    const int u = (int)((q ? 0x432186758ull : 0x327064105ull) >> (4 * (t - 9 * q))) & 15;
                    const int cw = (j & 1) * 4 + ((p & 2) ^ ((t == 5 || t > 9) ? 0 : 2)), cc = 64 * cw;
                    if (sl < 5) {
                        full = sb + B_FULL + 8 * sl; dst = sb + OFF_RING + sl * 16384;
                        mbar_wait(sb + B_EMPTY + 8 * sl, q ^ 1);
                    } else {
                        full = sb + B_EFULL + 8 * (sl - 5); dst = sb + OFF_X + (sl == 7 ? 8 : sl == 8 ? 7 : sl) * 16384;
                        mbar_wait(sb + B_EEMPTY + 8 * (sl - 5), q);
                    }
                    TS2(40 + t);
                    mbar_expect(full, 16384);
                    if (!MC || ((t ^ rank) & 1) == 0) {
                        if (u > 4) {
                            const int js = u > 6 ? j ^ 1 : j;
                            tmaw3(dst, (u & 1) ? &maps.wow : &maps.wdw, 0, (u & 1) ? 64 * js : 448 * p + 256 * (js & 1) + 128, cw, full);
                        } else {
                            const int g = 14 * p + (u == 4 ? 6 : 8 * (u & 1) + (u & 2));
                            tmaw5(dst, &maps.wdp, cc, g, full); tmaw5(dst + 8192, &maps.wdp, cc + 64, g, full);
                        }
                    }
                }
            }
        } else if (warp < 11) {
            const int hx = warp - 9;
            uint32_t epoch;
            asm volatile("ld.relaxed.gpu.global.u32 %0, [%1];" : "=r"(epoch) : "l"(g_epoch + blockIdx.x) : "memory");
            {
                const uint4* xr = (const uint4*)(xg + (size_t)(r * 128 + j * 16 + hx * 8) * kD) + lane;
                const uint4 wa = __ldg((const uint4*)gate_w + lane), wb = __ldg((const uint4*)gate_w + 32 + lane);
                const uint32_t tag = (epoch + 1) & 1;
                uint4* gp = g_gx + r * 32;
                if (lane < 2) st_pkt(gp + j * 4 + hx * 2 + lane, tag ^ 1, 0, 0, 0);
                float s[8];
                if (GDELAY) mbar_wait(sb + B_XFULL, 0);
#pragma unroll
                for (int i0 = 0; i0 < 8; i0 += 4) {
                    uint4 va[4], vb[4];
#pragma unroll
                    for (int i = 0; i < 4; i++) { va[i] = __ldg(xr + (i0 + i) * 64); vb[i] = __ldg(xr + (i0 + i) * 64 + 32); }
#pragma unroll
                    for (int i = 0; i < 4; i++) {
                        float t0 = bf_lo(va[i].x) * bf_lo(wa.x), t1 = bf_hi(va[i].x) * bf_hi(wa.x);
                        t0 = fmaf(bf_lo(va[i].y), bf_lo(wa.y), t0); t1 = fmaf(bf_hi(va[i].y), bf_hi(wa.y), t1);
                        t0 = fmaf(bf_lo(va[i].z), bf_lo(wa.z), t0); t1 = fmaf(bf_hi(va[i].z), bf_hi(wa.z), t1);
                        t0 = fmaf(bf_lo(va[i].w), bf_lo(wa.w), t0); t1 = fmaf(bf_hi(va[i].w), bf_hi(wa.w), t1);
                        t0 = fmaf(bf_lo(vb[i].x), bf_lo(wb.x), t0); t1 = fmaf(bf_hi(vb[i].x), bf_hi(wb.x), t1);
                        t0 = fmaf(bf_lo(vb[i].y), bf_lo(wb.y), t0); t1 = fmaf(bf_hi(vb[i].y), bf_hi(wb.y), t1);
                        t0 = fmaf(bf_lo(vb[i].z), bf_lo(wb.z), t0); t1 = fmaf(bf_hi(vb[i].z), bf_hi(wb.z), t1);
                        t0 = fmaf(bf_lo(vb[i].w), bf_lo(wb.w), t0); t1 = fmaf(bf_hi(vb[i].w), bf_hi(wb.w), t1);
                        s[i0 + i] = t0 + t1;
                    }
                }
#pragma unroll
                for (int i = 0; i < 8; i++) {
#pragma unroll
                    for (int o = 16; o; o >>= 1) s[i] += __shfl_xor_sync(0xffffffffu, s[i], o);
                    s[i] = 1.f / (1.f + __expf(-s[i]));
                }
                if (lane < 2) {
                    const float v0 = lane ? s[4] : s[0], v1 = lane ? s[5] : s[1], v2 = lane ? s[6] : s[2], v3 = lane ? s[7] : s[3];
                    st_pkt(gp + j * 4 + hx * 2 + lane, (__float_as_uint(v0) & ~1u) | tag, __float_as_uint(v1), __float_as_uint(v2), __float_as_uint(v3));
                }
                if (hx == 1) {
                    asm volatile("st.shared.u32 [%0], %1;" :: "r"(sb + OFF_ONES + lane * 4), "r"(0x3f803f80u) : "memory");
                    asm volatile("fence.proxy.async.shared::cta;" ::: "memory");
                }
                asm volatile("bar.sync 3, 96;" ::: "memory");
                if (hx == 0) {
                    uint32_t q[4];
                    recv_issue(q, gp + lane);
                    recv_check(q, gp + lane, tag);
                    asm volatile("st.shared.v4.u32 [%0], {%1,%2,%3,%4};" :: "r"(sb + OFF_G + lane * 16), "r"(q[0]), "r"(q[1]), "r"(q[2]), "r"(q[3]) : "memory");
                    if (lane == 0) {
                        asm volatile("st.shared.u32 [%0], %1;" :: "r"(sb + OFF_EPOCH), "r"(epoch) : "memory");
                        g_epoch[blockIdx.x] = epoch + 1;
                    }
                    __syncwarp();
                    if (lane == 0) mbar_arrive(sb + B_GRDY);
                } else {
                    if (r == 0) {
                        float4* zp = (float4*)(g_kvacc + (((epoch & 1) ^ 1) * 8 + j) * 4 * 272);
                        for (int i = lane; i < 272; i += 32) zp[i] = make_float4(0.f, 0.f, 0.f, 0.f);
                    }
                }
            }
            TS(2 + hx, 1);
#define PUBLISH_H(B) do { mbar_wait(sb + B_HSENT + 8 * (B), 0); if (lane == 0) { \
                asm volatile("st.release.gpu.global.u32 [%0], %1;" :: "l"(g_hflag + (r * 8 + j) * 8 + (B)), "r"(epoch + 1) : "memory"); } __syncwarp(); } while (0)
            if (hx == 1) {
#pragma unroll 1
                for (int b = 0; b < 3; b++) { PUBLISH_H(b); TS(3, 5 + b); }
            } else {
                const float* accp = g_kvacc + ((epoch & 1) * 8 + j) * 4 * 272;
                unsigned* cnt = g_kvcnt + j * 32;
                mbar_wait(sb + B_KVDONE, 0);
                TS(2, 5);
                if (lane == 0) asm volatile("red.release.gpu.global.add.u32 [%0], 1;" :: "l"(cnt) : "memory");
                __syncwarp();
                TS(2, 2);
                {
                    const unsigned target = 16u * (epoch + 1);
                    uint32_t it = 0, v;
                    do {
                        asm volatile("ld.acquire.gpu.global.u32 %0, [%1];" : "=r"(v) : "l"(cnt) : "memory");
                    } while ((int)(v - target) < 0 && ++it < SPIN_GLOBAL);
                }
                TS(2, 3);
#pragma unroll
                for (int h = 0; h < 4; h++) {
                    const float4 d0 = __ldcg((const float4*)(accp + h * 272) + lane);
                    const float4 d1 = __ldcg((const float4*)(accp + h * 272 + 128) + lane);
                    const float4 zz = __ldcg((const float4*)(accp + h * 272 + 256) + (lane & 3));
                    const uint32_t ba = sb + OFF_STG + h * 768 + lane * 4;
                    asm volatile("st.shared.u32 [%0], %1;" :: "r"(ba), "r"(pack2(d0.x, d0.y)) : "memory");
                    asm volatile("st.shared.u32 [%0], %1;" :: "r"(ba + 128), "r"(pack2(d1.x, d1.y)) : "memory");
                    asm volatile("st.shared.u32 [%0], %1;" :: "r"(ba + 256), "r"(pack2(d0.z, d0.w)) : "memory");
                    asm volatile("st.shared.u32 [%0], %1;" :: "r"(ba + 384), "r"(pack2(d1.z, d1.w)) : "memory");
                    asm volatile("st.shared.u32 [%0], %1;" :: "r"(ba + 512), "r"(pack2(zz.x, zz.z)) : "memory");
                    asm volatile("st.shared.u32 [%0], %1;" :: "r"(ba + 640), "r"(pack2(zz.y, zz.w)) : "memory");
                }
                asm volatile("fence.proxy.async.shared::cta;" ::: "memory");
                __syncwarp();
                if (lane == 0) mbar_arrive(sb + B_KVRDY);
                TS(2, 4);
            }
        } else {
            uint32_t epoch;
            asm volatile("ld.relaxed.gpu.global.u32 %0, [%1];" : "=r"(epoch) : "l"(g_epoch + blockIdx.x) : "memory");
            asm volatile("bar.arrive 3, 96;" :: "r"(epoch) : "memory");
            const int b = blockIdx.x, p = j >> 1;
            mbar_wait(sb + B_XFULL, 0);
            if (PF0 && r >= PF0) {
                const int row = r * 32 + lane;
                asm volatile("prefetch.global.L2 [%0];" :: "l"(pf_qkv + row * 3072 + 1024 + j * 128));
                asm volatile("prefetch.global.L2 [%0];" :: "l"(pf_qkv + row * 3072 + 2048 + j * 128));
                asm volatile("prefetch.global.L2 [%0];" :: "l"(pf_g + row * 3584 + fc * 2));
                asm volatile("prefetch.global.L2 [%0];" :: "l"(pf_u + row * 3584 + fc * 2));
            }
#pragma unroll 1
            for (int kb = 1; kb < 8; kb++) {
                mbar_wait(sb + B_XFULL + 8 * kb, 0);
                const char* base = kb < 3 ? pf_g : kb < 5 ? pf_u : kb == 5 ? pf_qkv : pf_d;
                const int off = kb == 5 ? b * 12288 : b * 14336 + ((kb < 5 ? kb - 1 : kb) & 1) * 7168;
                if (kb == 5) {
                    asm volatile("prefetch.global.L2 [%0];" :: "l"(base + off + (lane >> 3) * 3072 + (lane & 7) * 128));
                } else {
                    asm volatile("prefetch.global.L2 [%0];" :: "l"(base + off + lane * 128));
                    if (lane < 24) asm volatile("prefetch.global.L2 [%0];" :: "l"(base + off + 4096 + lane * 128));
                }
                if (kb == 7) asm volatile("prefetch.global.L2 [%0];" :: "l"(pf_o + b * 4096 + lane * 128));
            }
            {
                uint4* mb = g_part + (size_t)(r * 2 + (j & 1)) * 16384 + (((p ^ 1) * 4 + p) << 10) + lane;
#pragma unroll 1
                for (int i = 0; i < ((NOPRE || CL) ? 0 : 32); i++) { st_pkt(mb + i * 32, epoch & 1, 0, 0, 0); __nanosleep(40); }
                __syncwarp();
                if (lane == 0) mbar_arrive(sb + B_KVRDY);
            }
            {
                const uint32_t want = epoch + 1;
                const int hrow = (r * 4 + p) * 5 * 128;
                const unsigned* fl = g_hflag + (r * 8 + (j & 6)) * 8 + (lane & 15);
                uint32_t it = 0;
                int i = 0;
                mbar_wait(sb + B_HSENT + 8, 0);
#pragma unroll 1
                while (i < 3 && ++it < SPIN_GLOBAL) {
                    uint32_t v;
                    asm volatile("ld.acquire.gpu.global.u32 %0, [%1];" : "=r"(v) : "l"(fl) : "memory");
                    const uint32_t rdy = __ballot_sync(0xffffffffu, v == want);
#pragma unroll 1
                    while (i < 3 && ((rdy >> i) & 0x101u) == 0x101u) {
                        if (i < 2) mbar_wait(sb + B_XFREE + 8 * i, 0);
                        if (lane == 0) {
                            const int pc = (6 - 2 * i) % 6;
                            asm volatile("fence.proxy.async.global;" ::: "memory");
                            TS2(140 + i);
                            mbar_expect(sb + B_XFULL + 8 * pc, i != 1 ? 32768 : 16384);
                            tma2(sb + OFF_X + pc * 16384, i != 1 ? &maps.hx2 : &maps.hx, 0, hrow + pc * 128, sb + B_XFULL + 8 * pc);
                        }
                        i++;
                    }
                }
            }
        }
        if (CL) asm volatile("barrier.cluster.wait;" ::: "memory");
    } else {
        asm volatile("setmaxnreg.inc.sync.aligned.u32 224;");
        const int wg = warp >> 2;
        const bool elect = (tid & 127) == 0;
        const uint32_t sbd = (sb & 0x3FFFFu) >> 4, xlo = (sbd + wg * 512) | LBO1;
        auto release = [&](uint32_t bar) {
            if (elect) {
                mbar_arrive(sb + bar);
            }
        };
#define S_SL(S) ((S) < 40 ? (S) % 5 : (int)((0x846352107ull >> (4 * (((S) - 40) % 9))) & 15))
#define S_WAIT(S) do { mbar_wait(sb + (S_SL(S) < 5 ? B_FULL + 8 * S_SL(S) : B_EFULL + 8 * (S_SL(S) - 5)), (S) < 40 ? ((S) / 5) & 1 : (S) >= 49); \
            if (PROF && tid == 0) TS2(64 + (S)); } while (0)
#define S_B(S) (S_SL(S) < 5 ? OFF_RING / 16 + S_SL(S) * 1024 : (S_SL(S) == 7 ? 8 : S_SL(S) == 8 ? 7 : S_SL(S)) * 1024)
#define S_REL(S) do { if ((S) < 49) release(S_SL(S) < 5 ? B_EMPTY + 8 * S_SL(S) : B_EEMPTY + 8 * (S_SL(S) - 5)); } while (0)
#define G1(S, acc, SW, KB) stage_ss<(KB) * 1024, S_B(S), SW, (KB) == 0>(acc, xlo, sbd)
#define RET(S) do { S_WAIT((S) + 1); wg_wait<1>(); S_REL((S) - 1); } while (0)
#define RET2(S) do { S_WAIT((S) + 1); wg_wait<2>(); S_REL((S) - 1); } while (0)
#define SCHED() mbar_wait(sb + B_XFULL + 8 * 7, 0)
#define A2_SYNC() do { asm volatile("fence.proxy.async.shared::cta;" ::: "memory"); asm volatile("bar.sync %0, 128;" :: "r"(wg + 1) : "memory"); } while (0)
#define H_EPI(acc, F, I0, I1, OG, OU) _Pragma("unroll") for (int i = (I0); i < (I1); i++) \
            F[i] = keep(hmul2(pack2(acc[(OG) + 2 * i] * acc[(OU) + 2 * i], acc[(OG) + 2 * i + 1] * acc[(OU) + 2 * i + 1]), (i & 1) ? m_hi : m_lo))
#define PHI(acc, F, I0, I1) _Pragma("unroll") for (int i = (I0); i < (I1); i++) F[i] = keep(phi2(acc[2 * i], acc[2 * i + 1]))

        float a0[64], b0[64], a1[64], a2_[64], a3[64];
        mbar_wait(sb + B_XFULL, 0);
#define X_WAIT(KB) do { mbar_wait(sb + B_XFULL + 8 * (KB), 0); if (PROF && tid == 0) TS2(128 + (KB)); } while (0)
        S_WAIT(0); G1(0, b0, false, 0);
        if ((warp & 3) == 0) TS(wg, 1);
        S_WAIT(1); G1(1, a0, false, 0); RET(1);
        X_WAIT(1); G1(2, b0, false, 1); RET(2);
        X_WAIT(2); G1(3, b0, false, 2); RET(3);
        G1(4, a0, false, 1); RET(4);
        X_WAIT(3); G1(5, b0, false, 3); RET(5);
        G1(6, a0, false, 2); RET(6);
        X_WAIT(4); G1(7, b0, false, 4); RET(7);
        X_WAIT(5); G1(8, b0, false, 5); RET(8);
        G1(9, a0, false, 3); RET(9);
        X_WAIT(6); G1(10, b0, false, 6); RET(10);
        X_WAIT(7); G1(11, b0, false, 7); RET(11);
        G1(12, a0, false, 4);
        const uint32_t lrow = ((lane & 7) + 8 * ((lane >> 3) & 1)) * 128;
        const uint32_t srow = (warp & 3) * 2048 + lrow;
        const uint32_t ssw = (lane >> 4) ^ (lane & 7);
        uint4* const hsend = g_hx + (size_t)((r * 4 + (j >> 1)) * 5 + (j & 1)) * 1024 + warp * 128 + (lane >> 2) * 8 + (lane & 3);
#define SENT_H(B) do { __syncwarp(); if (lane == 0) mbar_arrive(sb + B_HSENT + 8 * (B)); } while (0)
        uint32_t fh0[16], fh1[16], fh2[16], fh3[8], fo[16], pk[16], pv[16];
        float kv[32], zs[4];
        const uint32_t stg = sb + OFF_STG + wg * 8192, stl = stg + (warp & 1) * 2048 + lrow;
#define KV_ROUND(Z) do { A2_SYNC(); wg_fence(); \
            wg_ss64t##Z<8192 + 256, 8192, DH128>(kv, xlo, xlo); wg_ss64t<8192 + 384, 8192 + 128, DH128>(kv, xlo, xlo); \
            wg_ss8t##Z<8192, OFF_ONES / 16, 0>(zs, xlo, sbd); wg_ss8t<8192 + 128, OFF_ONES / 16, 0>(zs, xlo, sbd); wg_commit(); } while (0)
        wg_wait<1>(); S_REL(11);
        pin(b0);
        pack_sub<32>(pv, b0);
        S_WAIT(13);
        G1(13, a0, false, 5); SCHED(); PHI(b0, pk, 0, 5); RET(13);
        G1(14, a0, false, 6); SCHED(); PHI(b0, pk, 5, 11); RET(14);
        G1(15, a0, false, 7); SCHED(); PHI(b0, pk, 11, 16); if (!(warp & 2)) stash<16>(stl + 4096, ssw, pv); RET(15);
        if ((warp & 3) == 0) TS(wg, 2);

        G1(16, a1, true, 0); SCHED(); if (!(warp & 2)) stash<16>(stl, ssw, pk);
        mbar_wait(sb + B_GRDY, 0);
        float g_lo, g_hi;
        uint32_t tag;
        {
            const uint32_t ga = sb + OFF_G + (warp * 16 + (lane >> 2)) * 4;
            asm volatile("ld.shared.f32 %0, [%1];" : "=f"(g_lo) : "r"(ga) : "memory");
            asm volatile("ld.shared.f32 %0, [%1];" : "=f"(g_hi) : "r"(ga + 32) : "memory");
            asm volatile("ld.shared.u32 %0, [%1];" : "=r"(tag) : "r"(sb + OFF_EPOCH) : "memory");
        }
        float* const kvp = g_kvacc + (((tag & 1) * 8 + j) * 4 + (warp & 3)) * 272;
        tag = (tag + 1) & 1;
        const uint32_t m_lo = pack2(1.f - g_lo, 1.f - g_lo), m_hi = pack2(1.f - g_hi, 1.f - g_hi);
        RET(16);
        pin(a0);
        G1(17, a1, true, 1); SCHED(); H_EPI(a0, fh0, 0, 16, 0, 32); RET(17);
        G1(18, a1, true, 2); KV_ROUND(_z); RET2(18);
        G1(19, a1, true, 3); SCHED(); send_h<0, 1>(fh0, hsend); RET(19);
        G1(20, a1, true, 4); SCHED(); if (warp & 2) { stash<16>(stl, ssw, pk); stash<16>(stl + 4096, ssw, pv); } RET(20);
        G1(21, a1, true, 5); KV_ROUND(); RET2(21);
        G1(22, a1, true, 6); RET(22);
        pin(kv); pin(zs);
        G1(23, a1, true, 7); SCHED();
#define KV_RED(W) do { asm volatile("red.global.add.v4.f32 [%0], {%1,%2,%3,%4};" :: "l"(kvp + lane * 4), "f"(kv[8 * W]), "f"(kv[8 * W + 1]), "f"(kv[8 * W + 2]), "f"(kv[8 * W + 3]) : "memory"); \
                       asm volatile("red.global.add.v4.f32 [%0], {%1,%2,%3,%4};" :: "l"(kvp + 128 + lane * 4), "f"(kv[8 * W + 4]), "f"(kv[8 * W + 5]), "f"(kv[8 * W + 6]), "f"(kv[8 * W + 7]) : "memory"); } while (0)
        if ((warp & 3) == 0) KV_RED(0); else if ((warp & 3) == 1) KV_RED(1); else if ((warp & 3) == 2) KV_RED(2); else KV_RED(3);
        if ((lane & 3) == 0) asm volatile("red.global.add.v2.f32 [%0], {%1,%2};" :: "l"(kvp + 256 + (lane >> 1)), "f"(zs[0]), "f"(zs[2]) : "memory");
        __syncwarp();
        if (lane == 0) mbar_arrive(sb + B_KVDONE);
        RET(23);
        if ((warp & 3) == 0) TS(wg, 3);
        G1(24, a2_, false, 0); SCHED(); send_h<1, 2>(fh0, hsend); RET(24);
        pin(a1);
        G1(25, a2_, false, 1); SCHED(); send_h<2, 3>(fh0, hsend); H_EPI(a1, fh3, 0, 8, 32, 48); RET(25);
        G1(26, a2_, false, 2); SCHED(); send_h<3, 4>(fh0, hsend); SENT_H(0); PHI(a1, fo, 0, 4); RET(26);
        G1(27, a2_, false, 3); SCHED(); send_h<0, 1>(fh3, hsend + 4 * 1024 - (j & 1) * 1020); PHI(a1, fo, 4, 8); RET(27);
        G1(28, a2_, false, 4); SCHED(); send_h<1, 2>(fh3, hsend + 4 * 1024 - (j & 1) * 1020); SENT_H(1); PHI(a1, fo, 8, 12); RET(28);
        G1(29, a2_, false, 5); SCHED(); PHI(a1, fo, 12, 16); RET(29);
        G1(30, a2_, false, 6); RET(30);
        G1(31, a2_, false, 7); RET(31);
        if ((warp & 3) == 0) TS(wg, 4);

        float on[4][12];
#define O_SCALE(h) do { const float s_lo = __fdividef(g_lo, on[h][8] + 1e-6f), s_hi = __fdividef(g_hi, on[h][10] + 1e-6f); \
            const uint32_t sl_ = pack2(s_lo, s_lo), sh_ = pack2(s_hi, s_hi); \
            fo[4 * h] = keep(hmul2(pack2(on[h][0], on[h][1]), sl_)); fo[4 * h + 1] = keep(hmul2(pack2(on[h][2], on[h][3]), sh_)); \
            fo[4 * h + 2] = keep(hmul2(pack2(on[h][4], on[h][5]), sl_)); fo[4 * h + 3] = keep(hmul2(pack2(on[h][6], on[h][7]), sh_)); } while (0)
        uint4* const lsend = g_lx + (size_t)(r * 8 + j) * 2048 + warp * 128 + lane;
        const uint4* const lrecv = g_lx + (size_t)(r * 8 + (j ^ 1)) * 2048 + warp * 128 + lane;
        G1(32, a3, false, 0); RET(32);
        pin(a2_);
        G1(33, a3, false, 1); SCHED(); H_EPI(a2_, fh1, 0, 16, 0, 32); send_h<0, 1>(fh1, hsend + 2 * 1024); RET(33);
        G1(34, a3, false, 2); SCHED(); send_h<1, 3>(fh1, hsend + 2 * 1024); RET(34);
        if (elect) mbar_arrive(sb + B_XFREE);
        G1(35, a3, false, 3); SCHED(); send_h<3, 4>(fh1, hsend + 2 * 1024); SENT_H(2);
        if ((warp & 3) == 0) TS(wg, 5);
        mbar_wait(sb + B_KVRDY, 0);
        if ((warp & 3) == 0) TS(wg, 6);
        wg_fence();
#define O_MMA(h) wg_rs24_z<OFF_STG / 16 + (h) * 48 + (8u << 16), 16>(on[h], fo[4 * (h)], fo[4 * (h) + 1], fo[4 * (h) + 2], fo[4 * (h) + 3], sbd)
        O_MMA(0); O_MMA(1); O_MMA(2); O_MMA(3);
        wg_commit();
        RET2(35);
        G1(36, a3, false, 4); RET(36);
        pin(on[0]); pin(on[1]); pin(on[2]); pin(on[3]);
        release(B_EEMPTY + 16);
        G1(37, a3, false, 5); SCHED(); O_SCALE(0); O_SCALE(1); if (!OD) { O_SCALE(2); O_SCALE(3); } RET(37);
        if (elect) mbar_arrive(sb + B_XFREE + 8);
        G1(38, a3, false, 6); SCHED(); send_frag<0, 2>(fo, lsend, tag); if (OD) { O_SCALE(2); O_SCALE(3); } RET(38);
        release(B_EEMPTY);
        G1(39, a3, false, 7); SCHED(); send_frag<2, 4>(fo, lsend, tag); RET(39);
        release(B_EEMPTY + 8);
        if ((warp & 3) == 0) TS(wg, 7);

#define G2S(S, acc, U) stage_ss<(U) * 1024, S_B(S), false, (S) == 45>(acc, xlo, sbd)
#define G2R(S, acc, F) stage_rs<S_B(S), (S) == 40>(acc, F, sbd)
#define H_WAIT(P) do { mbar_wait(sb + B_XFULL + 8 * (P), 1); if (PROF && tid == 0) TS2(150 + (P)); } while (0)
        const int p = j >> 1, pw = (p & 2) ^ 2;
        const bool own = wg == (p & 1);
        uint4* const pbase = g_part + (size_t)(r * 2 + (j & 1)) * 16384 + (warp & 3) * 256 + lane;

        float p1[64], p2[64];
        uint32_t po[16], ph2[16];
        G2R(40, p1, fo); RET(40);
        release(B_EEMPTY + 24);
        pin(a3);
        H_WAIT(0); G2S(41, p1, 0); SCHED(); H_EPI(a3, fh2, 0, 16, 0, 32); send_frag<0, 2>(fh2, lsend + 1024, tag); RET(41);
        G2S(42, p1, 1); SCHED(); recv_issue(po, lrecv); send_frag<2, 4>(fh2, lsend + 1024, tag); RET(42);
        H_WAIT(4); G2S(43, p1, 4); RET(43);
        G2R(44, p1, fh2); RET(44);
        G2S(45, p2, 0); SCHED(); if (PROF && tid == 0) TS2(160); CNT(170, recv_check(po, lrecv, tag)); if (PROF && tid == 0) TS2(161); recv_issue(ph2, lrecv + 1024); RET(45);
        G2R(46, p1, po); RET(46);
        if (CL) {
            asm volatile("barrier.cluster.wait.aligned;" ::: "memory");
            if (elect) mbar_arrive_cta(sb + B_RFREE, (blockIdx.x & 1) ^ 1);
        }
        H_WAIT(2); G2S(47, p1, 2); RET(47);
        G2S(48, p1, 3); SCHED(); if (PROF && tid == 0) TS2(162); CNT(171, recv_check(ph2, lrecv + 1024, tag)); if (PROF && tid == 0) TS2(163); RET(48);
        G2R(49, p1, ph2); RET(49);
        if ((warp & 3) == 0) TS(wg, 8);
        uint32_t sp[32], qa[16], qb[16], qc[16];
        uint4* const s1 = pbase + (((pw + wg) * 4 + p) << 10);
        G2R(50, p2, fo); RET(50);
        pin(p1);
        const uint4* ra = pbase + ((p * 4 + pw) << 10);
        const uint4* rc = pbase + ((p * 4 + (p ^ 1)) << 10);
        G2R(51, p2, po); SCHED(); pack_sub<0>(sp, p1); send_frag<0, 4>(sp, s1, tag); RET(51);
        G2R(52, p2, fh2); SCHED(); send_frag<4, 8>(sp, s1, tag); RET(52);
        if (elect) mbar_arrive(sb + B_XFREE + 16);
        if (own) mbar_wait(sb + B_AHEAD, 0);
        G2R(53, p2, ph2); RET(53);
        G2S(54, p2, 1); RET(54);
        G2S(55, p2, 2); RET(55);
        G2S(56, p2, 3); RET(56);
        G2S(57, p2, 4); SCHED();
        if ((warp & 3) == 0) TS(wg, 9);
        if (!own && elect) {
            mbar_arrive(sb + B_AHEAD);
            mbar_wait(sb + B_XFREE + 16, 0);
            bulk_in(sb + OFF_RING, ra, 32768, sb + B_PART);
        }
        wg_wait<0>();
        pin(p2);
        if ((warp & 3) == 0) TS(wg, 11);
        uint32_t f[16];
        const uint32_t ho = sb + OFF_X + (warp & 3) * 2048 + lane * 16;
        const int hv = own ? 0 : 128;
        if (!own) {
            pack_sub<0>(sp, p2);
            send_frag<0, 8>(sp, pbase + (((p ^ 1) * 4 + p) << 10), tag);
        } else {
            pack_sub<32>(f, p2);
#pragma unroll
            for (int v = 0; v < 4; v++)
                asm volatile("st.shared.v4.u32 [%0], {%1,%2,%3,%4};" :: "r"(ho + v * 512), "r"(f[4 * v]), "r"(f[4 * v + 1]), "r"(f[4 * v + 2]), "r"(f[4 * v + 3]) : "memory");
            asm volatile("bar.arrive 5, 256;" ::: "memory");
            pack_sub<0>(f, p2);
        }
        if (OE == 1 || own) recv_issue(qc, rc + hv);
        mbar_wait(sb + B_PART, 0);
        if ((warp & 3) == 0) TS(wg, 10);
        lds_pkts(qa, sb + OFF_RING + (warp & 3) * 4096 + lane * 16 + hv * 16);
        lds_pkts(qb, sb + OFF_RING + 16384 + (warp & 3) * 4096 + lane * 16 + hv * 16);
        CNT(172, recv_check(qa, ra + hv, tag)); CNT(173, recv_check(qb, ra + 1024 + hv, tag));
#pragma unroll
        for (int i = 0; i < 16; i++) qa[i] = keep(hadd2(qa[i], qb[i]));
        if ((warp & 3) == 0) TS(wg, 12);
        if (OE == 2 && !own) { asm volatile("bar.sync 5, 256;" ::: "memory"); recv_issue(qc, rc + hv); lds_pkts(f, ho); }
        CNT(174, recv_check(qc, rc + hv, tag));
        if (OE == 1 && !own) { asm volatile("bar.sync 5, 256;" ::: "memory"); lds_pkts(f, ho); }
        if ((warp & 3) == 0) TS(wg, 13);
#pragma unroll
        for (int i = 0; i < 16; i++) f[i] = hadd2(hadd2(f[i], qc[i]), qa[i]);
        {
            const uint32_t slab = sb + OFF_RING + 2 * 16384 + wg * 8192;
            stash<16>(slab + srow, ssw, f);
            __syncwarp();
            __nv_bfloat16* op = out + (size_t)(r * 128 + (p & 1) * 64 + (warp & 3) * 16 + (lane >> 3)) * kD + (j & 1) * 256 + (p & 2) * 64 + (hv >> 1) + (lane & 7) * 8;
#pragma unroll
            for (int i = 0; i < 4; i++) {
                const int row = i * 4 + (lane >> 3);
                uint4 v;
                asm volatile("ld.shared.v4.u32 {%0,%1,%2,%3}, [%4];" : "=r"(v.x), "=r"(v.y), "=r"(v.z), "=r"(v.w)
                             : "r"(slab + ((warp & 3) * 16 + row) * 128 + (((lane & 7) ^ (row & 7)) << 4)) : "memory");
                *(uint4*)(op + i * 4 * kD) = v;
            }
        }
        if ((warp & 3) == 0) { TS(wg, 14); TSG(wg, 31); }
    }
}

typedef CUresult (*EncodeFn)(CUtensorMap*, CUtensorMapDataType, cuuint32_t, void*, const cuuint64_t*, const cuuint64_t*, const cuuint32_t*,
                             const cuuint32_t*, CUtensorMapInterleave, CUtensorMapSwizzle, CUtensorMapL2promotion, CUtensorMapFloatOOBfill);

static void encode(EncodeFn fn, CUtensorMap* m, int rank, const void* base, const cuuint64_t (&gd)[5], const cuuint64_t (&gs)[4],
                   const cuuint32_t (&bd)[5], CUtensorMapSwizzle sw) {
    cuuint32_t es[5] = {1, 1, 1, 1, 1};
    fn(m, CU_TENSOR_MAP_DATA_TYPE_BFLOAT16, rank, const_cast<void*>(base), gd, gs, bd, es, CU_TENSOR_MAP_INTERLEAVE_NONE, sw,
       CU_TENSOR_MAP_L2_PROMOTION_L2_128B, CU_TENSOR_MAP_FLOAT_OOB_FILL_NONE);
}

extern "C" void kernel_launch(void* const* d_in, const int* in_sizes, int n_in, void* d_out, int out_size) {
    const char* x = (const char*)d_in[0];
    const char* wqkv = (const char*)d_in[1];
    const char* wo = (const char*)d_in[2];
    const char* wg = (const char*)d_in[4];
    const char* wu = (const char*)d_in[5];
    const char* wd = (const char*)d_in[6];
    void* fnp = nullptr;
    cudaDriverEntryPointQueryResult qr;
    cudaGetDriverEntryPoint("cuTensorMapEncodeTiled", &fnp, cudaEnableDefault, &qr);
    EncodeFn fn = (EncodeFn)fnp;
    Maps maps;
    const char* lo = wg < wu ? wg : wu;
    const uint64_t diff = wg < wu ? (uint64_t)(wu - wg) : (uint64_t)(wg - wu);
    const CUtensorMapSwizzle S128 = CU_TENSOR_MAP_SWIZZLE_128B, S64 = CU_TENSOR_MAP_SWIZZLE_64B;
    encode(fn, &maps.x, 2, x, {512, 2048, 1, 1}, {1024, 0, 0}, {64, 128, 1, 1}, S128);
    encode(fn, &maps.gu, 3, lo, {1792, 512, 2, 1}, {3584, diff, 0}, {64, 64, 2, 1}, S128);
    encode(fn, &maps.kv, 3, wqkv, {512, 512, 3, 1}, {3072, 1024, 0}, {64, 64, 2, 1}, S128);
    encode(fn, &maps.q64, 3, wqkv, {32, 512, 48, 1}, {3072, 64, 0}, {32, 64, 2, 1}, S64);
    encode(fn, &maps.gu64, 3, lo, {1792, 512, 2, 1}, {3584, diff, 0}, {32, 64, 2, 1}, S64);
    encode(fn, &maps.wdw, 3, wd, {64, 1792, 8, 1}, {1024, 128, 0}, {64, 64, 2, 1}, S128);
    encode(fn, &maps.wow, 3, wo, {64, 512, 8}, {1024, 128}, {64, 64, 2}, S128);
    encode(fn, &maps.wdp, 5, wd, {512, 2, 4, 4, 56}, {1024, 8192, 2048, 32768}, {64, 2, 4, 4, 2}, S128);
    void* hx = nullptr;
    cudaGetSymbolAddress(&hx, g_hx);
    encode(fn, &maps.hx, 2, hx, {64, 16 * 4 * 5 * 128}, {128}, {64, 128}, S128);
    encode(fn, &maps.hx2, 2, hx, {64, 16 * 4 * 5 * 128}, {128}, {64, 256}, S128);
    cudaFuncSetAttribute(fused_kernel, cudaFuncAttributeMaxDynamicSharedMemorySize, SMEM_BYTES);
    cudaLaunchConfig_t cfg = {};
    cfg.gridDim = dim3(128);
    cfg.blockDim = dim3(384);
    cfg.dynamicSmemBytes = SMEM_BYTES;
    cfg.stream = cudaStreamPerThread;
    cudaLaunchAttribute at[1];
    at[0].id = cudaLaunchAttributeClusterDimension;
    at[0].val.clusterDim.x = 2; at[0].val.clusterDim.y = 1; at[0].val.clusterDim.z = 1;
    cfg.attrs = at;
    cfg.numAttrs = (MC || CL || FORCECL) ? 1 : 0;
    cudaLaunchKernelEx(&cfg, fused_kernel, maps, (const __nv_bfloat16*)d_in[0], (const __nv_bfloat16*)d_in[7], wqkv, wg, wu, wd, wo, (__nv_bfloat16*)d_out);
}
```

```cpp
#include <cuda_runtime.h>
#include <cuda.h>
#include <cuda_bf16.h>
#include <stdint.h>

#define PROF 0

namespace {

constexpr int kD = 512;
constexpr uint32_t OFF_X = 0, OFF_STG = 131072, OFF_RING = 147456, OFF_MISC = 229376;
constexpr uint32_t B_FULL = OFF_MISC, B_EMPTY = OFF_MISC + 40, B_XFULL = OFF_MISC + 80;
constexpr uint32_t B_GRDY = OFF_MISC + 152, B_KVDONE = OFF_MISC + 160, B_KVRDY = OFF_MISC + 168;
constexpr uint32_t B_HSENT = OFF_MISC + 176, B_XFREE = OFF_MISC + 200;
constexpr uint32_t OFF_EPOCH = OFF_MISC + 240, OFF_G = OFF_MISC + 256;
constexpr uint32_t B_AHEAD = OFF_MISC + 248, B_PART = OFF_MISC + 232;
constexpr uint32_t OFF_ONES = OFF_MISC + 1024;
constexpr uint32_t B_EFULL = OFF_MISC + 896, B_EEMPTY = OFF_MISC + 928;
constexpr uint32_t SMEM_BYTES = OFF_ONES + 256;
constexpr uint32_t SPIN_GLOBAL = 1u << 17;

struct alignas(64) Maps { CUtensorMap x, gu, kv, q64, gu64, wdw, wow, wdp, hx, hx2; };

}

__device__ __align__(128) uint4 g_part[16 * 2 * 4 * 4 * 1024];
__device__ __align__(128) uint4 g_hx[16 * 4 * 5 * 1024];
__device__ __align__(128) uint4 g_lx[16 * 8 * 2 * 1024];
__device__ __align__(128) unsigned g_hflag[128 * 8];
__device__ __align__(128) uint4 g_gx[16 * 32];
__device__ __align__(128) float g_kvacc[2 * 8 * 4 * 272];
__device__ __align__(128) unsigned g_kvcnt[8 * 32];
__device__ unsigned g_epoch[128];
#define TS(role, idx)
#define TS2(idx)
#define CNT(idx, v) (void)(v)
#define TSG(role, idx)

namespace {

__device__ __forceinline__ void mbar_init(uint32_t bar, uint32_t cnt) { asm volatile("mbarrier.init.shared::cta.b64 [%0], %1;" :: "r"(bar), "r"(cnt) : "memory"); }
__device__ __forceinline__ void mbar_expect(uint32_t bar, uint32_t bytes) { asm volatile("mbarrier.arrive.expect_tx.shared::cta.b64 _, [%0], %1;" :: "r"(bar), "r"(bytes) : "memory"); }
__device__ __forceinline__ void mbar_arrive(uint32_t bar) { asm volatile("mbarrier.arrive.shared::cta.b64 _, [%0];" :: "r"(bar) : "memory"); }
__device__ __forceinline__ void mbar_wait(uint32_t bar, uint32_t parity) {
    asm volatile("{\n.reg .pred p;\n.reg .u32 c;\n"
                 "mbarrier.try_wait.parity.shared::cta.b64 p, [%0], %1;\n@p bra DONE;\n"
                 "mov.u32 c, 0;\nLAB_WAIT:\nmbarrier.try_wait.parity.shared::cta.b64 p, [%0], %1;\n@p bra DONE;\n"
                 "add.u32 c, c, 1;\nsetp.lt.u32 p, c, 65536;\n@p bra LAB_WAIT;\nDONE:\n}" :: "r"(bar), "r"(parity) : "memory");
}
__device__ __forceinline__ void tma2(uint32_t dst, const CUtensorMap* m, int c0, int c1, uint32_t bar) {
    asm volatile("cp.async.bulk.tensor.2d.shared::cluster.global.mbarrier::complete_tx::bytes [%0], [%1, {%3, %4}], [%2];"
        :: "r"(dst), "l"(m), "r"(bar), "r"(c0), "r"(c1) : "memory");
}
__device__ __forceinline__ void tma3(uint32_t dst, const CUtensorMap* m, int c0, int c1, int c2, uint32_t bar) {
    asm volatile("cp.async.bulk.tensor.3d.shared::cluster.global.mbarrier::complete_tx::bytes [%0], [%1, {%3, %4, %5}], [%2];"
        :: "r"(dst), "l"(m), "r"(bar), "r"(c0), "r"(c1), "r"(c2) : "memory");
}
__device__ __forceinline__ void tma5(uint32_t dst, const CUtensorMap* m, int c0, int c4, uint32_t bar) {
    asm volatile("cp.async.bulk.tensor.5d.shared::cluster.global.mbarrier::complete_tx::bytes [%0], [%1, {%3, %5, %5, %5, %4}], [%2];"
        :: "r"(dst), "l"(m), "r"(bar), "r"(c0), "r"(c4), "r"(0) : "memory");
}
__device__ __forceinline__ void bulk_in(uint32_t dst, const void* src, uint32_t bytes, uint32_t bar) {
    mbar_expect(bar, bytes);
    asm volatile("cp.async.bulk.shared::cluster.global.mbarrier::complete_tx::bytes [%0], [%1], %2, [%3];" :: "r"(dst), "l"(src), "r"(bytes), "r"(bar) : "memory");
}
__device__ __forceinline__ void wg_fence() { asm volatile("wgmma.fence.sync.aligned;" ::: "memory"); }
__device__ __forceinline__ void wg_commit() { asm volatile("wgmma.commit_group.sync.aligned;" ::: "memory"); }
template <int N> __device__ __forceinline__ void wg_wait() { asm volatile("wgmma.wait_group.sync.aligned %0;" :: "n"(N) : "memory"); }
template <int N> __device__ __forceinline__ void pin(float (&d)[N]) {
#pragma unroll
    for (int i = 0; i < N; i++) asm volatile("" : "+f"(d[i]) :: "memory");
}
__device__ __forceinline__ uint32_t pack2(float lo, float hi) { uint32_t r; asm("cvt.rn.bf16x2.f32 %0, %1, %2;" : "=r"(r) : "f"(hi), "f"(lo)); return r; }
__device__ __forceinline__ uint32_t keep(uint32_t v) { asm volatile("" : "+r"(v)); return v; }
__device__ __forceinline__ float rcp(float v) { float r; asm("rcp.approx.ftz.f32 %0, %1;" : "=f"(r) : "f"(v)); return r; }
__device__ __forceinline__ uint32_t hadd2(uint32_t a, uint32_t b) { uint32_t r; asm("add.bf16x2 %0, %1, %2;" : "=r"(r) : "r"(a), "r"(b)); return r; }
__device__ __forceinline__ uint32_t hmul2(uint32_t a, uint32_t b) { uint32_t r; asm("mul.bf16x2 %0, %1, %2;" : "=r"(r) : "r"(a), "r"(b)); return r; }
__device__ __forceinline__ uint32_t phi2(float t0, float t1) {
    float e0, e1;
    asm("ex2.approx.ftz.f32 %0, %1;" : "=f"(e0) : "f"(t0 * 1.4426950408889634f));
    asm("ex2.approx.ftz.f32 %0, %1;" : "=f"(e1) : "f"(t1 * 1.4426950408889634f));
    uint32_t e = pack2(e0, e1), t = pack2(t0, t1), r;
    asm("min.bf16x2 %0, %0, %1;" : "+r"(e) : "r"(0x3f803f80u));
    asm("max.bf16x2 %0, %0, %1;" : "+r"(t) : "r"(0x35863586u));
    asm("add.bf16x2 %0, %1, %2;" : "=r"(r) : "r"(e), "r"(t));
    return r;
}
__device__ __forceinline__ void stsm4(uint32_t a, uint32_t r0, uint32_t r1, uint32_t r2, uint32_t r3) {
    asm volatile("stmatrix.sync.aligned.m8n8.x4.shared.b16 [%0], {%1,%2,%3,%4};" :: "r"(a), "r"(r0), "r"(r1), "r"(r2), "r"(r3) : "memory");
}
__device__ __forceinline__ float bf_lo(uint32_t w) { return __uint_as_float(w << 16); }
__device__ __forceinline__ float bf_hi(uint32_t w) { return __uint_as_float(w & 0xffff0000u); }
__device__ __forceinline__ void st_pkt(uint4* p, uint32_t w0, uint32_t w1, uint32_t w2, uint32_t w3) {
    asm volatile("{\n.reg .b64 lo, hi;\n.reg .b128 v;\nmov.b64 lo, {%1, %2};\nmov.b64 hi, {%3, %4};\nmov.b128 v, {lo, hi};\nst.relaxed.gpu.global.b128 [%0], v;\n}"
        :: "l"(p), "r"(w0), "r"(w1), "r"(w2), "r"(w3) : "memory");
}
__device__ __forceinline__ void ld_pkt(const uint4* p, uint32_t& w0, uint32_t& w1, uint32_t& w2, uint32_t& w3) {
    asm volatile("{\n.reg .b64 lo, hi;\n.reg .b128 v;\nld.relaxed.gpu.global.b128 v, [%4];\nmov.b128 {lo, hi}, v;\nmov.b64 {%0, %1}, lo;\nmov.b64 {%2, %3}, hi;\n}"
        : "=r"(w0), "=r"(w1), "=r"(w2), "=r"(w3) : "l"(p) : "memory");
}

template <uint32_t AO, uint32_t BO, uint32_t BH> __device__ __forceinline__ void wg_ss128(float (&d)[64], uint32_t ab, uint32_t bb) {
    asm volatile("{\n.reg .b64 da, db;\n.reg .b32 ta, tb, th, ah;\nadd.u32 ta, %64, %66;\nadd.u32 tb, %65, %67;\nmov.b32 th, %68;\nmov.b32 ah, 0x40000040;\nmov.b64 da, {ta, ah};\nmov.b64 db, {tb, th};\n"
        "wgmma.mma_async.sync.aligned.m64n128k16.f32.bf16.bf16 {%0,%1,%2,%3,%4,%5,%6,%7,%8,%9,%10,%11,%12,%13,%14,%15,%16,%17,%18,%19,%20,%21,%22,%23,%24,%25,%26,%27,%28,%29,%30,%31,%32,%33,%34,%35,%36,%37,%38,%39,%40,%41,%42,%43,%44,%45,%46,%47,%48,%49,%50,%51,%52,%53,%54,%55,%56,%57,%58,%59,%60,%61,%62,%63}, da, db, 1, 1, 1, 0, 1;\n}\n"
        : "+f"(d[0]),"+f"(d[1]),"+f"(d[2]),"+f"(d[3]),"+f"(d[4]),"+f"(d[5]),"+f"(d[6]),"+f"(d[7]),"+f"(d[8]),"+f"(d[9]),"+f"(d[10]),"+f"(d[11]),"+f"(d[12]),"+f"(d[13]),"+f"(d[14]),"+f"(d[15]),"+f"(d[16]),"+f"(d[17]),"+f"(d[18]),"+f"(d[19]),"+f"(d[20]),"+f"(d[21]),"+f"(d[22]),"+f"(d[23]),"+f"(d[24]),"+f"(d[25]),"+f"(d[26]),"+f"(d[27]),"+f"(d[28]),"+f"(d[29]),"+f"(d[30]),"+f"(d[31]),"+f"(d[32]),"+f"(d[33]),"+f"(d[34]),"+f"(d[35]),"+f"(d[36]),"+f"(d[37]),"+f"(d[38]),"+f"(d[39]),"+f"(d[40]),"+f"(d[41]),"+f"(d[42]),"+f"(d[43]),"+f"(d[44]),"+f"(d[45]),"+f"(d[46]),"+f"(d[47]),"+f"(d[48]),"+f"(d[49]),"+f"(d[50]),"+f"(d[51]),"+f"(d[52]),"+f"(d[53]),"+f"(d[54]),"+f"(d[55]),"+f"(d[56]),"+f"(d[57]),"+f"(d[58]),"+f"(d[59]),"+f"(d[60]),"+f"(d[61]),"+f"(d[62]),"+f"(d[63])
        : "r"(ab), "r"(bb), "n"(AO), "n"(BO), "n"(BH));
}
template <uint32_t AO, uint32_t BO, uint32_t BH> __device__ __forceinline__ void wg_ss128_z(float (&d)[64], uint32_t ab, uint32_t bb) {
    asm volatile("{\n.reg .b64 da, db;\n.reg .b32 ta, tb, th, ah;\nadd.u32 ta, %64, %66;\nadd.u32 tb, %65, %67;\nmov.b32 th, %68;\nmov.b32 ah, 0x40000040;\nmov.b64 da, {ta, ah};\nmov.b64 db, {tb, th};\n"
        "wgmma.mma_async.sync.aligned.m64n128k16.f32.bf16.bf16 {%0,%1,%2,%3,%4,%5,%6,%7,%8,%9,%10,%11,%12,%13,%14,%15,%16,%17,%18,%19,%20,%21,%22,%23,%24,%25,%26,%27,%28,%29,%30,%31,%32,%33,%34,%35,%36,%37,%38,%39,%40,%41,%42,%43,%44,%45,%46,%47,%48,%49,%50,%51,%52,%53,%54,%55,%56,%57,%58,%59,%60,%61,%62,%63}, da, db, 0, 1, 1, 0, 1;\n}\n"
        : "=f"(d[0]),"=f"(d[1]),"=f"(d[2]),"=f"(d[3]),"=f"(d[4]),"=f"(d[5]),"=f"(d[6]),"=f"(d[7]),"=f"(d[8]),"=f"(d[9]),"=f"(d[10]),"=f"(d[11]),"=f"(d[12]),"=f"(d[13]),"=f"(d[14]),"=f"(d[15]),"=f"(d[16]),"=f"(d[17]),"=f"(d[18]),"=f"(d[19]),"=f"(d[20]),"=f"(d[21]),"=f"(d[22]),"=f"(d[23]),"=f"(d[24]),"=f"(d[25]),"=f"(d[26]),"=f"(d[27]),"=f"(d[28]),"=f"(d[29]),"=f"(d[30]),"=f"(d[31]),"=f"(d[32]),"=f"(d[33]),"=f"(d[34]),"=f"(d[35]),"=f"(d[36]),"=f"(d[37]),"=f"(d[38]),"=f"(d[39]),"=f"(d[40]),"=f"(d[41]),"=f"(d[42]),"=f"(d[43]),"=f"(d[44]),"=f"(d[45]),"=f"(d[46]),"=f"(d[47]),"=f"(d[48]),"=f"(d[49]),"=f"(d[50]),"=f"(d[51]),"=f"(d[52]),"=f"(d[53]),"=f"(d[54]),"=f"(d[55]),"=f"(d[56]),"=f"(d[57]),"=f"(d[58]),"=f"(d[59]),"=f"(d[60]),"=f"(d[61]),"=f"(d[62]),"=f"(d[63])
        : "r"(ab), "r"(bb), "n"(AO), "n"(BO), "n"(BH));
}
template <uint32_t BO, uint32_t BH> __device__ __forceinline__ void wg_rs128(float (&d)[64], uint32_t a0, uint32_t a1, uint32_t a2, uint32_t a3, uint32_t bb) {
    asm volatile("{\n.reg .b64 db;\n.reg .b32 tb, th;\nadd.u32 tb, %68, %69;\nmov.b32 th, %70;\nmov.b64 db, {tb, th};\n"
        "wgmma.mma_async.sync.aligned.m64n128k16.f32.bf16.bf16 {%0,%1,%2,%3,%4,%5,%6,%7,%8,%9,%10,%11,%12,%13,%14,%15,%16,%17,%18,%19,%20,%21,%22,%23,%24,%25,%26,%27,%28,%29,%30,%31,%32,%33,%34,%35,%36,%37,%38,%39,%40,%41,%42,%43,%44,%45,%46,%47,%48,%49,%50,%51,%52,%53,%54,%55,%56,%57,%58,%59,%60,%61,%62,%63}, {%64,%65,%66,%67}, db, 1, 1, 1, 1;\n}\n"
        : "+f"(d[0]),"+f"(d[1]),"+f"(d[2]),"+f"(d[3]),"+f"(d[4]),"+f"(d[5]),"+f"(d[6]),"+f"(d[7]),"+f"(d[8]),"+f"(d[9]),"+f"(d[10]),"+f"(d[11]),"+f"(d[12]),"+f"(d[13]),"+f"(d[14]),"+f"(d[15]),"+f"(d[16]),"+f"(d[17]),"+f"(d[18]),"+f"(d[19]),"+f"(d[20]),"+f"(d[21]),"+f"(d[22]),"+f"(d[23]),"+f"(d[24]),"+f"(d[25]),"+f"(d[26]),"+f"(d[27]),"+f"(d[28]),"+f"(d[29]),"+f"(d[30]),"+f"(d[31]),"+f"(d[32]),"+f"(d[33]),"+f"(d[34]),"+f"(d[35]),"+f"(d[36]),"+f"(d[37]),"+f"(d[38]),"+f"(d[39]),"+f"(d[40]),"+f"(d[41]),"+f"(d[42]),"+f"(d[43]),"+f"(d[44]),"+f"(d[45]),"+f"(d[46]),"+f"(d[47]),"+f"(d[48]),"+f"(d[49]),"+f"(d[50]),"+f"(d[51]),"+f"(d[52]),"+f"(d[53]),"+f"(d[54]),"+f"(d[55]),"+f"(d[56]),"+f"(d[57]),"+f"(d[58]),"+f"(d[59]),"+f"(d[60]),"+f"(d[61]),"+f"(d[62]),"+f"(d[63])
        : "r"(a0), "r"(a1), "r"(a2), "r"(a3), "r"(bb), "n"(BO), "n"(BH));
}
template <uint32_t BO, uint32_t BH> __device__ __forceinline__ void wg_rs128_z(float (&d)[64], uint32_t a0, uint32_t a1, uint32_t a2, uint32_t a3, uint32_t bb) {
    asm volatile("{\n.reg .b64 db;\n.reg .b32 tb, th;\nadd.u32 tb, %68, %69;\nmov.b32 th, %70;\nmov.b64 db, {tb, th};\n"
        "wgmma.mma_async.sync.aligned.m64n128k16.f32.bf16.bf16 {%0,%1,%2,%3,%4,%5,%6,%7,%8,%9,%10,%11,%12,%13,%14,%15,%16,%17,%18,%19,%20,%21,%22,%23,%24,%25,%26,%27,%28,%29,%30,%31,%32,%33,%34,%35,%36,%37,%38,%39,%40,%41,%42,%43,%44,%45,%46,%47,%48,%49,%50,%51,%52,%53,%54,%55,%56,%57,%58,%59,%60,%61,%62,%63}, {%64,%65,%66,%67}, db, 0, 1, 1, 1;\n}\n"
        : "=f"(d[0]),"=f"(d[1]),"=f"(d[2]),"=f"(d[3]),"=f"(d[4]),"=f"(d[5]),"=f"(d[6]),"=f"(d[7]),"=f"(d[8]),"=f"(d[9]),"=f"(d[10]),"=f"(d[11]),"=f"(d[12]),"=f"(d[13]),"=f"(d[14]),"=f"(d[15]),"=f"(d[16]),"=f"(d[17]),"=f"(d[18]),"=f"(d[19]),"=f"(d[20]),"=f"(d[21]),"=f"(d[22]),"=f"(d[23]),"=f"(d[24]),"=f"(d[25]),"=f"(d[26]),"=f"(d[27]),"=f"(d[28]),"=f"(d[29]),"=f"(d[30]),"=f"(d[31]),"=f"(d[32]),"=f"(d[33]),"=f"(d[34]),"=f"(d[35]),"=f"(d[36]),"=f"(d[37]),"=f"(d[38]),"=f"(d[39]),"=f"(d[40]),"=f"(d[41]),"=f"(d[42]),"=f"(d[43]),"=f"(d[44]),"=f"(d[45]),"=f"(d[46]),"=f"(d[47]),"=f"(d[48]),"=f"(d[49]),"=f"(d[50]),"=f"(d[51]),"=f"(d[52]),"=f"(d[53]),"=f"(d[54]),"=f"(d[55]),"=f"(d[56]),"=f"(d[57]),"=f"(d[58]),"=f"(d[59]),"=f"(d[60]),"=f"(d[61]),"=f"(d[62]),"=f"(d[63])
        : "r"(a0), "r"(a1), "r"(a2), "r"(a3), "r"(bb), "n"(BO), "n"(BH));
}
template <uint32_t AO, uint32_t BO, uint32_t BH> __device__ __forceinline__ void wg_ss64t(float (&d)[32], uint32_t ab, uint32_t bb) {
    asm volatile("{\n.reg .b64 da, db;\n.reg .b32 ta, tb, th, ah;\nadd.u32 ta, %32, %34;\nadd.u32 tb, %33, %35;\nmov.b32 th, %36;\nmov.b32 ah, 0x40000040;\nmov.b64 da, {ta, ah};\nmov.b64 db, {tb, th};\n"
        "wgmma.mma_async.sync.aligned.m64n64k16.f32.bf16.bf16 {%0,%1,%2,%3,%4,%5,%6,%7,%8,%9,%10,%11,%12,%13,%14,%15,%16,%17,%18,%19,%20,%21,%22,%23,%24,%25,%26,%27,%28,%29,%30,%31}, da, db, 1, 1, 1, 1, 1;\n}\n"
        : "+f"(d[0]),"+f"(d[1]),"+f"(d[2]),"+f"(d[3]),"+f"(d[4]),"+f"(d[5]),"+f"(d[6]),"+f"(d[7]),"+f"(d[8]),"+f"(d[9]),"+f"(d[10]),"+f"(d[11]),"+f"(d[12]),"+f"(d[13]),"+f"(d[14]),"+f"(d[15]),"+f"(d[16]),"+f"(d[17]),"+f"(d[18]),"+f"(d[19]),"+f"(d[20]),"+f"(d[21]),"+f"(d[22]),"+f"(d[23]),"+f"(d[24]),"+f"(d[25]),"+f"(d[26]),"+f"(d[27]),"+f"(d[28]),"+f"(d[29]),"+f"(d[30]),"+f"(d[31])
        : "r"(ab), "r"(bb), "n"(AO), "n"(BO), "n"(BH));
}
template <uint32_t AO, uint32_t BO, uint32_t BH> __device__ __forceinline__ void wg_ss64t_z(float (&d)[32], uint32_t ab, uint32_t bb) {
    asm volatile("{\n.reg .b64 da, db;\n.reg .b32 ta, tb, th, ah;\nadd.u32 ta, %32, %34;\nadd.u32 tb, %33, %35;\nmov.b32 th, %36;\nmov.b32 ah, 0x40000040;\nmov.b64 da, {ta, ah};\nmov.b64 db, {tb, th};\n"
        "wgmma.mma_async.sync.aligned.m64n64k16.f32.bf16.bf16 {%0,%1,%2,%3,%4,%5,%6,%7,%8,%9,%10,%11,%12,%13,%14,%15,%16,%17,%18,%19,%20,%21,%22,%23,%24,%25,%26,%27,%28,%29,%30,%31}, da, db, 0, 1, 1, 1, 1;\n}\n"
        : "=f"(d[0]),"=f"(d[1]),"=f"(d[2]),"=f"(d[3]),"=f"(d[4]),"=f"(d[5]),"=f"(d[6]),"=f"(d[7]),"=f"(d[8]),"=f"(d[9]),"=f"(d[10]),"=f"(d[11]),"=f"(d[12]),"=f"(d[13]),"=f"(d[14]),"=f"(d[15]),"=f"(d[16]),"=f"(d[17]),"=f"(d[18]),"=f"(d[19]),"=f"(d[20]),"=f"(d[21]),"=f"(d[22]),"=f"(d[23]),"=f"(d[24]),"=f"(d[25]),"=f"(d[26]),"=f"(d[27]),"=f"(d[28]),"=f"(d[29]),"=f"(d[30]),"=f"(d[31])
        : "r"(ab), "r"(bb), "n"(AO), "n"(BO), "n"(BH));
}
template <uint32_t AO, uint32_t BO, uint32_t BH> __device__ __forceinline__ void wg_ss8t(float (&d)[4], uint32_t ab, uint32_t bb) {
    asm volatile("{\n.reg .b64 da, db;\n.reg .b32 ta, tb, th, ah;\nadd.u32 ta, %4, %6;\nadd.u32 tb, %5, %7;\nmov.b32 th, %8;\nmov.b32 ah, 0x40000040;\nmov.b64 da, {ta, ah};\nmov.b64 db, {tb, th};\n"
        "wgmma.mma_async.sync.aligned.m64n8k16.f32.bf16.bf16 {%0,%1,%2,%3}, da, db, 1, 1, 1, 1, 0;\n}\n"
        : "+f"(d[0]),"+f"(d[1]),"+f"(d[2]),"+f"(d[3])
        : "r"(ab), "r"(bb), "n"(AO), "n"(BO), "n"(BH));
}
template <uint32_t AO, uint32_t BO, uint32_t BH> __device__ __forceinline__ void wg_ss8t_z(float (&d)[4], uint32_t ab, uint32_t bb) {
    asm volatile("{\n.reg .b64 da, db;\n.reg .b32 ta, tb, th, ah;\nadd.u32 ta, %4, %6;\nadd.u32 tb, %5, %7;\nmov.b32 th, %8;\nmov.b32 ah, 0x40000040;\nmov.b64 da, {ta, ah};\nmov.b64 db, {tb, th};\n"
        "wgmma.mma_async.sync.aligned.m64n8k16.f32.bf16.bf16 {%0,%1,%2,%3}, da, db, 0, 1, 1, 1, 0;\n}\n"
        : "=f"(d[0]),"=f"(d[1]),"=f"(d[2]),"=f"(d[3])
        : "r"(ab), "r"(bb), "n"(AO), "n"(BO), "n"(BH));
}
template <uint32_t BO, uint32_t BH> __device__ __forceinline__ void wg_rs24_z(float (&d)[12], uint32_t a0, uint32_t a1, uint32_t a2, uint32_t a3, uint32_t bb) {
    asm volatile("{\n.reg .b64 db;\n.reg .b32 tb, th;\nadd.u32 tb, %16, %17;\nmov.b32 th, %18;\nmov.b64 db, {tb, th};\n"
        "wgmma.mma_async.sync.aligned.m64n24k16.f32.bf16.bf16 {%0,%1,%2,%3,%4,%5,%6,%7,%8,%9,%10,%11}, {%12,%13,%14,%15}, db, 0, 1, 1, 0;\n}\n"
        : "=f"(d[0]),"=f"(d[1]),"=f"(d[2]),"=f"(d[3]),"=f"(d[4]),"=f"(d[5]),"=f"(d[6]),"=f"(d[7]),"=f"(d[8]),"=f"(d[9]),"=f"(d[10]),"=f"(d[11])
        : "r"(a0), "r"(a1), "r"(a2), "r"(a3), "r"(bb), "n"(BO), "n"(BH));
}

constexpr uint32_t DH128 = 64u | 0x40000000u;
constexpr uint32_t DH64 = 32u | 0x80000000u;
constexpr uint32_t LBO4K = (4096u >> 4) << 16, LBO8K = (8192u >> 4) << 16, LBO1 = 1u << 16;

template <uint32_t AO, uint32_t BO, bool SW64, bool FIRST> __device__ __forceinline__ void stage_ss(float (&acc)[64], uint32_t ab, uint32_t bb) {
    constexpr uint32_t KS = SW64 ? 64 : 128, BH = SW64 ? DH64 : DH128, B0 = BO + (SW64 ? LBO4K : LBO8K);
    wg_fence();
    if (FIRST) wg_ss128_z<AO, B0, BH>(acc, ab, bb); else wg_ss128<AO, B0, BH>(acc, ab, bb);
    wg_ss128<AO + 2, B0 + KS, BH>(acc, ab, bb);
    wg_ss128<AO + 4, B0 + 2 * KS, BH>(acc, ab, bb);
    wg_ss128<AO + 6, B0 + 3 * KS, BH>(acc, ab, bb);
    wg_commit();
}
template <uint32_t BO, bool FIRST> __device__ __forceinline__ void stage_rs(float (&acc)[64], const uint32_t (&f)[16], uint32_t bb) {
    wg_fence();
    if (FIRST) wg_rs128_z<BO + LBO8K, DH128>(acc, f[0], f[1], f[2], f[3], bb); else wg_rs128<BO + LBO8K, DH128>(acc, f[0], f[1], f[2], f[3], bb);
    wg_rs128<BO + LBO8K + 128, DH128>(acc, f[4], f[5], f[6], f[7], bb);
    wg_rs128<BO + LBO8K + 256, DH128>(acc, f[8], f[9], f[10], f[11], bb);
    wg_rs128<BO + LBO8K + 384, DH128>(acc, f[12], f[13], f[14], f[15], bb);
    wg_commit();
}

template <int N> __device__ __forceinline__ void stash(uint32_t base, uint32_t sw, const uint32_t (&f)[N]) {
#pragma unroll
    for (int t = 0; t < N / 4; t++) stsm4(base + ((sw ^ (2 * t)) << 4), f[4 * t], f[4 * t + 1], f[4 * t + 2], f[4 * t + 3]);
}

template <int V0, int V1, int N> __device__ __forceinline__ void send_frag(const uint32_t (&f)[N], uint4* p, uint32_t tag) {
#pragma unroll
    for (int v = V0; v < V1; v++) st_pkt(p + v * 32, (f[4 * v] & ~1u) | tag, f[4 * v + 1], f[4 * v + 2], f[4 * v + 3]);
}
template <int V0, int V1, int N> __device__ __forceinline__ void send_h(const uint32_t (&f)[N], uint4* p) {
#pragma unroll
    for (int v = V0; v < V1; v++) {
        const int h = v >> 1, hi = v & 1;
        asm volatile("st.global.v4.u32 [%0], {%1,%2,%3,%4};" :: "l"(p + 4 * h + 64 * hi),
                     "r"(f[8 * h + hi]), "r"(f[8 * h + 2 + hi]), "r"(f[8 * h + 4 + hi]), "r"(f[8 * h + 6 + hi]) : "memory");
    }
}
template <int O, int N, int M> __device__ __forceinline__ void pack_sub(uint32_t (&f)[N], const float (&acc)[M]) {
#pragma unroll
    for (int i = 0; i < N; i++) f[i] = keep(pack2(acc[O + 2 * i], acc[O + 2 * i + 1]));
}
template <int N> __device__ __forceinline__ void recv_issue(uint32_t (&q)[N], const uint4* p) {
#pragma unroll
    for (int v = 0; v < N / 4; v++) ld_pkt(p + v * 32, q[4 * v], q[4 * v + 1], q[4 * v + 2], q[4 * v + 3]);
}
template <int N> __device__ __forceinline__ void lds_pkts(uint32_t (&q)[N], uint32_t a) {
#pragma unroll
    for (int v = 0; v < N / 4; v++)
        asm volatile("ld.shared.v4.u32 {%0,%1,%2,%3}, [%4];" : "=r"(q[4 * v]), "=r"(q[4 * v + 1]), "=r"(q[4 * v + 2]), "=r"(q[4 * v + 3]) : "r"(a + v * 512) : "memory");
}
template <int N> __device__ __forceinline__ uint32_t recv_check(uint32_t (&q)[N], const uint4* p, uint32_t tag) {
    uint32_t it = 0;
    while (true) {
        uint32_t bad = 0;
#pragma unroll
        for (int v = 0; v < N / 4; v++) bad |= q[4 * v] ^ tag;
        if (__all_sync(0xffffffffu, (bad & 1u) == 0) || ++it > SPIN_GLOBAL) break;
        recv_issue(q, p);
    }
    return it;
}
}

__global__ void __launch_bounds__(384, 1)
fused_kernel(const __grid_constant__ Maps maps, const __nv_bfloat16* __restrict__ xg, const __nv_bfloat16* __restrict__ gate_w,
             const char* __restrict__ pf_qkv, const char* __restrict__ pf_g, const char* __restrict__ pf_u,
             const char* __restrict__ pf_d, const char* __restrict__ pf_o, __nv_bfloat16* __restrict__ out) {
    extern __shared__ __align__(1024) uint8_t smem_raw[];
    const uint32_t sb = (uint32_t)__cvta_generic_to_shared(smem_raw);
    const int tid = threadIdx.x, lane = tid & 31;
    const int warp = __shfl_sync(0xffffffffu, tid >> 5, 0);
    const int j = (blockIdx.x >> 2) & 7, r = (blockIdx.x & 3) | ((blockIdx.x >> 5) << 2);
    const int fc = 448 * (j >> 1) + 256 * (j & 1);
    if (warp == 0) { TSG(0, 30); TS(0, 0); }
    if (tid == 256) {
        mbar_init(sb + B_XFULL, 1); mbar_init(sb + B_FULL, 1); mbar_init(sb + B_FULL + 8, 1);
        asm volatile("fence.mbarrier_init.release.cluster;" ::: "memory");
        TS2(0);
        mbar_expect(sb + B_FULL, 16384);
        tma3(sb + OFF_RING, &maps.kv, 64 * j, 0, 1, sb + B_FULL);
        mbar_expect(sb + B_XFULL, 16384);
        tma2(sb + OFF_X, &maps.x, 0, r * 128, sb + B_XFULL);
        TS2(1);
        mbar_expect(sb + B_FULL + 8, 16384);
        tma3(sb + OFF_RING + 16384, &maps.gu, fc, 0, 0, sb + B_FULL + 8);
    } else if (tid == 352) {
        for (int i = 0; i < 5; i++) { if (i > 1) mbar_init(sb + B_FULL + 8 * i, 1); mbar_init(sb + B_EMPTY + 8 * i, 2); }
        for (int i = 1; i < 8; i++) mbar_init(sb + B_XFULL + 8 * i, 1);
        asm volatile("fence.mbarrier_init.release.cluster;" ::: "memory");
    } else if (tid == 288) {
        for (int i = 0; i < 3; i++) mbar_init(sb + B_HSENT + 8 * i, 8);
        for (int i = 0; i < 4; i++) { mbar_init(sb + B_EFULL + 8 * i, 1); mbar_init(sb + B_EEMPTY + 8 * i, 2); }
        mbar_init(sb + B_XFREE, 2); mbar_init(sb + B_XFREE + 8, 2); mbar_init(sb + B_XFREE + 16, 2);
        mbar_init(sb + B_AHEAD, 1); mbar_init(sb + B_PART, 1); mbar_init(sb + B_GRDY, 1); mbar_init(sb + B_KVDONE, 8); mbar_init(sb + B_KVRDY, 2);
        asm volatile("fence.mbarrier_init.release.cluster;" ::: "memory");
    } else if (warp == 10 && lane < 10) {
        asm volatile("prefetch.tensormap [%0];" :: "l"(&maps.x + lane) : "memory");
    }
    __syncthreads();

    if (warp >= 8) {
        asm volatile("setmaxnreg.dec.sync.aligned.u32 56;");
        if (warp == 8) {
            if (lane == 0) {
                int slot = 2, ph = 1;
                uint32_t full, dst;
                mbar_expect(sb + B_XFULL + 8, 16384); tma2(sb + OFF_X + 16384, &maps.x, 64, r * 128, sb + B_XFULL + 8);
#define P_BEGIN(S, BYTES) full = sb + B_FULL + 8 * slot; dst = sb + OFF_RING + slot * 16384; \
                mbar_wait(sb + B_EMPTY + 8 * slot, ph); TS2(S); mbar_expect(full, BYTES);
#define P_END() if (++slot == 5) { slot = 0; ph ^= 1; }
                for (int s = 2; s < 16; s++) {
                    const int kb = (int)(0x7654376524312100ull >> (4 * s)) & 15;
                    P_BEGIN(s, 16384) {
                        if ((0x076Du >> s) & 1) tma3(dst, &maps.kv, 64 * j, 64 * kb, 1, full);
                        else tma3(dst, &maps.gu, fc, 64 * kb, 0, full);
                    }
                    if (s < 8) { mbar_expect(sb + B_XFULL + 8 * s, 16384); tma2(sb + OFF_X + s * 16384, &maps.x, 64 * s, r * 128, sb + B_XFULL + 8 * s); }
                    P_END()
                }
                for (int s = 0; s < 24; s++) {
                    P_BEGIN(16 + s, 16384) {
                        if (s < 8) {
                            tma3(dst, &maps.q64, 0, 64 * s, 2 * j, full);
                            tma3(dst + 8192, &maps.gu64, 224 * (j & 6) + 192 + 32 * (j & 1), 64 * s, 0, full);
                        } else {
                            tma3(dst, &maps.gu, fc + 64 * (s >> 3), 64 * (s & 7), 0, full);
                        }
                    }
                    P_END()
                }
                const int p = j >> 1;
#pragma unroll 1
                for (int t = 0; t < 18; t++) {
                    const int q = t >= 9, sl = (int)(0x846352107ull >> (4 * (t - 9 * q))) & 15;
                    const int u = (int)((q ? 0x432186758ull : 0x327064105ull) >> (4 * (t - 9 * q))) & 15;
                    const int cw = (j & 1) * 4 + ((p & 2) ^ ((t == 5 || t > 9) ? 0 : 2)), cc = 64 * cw;
                    if (sl < 5) {
                        full = sb + B_FULL + 8 * sl; dst = sb + OFF_RING + sl * 16384;
                        mbar_wait(sb + B_EMPTY + 8 * sl, q ^ 1);
                    } else {
                        full = sb + B_EFULL + 8 * (sl - 5); dst = sb + OFF_X + (sl == 7 ? 8 : sl == 8 ? 7 : sl) * 16384;
                        mbar_wait(sb + B_EEMPTY + 8 * (sl - 5), q);
                    }
                    TS2(40 + t);
                    mbar_expect(full, 16384);
                    if (u > 4) {
                        const int js = u > 6 ? j ^ 1 : j;
                        tma3(dst, (u & 1) ? &maps.wow : &maps.wdw, 0, (u & 1) ? 64 * js : 448 * p + 256 * (js & 1) + 128, cw, full);
                    } else {
                        const int g = 14 * p + (u == 4 ? 6 : 8 * (u & 1) + (u & 2));
                        tma5(dst, &maps.wdp, cc, g, full); tma5(dst + 8192, &maps.wdp, cc + 64, g, full);
                    }
                }
            }
        } else if (warp < 11) {
            const int hx = warp - 9;
            uint32_t epoch;
            asm volatile("ld.relaxed.gpu.global.u32 %0, [%1];" : "=r"(epoch) : "l"(g_epoch + blockIdx.x) : "memory");
            {
                const uint4* xr = (const uint4*)(xg + (size_t)(r * 128 + j * 16 + hx * 8) * kD) + lane;
                const uint4 wa = __ldg((const uint4*)gate_w + lane), wb = __ldg((const uint4*)gate_w + 32 + lane);
                const uint32_t tag = (epoch + 1) & 1;
                uint4* gp = g_gx + r * 32;
                if (lane < 2) st_pkt(gp + j * 4 + hx * 2 + lane, tag ^ 1, 0, 0, 0);
                float s[8];
                mbar_wait(sb + B_XFULL, 0);
#pragma unroll
                for (int i0 = 0; i0 < 8; i0 += 4) {
                    uint4 va[4], vb[4];
#pragma unroll
                    for (int i = 0; i < 4; i++) { va[i] = __ldg(xr + (i0 + i) * 64); vb[i] = __ldg(xr + (i0 + i) * 64 + 32); }
#pragma unroll
                    for (int i = 0; i < 4; i++) {
                        float t0 = bf_lo(va[i].x) * bf_lo(wa.x), t1 = bf_hi(va[i].x) * bf_hi(wa.x);
                        t0 = fmaf(bf_lo(va[i].y), bf_lo(wa.y), t0); t1 = fmaf(bf_hi(va[i].y), bf_hi(wa.y), t1);
                        t0 = fmaf(bf_lo(va[i].z), bf_lo(wa.z), t0); t1 = fmaf(bf_hi(va[i].z), bf_hi(wa.z), t1);
                        t0 = fmaf(bf_lo(va[i].w), bf_lo(wa.w), t0); t1 = fmaf(bf_hi(va[i].w), bf_hi(wa.w), t1);
                        t0 = fmaf(bf_lo(vb[i].x), bf_lo(wb.x), t0); t1 = fmaf(bf_hi(vb[i].x), bf_hi(wb.x), t1);
                        t0 = fmaf(bf_lo(vb[i].y), bf_lo(wb.y), t0); t1 = fmaf(bf_hi(vb[i].y), bf_hi(wb.y), t1);
                        t0 = fmaf(bf_lo(vb[i].z), bf_lo(wb.z), t0); t1 = fmaf(bf_hi(vb[i].z), bf_hi(wb.z), t1);
                        t0 = fmaf(bf_lo(vb[i].w), bf_lo(wb.w), t0); t1 = fmaf(bf_hi(vb[i].w), bf_hi(wb.w), t1);
                        s[i0 + i] = t0 + t1;
                    }
                }
#pragma unroll
                for (int i = 0; i < 8; i++) {
#pragma unroll
                    for (int o = 16; o; o >>= 1) s[i] += __shfl_xor_sync(0xffffffffu, s[i], o);
                    s[i] = 1.f / (1.f + __expf(-s[i]));
                }
                if (lane < 2) {
                    const float v0 = lane ? s[4] : s[0], v1 = lane ? s[5] : s[1], v2 = lane ? s[6] : s[2], v3 = lane ? s[7] : s[3];
                    st_pkt(gp + j * 4 + hx * 2 + lane, (__float_as_uint(v0) & ~1u) | tag, __float_as_uint(v1), __float_as_uint(v2), __float_as_uint(v3));
                }
                if (hx == 1) {
                    asm volatile("st.shared.v2.u32 [%0], {%1, %1};" :: "r"(sb + OFF_ONES + lane * 8), "r"(0x3f803f80u) : "memory");
                    asm volatile("fence.proxy.async.shared::cta;" ::: "memory");
                }
                asm volatile("bar.sync 3, 96;" ::: "memory");
                if (hx == 0) {
                    uint32_t q[4];
                    recv_issue(q, gp + lane);
                    recv_check(q, gp + lane, tag);
                    asm volatile("st.shared.v4.u32 [%0], {%1,%2,%3,%4};" :: "r"(sb + OFF_G + lane * 16), "r"(q[0]), "r"(q[1]), "r"(q[2]), "r"(q[3]) : "memory");
                    if (lane == 0) {
                        asm volatile("st.shared.u32 [%0], %1;" :: "r"(sb + OFF_EPOCH), "r"(epoch) : "memory");
                        g_epoch[blockIdx.x] = epoch + 1;
                    }
                    __syncwarp();
                    if (lane == 0) mbar_arrive(sb + B_GRDY);
                } else {
                    if (r == 0) {
                        float4* zp = (float4*)(g_kvacc + (((epoch & 1) ^ 1) * 8 + j) * 4 * 272);
                        for (int i = lane; i < 272; i += 32) zp[i] = make_float4(0.f, 0.f, 0.f, 0.f);
                    }
                }
            }
            TS(2 + hx, 1);
#define PUBLISH_H(B) do { mbar_wait(sb + B_HSENT + 8 * (B), 0); if (lane == 0) { \
                asm volatile("st.release.gpu.global.u32 [%0], %1;" :: "l"(g_hflag + (r * 8 + j) * 8 + (B)), "r"(epoch + 1) : "memory"); } __syncwarp(); } while (0)
            if (hx == 1) {
#pragma unroll 1
                for (int b = 0; b < 3; b++) { PUBLISH_H(b); TS(3, 5 + b); }
            } else {
                const float* accp = g_kvacc + ((epoch & 1) * 8 + j) * 4 * 272;
                unsigned* cnt = g_kvcnt + j * 32;
                mbar_wait(sb + B_KVDONE, 0);
                TS(2, 5);
                if (lane == 0) asm volatile("red.release.gpu.global.add.u32 [%0], 1;" :: "l"(cnt) : "memory");
                __syncwarp();
                TS(2, 2);
                {
                    const unsigned target = 16u * (epoch + 1);
                    uint32_t it = 0, v;
                    do {
                        asm volatile("ld.acquire.gpu.global.u32 %0, [%1];" : "=r"(v) : "l"(cnt) : "memory");
                    } while ((int)(v - target) < 0 && ++it < SPIN_GLOBAL);
                }
                TS(2, 3);
#pragma unroll
                for (int h = 0; h < 4; h++) {
                    const float4 d0 = __ldcg((const float4*)(accp + h * 272) + lane);
                    const float4 d1 = __ldcg((const float4*)(accp + h * 272 + 128) + lane);
                    const float4 zz = __ldcg((const float4*)(accp + h * 272 + 256) + (lane & 3));
                    const uint32_t ba = sb + OFF_STG + h * 768 + lane * 4;
                    asm volatile("st.shared.u32 [%0], %1;" :: "r"(ba), "r"(pack2(d0.x, d0.y)) : "memory");
                    asm volatile("st.shared.u32 [%0], %1;" :: "r"(ba + 128), "r"(pack2(d1.x, d1.y)) : "memory");
                    asm volatile("st.shared.u32 [%0], %1;" :: "r"(ba + 256), "r"(pack2(d0.z, d0.w)) : "memory");
                    asm volatile("st.shared.u32 [%0], %1;" :: "r"(ba + 384), "r"(pack2(d1.z, d1.w)) : "memory");
                    asm volatile("st.shared.u32 [%0], %1;" :: "r"(ba + 512), "r"(pack2(zz.x, zz.z)) : "memory");
                    asm volatile("st.shared.u32 [%0], %1;" :: "r"(ba + 640), "r"(pack2(zz.y, zz.w)) : "memory");
                }
                asm volatile("fence.proxy.async.shared::cta;" ::: "memory");
                __syncwarp();
                if (lane == 0) mbar_arrive(sb + B_KVRDY);
                TS(2, 4);
            }
        } else {
            uint32_t epoch;
            asm volatile("ld.relaxed.gpu.global.u32 %0, [%1];" : "=r"(epoch) : "l"(g_epoch + blockIdx.x) : "memory");
            asm volatile("bar.arrive 3, 96;" :: "r"(epoch) : "memory");
            const int b = blockIdx.x, p = j >> 1;
            mbar_wait(sb + B_XFULL, 0);
            if (r >= 4) {
                const int row = r * 32 + lane;
                asm volatile("prefetch.global.L2 [%0];" :: "l"(pf_qkv + row * 3072 + 1024 + j * 128));
                asm volatile("prefetch.global.L2 [%0];" :: "l"(pf_qkv + row * 3072 + 2048 + j * 128));
                asm volatile("prefetch.global.L2 [%0];" :: "l"(pf_g + row * 3584 + fc * 2));
                asm volatile("prefetch.global.L2 [%0];" :: "l"(pf_u + row * 3584 + fc * 2));
            }
#pragma unroll 1
            for (int kb = 1; kb < 8; kb++) {
                mbar_wait(sb + B_XFULL + 8 * kb, 0);
                const char* base = kb < 3 ? pf_g : kb < 5 ? pf_u : kb == 5 ? pf_qkv : pf_d;
                const int off = kb == 5 ? b * 12288 : b * 14336 + ((kb < 5 ? kb - 1 : kb) & 1) * 7168;
                if (kb == 5) {
                    asm volatile("prefetch.global.L2 [%0];" :: "l"(base + off + (lane >> 3) * 3072 + (lane & 7) * 128));
                } else {
                    asm volatile("prefetch.global.L2 [%0];" :: "l"(base + off + lane * 128));
                    if (lane < 24) asm volatile("prefetch.global.L2 [%0];" :: "l"(base + off + 4096 + lane * 128));
                }
                if (kb == 7) asm volatile("prefetch.global.L2 [%0];" :: "l"(pf_o + b * 4096 + lane * 128));
            }
            {
                uint4* mb = g_part + (size_t)(r * 2 + (j & 1)) * 16384 + (((p ^ 1) * 4 + p) << 10) + lane;
#pragma unroll 1
                for (int i = 0; i < 32; i++) { st_pkt(mb + i * 32, epoch & 1, 0, 0, 0); __nanosleep(40); }
                __syncwarp();
                if (lane == 0) mbar_arrive(sb + B_KVRDY);
            }
            {
                const uint32_t want = epoch + 1;
                const int hrow = (r * 4 + p) * 5 * 128;
                const unsigned* fl = g_hflag + (r * 8 + (j & 6)) * 8 + (lane & 15);
                uint32_t it = 0;
                int i = 0;
#pragma unroll 1
                while (i < 3 && ++it < SPIN_GLOBAL) {
                    uint32_t v;
                    if (i < 2) mbar_wait(sb + B_XFREE + 8 * i, 0);
                    asm volatile("ld.acquire.gpu.global.u32 %0, [%1];" : "=r"(v) : "l"(fl) : "memory");
                    const uint32_t rdy = __ballot_sync(0xffffffffu, v == want);
#pragma unroll 1
                    while (i < 3 && ((rdy >> i) & 0x101u) == 0x101u) {
                        if (i < 2) mbar_wait(sb + B_XFREE + 8 * i, 0);
                        if (lane == 0) {
                            const int pc = (6 - 2 * i) % 6;
                            asm volatile("fence.proxy.async.global;" ::: "memory");
                            TS2(140 + i);
                            mbar_expect(sb + B_XFULL + 8 * pc, i != 1 ? 32768 : 16384);
                            tma2(sb + OFF_X + pc * 16384, i != 1 ? &maps.hx2 : &maps.hx, 0, hrow + pc * 128, sb + B_XFULL + 8 * pc);
                        }
                        i++;
                    }
                }
            }
        }
    } else {
        asm volatile("setmaxnreg.inc.sync.aligned.u32 224;");
        const int wg = warp >> 2;
        const bool elect = (tid & 127) == 0;
        const uint32_t sbd = (sb & 0x3FFFFu) >> 4, xlo = (sbd + wg * 512) | LBO1;
        auto release = [&](uint32_t bar) { if (elect) mbar_arrive(sb + bar); };
#define S_SL(S) ((S) < 40 ? (S) % 5 : (int)((0x846352107ull >> (4 * (((S) - 40) % 9))) & 15))
#define S_WAIT(S) do { mbar_wait(sb + (S_SL(S) < 5 ? B_FULL + 8 * S_SL(S) : B_EFULL + 8 * (S_SL(S) - 5)), (S) < 40 ? ((S) / 5) & 1 : (S) >= 49); \
            if (PROF && tid == 0) TS2(64 + (S)); } while (0)
#define S_B(S) (S_SL(S) < 5 ? OFF_RING / 16 + S_SL(S) * 1024 : (S_SL(S) == 7 ? 8 : S_SL(S) == 8 ? 7 : S_SL(S)) * 1024)
#define S_REL(S) do { if ((S) < 49) release(S_SL(S) < 5 ? B_EMPTY + 8 * S_SL(S) : B_EEMPTY + 8 * (S_SL(S) - 5)); } while (0)
#define G1(S, acc, SW, KB) stage_ss<(KB) * 1024, S_B(S), SW, (KB) == 0>(acc, xlo, sbd)
#define RET(S) do { S_WAIT((S) + 1); wg_wait<1>(); S_REL((S) - 1); } while (0)
#define RET2(S) do { S_WAIT((S) + 1); wg_wait<2>(); S_REL((S) - 1); } while (0)
#define SCHED() mbar_wait(sb + B_XFULL + 8 * 7, 0)
#define H_EPI(acc, F, I0, I1, OG, OU) _Pragma("unroll") for (int i = (I0); i < (I1); i++) \
            F[i] = keep(hmul2(pack2(acc[(OG) + 2 * i] * acc[(OU) + 2 * i], acc[(OG) + 2 * i + 1] * acc[(OU) + 2 * i + 1]), (i & 1) ? m_hi : m_lo))
#define PHI(acc, F, I0, I1) _Pragma("unroll") for (int i = (I0); i < (I1); i++) F[i] = keep(phi2(acc[2 * i], acc[2 * i + 1]))

        float a0[64], b0[64], a1[64], a2_[64], a3[64];
        mbar_wait(sb + B_XFULL, 0);
#define X_WAIT(KB) do { mbar_wait(sb + B_XFULL + 8 * (KB), 0); if (PROF && tid == 0) TS2(128 + (KB)); } while (0)
        S_WAIT(0); G1(0, b0, false, 0);
        if ((warp & 3) == 0) TS(wg, 1);
        S_WAIT(1); G1(1, a0, false, 0); RET(1);
        X_WAIT(1); G1(2, b0, false, 1); RET(2);
        X_WAIT(2); G1(3, b0, false, 2); RET(3);
        G1(4, a0, false, 1); RET(4);
        X_WAIT(3); G1(5, b0, false, 3); RET(5);
        X_WAIT(4); G1(6, b0, false, 4); RET(6);
        G1(7, a0, false, 2); RET(7);
        X_WAIT(5); G1(8, b0, false, 5); RET(8);
        X_WAIT(6); G1(9, b0, false, 6); RET(9);
        X_WAIT(7); G1(10, b0, false, 7); RET(10);
        G1(11, a0, false, 3);
        const uint32_t lrow = ((lane & 7) + 8 * ((lane >> 3) & 1)) * 128;
        const uint32_t srow = (warp & 3) * 2048 + lrow;
        const uint32_t ssw = (lane >> 4) ^ (lane & 7);
        uint4* const hsend = g_hx + (size_t)((r * 4 + (j >> 1)) * 5 + (j & 1)) * 1024 + warp * 128 + (lane >> 2) * 8 + (lane & 3);
#define SENT_H(B) do { __syncwarp(); if (lane == 0) mbar_arrive(sb + B_HSENT + 8 * (B)); } while (0)
        uint32_t fh0[16], fh1[16], fh2[16], fh3[8], fo[16], pk[16], pv[16];
        float kv[32], zs[4];
        const uint32_t stg = sb + OFF_STG + wg * 8192, stl = stg + (warp & 1) * 2048 + lrow;
#define KV_ROUND(Z) do { asm volatile("fence.proxy.async.shared::cta;" ::: "memory"); \
            asm volatile("bar.sync %0, 128;" :: "r"(wg + 1) : "memory"); wg_fence(); \
            wg_ss64t##Z<8192 + 256, 8192, DH128>(kv, xlo, xlo); wg_ss64t<8192 + 384, 8192 + 128, DH128>(kv, xlo, xlo); \
            wg_ss8t##Z<8192, OFF_ONES / 16 + (8u << 16), 16>(zs, xlo, sbd); wg_ss8t<8192 + 128, OFF_ONES / 16 + (8u << 16), 16>(zs, xlo, sbd); wg_commit(); } while (0)
        RET(11);
        pin(b0);
        G1(12, a0, false, 4); SCHED(); pack_sub<32>(pv, b0); PHI(b0, pk, 0, 3); RET(12);
        G1(13, a0, false, 5); SCHED(); PHI(b0, pk, 3, 8); RET(13);
        G1(14, a0, false, 6); SCHED(); PHI(b0, pk, 8, 12); if (!(warp & 2)) stash<16>(stl + 4096, ssw, pv); RET(14);
        G1(15, a0, false, 7); SCHED(); PHI(b0, pk, 12, 16); RET(15);
        if ((warp & 3) == 0) TS(wg, 2);

        G1(16, a1, true, 0); SCHED(); if (!(warp & 2)) stash<16>(stl, ssw, pk);
        mbar_wait(sb + B_GRDY, 0);
        float g_lo, g_hi;
        uint32_t tag;
        {
            const uint32_t ga = sb + OFF_G + (warp * 16 + (lane >> 2)) * 4;
            asm volatile("ld.shared.f32 %0, [%1];" : "=f"(g_lo) : "r"(ga) : "memory");
            asm volatile("ld.shared.f32 %0, [%1];" : "=f"(g_hi) : "r"(ga + 32) : "memory");
            asm volatile("ld.shared.u32 %0, [%1];" : "=r"(tag) : "r"(sb + OFF_EPOCH) : "memory");
        }
        float* const kvp = g_kvacc + (((tag & 1) * 8 + j) * 4 + (warp & 3)) * 272;
        tag = (tag + 1) & 1;
        const uint32_t m_lo = pack2(1.f - g_lo, 1.f - g_lo), m_hi = pack2(1.f - g_hi, 1.f - g_hi);
        RET(16);
        pin(a0);
        G1(17, a1, true, 1); SCHED(); H_EPI(a0, fh0, 0, 16, 0, 32); RET(17);
        G1(18, a1, true, 2); KV_ROUND(_z); RET2(18);
        G1(19, a1, true, 3); SCHED(); send_h<0, 1>(fh0, hsend); RET(19);
        G1(20, a1, true, 4); SCHED(); if (warp & 2) { stash<16>(stl, ssw, pk); stash<16>(stl + 4096, ssw, pv); } RET(20);
        G1(21, a1, true, 5); KV_ROUND(); RET2(21);
        G1(22, a1, true, 6); RET(22);
        pin(kv); pin(zs);
        G1(23, a1, true, 7); SCHED();
#define KV_RED(W) do { asm volatile("red.global.add.v4.f32 [%0], {%1,%2,%3,%4};" :: "l"(kvp + lane * 4), "f"(kv[8 * W]), "f"(kv[8 * W + 1]), "f"(kv[8 * W + 2]), "f"(kv[8 * W + 3]) : "memory"); \
                       asm volatile("red.global.add.v4.f32 [%0], {%1,%2,%3,%4};" :: "l"(kvp + 128 + lane * 4), "f"(kv[8 * W + 4]), "f"(kv[8 * W + 5]), "f"(kv[8 * W + 6]), "f"(kv[8 * W + 7]) : "memory"); } while (0)
        if ((warp & 3) == 0) KV_RED(0); else if ((warp & 3) == 1) KV_RED(1); else if ((warp & 3) == 2) KV_RED(2); else KV_RED(3);
        if ((lane & 3) == 0) asm volatile("red.global.add.v2.f32 [%0], {%1,%2};" :: "l"(kvp + 256 + (lane >> 1)), "f"(zs[0]), "f"(zs[2]) : "memory");
        __syncwarp();
        if (lane == 0) mbar_arrive(sb + B_KVDONE);
        RET(23);
        if ((warp & 3) == 0) TS(wg, 3);

        G1(24, a2_, false, 0); SCHED(); send_h<1, 2>(fh0, hsend); RET(24);
        pin(a1);
        G1(25, a2_, false, 1); SCHED(); send_h<2, 3>(fh0, hsend); H_EPI(a1, fh3, 0, 8, 32, 48); RET(25);
        G1(26, a2_, false, 2); SCHED(); send_h<3, 4>(fh0, hsend); SENT_H(0); PHI(a1, fo, 0, 4); RET(26);
        G1(27, a2_, false, 3); SCHED(); send_h<0, 1>(fh3, hsend + 4 * 1024 - (j & 1) * 1020); PHI(a1, fo, 4, 8); RET(27);
        G1(28, a2_, false, 4); SCHED(); send_h<1, 2>(fh3, hsend + 4 * 1024 - (j & 1) * 1020); SENT_H(1); PHI(a1, fo, 8, 12); RET(28);
        G1(29, a2_, false, 5); SCHED(); PHI(a1, fo, 12, 16); RET(29);
        G1(30, a2_, false, 6); RET(30);
        G1(31, a2_, false, 7); RET(31);
        if ((warp & 3) == 0) TS(wg, 4);

        float on[4][12];
#define O_SCALE(h) do { const float s_lo = g_lo * rcp(on[h][8] + 1e-6f), s_hi = g_hi * rcp(on[h][10] + 1e-6f); \
            const uint32_t sl_ = pack2(s_lo, s_lo), sh_ = pack2(s_hi, s_hi); \
            fo[4 * h] = keep(hmul2(pack2(on[h][0], on[h][1]), sl_)); fo[4 * h + 1] = keep(hmul2(pack2(on[h][2], on[h][3]), sh_)); \
            fo[4 * h + 2] = keep(hmul2(pack2(on[h][4], on[h][5]), sl_)); fo[4 * h + 3] = keep(hmul2(pack2(on[h][6], on[h][7]), sh_)); } while (0)
        uint4* const lsend = g_lx + (size_t)(r * 8 + j) * 2048 + warp * 128 + lane;
        const uint4* const lrecv = g_lx + (size_t)(r * 8 + (j ^ 1)) * 2048 + warp * 128 + lane;
        G1(32, a3, false, 0); RET(32);
        pin(a2_);
        G1(33, a3, false, 1); SCHED(); H_EPI(a2_, fh1, 0, 8, 0, 32); send_h<0, 1>(fh1, hsend + 2 * 1024); RET(33);
        G1(34, a3, false, 2); SCHED(); send_h<1, 2>(fh1, hsend + 2 * 1024); H_EPI(a2_, fh1, 8, 16, 0, 32); send_h<2, 3>(fh1, hsend + 2 * 1024); RET(34);
        if (elect) mbar_arrive(sb + B_XFREE);
        G1(35, a3, false, 3); SCHED(); send_h<3, 4>(fh1, hsend + 2 * 1024); SENT_H(2);
        if ((warp & 3) == 0) TS(wg, 5);
        mbar_wait(sb + B_KVRDY, 0);
        if ((warp & 3) == 0) TS(wg, 6);
        wg_fence();
#define O_MMA(h) wg_rs24_z<OFF_STG / 16 + (h) * 48 + (8u << 16), 16>(on[h], fo[4 * (h)], fo[4 * (h) + 1], fo[4 * (h) + 2], fo[4 * (h) + 3], sbd)
        O_MMA(0); O_MMA(1); O_MMA(2); O_MMA(3);
        wg_commit();
        RET2(35);
        G1(36, a3, false, 4); RET(36);
        pin(on[0]); pin(on[1]); pin(on[2]); pin(on[3]);
        release(B_EEMPTY + 16);
        G1(37, a3, false, 5); SCHED(); O_SCALE(0); O_SCALE(1); O_SCALE(2); O_SCALE(3); RET(37);
        G1(38, a3, false, 6); SCHED(); send_frag<0, 2>(fo, lsend, tag); RET(38);
        release(B_EEMPTY);
        if (elect) mbar_arrive(sb + B_XFREE + 8);
        G1(39, a3, false, 7); SCHED(); send_frag<2, 4>(fo, lsend, tag); RET(39);
        release(B_EEMPTY + 8);
        if ((warp & 3) == 0) TS(wg, 7);

#define G2S(S, acc, U) stage_ss<(U) * 1024, S_B(S), false, (S) == 45>(acc, xlo, sbd)
#define G2R(S, acc, F) stage_rs<S_B(S), (S) == 40>(acc, F, sbd)
#define H_WAIT(P) do { mbar_wait(sb + B_XFULL + 8 * (P), 1); if (PROF && tid == 0) TS2(150 + (P)); } while (0)
        const int p = j >> 1, pw = (p & 2) ^ 2;
        const bool own = wg == (p & 1);
        uint4* const pbase = g_part + (size_t)(r * 2 + (j & 1)) * 16384 + (warp & 3) * 256 + lane;

        float p1[64], p2[64];
        uint32_t po[16], ph2[16];
        G2R(40, p1, fo); RET(40);
        release(B_EEMPTY + 24);
        pin(a3);
        H_WAIT(0); G2S(41, p1, 0); SCHED(); H_EPI(a3, fh2, 0, 8, 0, 32); send_frag<0, 2>(fh2, lsend + 1024, tag); RET(41);
        G2S(42, p1, 1); SCHED(); recv_issue(po, lrecv); H_EPI(a3, fh2, 8, 16, 0, 32); send_frag<2, 4>(fh2, lsend + 1024, tag); RET(42);
        H_WAIT(4); G2S(43, p1, 4); RET(43);
        G2R(44, p1, fh2); RET(44);
        G2S(45, p2, 0); SCHED(); if (PROF && tid == 0) TS2(160); CNT(170, recv_check(po, lrecv, tag)); if (PROF && tid == 0) TS2(161); recv_issue(ph2, lrecv + 1024); RET(45);
        G2R(46, p1, po); RET(46);
        H_WAIT(2); G2S(47, p1, 2); RET(47);
        G2S(48, p1, 3); SCHED(); if (PROF && tid == 0) TS2(162); CNT(171, recv_check(ph2, lrecv + 1024, tag)); if (PROF && tid == 0) TS2(163); RET(48);
        G2R(49, p1, ph2); RET(49);
        if ((warp & 3) == 0) TS(wg, 8);
        uint32_t sp[32], qa[16], qb[16], qc[16];
        uint4* const s1 = pbase + (((pw + wg) * 4 + p) << 10);
        G2R(50, p2, fo); RET(50);
        pin(p1);
        const uint4* ra = pbase + ((p * 4 + pw) << 10);
        const uint4* rc = pbase + ((p * 4 + (p ^ 1)) << 10);
        G2R(51, p2, po); SCHED(); pack_sub<0>(qa, p1); send_frag<0, 4>(qa, s1, tag); RET(51);
        G2R(52, p2, fh2); SCHED(); pack_sub<32>(qb, p1); send_frag<0, 4>(qb, s1 + 128, tag); RET(52);
        if (elect) mbar_arrive(sb + B_XFREE + 16);
        if (own) mbar_wait(sb + B_AHEAD, 0);
        G2R(53, p2, ph2); RET(53);
        G2S(54, p2, 1); RET(54);
        G2S(55, p2, 2); RET(55);
        G2S(56, p2, 3); RET(56);
        G2S(57, p2, 4); SCHED();
        if ((warp & 3) == 0) TS(wg, 9);
        if (!own && elect) {
            mbar_arrive(sb + B_AHEAD);
            mbar_wait(sb + B_XFREE + 16, 0);
            bulk_in(sb + OFF_RING, ra, 32768, sb + B_PART);
        }
        wg_wait<0>();
        pin(p2);
        if ((warp & 3) == 0) TS(wg, 11);
        uint32_t f[16];
        const uint32_t ho = sb + OFF_X + (warp & 3) * 2048 + lane * 16;
        const int hv = own ? 0 : 128;
        if (!own) {
            pack_sub<0>(sp, p2);
            send_frag<0, 8>(sp, pbase + (((p ^ 1) * 4 + p) << 10), tag);
        } else {
            pack_sub<32>(f, p2);
#pragma unroll
            for (int v = 0; v < 4; v++)
                asm volatile("st.shared.v4.u32 [%0], {%1,%2,%3,%4};" :: "r"(ho + v * 512), "r"(f[4 * v]), "r"(f[4 * v + 1]), "r"(f[4 * v + 2]), "r"(f[4 * v + 3]) : "memory");
            asm volatile("bar.arrive 5, 256;" ::: "memory");
            pack_sub<0>(f, p2);
        }
        recv_issue(qc, rc + hv);
        mbar_wait(sb + B_PART, 0);
        if ((warp & 3) == 0) TS(wg, 10);
        lds_pkts(qa, sb + OFF_RING + (warp & 3) * 4096 + lane * 16 + hv * 16);
        lds_pkts(qb, sb + OFF_RING + 16384 + (warp & 3) * 4096 + lane * 16 + hv * 16);
        CNT(172, recv_check(qa, ra + hv, tag)); CNT(173, recv_check(qb, ra + 1024 + hv, tag));
#pragma unroll
        for (int i = 0; i < 16; i++) qa[i] = keep(hadd2(qa[i], qb[i]));
        if ((warp & 3) == 0) TS(wg, 12);
        CNT(174, recv_check(qc, rc + hv, tag));
        if (!own) { asm volatile("bar.sync 5, 256;" ::: "memory"); lds_pkts(f, ho); }
        if ((warp & 3) == 0) TS(wg, 13);
#pragma unroll
        for (int i = 0; i < 16; i++) f[i] = hadd2(hadd2(f[i], qc[i]), qa[i]);
        {
            const uint32_t slab = sb + OFF_RING + 2 * 16384 + wg * 8192;
            stash<16>(slab + srow, ssw, f);
            __syncwarp();
            __nv_bfloat16* op = out + (size_t)(r * 128 + (p & 1) * 64 + (warp & 3) * 16 + (lane >> 3)) * kD + (j & 1) * 256 + (p & 2) * 64 + (hv >> 1) + (lane & 7) * 8;
#pragma unroll
            for (int i = 0; i < 4; i++) {
                const int row = i * 4 + (lane >> 3);
                uint4 v;
                asm volatile("ld.shared.v4.u32 {%0,%1,%2,%3}, [%4];" : "=r"(v.x), "=r"(v.y), "=r"(v.z), "=r"(v.w)
                             : "r"(slab + ((warp & 3) * 16 + row) * 128 + (((lane & 7) ^ (row & 7)) << 4)) : "memory");
                *(uint4*)(op + i * 4 * kD) = v;
            }
        }
        if ((warp & 3) == 0) { TS(wg, 14); TSG(wg, 31); }
    }
}

typedef CUresult (*EncodeFn)(CUtensorMap*, CUtensorMapDataType, cuuint32_t, void*, const cuuint64_t*, const cuuint64_t*, const cuuint32_t*,
                             const cuuint32_t*, CUtensorMapInterleave, CUtensorMapSwizzle, CUtensorMapL2promotion, CUtensorMapFloatOOBfill);

static void encode(EncodeFn fn, CUtensorMap* m, int rank, const void* base, const cuuint64_t (&gd)[5], const cuuint64_t (&gs)[4],
                   const cuuint32_t (&bd)[5], CUtensorMapSwizzle sw) {
    cuuint32_t es[5] = {1, 1, 1, 1, 1};
    fn(m, CU_TENSOR_MAP_DATA_TYPE_BFLOAT16, rank, const_cast<void*>(base), gd, gs, bd, es, CU_TENSOR_MAP_INTERLEAVE_NONE, sw,
       CU_TENSOR_MAP_L2_PROMOTION_NONE, CU_TENSOR_MAP_FLOAT_OOB_FILL_NONE);
}

extern "C" void kernel_launch(void* const* d_in, const int* in_sizes, int n_in, void* d_out, int out_size) {
    const char* x = (const char*)d_in[0];
    const char* wqkv = (const char*)d_in[1];
    const char* wo = (const char*)d_in[2];
    const char* wg = (const char*)d_in[4];
    const char* wu = (const char*)d_in[5];
    const char* wd = (const char*)d_in[6];
    void* fnp = nullptr;
    cudaDriverEntryPointQueryResult qr;
    cudaGetDriverEntryPoint("cuTensorMapEncodeTiled", &fnp, cudaEnableDefault, &qr);
    EncodeFn fn = (EncodeFn)fnp;
    Maps maps;
    const char* lo = wg < wu ? wg : wu;
    const uint64_t diff = wg < wu ? (uint64_t)(wu - wg) : (uint64_t)(wg - wu);
    const CUtensorMapSwizzle S128 = CU_TENSOR_MAP_SWIZZLE_128B, S64 = CU_TENSOR_MAP_SWIZZLE_64B;
    encode(fn, &maps.x, 2, x, {512, 2048, 1, 1}, {1024, 0, 0}, {64, 128, 1, 1}, S128);
    encode(fn, &maps.gu, 3, lo, {1792, 512, 2, 1}, {3584, diff, 0}, {64, 64, 2, 1}, S128);
    encode(fn, &maps.kv, 3, wqkv, {512, 512, 3, 1}, {3072, 1024, 0}, {64, 64, 2, 1}, S128);
    encode(fn, &maps.q64, 3, wqkv, {32, 512, 48, 1}, {3072, 64, 0}, {32, 64, 2, 1}, S64);
    encode(fn, &maps.gu64, 3, lo, {1792, 512, 2, 1}, {3584, diff, 0}, {32, 64, 2, 1}, S64);
    encode(fn, &maps.wdw, 3, wd, {64, 1792, 8, 1}, {1024, 128, 0}, {64, 64, 2, 1}, S128);
    encode(fn, &maps.wow, 3, wo, {64, 512, 8}, {1024, 128}, {64, 64, 2}, S128);
    encode(fn, &maps.wdp, 5, wd, {512, 2, 4, 4, 56}, {1024, 8192, 2048, 32768}, {64, 2, 4, 4, 2}, S128);
    void* hx = nullptr;
    cudaGetSymbolAddress(&hx, g_hx);
    encode(fn, &maps.hx, 2, hx, {64, 16 * 4 * 5 * 128}, {128}, {64, 128}, S128);
    encode(fn, &maps.hx2, 2, hx, {64, 16 * 4 * 5 * 128}, {128}, {64, 256}, S128);
    cudaFuncSetAttribute(fused_kernel, cudaFuncAttributeMaxDynamicSharedMemorySize, SMEM_BYTES);
    fused_kernel<<<128, 384, SMEM_BYTES, cudaStreamPerThread>>>(maps, (const __nv_bfloat16*)d_in[0], (const __nv_bfloat16*)d_in[7], wqkv, wg, wu, wd, wo,
                                                                (__nv_bfloat16*)d_out);
}
```
